```python
import torch

def _softmax(x, axis=-1):
    return torch.softmax(x, dim=axis)
def _gelu(x):
    return torch.nn.functional.gelu(x, approximate="tanh")
def _silu(x):
    return torch.nn.functional.silu(x)
def _sigmoid(x):
    return torch.sigmoid(x)
def _layernorm(x, axis=-1, eps=1e-5):
    m = x.mean(dim=axis, keepdim=True)
    v = x.var(dim=axis, keepdim=True, unbiased=False)
    return (x - m) / torch.sqrt(v + eps)
def _scatter_add(tgt, idx, src, axis=0):
    return tgt.clone().index_add_(axis, idx, src)
def _segment_sum(src, seg, n):
    out = torch.zeros((n,) + src.shape[1:], dtype=src.dtype)
    return out.index_add_(0, seg, src)
def _pad(x, pw):
    flat = tuple(v for pair in reversed(pw) for v in pair)
    return torch.nn.functional.pad(x, flat)

kernel_name = 'concat_heads__spectral_gfnet__ssm_conv_s5__prompt'

def setup_inputs():

    _w = (lambda a: (lambda t: t.to(torch.bfloat16) if t.is_floating_point() else t)(torch.as_tensor(a)))
    def _A_setup():
        B, S, D = 1, 2048, 1024
        Df = D // 2 + 1
        return {
            "x": _w((lambda *s: torch.randn(*s, dtype=torch.bfloat16) * 0.05)(B, S, D)),
            "w_r": _w((lambda *s: torch.randn(*s, dtype=torch.bfloat16) * 0.8)(S, Df) * 0.02),
            "w_i": _w((lambda *s: torch.randn(*s, dtype=torch.bfloat16) * 0.8)(S, Df) * 0.02),
        }
    _A_in = _A_setup()

    def _B_setup():
        B, S, D = 1, 2048, 1024
        P = D
        Lambda_re = -0.5 * (lambda _x: torch.exp(torch.as_tensor(_x)))((lambda *s: torch.randn(*s, dtype=torch.bfloat16) * 0.2)(P))
        Lambda_im = (lambda *s: torch.randn(*s, dtype=torch.bfloat16) * 0.4)(P) * 1.0
        B_re = (lambda *s: torch.randn(*s, dtype=torch.bfloat16) * 0.2)(P, D) * (D ** -0.5)
        B_im = (lambda *s: torch.randn(*s, dtype=torch.bfloat16) * 0.2)(P, D) * (D ** -0.5)
        C_re = (lambda *s: torch.randn(*s, dtype=torch.bfloat16) * 0.2)(D, P) * (P ** -0.5)
        C_im = (lambda *s: torch.randn(*s, dtype=torch.bfloat16) * 0.2)(D, P) * (P ** -0.5)
        log_dt = (lambda *s: torch.randn(*s, dtype=torch.bfloat16) * 0.2)(P) * 0.3 - 2.0
        Dskip = (lambda *s: torch.randn(*s, dtype=torch.bfloat16) * 0.05)(D)
        return {
            "x": _w((lambda *s: torch.randn(*s, dtype=torch.bfloat16) * 0.05)(B, S, D)),
            "Lambda_re": _w(Lambda_re),
            "Lambda_im": _w(Lambda_im),
            "B_re": _w(B_re),
            "B_im": _w(B_im),
            "C_re": _w(C_re),
            "C_im": _w(C_im),
            "log_dt": _w(log_dt),
            "Dskip": _w(Dskip),
        }
    _B_in = _B_setup()

    return {
        "A_x": _A_in["x"],
        "A_w_r": _A_in["w_r"],
        "A_w_i": _A_in["w_i"],
        "B_x": _B_in["x"],
        "B_Lambda_re": _B_in["Lambda_re"],
        "B_Lambda_im": _B_in["Lambda_im"],
        "B_B_re": _B_in["B_re"],
        "B_B_im": _B_in["B_im"],
        "B_C_re": _B_in["C_re"],
        "B_C_im": _B_in["C_im"],
        "B_log_dt": _B_in["log_dt"],
        "B_Dskip": _B_in["Dskip"],
    }

def reference(A_x, A_w_r, A_w_i, B_x, B_Lambda_re, B_Lambda_im, B_B_re, B_B_im, B_C_re, B_C_im, B_log_dt, B_Dskip):
    def _A_ref(x, w_r, w_i):
        B, S, D = x.shape
        X = (lambda x, axes=(-2,-1): torch.fft.rfft2(x.float(), dim=axes))(x, axes=(-2, -1))
        W = w_r + 1j * w_i
        X = X * W
        y = (lambda x, s, axes=(-2,-1): torch.fft.irfft2(x, s=s, dim=axes).to(torch.bfloat16))(X, (S, D), axes=(-2, -1))
        return y

    def _B_ref(x, Lambda_re, Lambda_im, B_re, B_im, C_re, C_im, log_dt, Dskip):
        Bsz, L, H = x.shape
        Lam = Lambda_re + 1j * Lambda_im
        Bmat = B_re + 1j * B_im
        Cmat = C_re + 1j * C_im
        dt = torch.exp(log_dt)
        Lam_bar = torch.exp(dt * Lam)
        B_bar = ((Lam_bar - 1.0) / Lam)[:, None] * Bmat
        Bu = torch.einsum("bld,pd->blp", x + 0j, B_bar)
        h = torch.zeros_like(Bu[:, 0, :])
        hs = []
        for t in range(L):
            h = Lam_bar[None, :] * h + Bu[:, t, :]
            hs.append(h)
        hseq = torch.stack(hs, 1)
        y = 2.0 * torch.einsum("blp,dp->bld", hseq, Cmat).real + x * Dskip[None, None, :]
        return y

    a = _A_ref(A_x, A_w_r, A_w_i)
    b = _B_ref(B_x, B_Lambda_re, B_Lambda_im, B_B_re, B_B_im, B_C_re, B_C_im, B_log_dt, B_Dskip)
    return torch.concatenate([a, b], axis=-1)
```

```cpp
#include <cuda_runtime.h>
#include <cuda.h>
#include <cuda_bf16.h>
#include <stdint.h>

#define NST 5
#define SB0 1024
#define WPITCH 1056
#define OFF_P (NST * 32768)
#define OFF_F (OFF_P + 32768)
#define OFF_W (OFF_F + 8192)
#define OFF_TL (OFF_W + 16 * WPITCH)
#define OFF_TM (OFF_TL + 4096)
#define OFF_T1 (OFF_TM + 4096)
#define OFF_BAR (OFF_T1 + 2048)
#define OFF_STAMP (OFF_BAR + 284)
#define SMEM_BYTES (OFF_BAR + 512)
#define B_FULL 0
#define B_EMPTY 40
#define B_STGU 80
#define B_HGO 88
#define B_LAM 120
#define B_STG 128
#define B_WFREE 136
#define B_EP 144
#define B_LDONE 152
#define B_UIN 160
#define B_WIN 176
#define B_XIN 184
#define B_VIN 200
#define B_HRTY 232
#define B_HLD 240
#define B_END 280
#define B_EPOCH 280

#define PACE_U 250
#define PACE_V 250
#define PACE_O 150
#define PACE_H 60
#define HDELAY 0
#define LDK 14
#define POLL_AT 24
#define XA_FIRST 2
#define XA_AT 0
#define YS 3
#define UDELAY 250
#define PACE_W 120
#define HINT_LATE 1
#define XLATE 0
#define GRP 2
#define WAITN 1
#define LASTW 2
#define UBOX 32
#define VBOX 64
#define SKEW 4
#define SPIN_LIMIT 32768

#define YIELD() asm volatile("pmevent 0;")
#define YF 1
#define YIELD2() do { if (YF > 1) YIELD(); } while (0)

__device__ __align__(1024) uint8_t g_U[4 << 20];
__device__ __align__(1024) uint8_t g_V[4 << 20];
__device__ __align__(1024) uint8_t g_H[8 << 20];
__device__ __align__(1024) uint4 g_carry[16 * 512];
__device__ __align__(1024) unsigned g_hcnt[16 * 64];
__device__ __align__(128) unsigned g_cnt[128];
__device__ __align__(128) unsigned g_epoch[129 * 8];

#define STAMP(i) do { } while (0)
#define STAMPR(i) do { } while (0)
#define STAMPW(a, b) do { } while (0)
#define STAMPX(a, b) do { } while (0)
#define STAMP3(i) do { } while (0)

#define TAB_FG 0
#define TAB_F1 2048
#define TAB_T 4096
#define TAB_SP 6144
#define TAB_TW 7168
#define TAB_FX 7680
__device__ __align__(1024) const uint32_t g_tab[7808] = {
0x80003d80,0x80003d80,0x80003d80,0x80003d80,0x80003d80,0x80003d80,0x80003d80,0x80003d80,0x80003d80,0x80003d80,0x80003d80,0x80003d80,0x80003d80,0x80003d80,0x80003d80,0x80003d80,
0x80003d80,0x80003d80,0x80003d80,0x80003d80,0x80003d80,0x80003d80,0x80003d80,0x80003d80,0x80003d80,0x80003d80,0x80003d80,0x80003d80,0x80003d80,0x80003d80,0x80003d80,0x80003d80,
0x3c483d7b,0x3d0e3d55,0x3d553d0e,0x3d7b3c48,0x80003d80,0x3cc43d6d,0x3d353d35,0x3d6d3cc4,0x3d7bbc48,0x3d55bd0e,0x3d0ebd55,0x3c48bd7b,0x3d800000,0x3d6dbcc4,0x3d35bd35,0x3cc4bd6d,
0xbc48bd7b,0xbd0ebd55,0xbd55bd0e,0xbd7bbc48,0x8000bd80,0xbcc4bd6d,0xbd35bd35,0xbd6dbcc4,0xbd7b3c48,0xbd553d0e,0xbd0e3d55,0xbc483d7b,0xbd800000,0xbd6d3cc4,0xbd353d35,0xbcc43d6d,
0x8000bd80,0xbd35bd35,0xbd800000,0xbd353d35,0xbcc4bd6d,0xbd6dbcc4,0xbd6d3cc4,0xbcc43d6d,0x80003d80,0x3d353d35,0x3d800000,0x3d35bd35,0x3cc43d6d,0x3d6d3cc4,0x3d6dbcc4,0x3cc4bd6d,
0x8000bd80,0xbd35bd35,0xbd800000,0xbd353d35,0xbcc4bd6d,0xbd6dbcc4,0xbd6d3cc4,0xbcc43d6d,0x80003d80,0x3d353d35,0x3d800000,0x3d35bd35,0x3cc43d6d,0x3d6d3cc4,0x3d6dbcc4,0x3cc4bd6d,
0xbd553d0e,0x3c483d7b,0x3d7b3c48,0x3d0ebd55,0xbd800000,0xbcc43d6d,0x3d353d35,0x3d6dbcc4,0x3d0e3d55,0x3d7bbc48,0x3c48bd7b,0xbd55bd0e,0x80003d80,0x3d6d3cc4,0x3d35bd35,0xbcc4bd6d,
0x3d55bd0e,0xbc48bd7b,0xbd7bbc48,0xbd0e3d55,0x3d800000,0x3cc4bd6d,0xbd35bd35,0xbd6d3cc4,0xbd0ebd55,0xbd7b3c48,0xbc483d7b,0x3d553d0e,0x8000bd80,0xbd6dbcc4,0xbd353d35,0x3cc43d6d,
0x80003d80,0x3d800000,0x8000bd80,0xbd800000,0x3d353d35,0x3d35bd35,0xbd35bd35,0xbd353d35,0x80003d80,0x3d800000,0x8000bd80,0xbd800000,0x3d353d35,0x3d35bd35,0xbd35bd35,0xbd353d35,
0x80003d80,0x3d800000,0x8000bd80,0xbd800000,0x3d353d35,0x3d35bd35,0xbd35bd35,0xbd353d35,0x80003d80,0x3d800000,0x8000bd80,0xbd800000,0x3d353d35,0x3d35bd35,0xbd35bd35,0xbd353d35,
0xbd55bd0e,0xbc483d7b,0x3d7bbc48,0xbd0ebd55,0x8000bd80,0xbd6d3cc4,0x3d353d35,0x3cc4bd6d,0xbd0e3d55,0x3d7b3c48,0xbc48bd7b,0xbd553d0e,0xbd800000,0x3cc43d6d,0x3d35bd35,0xbd6dbcc4,
0x3d553d0e,0x3c48bd7b,0xbd7b3c48,0x3d0e3d55,0x80003d80,0x3d6dbcc4,0xbd35bd35,0xbcc43d6d,0x3d0ebd55,0xbd7bbc48,0x3c483d7b,0x3d55bd0e,0x3d800000,0xbcc4bd6d,0xbd353d35,0x3d6d3cc4,
0x8000bd80,0xbd353d35,0x3d800000,0xbd35bd35,0xbd6dbcc4,0x3cc43d6d,0x3cc4bd6d,0xbd6d3cc4,0x80003d80,0x3d35bd35,0xbd800000,0x3d353d35,0x3d6d3cc4,0xbcc4bd6d,0xbcc43d6d,0x3d6dbcc4,
0x8000bd80,0xbd353d35,0x3d800000,0xbd35bd35,0xbd6dbcc4,0x3cc43d6d,0x3cc4bd6d,0xbd6d3cc4,0x80003d80,0x3d35bd35,0xbd800000,0x3d353d35,0x3d6d3cc4,0xbcc4bd6d,0xbcc43d6d,0x3d6dbcc4,
0x3c48bd7b,0xbd0e3d55,0x3d55bd0e,0xbd7b3c48,0x3d800000,0xbd6dbcc4,0x3d353d35,0xbcc4bd6d,0xbd7bbc48,0x3d553d0e,0xbd0ebd55,0x3c483d7b,0x8000bd80,0xbcc43d6d,0x3d35bd35,0xbd6d3cc4,
0xbc483d7b,0x3d0ebd55,0xbd553d0e,0x3d7bbc48,0xbd800000,0x3d6d3cc4,0xbd35bd35,0x3cc43d6d,0x3d7b3c48,0xbd55bd0e,0x3d0e3d55,0xbc48bd7b,0x80003d80,0x3cc4bd6d,0xbd353d35,0x3d6dbcc4,
0x3d800000,0x3d800000,0x3d800000,0x3d800000,0x3d800000,0x3d800000,0x3d800000,0x3d800000,0x3d800000,0x3d800000,0x3d800000,0x3d800000,0x3d800000,0x3d800000,0x3d800000,0x3d800000,
0x3d800000,0x3d800000,0x3d800000,0x3d800000,0x3d800000,0x3d800000,0x3d800000,0x3d800000,0x3d800000,0x3d800000,0x3d800000,0x3d800000,0x3d800000,0x3d800000,0x3d800000,0x3d800000,
0x3d7bbc48,0x3d55bd0e,0x3d0ebd55,0x3c48bd7b,0x3d800000,0x3d6dbcc4,0x3d35bd35,0x3cc4bd6d,0xbc48bd7b,0xbd0ebd55,0xbd55bd0e,0xbd7bbc48,0xbd80,0xbcc4bd6d,0xbd35bd35,0xbd6dbcc4,
0xbd7b3c48,0xbd553d0e,0xbd0e3d55,0xbc483d7b,0xbd800000,0xbd6d3cc4,0xbd353d35,0xbcc43d6d,0x3c483d7b,0x3d0e3d55,0x3d553d0e,0x3d7b3c48,0x3d80,0x3cc43d6d,0x3d353d35,0x3d6d3cc4,
0xbd800000,0xbd353d35,0x3d80,0x3d353d35,0xbd6d3cc4,0xbcc43d6d,0x3cc43d6d,0x3d6d3cc4,0x3d800000,0x3d35bd35,0xbd80,0xbd35bd35,0x3d6dbcc4,0x3cc4bd6d,0xbcc4bd6d,0xbd6dbcc4,
0xbd800000,0xbd353d35,0x3d80,0x3d353d35,0xbd6d3cc4,0xbcc43d6d,0x3cc43d6d,0x3d6d3cc4,0x3d800000,0x3d35bd35,0xbd80,0xbd35bd35,0x3d6dbcc4,0x3cc4bd6d,0xbcc4bd6d,0xbd6dbcc4,
0x3d0e3d55,0x3d7bbc48,0x3c48bd7b,0xbd55bd0e,0x3d80,0x3d6d3cc4,0x3d35bd35,0xbcc4bd6d,0x3d55bd0e,0xbc48bd7b,0xbd7bbc48,0xbd0e3d55,0x3d800000,0x3cc4bd6d,0xbd35bd35,0xbd6d3cc4,
0xbd0ebd55,0xbd7b3c48,0xbc483d7b,0x3d553d0e,0xbd80,0xbd6dbcc4,0xbd353d35,0x3cc43d6d,0xbd553d0e,0x3c483d7b,0x3d7b3c48,0x3d0ebd55,0xbd800000,0xbcc43d6d,0x3d353d35,0x3d6dbcc4,
0x3d800000,0xbd80,0xbd800000,0x3d80,0x3d35bd35,0xbd35bd35,0xbd353d35,0x3d353d35,0x3d800000,0xbd80,0xbd800000,0x3d80,0x3d35bd35,0xbd35bd35,0xbd353d35,0x3d353d35,
0x3d800000,0xbd80,0xbd800000,0x3d80,0x3d35bd35,0xbd35bd35,0xbd353d35,0x3d353d35,0x3d800000,0xbd80,0xbd800000,0x3d80,0x3d35bd35,0xbd35bd35,0xbd353d35,0x3d353d35,
0xbd0e3d55,0x3d7b3c48,0xbc48bd7b,0xbd553d0e,0xbd800000,0x3cc43d6d,0x3d35bd35,0xbd6dbcc4,0x3d553d0e,0x3c48bd7b,0xbd7b3c48,0x3d0e3d55,0x3d80,0x3d6dbcc4,0xbd35bd35,0xbcc43d6d,
0x3d0ebd55,0xbd7bbc48,0x3c483d7b,0x3d55bd0e,0x3d800000,0xbcc4bd6d,0xbd353d35,0x3d6d3cc4,0xbd55bd0e,0xbc483d7b,0x3d7bbc48,0xbd0ebd55,0xbd80,0xbd6d3cc4,0x3d353d35,0x3cc4bd6d,
0xbd800000,0x3d353d35,0xbd80,0xbd353d35,0xbcc43d6d,0x3d6dbcc4,0xbd6dbcc4,0x3cc43d6d,0x3d800000,0xbd35bd35,0x3d80,0x3d35bd35,0x3cc4bd6d,0xbd6d3cc4,0x3d6d3cc4,0xbcc4bd6d,
0xbd800000,0x3d353d35,0xbd80,0xbd353d35,0xbcc43d6d,0x3d6dbcc4,0xbd6dbcc4,0x3cc43d6d,0x3d800000,0xbd35bd35,0x3d80,0x3d35bd35,0x3cc4bd6d,0xbd6d3cc4,0x3d6d3cc4,0xbcc4bd6d,
0xbd7bbc48,0x3d553d0e,0xbd0ebd55,0x3c483d7b,0xbd80,0xbcc43d6d,0x3d35bd35,0xbd6d3cc4,0xbc483d7b,0x3d0ebd55,0xbd553d0e,0x3d7bbc48,0xbd800000,0x3d6d3cc4,0xbd35bd35,0x3cc43d6d,
0x3d7b3c48,0xbd55bd0e,0x3d0e3d55,0xbc48bd7b,0x3d80,0x3cc4bd6d,0xbd353d35,0x3d6dbcc4,0x3c48bd7b,0xbd0e3d55,0x3d55bd0e,0xbd7b3c48,0x3d800000,0xbd6dbcc4,0x3d353d35,0xbcc4bd6d,
0x80003d80,0x8000bd80,0x80003d80,0x8000bd80,0x3d800000,0xbd800000,0x3d800000,0xbd800000,0x80003d80,0x8000bd80,0x80003d80,0x8000bd80,0x3d800000,0xbd800000,0x3d800000,0xbd800000,
0x80003d80,0x8000bd80,0x80003d80,0x8000bd80,0x3d800000,0xbd800000,0x3d800000,0xbd800000,0x80003d80,0x8000bd80,0x80003d80,0x8000bd80,0x3d800000,0xbd800000,0x3d800000,0xbd800000,
0x3d7bbc48,0xbd553d0e,0x3d0ebd55,0xbc483d7b,0x80003d80,0xbcc4bd6d,0x3d353d35,0xbd6dbcc4,0xbc48bd7b,0x3d0e3d55,0xbd55bd0e,0x3d7b3c48,0x3d800000,0xbd6d3cc4,0x3d35bd35,0xbcc43d6d,
0xbd7b3c48,0x3d55bd0e,0xbd0e3d55,0x3c48bd7b,0x8000bd80,0x3cc43d6d,0xbd35bd35,0x3d6d3cc4,0x3c483d7b,0xbd0ebd55,0x3d553d0e,0xbd7bbc48,0xbd800000,0x3d6dbcc4,0xbd353d35,0x3cc4bd6d,
0x8000bd80,0x3d353d35,0xbd800000,0x3d35bd35,0xbd6d3cc4,0x3cc4bd6d,0x3cc43d6d,0xbd6dbcc4,0x80003d80,0xbd35bd35,0x3d800000,0xbd353d35,0x3d6dbcc4,0xbcc43d6d,0xbcc4bd6d,0x3d6d3cc4,
0x8000bd80,0x3d353d35,0xbd800000,0x3d35bd35,0xbd6d3cc4,0x3cc4bd6d,0x3cc43d6d,0xbd6dbcc4,0x80003d80,0xbd35bd35,0x3d800000,0xbd353d35,0x3d6dbcc4,0xbcc43d6d,0xbcc4bd6d,0x3d6d3cc4,
0x3d0e3d55,0xbd7b3c48,0x3c48bd7b,0x3d553d0e,0xbd800000,0x3cc4bd6d,0x3d353d35,0xbd6d3cc4,0x3d55bd0e,0x3c483d7b,0xbd7bbc48,0x3d0ebd55,0x80003d80,0xbd6dbcc4,0x3d35bd35,0x3cc43d6d,
0xbd0ebd55,0x3d7bbc48,0xbc483d7b,0xbd55bd0e,0x3d800000,0xbcc43d6d,0xbd35bd35,0x3d6dbcc4,0xbd553d0e,0xbc48bd7b,0x3d7b3c48,0xbd0e3d55,0x8000bd80,0x3d6d3cc4,0xbd353d35,0xbcc4bd6d,
0x80003d80,0xbd800000,0x8000bd80,0x3d800000,0x3d35bd35,0x3d353d35,0xbd353d35,0xbd35bd35,0x80003d80,0xbd800000,0x8000bd80,0x3d800000,0x3d35bd35,0x3d353d35,0xbd353d35,0xbd35bd35,
0x80003d80,0xbd800000,0x8000bd80,0x3d800000,0x3d35bd35,0x3d353d35,0xbd353d35,0xbd35bd35,0x80003d80,0xbd800000,0x8000bd80,0x3d800000,0x3d35bd35,0x3d353d35,0xbd353d35,0xbd35bd35,
0xbd0e3d55,0xbd7bbc48,0xbc48bd7b,0x3d55bd0e,0x8000bd80,0x3d6dbcc4,0x3d353d35,0xbcc43d6d,0x3d553d0e,0xbc483d7b,0xbd7b3c48,0xbd0ebd55,0xbd800000,0xbcc4bd6d,0x3d35bd35,0x3d6d3cc4,
0x3d0ebd55,0x3d7b3c48,0x3c483d7b,0xbd553d0e,0x80003d80,0xbd6d3cc4,0xbd35bd35,0x3cc4bd6d,0xbd55bd0e,0x3c48bd7b,0x3d7bbc48,0x3d0e3d55,0x3d800000,0x3cc43d6d,0xbd353d35,0xbd6dbcc4,
0x8000bd80,0x3d35bd35,0x3d800000,0x3d353d35,0xbcc43d6d,0xbd6d3cc4,0xbd6dbcc4,0xbcc4bd6d,0x80003d80,0xbd353d35,0xbd800000,0xbd35bd35,0x3cc4bd6d,0x3d6dbcc4,0x3d6d3cc4,0x3cc43d6d,
0x8000bd80,0x3d35bd35,0x3d800000,0x3d353d35,0xbcc43d6d,0xbd6d3cc4,0xbd6dbcc4,0xbcc4bd6d,0x80003d80,0xbd353d35,0xbd800000,0xbd35bd35,0x3cc4bd6d,0x3d6dbcc4,0x3d6d3cc4,0x3cc43d6d,
0xbd7bbc48,0xbd55bd0e,0xbd0ebd55,0xbc48bd7b,0x3d800000,0x3d6d3cc4,0x3d353d35,0x3cc43d6d,0xbc483d7b,0xbd0e3d55,0xbd553d0e,0xbd7b3c48,0x8000bd80,0x3cc4bd6d,0x3d35bd35,0x3d6dbcc4,
0x3d7b3c48,0x3d553d0e,0x3d0e3d55,0x3c483d7b,0xbd800000,0xbd6dbcc4,0xbd35bd35,0xbcc4bd6d,0x3c48bd7b,0x3d0ebd55,0x3d55bd0e,0x3d7bbc48,0x80003d80,0xbcc43d6d,0xbd353d35,0xbd6d3cc4,
0x3d800000,0xbd800000,0x3d800000,0xbd800000,0xbd80,0x3d80,0xbd80,0x3d80,0x3d800000,0xbd800000,0x3d800000,0xbd800000,0xbd80,0x3d80,0xbd80,0x3d80,
0x3d800000,0xbd800000,0x3d800000,0xbd800000,0xbd80,0x3d80,0xbd80,0x3d80,0x3d800000,0xbd800000,0x3d800000,0xbd800000,0xbd80,0x3d80,0xbd80,0x3d80,
0xbc48bd7b,0x3d0e3d55,0xbd55bd0e,0x3d7b3c48,0x3d800000,0xbd6d3cc4,0x3d35bd35,0xbcc43d6d,0xbd7b3c48,0x3d55bd0e,0xbd0e3d55,0x3c48bd7b,0xbd80,0x3cc43d6d,0xbd35bd35,0x3d6d3cc4,
0x3c483d7b,0xbd0ebd55,0x3d553d0e,0xbd7bbc48,0xbd800000,0x3d6dbcc4,0xbd353d35,0x3cc4bd6d,0x3d7bbc48,0xbd553d0e,0x3d0ebd55,0xbc483d7b,0x3d80,0xbcc4bd6d,0x3d353d35,0xbd6dbcc4,
0xbd800000,0x3d35bd35,0x3d80,0xbd35bd35,0x3cc43d6d,0xbd6dbcc4,0x3d6dbcc4,0xbcc43d6d,0x3d800000,0xbd353d35,0xbd80,0x3d353d35,0xbcc4bd6d,0x3d6d3cc4,0xbd6d3cc4,0x3cc4bd6d,
0xbd800000,0x3d35bd35,0x3d80,0xbd35bd35,0x3cc43d6d,0xbd6dbcc4,0x3d6dbcc4,0xbcc43d6d,0x3d800000,0xbd353d35,0xbd80,0x3d353d35,0xbcc4bd6d,0x3d6d3cc4,0xbd6d3cc4,0x3cc4bd6d,
0x3d55bd0e,0x3c483d7b,0xbd7bbc48,0x3d0ebd55,0x3d80,0xbd6dbcc4,0x3d35bd35,0x3cc43d6d,0xbd0ebd55,0x3d7bbc48,0xbc483d7b,0xbd55bd0e,0x3d800000,0xbcc43d6d,0xbd35bd35,0x3d6dbcc4,
0xbd553d0e,0xbc48bd7b,0x3d7b3c48,0xbd0e3d55,0xbd80,0x3d6d3cc4,0xbd353d35,0xbcc4bd6d,0x3d0e3d55,0xbd7b3c48,0x3c48bd7b,0x3d553d0e,0xbd800000,0x3cc4bd6d,0x3d353d35,0xbd6d3cc4,
0x3d800000,0x3d80,0xbd800000,0xbd80,0xbd35bd35,0x3d35bd35,0x3d353d35,0xbd353d35,0x3d800000,0x3d80,0xbd800000,0xbd80,0xbd35bd35,0x3d35bd35,0x3d353d35,0xbd353d35,
0x3d800000,0x3d80,0xbd800000,0xbd80,0xbd35bd35,0x3d35bd35,0x3d353d35,0xbd353d35,0x3d800000,0x3d80,0xbd800000,0xbd80,0xbd35bd35,0x3d35bd35,0x3d353d35,0xbd353d35,
0x3d553d0e,0xbc483d7b,0xbd7b3c48,0xbd0ebd55,0xbd800000,0xbcc4bd6d,0x3d35bd35,0x3d6d3cc4,0x3d0ebd55,0x3d7b3c48,0x3c483d7b,0xbd553d0e,0x3d80,0xbd6d3cc4,0xbd35bd35,0x3cc4bd6d,
0xbd55bd0e,0x3c48bd7b,0x3d7bbc48,0x3d0e3d55,0x3d800000,0x3cc43d6d,0xbd353d35,0xbd6dbcc4,0xbd0e3d55,0xbd7bbc48,0xbc48bd7b,0x3d55bd0e,0xbd80,0x3d6dbcc4,0x3d353d35,0xbcc43d6d,
0xbd800000,0xbd35bd35,0xbd80,0x3d35bd35,0x3d6d3cc4,0x3cc43d6d,0xbcc43d6d,0xbd6d3cc4,0x3d800000,0x3d353d35,0x3d80,0xbd353d35,0xbd6dbcc4,0xbcc4bd6d,0x3cc4bd6d,0x3d6dbcc4,
0xbd800000,0xbd35bd35,0xbd80,0x3d35bd35,0x3d6d3cc4,0x3cc43d6d,0xbcc43d6d,0xbd6d3cc4,0x3d800000,0x3d353d35,0x3d80,0xbd353d35,0xbd6dbcc4,0xbcc4bd6d,0x3cc4bd6d,0x3d6dbcc4,
0xbc483d7b,0xbd0e3d55,0xbd553d0e,0xbd7b3c48,0xbd80,0x3cc4bd6d,0x3d35bd35,0x3d6dbcc4,0x3d7b3c48,0x3d553d0e,0x3d0e3d55,0x3c483d7b,0xbd800000,0xbd6dbcc4,0xbd35bd35,0xbcc4bd6d,
0x3c48bd7b,0x3d0ebd55,0x3d55bd0e,0x3d7bbc48,0x3d80,0xbcc43d6d,0xbd353d35,0xbd6d3cc4,0xbd7bbc48,0xbd55bd0e,0xbd0ebd55,0xbc48bd7b,0x3d800000,0x3d6d3cc4,0x3d353d35,0x3cc43d6d,
0x80003d80,0x80003d80,0x80003d80,0x80003d80,0x8000bd80,0x8000bd80,0x8000bd80,0x8000bd80,0x80003d80,0x80003d80,0x80003d80,0x80003d80,0x8000bd80,0x8000bd80,0x8000bd80,0x8000bd80,
0x80003d80,0x80003d80,0x80003d80,0x80003d80,0x8000bd80,0x8000bd80,0x8000bd80,0x8000bd80,0x80003d80,0x80003d80,0x80003d80,0x80003d80,0x8000bd80,0x8000bd80,0x8000bd80,0x8000bd80,
0xbc48bd7b,0xbd0ebd55,0xbd55bd0e,0xbd7bbc48,0x80003d80,0x3cc43d6d,0x3d353d35,0x3d6d3cc4,0xbd7b3c48,0xbd553d0e,0xbd0e3d55,0xbc483d7b,0x3d800000,0x3d6dbcc4,0x3d35bd35,0x3cc4bd6d,
0x3c483d7b,0x3d0e3d55,0x3d553d0e,0x3d7b3c48,0x8000bd80,0xbcc4bd6d,0xbd35bd35,0xbd6dbcc4,0x3d7bbc48,0x3d55bd0e,0x3d0ebd55,0x3c48bd7b,0xbd800000,0xbd6d3cc4,0xbd353d35,0xbcc43d6d,
0x8000bd80,0xbd35bd35,0xbd800000,0xbd353d35,0x3cc43d6d,0x3d6d3cc4,0x3d6dbcc4,0x3cc4bd6d,0x80003d80,0x3d353d35,0x3d800000,0x3d35bd35,0xbcc4bd6d,0xbd6dbcc4,0xbd6d3cc4,0xbcc43d6d,
0x8000bd80,0xbd35bd35,0xbd800000,0xbd353d35,0x3cc43d6d,0x3d6d3cc4,0x3d6dbcc4,0x3cc4bd6d,0x80003d80,0x3d353d35,0x3d800000,0x3d35bd35,0xbcc4bd6d,0xbd6dbcc4,0xbd6d3cc4,0xbcc43d6d,
0x3d55bd0e,0xbc48bd7b,0xbd7bbc48,0xbd0e3d55,0xbd800000,0xbcc43d6d,0x3d353d35,0x3d6dbcc4,0xbd0ebd55,0xbd7b3c48,0xbc483d7b,0x3d553d0e,0x80003d80,0x3d6d3cc4,0x3d35bd35,0xbcc4bd6d,
0xbd553d0e,0x3c483d7b,0x3d7b3c48,0x3d0ebd55,0x3d800000,0x3cc4bd6d,0xbd35bd35,0xbd6d3cc4,0x3d0e3d55,0x3d7bbc48,0x3c48bd7b,0xbd55bd0e,0x8000bd80,0xbd6dbcc4,0xbd353d35,0x3cc43d6d,
0x80003d80,0x3d800000,0x8000bd80,0xbd800000,0xbd35bd35,0xbd353d35,0x3d353d35,0x3d35bd35,0x80003d80,0x3d800000,0x8000bd80,0xbd800000,0xbd35bd35,0xbd353d35,0x3d353d35,0x3d35bd35,
0x80003d80,0x3d800000,0x8000bd80,0xbd800000,0xbd35bd35,0xbd353d35,0x3d353d35,0x3d35bd35,0x80003d80,0x3d800000,0x8000bd80,0xbd800000,0xbd35bd35,0xbd353d35,0x3d353d35,0x3d35bd35,
0x3d553d0e,0x3c48bd7b,0xbd7b3c48,0x3d0e3d55,0x8000bd80,0xbd6d3cc4,0x3d353d35,0x3cc4bd6d,0x3d0ebd55,0xbd7bbc48,0x3c483d7b,0x3d55bd0e,0xbd800000,0x3cc43d6d,0x3d35bd35,0xbd6dbcc4,
0xbd55bd0e,0xbc483d7b,0x3d7bbc48,0xbd0ebd55,0x80003d80,0x3d6dbcc4,0xbd35bd35,0xbcc43d6d,0xbd0e3d55,0x3d7b3c48,0xbc48bd7b,0xbd553d0e,0x3d800000,0xbcc4bd6d,0xbd353d35,0x3d6d3cc4,
0x8000bd80,0xbd353d35,0x3d800000,0xbd35bd35,0x3d6d3cc4,0xbcc4bd6d,0xbcc43d6d,0x3d6dbcc4,0x80003d80,0x3d35bd35,0xbd800000,0x3d353d35,0xbd6dbcc4,0x3cc43d6d,0x3cc4bd6d,0xbd6d3cc4,
0x8000bd80,0xbd353d35,0x3d800000,0xbd35bd35,0x3d6d3cc4,0xbcc4bd6d,0xbcc43d6d,0x3d6dbcc4,0x80003d80,0x3d35bd35,0xbd800000,0x3d353d35,0xbd6dbcc4,0x3cc43d6d,0x3cc4bd6d,0xbd6d3cc4,
0xbc483d7b,0x3d0ebd55,0xbd553d0e,0x3d7bbc48,0x3d800000,0xbd6dbcc4,0x3d353d35,0xbcc4bd6d,0x3d7b3c48,0xbd55bd0e,0x3d0e3d55,0xbc48bd7b,0x8000bd80,0xbcc43d6d,0x3d35bd35,0xbd6d3cc4,
0x3c48bd7b,0xbd0e3d55,0x3d55bd0e,0xbd7b3c48,0xbd800000,0x3d6d3cc4,0xbd35bd35,0x3cc43d6d,0xbd7bbc48,0x3d553d0e,0xbd0ebd55,0x3c483d7b,0x80003d80,0x3cc4bd6d,0xbd353d35,0x3d6dbcc4,
0x3d800000,0x3d800000,0x3d800000,0x3d800000,0xbd800000,0xbd800000,0xbd800000,0xbd800000,0x3d800000,0x3d800000,0x3d800000,0x3d800000,0xbd800000,0xbd800000,0xbd800000,0xbd800000,
0x3d800000,0x3d800000,0x3d800000,0x3d800000,0xbd800000,0xbd800000,0xbd800000,0xbd800000,0x3d800000,0x3d800000,0x3d800000,0x3d800000,0xbd800000,0xbd800000,0xbd800000,0xbd800000,
0xbd7b3c48,0xbd553d0e,0xbd0e3d55,0xbc483d7b,0x3d800000,0x3d6dbcc4,0x3d35bd35,0x3cc4bd6d,0x3c483d7b,0x3d0e3d55,0x3d553d0e,0x3d7b3c48,0xbd80,0xbcc4bd6d,0xbd35bd35,0xbd6dbcc4,
0x3d7bbc48,0x3d55bd0e,0x3d0ebd55,0x3c48bd7b,0xbd800000,0xbd6d3cc4,0xbd353d35,0xbcc43d6d,0xbc48bd7b,0xbd0ebd55,0xbd55bd0e,0xbd7bbc48,0x3d80,0x3cc43d6d,0x3d353d35,0x3d6d3cc4,
0xbd800000,0xbd353d35,0x3d80,0x3d353d35,0x3d6dbcc4,0x3cc4bd6d,0xbcc4bd6d,0xbd6dbcc4,0x3d800000,0x3d35bd35,0xbd80,0xbd35bd35,0xbd6d3cc4,0xbcc43d6d,0x3cc43d6d,0x3d6d3cc4,
0xbd800000,0xbd353d35,0x3d80,0x3d353d35,0x3d6dbcc4,0x3cc4bd6d,0xbcc4bd6d,0xbd6dbcc4,0x3d800000,0x3d35bd35,0xbd80,0xbd35bd35,0xbd6d3cc4,0xbcc43d6d,0x3cc43d6d,0x3d6d3cc4,
0xbd0ebd55,0xbd7b3c48,0xbc483d7b,0x3d553d0e,0x3d80,0x3d6d3cc4,0x3d35bd35,0xbcc4bd6d,0xbd553d0e,0x3c483d7b,0x3d7b3c48,0x3d0ebd55,0x3d800000,0x3cc4bd6d,0xbd35bd35,0xbd6d3cc4,
0x3d0e3d55,0x3d7bbc48,0x3c48bd7b,0xbd55bd0e,0xbd80,0xbd6dbcc4,0xbd353d35,0x3cc43d6d,0x3d55bd0e,0xbc48bd7b,0xbd7bbc48,0xbd0e3d55,0xbd800000,0xbcc43d6d,0x3d353d35,0x3d6dbcc4,
0x3d800000,0xbd80,0xbd800000,0x3d80,0xbd353d35,0x3d353d35,0x3d35bd35,0xbd35bd35,0x3d800000,0xbd80,0xbd800000,0x3d80,0xbd353d35,0x3d353d35,0x3d35bd35,0xbd35bd35,
0x3d800000,0xbd80,0xbd800000,0x3d80,0xbd353d35,0x3d353d35,0x3d35bd35,0xbd35bd35,0x3d800000,0xbd80,0xbd800000,0x3d80,0xbd353d35,0x3d353d35,0x3d35bd35,0xbd35bd35,
0x3d0ebd55,0xbd7bbc48,0x3c483d7b,0x3d55bd0e,0xbd800000,0x3cc43d6d,0x3d35bd35,0xbd6dbcc4,0xbd55bd0e,0xbc483d7b,0x3d7bbc48,0xbd0ebd55,0x3d80,0x3d6dbcc4,0xbd35bd35,0xbcc43d6d,
0xbd0e3d55,0x3d7b3c48,0xbc48bd7b,0xbd553d0e,0x3d800000,0xbcc4bd6d,0xbd353d35,0x3d6d3cc4,0x3d553d0e,0x3c48bd7b,0xbd7b3c48,0x3d0e3d55,0xbd80,0xbd6d3cc4,0x3d353d35,0x3cc4bd6d,
0xbd800000,0x3d353d35,0xbd80,0xbd353d35,0x3cc4bd6d,0xbd6d3cc4,0x3d6d3cc4,0xbcc4bd6d,0x3d800000,0xbd35bd35,0x3d80,0x3d35bd35,0xbcc43d6d,0x3d6dbcc4,0xbd6dbcc4,0x3cc43d6d,
0xbd800000,0x3d353d35,0xbd80,0xbd353d35,0x3cc4bd6d,0xbd6d3cc4,0x3d6d3cc4,0xbcc4bd6d,0x3d800000,0xbd35bd35,0x3d80,0x3d35bd35,0xbcc43d6d,0x3d6dbcc4,0xbd6dbcc4,0x3cc43d6d,
0x3d7b3c48,0xbd55bd0e,0x3d0e3d55,0xbc48bd7b,0xbd80,0xbcc43d6d,0x3d35bd35,0xbd6d3cc4,0x3c48bd7b,0xbd0e3d55,0x3d55bd0e,0xbd7b3c48,0xbd800000,0x3d6d3cc4,0xbd35bd35,0x3cc43d6d,
0xbd7bbc48,0x3d553d0e,0xbd0ebd55,0x3c483d7b,0x3d80,0x3cc4bd6d,0xbd353d35,0x3d6dbcc4,0xbc483d7b,0x3d0ebd55,0xbd553d0e,0x3d7bbc48,0x3d800000,0xbd6dbcc4,0x3d353d35,0xbcc4bd6d,
0x80003d80,0x8000bd80,0x80003d80,0x8000bd80,0xbd800000,0x3d800000,0xbd800000,0x3d800000,0x80003d80,0x8000bd80,0x80003d80,0x8000bd80,0xbd800000,0x3d800000,0xbd800000,0x3d800000,
0x80003d80,0x8000bd80,0x80003d80,0x8000bd80,0xbd800000,0x3d800000,0xbd800000,0x3d800000,0x80003d80,0x8000bd80,0x80003d80,0x8000bd80,0xbd800000,0x3d800000,0xbd800000,0x3d800000,
0xbd7b3c48,0x3d55bd0e,0xbd0e3d55,0x3c48bd7b,0x80003d80,0xbcc4bd6d,0x3d353d35,0xbd6dbcc4,0x3c483d7b,0xbd0ebd55,0x3d553d0e,0xbd7bbc48,0x3d800000,0xbd6d3cc4,0x3d35bd35,0xbcc43d6d,
0x3d7bbc48,0xbd553d0e,0x3d0ebd55,0xbc483d7b,0x8000bd80,0x3cc43d6d,0xbd35bd35,0x3d6d3cc4,0xbc48bd7b,0x3d0e3d55,0xbd55bd0e,0x3d7b3c48,0xbd800000,0x3d6dbcc4,0xbd353d35,0x3cc4bd6d,
0x8000bd80,0x3d353d35,0xbd800000,0x3d35bd35,0x3d6dbcc4,0xbcc43d6d,0xbcc4bd6d,0x3d6d3cc4,0x80003d80,0xbd35bd35,0x3d800000,0xbd353d35,0xbd6d3cc4,0x3cc4bd6d,0x3cc43d6d,0xbd6dbcc4,
0x8000bd80,0x3d353d35,0xbd800000,0x3d35bd35,0x3d6dbcc4,0xbcc43d6d,0xbcc4bd6d,0x3d6d3cc4,0x80003d80,0xbd35bd35,0x3d800000,0xbd353d35,0xbd6d3cc4,0x3cc4bd6d,0x3cc43d6d,0xbd6dbcc4,
0xbd0ebd55,0x3d7bbc48,0xbc483d7b,0xbd55bd0e,0xbd800000,0x3cc4bd6d,0x3d353d35,0xbd6d3cc4,0xbd553d0e,0xbc48bd7b,0x3d7b3c48,0xbd0e3d55,0x80003d80,0xbd6dbcc4,0x3d35bd35,0x3cc43d6d,
0x3d0e3d55,0xbd7b3c48,0x3c48bd7b,0x3d553d0e,0x3d800000,0xbcc43d6d,0xbd35bd35,0x3d6dbcc4,0x3d55bd0e,0x3c483d7b,0xbd7bbc48,0x3d0ebd55,0x8000bd80,0x3d6d3cc4,0xbd353d35,0xbcc4bd6d,
0x80003d80,0xbd800000,0x8000bd80,0x3d800000,0xbd353d35,0xbd35bd35,0x3d35bd35,0x3d353d35,0x80003d80,0xbd800000,0x8000bd80,0x3d800000,0xbd353d35,0xbd35bd35,0x3d35bd35,0x3d353d35,
0x80003d80,0xbd800000,0x8000bd80,0x3d800000,0xbd353d35,0xbd35bd35,0x3d35bd35,0x3d353d35,0x80003d80,0xbd800000,0x8000bd80,0x3d800000,0xbd353d35,0xbd35bd35,0x3d35bd35,0x3d353d35,
0x3d0ebd55,0x3d7b3c48,0x3c483d7b,0xbd553d0e,0x8000bd80,0x3d6dbcc4,0x3d353d35,0xbcc43d6d,0xbd55bd0e,0x3c48bd7b,0x3d7bbc48,0x3d0e3d55,0xbd800000,0xbcc4bd6d,0x3d35bd35,0x3d6d3cc4,
0xbd0e3d55,0xbd7bbc48,0xbc48bd7b,0x3d55bd0e,0x80003d80,0xbd6d3cc4,0xbd35bd35,0x3cc4bd6d,0x3d553d0e,0xbc483d7b,0xbd7b3c48,0xbd0ebd55,0x3d800000,0x3cc43d6d,0xbd353d35,0xbd6dbcc4,
0x8000bd80,0x3d35bd35,0x3d800000,0x3d353d35,0x3cc4bd6d,0x3d6dbcc4,0x3d6d3cc4,0x3cc43d6d,0x80003d80,0xbd353d35,0xbd800000,0xbd35bd35,0xbcc43d6d,0xbd6d3cc4,0xbd6dbcc4,0xbcc4bd6d,
0x8000bd80,0x3d35bd35,0x3d800000,0x3d353d35,0x3cc4bd6d,0x3d6dbcc4,0x3d6d3cc4,0x3cc43d6d,0x80003d80,0xbd353d35,0xbd800000,0xbd35bd35,0xbcc43d6d,0xbd6d3cc4,0xbd6dbcc4,0xbcc4bd6d,
0x3d7b3c48,0x3d553d0e,0x3d0e3d55,0x3c483d7b,0x3d800000,0x3d6d3cc4,0x3d353d35,0x3cc43d6d,0x3c48bd7b,0x3d0ebd55,0x3d55bd0e,0x3d7bbc48,0x8000bd80,0x3cc4bd6d,0x3d35bd35,0x3d6dbcc4,
0xbd7bbc48,0xbd55bd0e,0xbd0ebd55,0xbc48bd7b,0xbd800000,0xbd6dbcc4,0xbd35bd35,0xbcc4bd6d,0xbc483d7b,0xbd0e3d55,0xbd553d0e,0xbd7b3c48,0x80003d80,0xbcc43d6d,0xbd353d35,0xbd6d3cc4,
0x3d800000,0xbd800000,0x3d800000,0xbd800000,0x3d80,0xbd80,0x3d80,0xbd80,0x3d800000,0xbd800000,0x3d800000,0xbd800000,0x3d80,0xbd80,0x3d80,0xbd80,
0x3d800000,0xbd800000,0x3d800000,0xbd800000,0x3d80,0xbd80,0x3d80,0xbd80,0x3d800000,0xbd800000,0x3d800000,0xbd800000,0x3d80,0xbd80,0x3d80,0xbd80,
0x3c483d7b,0xbd0ebd55,0x3d553d0e,0xbd7bbc48,0x3d800000,0xbd6d3cc4,0x3d35bd35,0xbcc43d6d,0x3d7bbc48,0xbd553d0e,0x3d0ebd55,0xbc483d7b,0xbd80,0x3cc43d6d,0xbd35bd35,0x3d6d3cc4,
0xbc48bd7b,0x3d0e3d55,0xbd55bd0e,0x3d7b3c48,0xbd800000,0x3d6dbcc4,0xbd353d35,0x3cc4bd6d,0xbd7b3c48,0x3d55bd0e,0xbd0e3d55,0x3c48bd7b,0x3d80,0xbcc4bd6d,0x3d353d35,0xbd6dbcc4,
0xbd800000,0x3d35bd35,0x3d80,0xbd35bd35,0xbcc4bd6d,0x3d6d3cc4,0xbd6d3cc4,0x3cc4bd6d,0x3d800000,0xbd353d35,0xbd80,0x3d353d35,0x3cc43d6d,0xbd6dbcc4,0x3d6dbcc4,0xbcc43d6d,
0xbd800000,0x3d35bd35,0x3d80,0xbd35bd35,0xbcc4bd6d,0x3d6d3cc4,0xbd6d3cc4,0x3cc4bd6d,0x3d800000,0xbd353d35,0xbd80,0x3d353d35,0x3cc43d6d,0xbd6dbcc4,0x3d6dbcc4,0xbcc43d6d,
0xbd553d0e,0xbc48bd7b,0x3d7b3c48,0xbd0e3d55,0x3d80,0xbd6dbcc4,0x3d35bd35,0x3cc43d6d,0x3d0e3d55,0xbd7b3c48,0x3c48bd7b,0x3d553d0e,0x3d800000,0xbcc43d6d,0xbd35bd35,0x3d6dbcc4,
0x3d55bd0e,0x3c483d7b,0xbd7bbc48,0x3d0ebd55,0xbd80,0x3d6d3cc4,0xbd353d35,0xbcc4bd6d,0xbd0ebd55,0x3d7bbc48,0xbc483d7b,0xbd55bd0e,0xbd800000,0x3cc4bd6d,0x3d353d35,0xbd6d3cc4,
0x3d800000,0x3d80,0xbd800000,0xbd80,0x3d353d35,0xbd353d35,0xbd35bd35,0x3d35bd35,0x3d800000,0x3d80,0xbd800000,0xbd80,0x3d353d35,0xbd353d35,0xbd35bd35,0x3d35bd35,
0x3d800000,0x3d80,0xbd800000,0xbd80,0x3d353d35,0xbd353d35,0xbd35bd35,0x3d35bd35,0x3d800000,0x3d80,0xbd800000,0xbd80,0x3d353d35,0xbd353d35,0xbd35bd35,0x3d35bd35,
0xbd55bd0e,0x3c48bd7b,0x3d7bbc48,0x3d0e3d55,0xbd800000,0xbcc4bd6d,0x3d35bd35,0x3d6d3cc4,0xbd0e3d55,0xbd7bbc48,0xbc48bd7b,0x3d55bd0e,0x3d80,0xbd6d3cc4,0xbd35bd35,0x3cc4bd6d,
0x3d553d0e,0xbc483d7b,0xbd7b3c48,0xbd0ebd55,0x3d800000,0x3cc43d6d,0xbd353d35,0xbd6dbcc4,0x3d0ebd55,0x3d7b3c48,0x3c483d7b,0xbd553d0e,0xbd80,0x3d6dbcc4,0x3d353d35,0xbcc43d6d,
0xbd800000,0xbd35bd35,0xbd80,0x3d35bd35,0xbd6dbcc4,0xbcc4bd6d,0x3cc4bd6d,0x3d6dbcc4,0x3d800000,0x3d353d35,0x3d80,0xbd353d35,0x3d6d3cc4,0x3cc43d6d,0xbcc43d6d,0xbd6d3cc4,
0xbd800000,0xbd35bd35,0xbd80,0x3d35bd35,0xbd6dbcc4,0xbcc4bd6d,0x3cc4bd6d,0x3d6dbcc4,0x3d800000,0x3d353d35,0x3d80,0xbd353d35,0x3d6d3cc4,0x3cc43d6d,0xbcc43d6d,0xbd6d3cc4,
0x3c48bd7b,0x3d0ebd55,0x3d55bd0e,0x3d7bbc48,0xbd80,0x3cc4bd6d,0x3d35bd35,0x3d6dbcc4,0xbd7bbc48,0xbd55bd0e,0xbd0ebd55,0xbc48bd7b,0xbd800000,0xbd6dbcc4,0xbd35bd35,0xbcc4bd6d,
0xbc483d7b,0xbd0e3d55,0xbd553d0e,0xbd7b3c48,0x3d80,0xbcc43d6d,0xbd353d35,0xbd6d3cc4,0x3d7b3c48,0x3d553d0e,0x3d0e3d55,0x3c483d7b,0x3d800000,0x3d6d3cc4,0x3d353d35,0x3cc43d6d,
0x3f003f00,0xbf003f00,0x3f003f00,0xbf003f00,0x3f003f00,0xbf003f00,0x3f003f00,0xbf003f00,0x3f003f00,0xbf003f00,0x3f003f00,0xbf003f00,0x3f003f00,0xbf003f00,0x3f003f00,0xbf003f00,
0x3eff3f00,0xbd490000,0x3ea23eb5,0xbec6beb5,0x3ef53efb,0xbe15bdc8,0x3e713e8e,0xbee2bed5,0x3ee23eed,0xbe71be44,0x3e153e44,0xbef5beed,0x3ec63ed5,0xbea2be8e,0x3d493dc8,0xbeffbefb,
0x3efb3f00,0xbdc80000,0xbdc80000,0xbefbbf00,0x3ed53eed,0xbe8ebe44,0xbe8ebe44,0xbed5beed,0x3e8e3eb5,0xbed5beb5,0xbed5beb5,0xbe8ebeb5,0x3dc83e44,0xbefbbeed,0xbefbbeed,0xbdc8be44,
0x3ef53f00,0xbe150000,0xbee2beb5,0xbe71beb5,0x3ea23ed5,0xbec6be8e,0xbeffbefb,0x3d49bdc8,0x3d493e44,0xbeffbeed,0xbec6beed,0x3ea23e44,0xbe71bdc8,0xbee2befb,0xbe15be8e,0x3ef53ed5,
0x3eed3f00,0xbe440000,0xbeedbf00,0x3e440000,0x3e443eb5,0xbeedbeb5,0xbe44beb5,0x3eed3eb5,0xbe440000,0xbeedbf00,0x3e440000,0x3eed3f00,0xbeedbeb5,0xbe44beb5,0x3eed3eb5,0x3e443eb5,
0x3ee23f00,0xbe710000,0xbe15beb5,0x3ef53eb5,0x3d493e8e,0xbeffbed5,0x3ea23dc8,0x3ec63efb,0xbec6be44,0xbea2beed,0x3eff3eed,0xbd493e44,0xbef5befb,0x3e15bdc8,0x3e713ed5,0xbee2be8e,
0x3ed53f00,0xbe8e0000,0x3e8e0000,0x3ed53f00,0xbdc83e44,0xbefbbeed,0x3efb3eed,0xbdc83e44,0xbefbbeb5,0xbdc8beb5,0x3dc83eb5,0xbefbbeb5,0xbe8ebeed,0x3ed53e44,0xbed5be44,0xbe8ebeed,
0x3ec63f00,0xbea20000,0x3eff3eb5,0x3d493eb5,0xbe713dc8,0xbee2befb,0x3e153ed5,0xbef5be8e,0xbef5beed,0x3e15be44,0xbee2be44,0xbe71beed,0x3d49be8e,0x3eff3ed5,0xbea2befb,0x3ec63dc8,
0x3eb53f00,0xbeb50000,0x3eb53f00,0xbeb50000,0xbeb50000,0xbeb5bf00,0xbeb50000,0xbeb5bf00,0xbeb5bf00,0x3eb50000,0xbeb5bf00,0x3eb50000,0x3eb50000,0x3eb53f00,0x3eb50000,0x3eb53f00,
0x3ea23f00,0xbec60000,0xbd493eb5,0xbeffbeb5,0xbee2bdc8,0xbe71befb,0xbef5bed5,0x3e15be8e,0xbe15beed,0x3ef53e44,0x3e71be44,0x3ee23eed,0x3eff3e8e,0x3d493ed5,0x3ec63efb,0xbea23dc8,
0x3e8e3f00,0xbed50000,0xbed50000,0xbe8ebf00,0xbefbbe44,0xbdc8beed,0xbdc8beed,0x3efb3e44,0x3dc8beb5,0x3efb3eb5,0x3efb3eb5,0xbdc83eb5,0x3ed53eed,0xbe8e3e44,0xbe8e3e44,0xbed5beed,
0x3e713f00,0xbee20000,0xbef5beb5,0x3e15beb5,0xbeffbe8e,0x3d49bed5,0x3ec6bdc8,0x3ea23efb,0x3ea2be44,0x3ec63eed,0x3d493eed,0xbeffbe44,0x3e153efb,0xbef5bdc8,0xbee2bed5,0x3e71be8e,
0x3e443f00,0xbeed0000,0xbe44bf00,0x3eed0000,0xbeedbeb5,0x3e44beb5,0x3eed3eb5,0xbe443eb5,0x3eed0000,0x3e443f00,0xbeed0000,0xbe44bf00,0xbe443eb5,0xbeedbeb5,0x3e44beb5,0x3eed3eb5,
0x3e153f00,0xbef50000,0x3e71beb5,0x3ee23eb5,0xbec6bed5,0x3ea2be8e,0x3d493efb,0xbeffbdc8,0x3eff3e44,0xbd493eed,0xbea2beed,0x3ec6be44,0xbee23dc8,0xbe71befb,0x3ef53e8e,0xbe153ed5,
0x3dc83f00,0xbefb0000,0x3efb0000,0x3dc83f00,0xbe8ebeed,0x3ed5be44,0xbed53e44,0xbe8ebeed,0x3ed53eb5,0xbe8e3eb5,0x3e8ebeb5,0x3ed53eb5,0xbefbbe44,0x3dc8beed,0xbdc83eed,0xbefbbe44,
0x3d493f00,0xbeff0000,0x3ec63eb5,0xbea23eb5,0xbe15befb,0x3ef5bdc8,0xbee2be8e,0x3e71bed5,0x3e713eed,0xbee23e44,0x3ef53e44,0xbe153eed,0xbea2bed5,0x3ec6be8e,0xbeffbdc8,0x3d49befb,
0x3f00,0xbf000000,0x3f00,0xbf000000,0xbf00,0x3f000000,0xbf00,0x3f000000,0x3f00,0xbf000000,0x3f00,0xbf000000,0xbf00,0x3f000000,0xbf00,0x3f000000,
0xbd493f00,0xbeff0000,0xbec63eb5,0xbea2beb5,0x3e15befb,0x3ef53dc8,0x3ee2be8e,0x3e713ed5,0xbe713eed,0xbee2be44,0xbef53e44,0xbe15beed,0x3ea2bed5,0x3ec63e8e,0x3effbdc8,0x3d493efb,
0xbdc83f00,0xbefb0000,0xbefb0000,0x3dc8bf00,0x3e8ebeed,0x3ed53e44,0x3ed53e44,0xbe8e3eed,0xbed53eb5,0xbe8ebeb5,0xbe8ebeb5,0x3ed5beb5,0x3efbbe44,0x3dc83eed,0x3dc83eed,0xbefb3e44,
0xbe153f00,0xbef50000,0xbe71beb5,0x3ee2beb5,0x3ec6bed5,0x3ea23e8e,0xbd493efb,0xbeff3dc8,0xbeff3e44,0xbd49beed,0x3ea2beed,0x3ec63e44,0x3ee23dc8,0xbe713efb,0xbef53e8e,0xbe15bed5,
0xbe443f00,0xbeed0000,0x3e44bf00,0x3eed0000,0x3eedbeb5,0x3e443eb5,0xbeed3eb5,0xbe44beb5,0xbeed0000,0x3e44bf00,0x3eed0000,0xbe443f00,0x3e443eb5,0xbeed3eb5,0xbe44beb5,0x3eedbeb5,
0xbe713f00,0xbee20000,0x3ef5beb5,0x3e153eb5,0x3effbe8e,0x3d493ed5,0xbec6bdc8,0x3ea2befb,0xbea2be44,0x3ec6beed,0xbd493eed,0xbeff3e44,0xbe153efb,0xbef53dc8,0x3ee2bed5,0x3e713e8e,
0xbe8e3f00,0xbed50000,0x3ed50000,0xbe8e3f00,0x3efbbe44,0xbdc83eed,0x3dc8beed,0x3efbbe44,0xbdc8beb5,0x3efbbeb5,0xbefb3eb5,0xbdc8beb5,0xbed53eed,0xbe8ebe44,0x3e8e3e44,0xbed53eed,
0xbea23f00,0xbec60000,0x3d493eb5,0xbeff3eb5,0x3ee2bdc8,0xbe713efb,0x3ef5bed5,0x3e153e8e,0x3e15beed,0x3ef5be44,0xbe71be44,0x3ee2beed,0xbeff3e8e,0x3d49bed5,0xbec63efb,0xbea2bdc8,
0xbeb53f00,0xbeb50000,0xbeb53f00,0xbeb50000,0x3eb50000,0xbeb53f00,0x3eb50000,0xbeb53f00,0x3eb5bf00,0x3eb50000,0x3eb5bf00,0x3eb50000,0xbeb50000,0x3eb5bf00,0xbeb50000,0x3eb5bf00,
0xbec63f00,0xbea20000,0xbeff3eb5,0x3d49beb5,0x3e713dc8,0xbee23efb,0xbe153ed5,0xbef53e8e,0x3ef5beed,0x3e153e44,0x3ee2be44,0xbe713eed,0xbd49be8e,0x3effbed5,0x3ea2befb,0x3ec6bdc8,
0xbed53f00,0xbe8e0000,0xbe8e0000,0x3ed5bf00,0x3dc83e44,0xbefb3eed,0xbefb3eed,0xbdc8be44,0x3efbbeb5,0xbdc83eb5,0xbdc83eb5,0xbefb3eb5,0x3e8ebeed,0x3ed5be44,0x3ed5be44,0xbe8e3eed,
0xbee23f00,0xbe710000,0x3e15beb5,0x3ef5beb5,0xbd493e8e,0xbeff3ed5,0xbea23dc8,0x3ec6befb,0x3ec6be44,0xbea23eed,0xbeff3eed,0xbd49be44,0x3ef5befb,0x3e153dc8,0xbe713ed5,0xbee23e8e,
0xbeed3f00,0xbe440000,0x3eedbf00,0x3e440000,0xbe443eb5,0xbeed3eb5,0x3e44beb5,0x3eedbeb5,0x3e440000,0xbeed3f00,0xbe440000,0x3eedbf00,0x3eedbeb5,0xbe443eb5,0xbeed3eb5,0x3e44beb5,
0xbef53f00,0xbe150000,0x3ee2beb5,0xbe713eb5,0xbea23ed5,0xbec63e8e,0x3effbefb,0x3d493dc8,0xbd493e44,0xbeff3eed,0x3ec6beed,0x3ea2be44,0x3e71bdc8,0xbee23efb,0x3e15be8e,0x3ef5bed5,
0xbefb3f00,0xbdc80000,0x3dc80000,0xbefb3f00,0xbed53eed,0xbe8e3e44,0x3e8ebe44,0xbed53eed,0xbe8e3eb5,0xbed53eb5,0x3ed5beb5,0xbe8e3eb5,0xbdc83e44,0xbefb3eed,0x3efbbeed,0xbdc83e44,
0xbeff3f00,0xbd490000,0xbea23eb5,0xbec63eb5,0xbef53efb,0xbe153dc8,0xbe713e8e,0xbee23ed5,0xbee23eed,0xbe713e44,0xbe153e44,0xbef53eed,0xbec63ed5,0xbea23e8e,0xbd493dc8,0xbeff3efb,
0x3f003f00,0xbf003f00,0x3f003f00,0xbf003f00,0x3f003f00,0xbf003f00,0x3f003f00,0xbf003f00,0x3f003f00,0xbf003f00,0x3f003f00,0xbf003f00,0x3f003f00,0xbf003f00,0x3f003f00,0xbf003f00,
0xbd490000,0xbeffbf00,0xbec6beb5,0xbea2beb5,0xbe15bdc8,0xbef5befb,0xbee2bed5,0xbe71be8e,0xbe71be44,0xbee2beed,0xbef5beed,0xbe15be44,0xbea2be8e,0xbec6bed5,0xbeffbefb,0xbd49bdc8,
0xbefbbf00,0x3dc80000,0x3dc80000,0x3efb3f00,0xbed5beed,0x3e8e3e44,0x3e8e3e44,0x3ed53eed,0xbe8ebeb5,0x3ed53eb5,0x3ed53eb5,0x3e8e3eb5,0xbdc8be44,0x3efb3eed,0x3efb3eed,0x3dc83e44,
0x3e150000,0x3ef53f00,0x3e713eb5,0xbee2beb5,0x3ec63e8e,0x3ea23ed5,0xbd493dc8,0xbeffbefb,0x3eff3eed,0x3d493e44,0xbea2be44,0xbec6beed,0x3ee23efb,0xbe71bdc8,0xbef5bed5,0xbe15be8e,
0x3eed3f00,0xbe440000,0xbeedbf00,0x3e440000,0x3e443eb5,0xbeedbeb5,0xbe44beb5,0x3eed3eb5,0xbe440000,0xbeedbf00,0x3e440000,0x3eed3f00,0xbeedbeb5,0xbe44beb5,0x3eed3eb5,0x3e443eb5,
0xbe710000,0xbee2bf00,0x3ef53eb5,0x3e153eb5,0xbeffbed5,0xbd49be8e,0x3ec63efb,0xbea2bdc8,0xbea2beed,0x3ec63e44,0xbd493e44,0xbeffbeed,0x3e15bdc8,0x3ef53efb,0xbee2be8e,0xbe71bed5,
0xbed5bf00,0x3e8e0000,0xbe8e0000,0xbed5bf00,0x3dc8be44,0x3efb3eed,0xbefbbeed,0x3dc8be44,0x3efb3eb5,0x3dc83eb5,0xbdc8beb5,0x3efb3eb5,0x3e8e3eed,0xbed5be44,0x3ed53e44,0x3e8e3eed,
0x3ea20000,0x3ec63f00,0xbd49beb5,0x3eff3eb5,0x3ee23efb,0xbe713dc8,0x3ef53e8e,0x3e153ed5,0xbe153e44,0xbef5beed,0x3e713eed,0xbee2be44,0xbeffbed5,0x3d49be8e,0xbec6bdc8,0xbea2befb,
0x3eb53f00,0xbeb50000,0x3eb53f00,0xbeb50000,0xbeb50000,0xbeb5bf00,0xbeb50000,0xbeb5bf00,0xbeb5bf00,0x3eb50000,0xbeb5bf00,0x3eb50000,0x3eb50000,0x3eb53f00,0x3eb50000,0x3eb53f00,
0xbec60000,0xbea2bf00,0xbeffbeb5,0x3d49beb5,0xbe71befb,0x3ee23dc8,0x3e15be8e,0x3ef53ed5,0x3ef53e44,0x3e153eed,0x3ee23eed,0xbe713e44,0x3d493ed5,0xbeffbe8e,0xbea23dc8,0xbec6befb,
0xbe8ebf00,0x3ed50000,0x3ed50000,0x3e8e3f00,0x3efb3e44,0x3dc83eed,0x3dc83eed,0xbefbbe44,0xbdc83eb5,0xbefbbeb5,0xbefbbeb5,0x3dc8beb5,0xbed5beed,0x3e8ebe44,0x3e8ebe44,0x3ed53eed,
0x3ee20000,0x3e713f00,0xbe153eb5,0xbef5beb5,0xbd493ed5,0xbeffbe8e,0xbea2befb,0x3ec6bdc8,0xbec6beed,0x3ea2be44,0x3eff3e44,0x3d493eed,0x3ef53dc8,0x3e153efb,0xbe713e8e,0xbee2bed5,
0x3e443f00,0xbeed0000,0xbe44bf00,0x3eed0000,0xbeedbeb5,0x3e44beb5,0x3eed3eb5,0xbe443eb5,0x3eed0000,0x3e443f00,0xbeed0000,0xbe44bf00,0xbe443eb5,0xbeedbeb5,0x3e44beb5,0x3eed3eb5,
0xbef50000,0xbe15bf00,0x3ee23eb5,0xbe713eb5,0x3ea2be8e,0x3ec63ed5,0xbeffbdc8,0xbd49befb,0xbd493eed,0xbeffbe44,0x3ec6be44,0x3ea23eed,0xbe71befb,0x3ee2bdc8,0xbe153ed5,0xbef5be8e,
0xbdc8bf00,0x3efb0000,0xbefb0000,0xbdc8bf00,0x3e8e3eed,0xbed53e44,0x3ed5be44,0x3e8e3eed,0xbed5beb5,0x3e8ebeb5,0xbe8e3eb5,0xbed5beb5,0x3efb3e44,0xbdc83eed,0x3dc8beed,0x3efb3e44,
0x3eff0000,0x3d493f00,0x3ea2beb5,0x3ec63eb5,0xbef53dc8,0xbe15befb,0xbe713ed5,0xbee2be8e,0x3ee2be44,0x3e713eed,0x3e15beed,0x3ef53e44,0xbec63e8e,0xbea2bed5,0xbd493efb,0xbeffbdc8,
0x3f00,0xbf000000,0x3f00,0xbf000000,0xbf00,0x3f000000,0xbf00,0x3f000000,0x3f00,0xbf000000,0x3f00,0xbf000000,0xbf00,0x3f000000,0xbf00,0x3f000000,
0xbeff0000,0x3d49bf00,0xbea2beb5,0x3ec6beb5,0x3ef53dc8,0xbe153efb,0x3e713ed5,0xbee23e8e,0xbee2be44,0x3e71beed,0xbe15beed,0x3ef5be44,0x3ec63e8e,0xbea23ed5,0x3d493efb,0xbeff3dc8,
0x3dc8bf00,0x3efb0000,0x3efb0000,0xbdc83f00,0xbe8e3eed,0xbed5be44,0xbed5be44,0x3e8ebeed,0x3ed5beb5,0x3e8e3eb5,0x3e8e3eb5,0xbed53eb5,0xbefb3e44,0xbdc8beed,0xbdc8beed,0x3efbbe44,
0x3ef50000,0xbe153f00,0xbee23eb5,0xbe71beb5,0xbea2be8e,0x3ec6bed5,0x3effbdc8,0xbd493efb,0x3d493eed,0xbeff3e44,0xbec6be44,0x3ea2beed,0x3e71befb,0x3ee23dc8,0x3e153ed5,0xbef53e8e,
0xbe443f00,0xbeed0000,0x3e44bf00,0x3eed0000,0x3eedbeb5,0x3e443eb5,0xbeed3eb5,0xbe44beb5,0xbeed0000,0x3e44bf00,0x3eed0000,0xbe443f00,0x3e443eb5,0xbeed3eb5,0xbe44beb5,0x3eedbeb5,
0xbee20000,0x3e71bf00,0x3e153eb5,0xbef53eb5,0x3d493ed5,0xbeff3e8e,0x3ea2befb,0x3ec63dc8,0x3ec6beed,0x3ea23e44,0xbeff3e44,0x3d49beed,0xbef53dc8,0x3e15befb,0x3e713e8e,0xbee23ed5,
0x3e8ebf00,0x3ed50000,0xbed50000,0x3e8ebf00,0xbefb3e44,0x3dc8beed,0xbdc83eed,0xbefb3e44,0x3dc83eb5,0xbefb3eb5,0x3efbbeb5,0x3dc83eb5,0x3ed5beed,0x3e8e3e44,0xbe8ebe44,0x3ed5beed,
0x3ec60000,0xbea23f00,0x3effbeb5,0x3d493eb5,0x3e71befb,0x3ee2bdc8,0xbe15be8e,0x3ef5bed5,0xbef53e44,0x3e15beed,0xbee23eed,0xbe71be44,0xbd493ed5,0xbeff3e8e,0x3ea23dc8,0xbec63efb,
0xbeb53f00,0xbeb50000,0xbeb53f00,0xbeb50000,0x3eb50000,0xbeb53f00,0x3eb50000,0xbeb53f00,0x3eb5bf00,0x3eb50000,0x3eb5bf00,0x3eb50000,0xbeb50000,0x3eb5bf00,0xbeb50000,0x3eb5bf00,
0xbea20000,0x3ec6bf00,0x3d49beb5,0x3effbeb5,0xbee23efb,0xbe71bdc8,0xbef53e8e,0x3e15bed5,0x3e153e44,0xbef53eed,0xbe713eed,0xbee23e44,0x3effbed5,0x3d493e8e,0x3ec6bdc8,0xbea23efb,
0x3ed5bf00,0x3e8e0000,0x3e8e0000,0xbed53f00,0xbdc8be44,0x3efbbeed,0x3efbbeed,0x3dc83e44,0xbefb3eb5,0x3dc8beb5,0x3dc8beb5,0x3efbbeb5,0xbe8e3eed,0xbed53e44,0xbed53e44,0x3e8ebeed,
0x3e710000,0xbee23f00,0xbef53eb5,0x3e15beb5,0x3effbed5,0xbd493e8e,0xbec63efb,0xbea23dc8,0x3ea2beed,0x3ec6be44,0x3d493e44,0xbeff3eed,0xbe15bdc8,0x3ef5befb,0x3ee2be8e,0xbe713ed5,
0xbeed3f00,0xbe440000,0x3eedbf00,0x3e440000,0xbe443eb5,0xbeed3eb5,0x3e44beb5,0x3eedbeb5,0x3e440000,0xbeed3f00,0xbe440000,0x3eedbf00,0x3eedbeb5,0xbe443eb5,0xbeed3eb5,0x3e44beb5,
0xbe150000,0x3ef5bf00,0xbe713eb5,0xbee23eb5,0xbec63e8e,0x3ea2bed5,0x3d493dc8,0xbeff3efb,0xbeff3eed,0x3d49be44,0x3ea2be44,0xbec63eed,0xbee23efb,0xbe713dc8,0x3ef5bed5,0xbe153e8e,
0x3efbbf00,0x3dc80000,0xbdc80000,0x3efbbf00,0x3ed5beed,0x3e8ebe44,0xbe8e3e44,0x3ed5beed,0x3e8ebeb5,0x3ed5beb5,0xbed53eb5,0x3e8ebeb5,0x3dc8be44,0x3efbbeed,0xbefb3eed,0x3dc8be44,
0x3d490000,0xbeff3f00,0x3ec6beb5,0xbea23eb5,0x3e15bdc8,0xbef53efb,0x3ee2bed5,0xbe713e8e,0x3e71be44,0xbee23eed,0x3ef5beed,0xbe153e44,0x3ea2be8e,0xbec63ed5,0x3effbefb,0xbd493dc8,
0x3f003f00,0xbf003f00,0x3f003f00,0xbf003f00,0x3f003f00,0xbf003f00,0x3f003f00,0xbf003f00,0x3f003f00,0xbf003f00,0x3f003f00,0xbf003f00,0x3f003f00,0xbf003f00,0x3f003f00,0xbf003f00,
0xbeffbf00,0x3d490000,0xbea2beb5,0x3ec63eb5,0xbef5befb,0x3e153dc8,0xbe71be8e,0x3ee23ed5,0xbee2beed,0x3e713e44,0xbe15be44,0x3ef53eed,0xbec6bed5,0x3ea23e8e,0xbd49bdc8,0x3eff3efb,
0x3efb3f00,0xbdc80000,0xbdc80000,0xbefbbf00,0x3ed53eed,0xbe8ebe44,0xbe8ebe44,0xbed5beed,0x3e8e3eb5,0xbed5beb5,0xbed5beb5,0xbe8ebeb5,0x3dc83e44,0xbefbbeed,0xbefbbeed,0xbdc8be44,
0xbef5bf00,0x3e150000,0x3ee23eb5,0x3e713eb5,0xbea2bed5,0x3ec63e8e,0x3eff3efb,0xbd493dc8,0xbd49be44,0x3eff3eed,0x3ec63eed,0xbea2be44,0x3e713dc8,0x3ee23efb,0x3e153e8e,0xbef5bed5,
0x3eed3f00,0xbe440000,0xbeedbf00,0x3e440000,0x3e443eb5,0xbeedbeb5,0xbe44beb5,0x3eed3eb5,0xbe440000,0xbeedbf00,0x3e440000,0x3eed3f00,0xbeedbeb5,0xbe44beb5,0x3eed3eb5,0x3e443eb5,
0xbee2bf00,0x3e710000,0x3e153eb5,0xbef5beb5,0xbd49be8e,0x3eff3ed5,0xbea2bdc8,0xbec6befb,0x3ec63e44,0x3ea23eed,0xbeffbeed,0x3d49be44,0x3ef53efb,0xbe153dc8,0xbe71bed5,0x3ee23e8e,
0x3ed53f00,0xbe8e0000,0x3e8e0000,0x3ed53f00,0xbdc83e44,0xbefbbeed,0x3efb3eed,0xbdc83e44,0xbefbbeb5,0xbdc8beb5,0x3dc83eb5,0xbefbbeb5,0xbe8ebeed,0x3ed53e44,0xbed5be44,0xbe8ebeed,
0xbec6bf00,0x3ea20000,0xbeffbeb5,0xbd49beb5,0x3e71bdc8,0x3ee23efb,0xbe15bed5,0x3ef53e8e,0x3ef53eed,0xbe153e44,0x3ee23e44,0x3e713eed,0xbd493e8e,0xbeffbed5,0x3ea23efb,0xbec6bdc8,
0x3eb53f00,0xbeb50000,0x3eb53f00,0xbeb50000,0xbeb50000,0xbeb5bf00,0xbeb50000,0xbeb5bf00,0xbeb5bf00,0x3eb50000,0xbeb5bf00,0x3eb50000,0x3eb50000,0x3eb53f00,0x3eb50000,0x3eb53f00,
0xbea2bf00,0x3ec60000,0x3d49beb5,0x3eff3eb5,0x3ee23dc8,0x3e713efb,0x3ef53ed5,0xbe153e8e,0x3e153eed,0xbef5be44,0xbe713e44,0xbee2beed,0xbeffbe8e,0xbd49bed5,0xbec6befb,0x3ea2bdc8,
0x3e8e3f00,0xbed50000,0xbed50000,0xbe8ebf00,0xbefbbe44,0xbdc8beed,0xbdc8beed,0x3efb3e44,0x3dc8beb5,0x3efb3eb5,0x3efb3eb5,0xbdc83eb5,0x3ed53eed,0xbe8e3e44,0xbe8e3e44,0xbed5beed,
0xbe71bf00,0x3ee20000,0x3ef53eb5,0xbe153eb5,0x3eff3e8e,0xbd493ed5,0xbec63dc8,0xbea2befb,0xbea23e44,0xbec6beed,0xbd49beed,0x3eff3e44,0xbe15befb,0x3ef53dc8,0x3ee23ed5,0xbe713e8e,
0x3e443f00,0xbeed0000,0xbe44bf00,0x3eed0000,0xbeedbeb5,0x3e44beb5,0x3eed3eb5,0xbe443eb5,0x3eed0000,0x3e443f00,0xbeed0000,0xbe44bf00,0xbe443eb5,0xbeedbeb5,0x3e44beb5,0x3eed3eb5,
0xbe15bf00,0x3ef50000,0xbe713eb5,0xbee2beb5,0x3ec63ed5,0xbea23e8e,0xbd49befb,0x3eff3dc8,0xbeffbe44,0x3d49beed,0x3ea23eed,0xbec63e44,0x3ee2bdc8,0x3e713efb,0xbef5be8e,0x3e15bed5,
0x3dc83f00,0xbefb0000,0x3efb0000,0x3dc83f00,0xbe8ebeed,0x3ed5be44,0xbed53e44,0xbe8ebeed,0x3ed53eb5,0xbe8e3eb5,0x3e8ebeb5,0x3ed53eb5,0xbefbbe44,0x3dc8beed,0xbdc83eed,0xbefbbe44,
0xbd49bf00,0x3eff0000,0xbec6beb5,0x3ea2beb5,0x3e153efb,0xbef53dc8,0x3ee23e8e,0xbe713ed5,0xbe71beed,0x3ee2be44,0xbef5be44,0x3e15beed,0x3ea23ed5,0xbec63e8e,0x3eff3dc8,0xbd493efb,
0x3f00,0xbf000000,0x3f00,0xbf000000,0xbf00,0x3f000000,0xbf00,0x3f000000,0x3f00,0xbf000000,0x3f00,0xbf000000,0xbf00,0x3f000000,0xbf00,0x3f000000,
0x3d49bf00,0x3eff0000,0x3ec6beb5,0x3ea23eb5,0xbe153efb,0xbef5bdc8,0xbee23e8e,0xbe71bed5,0x3e71beed,0x3ee23e44,0x3ef5be44,0x3e153eed,0xbea23ed5,0xbec6be8e,0xbeff3dc8,0xbd49befb,
0xbdc83f00,0xbefb0000,0xbefb0000,0x3dc8bf00,0x3e8ebeed,0x3ed53e44,0x3ed53e44,0xbe8e3eed,0xbed53eb5,0xbe8ebeb5,0xbe8ebeb5,0x3ed5beb5,0x3efbbe44,0x3dc83eed,0x3dc83eed,0xbefb3e44,
0x3e15bf00,0x3ef50000,0x3e713eb5,0xbee23eb5,0xbec63ed5,0xbea2be8e,0x3d49befb,0x3effbdc8,0x3effbe44,0x3d493eed,0xbea23eed,0xbec6be44,0xbee2bdc8,0x3e71befb,0x3ef5be8e,0x3e153ed5,
0xbe443f00,0xbeed0000,0x3e44bf00,0x3eed0000,0x3eedbeb5,0x3e443eb5,0xbeed3eb5,0xbe44beb5,0xbeed0000,0x3e44bf00,0x3eed0000,0xbe443f00,0x3e443eb5,0xbeed3eb5,0xbe44beb5,0x3eedbeb5,
0x3e71bf00,0x3ee20000,0xbef53eb5,0xbe15beb5,0xbeff3e8e,0xbd49bed5,0x3ec63dc8,0xbea23efb,0x3ea23e44,0xbec63eed,0x3d49beed,0x3effbe44,0x3e15befb,0x3ef5bdc8,0xbee23ed5,0xbe71be8e,
0xbe8e3f00,0xbed50000,0x3ed50000,0xbe8e3f00,0x3efbbe44,0xbdc83eed,0x3dc8beed,0x3efbbe44,0xbdc8beb5,0x3efbbeb5,0xbefb3eb5,0xbdc8beb5,0xbed53eed,0xbe8ebe44,0x3e8e3e44,0xbed53eed,
0x3ea2bf00,0x3ec60000,0xbd49beb5,0x3effbeb5,0xbee23dc8,0x3e71befb,0xbef53ed5,0xbe15be8e,0xbe153eed,0xbef53e44,0x3e713e44,0xbee23eed,0x3effbe8e,0xbd493ed5,0x3ec6befb,0x3ea23dc8,
0xbeb53f00,0xbeb50000,0xbeb53f00,0xbeb50000,0x3eb50000,0xbeb53f00,0x3eb50000,0xbeb53f00,0x3eb5bf00,0x3eb50000,0x3eb5bf00,0x3eb50000,0xbeb50000,0x3eb5bf00,0xbeb50000,0x3eb5bf00,
0x3ec6bf00,0x3ea20000,0x3effbeb5,0xbd493eb5,0xbe71bdc8,0x3ee2befb,0x3e15bed5,0x3ef5be8e,0xbef53eed,0xbe15be44,0xbee23e44,0x3e71beed,0x3d493e8e,0xbeff3ed5,0xbea23efb,0xbec63dc8,
0xbed53f00,0xbe8e0000,0xbe8e0000,0x3ed5bf00,0x3dc83e44,0xbefb3eed,0xbefb3eed,0xbdc8be44,0x3efbbeb5,0xbdc83eb5,0xbdc83eb5,0xbefb3eb5,0x3e8ebeed,0x3ed5be44,0x3ed5be44,0xbe8e3eed,
0x3ee2bf00,0x3e710000,0xbe153eb5,0xbef53eb5,0x3d49be8e,0x3effbed5,0x3ea2bdc8,0xbec63efb,0xbec63e44,0x3ea2beed,0x3effbeed,0x3d493e44,0xbef53efb,0xbe15bdc8,0x3e71bed5,0x3ee2be8e,
0xbeed3f00,0xbe440000,0x3eedbf00,0x3e440000,0xbe443eb5,0xbeed3eb5,0x3e44beb5,0x3eedbeb5,0x3e440000,0xbeed3f00,0xbe440000,0x3eedbf00,0x3eedbeb5,0xbe443eb5,0xbeed3eb5,0x3e44beb5,
0x3ef5bf00,0x3e150000,0xbee23eb5,0x3e71beb5,0x3ea2bed5,0x3ec6be8e,0xbeff3efb,0xbd49bdc8,0x3d49be44,0x3effbeed,0xbec63eed,0xbea23e44,0xbe713dc8,0x3ee2befb,0xbe153e8e,0xbef53ed5,
0xbefb3f00,0xbdc80000,0x3dc80000,0xbefb3f00,0xbed53eed,0xbe8e3e44,0x3e8ebe44,0xbed53eed,0xbe8e3eb5,0xbed53eb5,0x3ed5beb5,0xbe8e3eb5,0xbdc83e44,0xbefb3eed,0x3efbbeed,0xbdc83e44,
0x3effbf00,0x3d490000,0x3ea2beb5,0x3ec6beb5,0x3ef5befb,0x3e15bdc8,0x3e71be8e,0x3ee2bed5,0x3ee2beed,0x3e71be44,0x3e15be44,0x3ef5beed,0x3ec6bed5,0x3ea2be8e,0x3d49bdc8,0x3effbefb,
0x3f003f00,0xbf003f00,0x3f003f00,0xbf003f00,0x3f003f00,0xbf003f00,0x3f003f00,0xbf003f00,0x3f003f00,0xbf003f00,0x3f003f00,0xbf003f00,0x3f003f00,0xbf003f00,0x3f003f00,0xbf003f00,
0x3d490000,0x3eff3f00,0x3ec63eb5,0x3ea23eb5,0x3e153dc8,0x3ef53efb,0x3ee23ed5,0x3e713e8e,0x3e713e44,0x3ee23eed,0x3ef53eed,0x3e153e44,0x3ea23e8e,0x3ec63ed5,0x3eff3efb,0x3d493dc8,
0xbefbbf00,0x3dc80000,0x3dc80000,0x3efb3f00,0xbed5beed,0x3e8e3e44,0x3e8e3e44,0x3ed53eed,0xbe8ebeb5,0x3ed53eb5,0x3ed53eb5,0x3e8e3eb5,0xbdc8be44,0x3efb3eed,0x3efb3eed,0x3dc83e44,
0xbe150000,0xbef5bf00,0xbe71beb5,0x3ee23eb5,0xbec6be8e,0xbea2bed5,0x3d49bdc8,0x3eff3efb,0xbeffbeed,0xbd49be44,0x3ea23e44,0x3ec63eed,0xbee2befb,0x3e713dc8,0x3ef53ed5,0x3e153e8e,
0x3eed3f00,0xbe440000,0xbeedbf00,0x3e440000,0x3e443eb5,0xbeedbeb5,0xbe44beb5,0x3eed3eb5,0xbe440000,0xbeedbf00,0x3e440000,0x3eed3f00,0xbeedbeb5,0xbe44beb5,0x3eed3eb5,0x3e443eb5,
0x3e710000,0x3ee23f00,0xbef5beb5,0xbe15beb5,0x3eff3ed5,0x3d493e8e,0xbec6befb,0x3ea23dc8,0x3ea23eed,0xbec6be44,0x3d49be44,0x3eff3eed,0xbe153dc8,0xbef5befb,0x3ee23e8e,0x3e713ed5,
0xbed5bf00,0x3e8e0000,0xbe8e0000,0xbed5bf00,0x3dc8be44,0x3efb3eed,0xbefbbeed,0x3dc8be44,0x3efb3eb5,0x3dc83eb5,0xbdc8beb5,0x3efb3eb5,0x3e8e3eed,0xbed5be44,0x3ed53e44,0x3e8e3eed,
0xbea20000,0xbec6bf00,0x3d493eb5,0xbeffbeb5,0xbee2befb,0x3e71bdc8,0xbef5be8e,0xbe15bed5,0x3e15be44,0x3ef53eed,0xbe71beed,0x3ee23e44,0x3eff3ed5,0xbd493e8e,0x3ec63dc8,0x3ea23efb,
0x3eb53f00,0xbeb50000,0x3eb53f00,0xbeb50000,0xbeb50000,0xbeb5bf00,0xbeb50000,0xbeb5bf00,0xbeb5bf00,0x3eb50000,0xbeb5bf00,0x3eb50000,0x3eb50000,0x3eb53f00,0x3eb50000,0x3eb53f00,
0x3ec60000,0x3ea23f00,0x3eff3eb5,0xbd493eb5,0x3e713efb,0xbee2bdc8,0xbe153e8e,0xbef5bed5,0xbef5be44,0xbe15beed,0xbee2beed,0x3e71be44,0xbd49bed5,0x3eff3e8e,0x3ea2bdc8,0x3ec63efb,
0xbe8ebf00,0x3ed50000,0x3ed50000,0x3e8e3f00,0x3efb3e44,0x3dc83eed,0x3dc83eed,0xbefbbe44,0xbdc83eb5,0xbefbbeb5,0xbefbbeb5,0x3dc8beb5,0xbed5beed,0x3e8ebe44,0x3e8ebe44,0x3ed53eed,
0xbee20000,0xbe71bf00,0x3e15beb5,0x3ef53eb5,0x3d49bed5,0x3eff3e8e,0x3ea23efb,0xbec63dc8,0x3ec63eed,0xbea23e44,0xbeffbe44,0xbd49beed,0xbef5bdc8,0xbe15befb,0x3e71be8e,0x3ee23ed5,
0x3e443f00,0xbeed0000,0xbe44bf00,0x3eed0000,0xbeedbeb5,0x3e44beb5,0x3eed3eb5,0xbe443eb5,0x3eed0000,0x3e443f00,0xbeed0000,0xbe44bf00,0xbe443eb5,0xbeedbeb5,0x3e44beb5,0x3eed3eb5,
0x3ef50000,0x3e153f00,0xbee2beb5,0x3e71beb5,0xbea23e8e,0xbec6bed5,0x3eff3dc8,0x3d493efb,0x3d49beed,0x3eff3e44,0xbec63e44,0xbea2beed,0x3e713efb,0xbee23dc8,0x3e15bed5,0x3ef53e8e,
0xbdc8bf00,0x3efb0000,0xbefb0000,0xbdc8bf00,0x3e8e3eed,0xbed53e44,0x3ed5be44,0x3e8e3eed,0xbed5beb5,0x3e8ebeb5,0xbe8e3eb5,0xbed5beb5,0x3efb3e44,0xbdc83eed,0x3dc8beed,0x3efb3e44,
0xbeff0000,0xbd49bf00,0xbea23eb5,0xbec6beb5,0x3ef5bdc8,0x3e153efb,0x3e71bed5,0x3ee23e8e,0xbee23e44,0xbe71beed,0xbe153eed,0xbef5be44,0x3ec6be8e,0x3ea23ed5,0x3d49befb,0x3eff3dc8,
0x3f00,0xbf000000,0x3f00,0xbf000000,0xbf00,0x3f000000,0xbf00,0x3f000000,0x3f00,0xbf000000,0x3f00,0xbf000000,0xbf00,0x3f000000,0xbf00,0x3f000000,
0x3eff0000,0xbd493f00,0x3ea23eb5,0xbec63eb5,0xbef5bdc8,0x3e15befb,0xbe71bed5,0x3ee2be8e,0x3ee23e44,0xbe713eed,0x3e153eed,0xbef53e44,0xbec6be8e,0x3ea2bed5,0xbd49befb,0x3effbdc8,
0x3dc8bf00,0x3efb0000,0x3efb0000,0xbdc83f00,0xbe8e3eed,0xbed5be44,0xbed5be44,0x3e8ebeed,0x3ed5beb5,0x3e8e3eb5,0x3e8e3eb5,0xbed53eb5,0xbefb3e44,0xbdc8beed,0xbdc8beed,0x3efbbe44,
0xbef50000,0x3e15bf00,0x3ee2beb5,0x3e713eb5,0x3ea23e8e,0xbec63ed5,0xbeff3dc8,0x3d49befb,0xbd49beed,0x3effbe44,0x3ec63e44,0xbea23eed,0xbe713efb,0xbee2bdc8,0xbe15bed5,0x3ef5be8e,
0xbe443f00,0xbeed0000,0x3e44bf00,0x3eed0000,0x3eedbeb5,0x3e443eb5,0xbeed3eb5,0xbe44beb5,0xbeed0000,0x3e44bf00,0x3eed0000,0xbe443f00,0x3e443eb5,0xbeed3eb5,0xbe44beb5,0x3eedbeb5,
0x3ee20000,0xbe713f00,0xbe15beb5,0x3ef5beb5,0xbd49bed5,0x3effbe8e,0xbea23efb,0xbec6bdc8,0xbec63eed,0xbea2be44,0x3effbe44,0xbd493eed,0x3ef5bdc8,0xbe153efb,0xbe71be8e,0x3ee2bed5,
0x3e8ebf00,0x3ed50000,0xbed50000,0x3e8ebf00,0xbefb3e44,0x3dc8beed,0xbdc83eed,0xbefb3e44,0x3dc83eb5,0xbefb3eb5,0x3efbbeb5,0x3dc83eb5,0x3ed5beed,0x3e8e3e44,0xbe8ebe44,0x3ed5beed,
0xbec60000,0x3ea2bf00,0xbeff3eb5,0xbd49beb5,0xbe713efb,0xbee23dc8,0x3e153e8e,0xbef53ed5,0x3ef5be44,0xbe153eed,0x3ee2beed,0x3e713e44,0x3d49bed5,0x3effbe8e,0xbea2bdc8,0x3ec6befb,
0xbeb53f00,0xbeb50000,0xbeb53f00,0xbeb50000,0x3eb50000,0xbeb53f00,0x3eb50000,0xbeb53f00,0x3eb5bf00,0x3eb50000,0x3eb5bf00,0x3eb50000,0xbeb50000,0x3eb5bf00,0xbeb50000,0x3eb5bf00,
0x3ea20000,0xbec63f00,0xbd493eb5,0xbeff3eb5,0x3ee2befb,0x3e713dc8,0x3ef5be8e,0xbe153ed5,0xbe15be44,0x3ef5beed,0x3e71beed,0x3ee2be44,0xbeff3ed5,0xbd49be8e,0xbec63dc8,0x3ea2befb,
0x3ed5bf00,0x3e8e0000,0x3e8e0000,0xbed53f00,0xbdc8be44,0x3efbbeed,0x3efbbeed,0x3dc83e44,0xbefb3eb5,0x3dc8beb5,0x3dc8beb5,0x3efbbeb5,0xbe8e3eed,0xbed53e44,0xbed53e44,0x3e8ebeed,
0xbe710000,0x3ee2bf00,0x3ef5beb5,0xbe153eb5,0xbeff3ed5,0x3d49be8e,0x3ec6befb,0x3ea2bdc8,0xbea23eed,0xbec63e44,0xbd49be44,0x3effbeed,0x3e153dc8,0xbef53efb,0xbee23e8e,0x3e71bed5,
0xbeed3f00,0xbe440000,0x3eedbf00,0x3e440000,0xbe443eb5,0xbeed3eb5,0x3e44beb5,0x3eedbeb5,0x3e440000,0xbeed3f00,0xbe440000,0x3eedbf00,0x3eedbeb5,0xbe443eb5,0xbeed3eb5,0x3e44beb5,
0x3e150000,0xbef53f00,0x3e71beb5,0x3ee2beb5,0x3ec6be8e,0xbea23ed5,0xbd49bdc8,0x3effbefb,0x3effbeed,0xbd493e44,0xbea23e44,0x3ec6beed,0x3ee2befb,0x3e71bdc8,0xbef53ed5,0x3e15be8e,
0x3efbbf00,0x3dc80000,0xbdc80000,0x3efbbf00,0x3ed5beed,0x3e8ebe44,0xbe8e3e44,0x3ed5beed,0x3e8ebeb5,0x3ed5beb5,0xbed53eb5,0x3e8ebeb5,0x3dc8be44,0x3efbbeed,0xbefb3eed,0x3dc8be44,
0xbd490000,0x3effbf00,0xbec63eb5,0x3ea2beb5,0xbe153dc8,0x3ef5befb,0xbee23ed5,0x3e71be8e,0xbe713e44,0x3ee2beed,0xbef53eed,0x3e15be44,0xbea23e8e,0x3ec6bed5,0xbeff3efb,0x3d49bdc8,
0x3f800000,0x0,0x3f800000,0x0,0x3f800000,0x0,0x3f800000,0x0,0x3f800000,0x0,0x3f800000,0x0,0x3f800000,0x0,0x3f800000,0x0,
0x3f800000,0x0,0x3f7ffec4,0xbbc90f88,0x3f7ffb11,0xbc490e90,0x3f7ff4e6,0xbc96c9b6,0x3f7fec43,0xbcc90ab0,0x3f7fe129,0xbcfb49ba,0x3f7fd397,0xbd16c32c,0x3f7fc38f,0xbd2fe007,
0x3f800000,0x0,0x3f7ffb11,0xbc490e90,0x3f7fec43,0xbcc90ab0,0x3f7fd397,0xbd16c32c,0x3f7fb10f,0xbd48fb30,0x3f7f84ab,0xbd7b2b74,0x3f7f4e6d,0xbd96a905,0x3f7f0e58,0xbdafb680,
0x3f800000,0x0,0x3f7ff4e6,0xbc96c9b6,0x3f7fd397,0xbd16c32c,0x3f7f9c18,0xbd621469,0x3f7f4e6d,0xbd96a905,0x3f7eea9d,0xbdbc3ac3,0x3f7e70b0,0xbde1bc2e,0x3f7de0b1,0xbe039502,
0x3f800000,0x0,0x3f7fec43,0xbcc90ab0,0x3f7fb10f,0xbd48fb30,0x3f7f4e6d,0xbd96a905,0x3f7ec46d,0xbdc8bd36,0x3f7e1324,0xbdfab273,0x3f7d3aac,0xbe164083,0x3f7c3b28,0xbe2f10a2,
0x3f800000,0x0,0x3f7fe129,0xbcfb49ba,0x3f7f84ab,0xbd7b2b74,0x3f7eea9d,0xbdbc3ac3,0x3f7e1324,0xbdfab273,0x3f7cfe73,0xbe1c76de,0x3f7baccd,0xbe3b6ecf,0x3f7a1e84,0xbe5a3997,
0x3f800000,0x0,0x3f7fd397,0xbd16c32c,0x3f7f4e6d,0xbd96a905,0x3f7e70b0,0xbde1bc2e,0x3f7d3aac,0xbe164083,0x3f7baccd,0xbe3b6ecf,0x3f79c79d,0xbe605c13,0x3f778bc5,0xbe827dc0,
0x3f800000,0x0,0x3f7fc38f,0xbd2fe007,0x3f7f0e58,0xbdafb680,0x3f7de0b1,0xbe039502,0x3f7c3b28,0xbe2f10a2,0x3f7a1e84,0xbe5a3997,0x3f778bc5,0xbe827dc0,0x3f748422,0xbe97a117,
0x3f800000,0x0,0x3f7fb10f,0xbd48fb30,0x3f7ec46d,0xbdc8bd36,0x3f7d3aac,0xbe164083,0x3f7b14be,0xbe47c5c2,0x3f7853f8,0xbe78cfcc,0x3f74fa0b,0xbe94a031,0x3f710908,0xbeac7cd4,
0x3f800000,0x0,0x3f7f9c18,0xbd621469,0x3f7e70b0,0xbde1bc2e,0x3f7c7eb0,0xbe28defc,0x3f79c79d,0xbe605c13,0x3f764d97,0xbe8b9507,0x3f721352,0xbea68f12,0x3f6d1c1d,0xbec1071e,
0x3f800000,0x0,0x3f7f84ab,0xbd7b2b74,0x3f7e1324,0xbdfab273,0x3f7baccd,0xbe3b6ecf,0x3f7853f8,0xbe78cfcc,0x3f740bdd,0xbe9aa086,0x3f6ed89e,0xbeb8442a,0x3f68bf3c,0xbed53641,
0x3f800000,0x0,0x3f7f6ac7,0xbd8a200a,0x3f7dabcc,0xbe09cf86,0x3f7ac516,0xbe4dee60,0x3f76ba07,0xbe888e93,0x3f718f57,0xbea986c4,0x3f6b4b0c,0xbec9b953,0x3f63f473,0xbee900b7,
0x3f800000,0x0,0x3f7f4e6d,0xbd96a905,0x3f7d3aac,0xbe164083,0x3f79c79d,0xbe605c13,0x3f74fa0b,0xbe94a031,0x3f6ed89e,0xbeb8442a,0x3f676bd8,0xbedae880,0x3f5ebe05,0xbefc5d27,
0x3f800000,0x0,0x3f7f2f9d,0xbda3308c,0x3f7cbfc9,0xbe22abb6,0x3f78b47b,0xbe72b651,0x3f731447,0xbea09ae5,0x3f6be858,0xbec6d529,0x3f633c5a,0xbeebcbbb,0x3f591e6a,0xbf07a136,
0x3f800000,0x0,0x3f7f0e58,0xbdafb680,0x3f7c3b28,0xbe2f10a2,0x3f778bc5,0xbe827dc0,0x3f710908,0xbeac7cd4,0x3f68bf3c,0xbed53641,0x3f5ebe05,0xbefc5d27,0x3f531849,0xbf10d3cd,
0x3f800000,0x0,0x3f7eea9d,0xbdbc3ac3,0x3f7baccd,0xbe3b6ecf,0x3f764d97,0xbe8b9507,0x3f6ed89e,0xbeb8442a,0x3f655e0b,0xbee363fa,0x3f59f26a,0xbf064b82,0x3f4cae79,0xbf19c200,
0x3f800000,0x0,0x3f7ec46d,0xbdc8bd36,0x3f7b14be,0xbe47c5c2,0x3f74fa0b,0xbe94a031,0x3f6c835e,0xbec3ef15,0x3f61c598,0xbef15aea,0x3f54db31,0xbf0e39da,0x3f45e403,0xbf226799,
0x3f800000,0x0,0x3f7e9bc9,0xbdd53db9,0x3f7a7302,0xbe541501,0x3f73913f,0xbe9d9e78,0x3f6a09a7,0xbecf7bca,0x3f5df6be,0xbeff17b2,0x3f4f7a1f,0xbf15f6d9,0x3f3ebc1b,0xbf2ac082,
0x3f800000,0x0,0x3f7e70b0,0xbde1bc2e,0x3f79c79d,0xbe605c13,0x3f721352,0xbea68f12,0x3f676bd8,0xbedae880,0x3f59f26a,0xbf064b82,0x3f49d112,0xbf1d7fd1,0x3f373a23,0xbf32c8c9,
0x3f800000,0x0,0x3f7e4323,0xbdee3876,0x3f791298,0xbe6c9a7f,0x3f708066,0xbeaf713a,0x3f64aa59,0xbee63375,0x3f55b993,0xbf0cead0,0x3f43e200,0xbf24d225,0x3f2f61a5,0xbf3a7ca4,
0x3f800000,0x0,0x3f7e1324,0xbdfab273,0x3f7853f8,0xbe78cfcc,0x3f6ed89e,0xbeb8442a,0x3f61c598,0xbef15aea,0x3f514d3d,0xbf13682a,0x3f3daef9,0xbf2beb4a,0x3f273656,0xbf41d870,
0x3f800000,0x0,0x3f7de0b1,0xbe039502,0x3f778bc5,0xbe827dc0,0x3f6d1c1d,0xbec1071e,0x3f5ebe05,0xbefc5d27,0x3f4cae79,0xbf19c200,0x3f373a23,0xbf32c8c9,0x3f1ebc12,0xbf48d8b3,
0x3f800000,0x0,0x3f7dabcc,0xbe09cf86,0x3f76ba07,0xbe888e93,0x3f6b4b0c,0xbec9b953,0x3f5b941a,0xbf039c3d,0x3f47de65,0xbf1ff6cb,0x3f3085bb,0xbf396842,0x3f15f6d9,0xbf4f7a1f,
0x3f800000,0x0,0x3f7d7474,0xbe1008b7,0x3f75dec6,0xbe8e9a22,0x3f696591,0xbed25a09,0x3f584853,0xbf08f59b,0x3f42de29,0xbf26050a,0x3f299415,0xbf3fc767,0x3f0cead0,0xbf55b993,
0x3f800000,0x0,0x3f7d3aac,0xbe164083,0x3f74fa0b,0xbe94a031,0x3f676bd8,0xbedae880,0x3f54db31,0xbf0e39da,0x3f3daef9,0xbf2beb4a,0x3f226799,0xbf45e403,0x3f039c3d,0xbf5b941a,
0x3f800000,0x0,0x3f7cfe73,0xbe1c76de,0x3f740bdd,0xbe9aa086,0x3f655e0b,0xbee363fa,0x3f514d3d,0xbf13682a,0x3f385216,0xbf31a81d,0x3f1b02c6,0xbf4bbbf8,0x3ef41f07,0xbf6106f2,
0x3f800000,0x0,0x3f7cbfc9,0xbe22abb6,0x3f731447,0xbea09ae5,0x3f633c5a,0xbeebcbbb,0x3f4d9f02,0xbf187fc0,0x3f32c8c9,0xbf373a23,0x3f13682a,0xbf514d3d,0x3ee0924f,0xbf660f88,
0x3f800000,0x0,0x3f7c7eb0,0xbe28defc,0x3f721352,0xbea68f12,0x3f6106f2,0xbef41f07,0x3f49d112,0xbf1d7fd1,0x3f2d1469,0xbf3ca003,0x3f0b9a6b,0xbf5695e5,0x3ecc9b8b,0xbf6aab7b,
0x3f800000,0x0,0x3f7c3b28,0xbe2f10a2,0x3f710908,0xbeac7cd4,0x3f5ebe05,0xbefc5d27,0x3f45e403,0xbf226799,0x3f273656,0xbf41d870,0x3f039c3d,0xbf5b941a,0x3eb8442a,0xbf6ed89e,
0x3f800000,0x0,0x3f7bf531,0xbe354098,0x3f6ff573,0xbeb263ef,0x3f5c61c7,0xbf0242b1,0x3f41d870,0xbf273656,0x3f212ff9,0xbf46e22a,0x3ef6e0cb,0xbf604621,0x3ea395c5,0xbf7294f8,
0x3f800000,0x0,0x3f7baccd,0xbe3b6ecf,0x3f6ed89e,0xbeb8442a,0x3f59f26a,0xbf064b82,0x3f3daef9,0xbf2beb4a,0x3f1b02c6,0xbf4bbbf8,0x3ee63375,0xbf64aa59,0x3e8e9a22,0xbf75dec6,
0x3f800000,0x0,0x3f7b61fc,0xbe419b37,0x3f6db293,0xbebe1d4a,0x3f577026,0xbf0a48ad,0x3f396842,0xbf3085bb,0x3f14b039,0xbf5064af,0x3ed53641,0xbf68bf3c,0x3e72b651,0xbf78b47b,
0x3f800000,0x0,0x3f800000,0x0,0x3f800000,0x0,0x3f800000,0x0,0x3f800000,0x0,0x3f800000,0x0,0x3f800000,0x0,0x3f800000,0x0,
0x3f7fb10f,0xbd48fb30,0x3f7f9c18,0xbd621469,0x3f7f84ab,0xbd7b2b74,0x3f7f6ac7,0xbd8a200a,0x3f7f4e6d,0xbd96a905,0x3f7f2f9d,0xbda3308c,0x3f7f0e58,0xbdafb680,0x3f7eea9d,0xbdbc3ac3,
0x3f7ec46d,0xbdc8bd36,0x3f7e70b0,0xbde1bc2e,0x3f7e1324,0xbdfab273,0x3f7dabcc,0xbe09cf86,0x3f7d3aac,0xbe164083,0x3f7cbfc9,0xbe22abb6,0x3f7c3b28,0xbe2f10a2,0x3f7baccd,0xbe3b6ecf,
0x3f7d3aac,0xbe164083,0x3f7c7eb0,0xbe28defc,0x3f7baccd,0xbe3b6ecf,0x3f7ac516,0xbe4dee60,0x3f79c79d,0xbe605c13,0x3f78b47b,0xbe72b651,0x3f778bc5,0xbe827dc0,0x3f764d97,0xbe8b9507,
0x3f7b14be,0xbe47c5c2,0x3f79c79d,0xbe605c13,0x3f7853f8,0xbe78cfcc,0x3f76ba07,0xbe888e93,0x3f74fa0b,0xbe94a031,0x3f731447,0xbea09ae5,0x3f710908,0xbeac7cd4,0x3f6ed89e,0xbeb8442a,
0x3f7853f8,0xbe78cfcc,0x3f764d97,0xbe8b9507,0x3f740bdd,0xbe9aa086,0x3f718f57,0xbea986c4,0x3f6ed89e,0xbeb8442a,0x3f6be858,0xbec6d529,0x3f68bf3c,0xbed53641,0x3f655e0b,0xbee363fa,
0x3f74fa0b,0xbe94a031,0x3f721352,0xbea68f12,0x3f6ed89e,0xbeb8442a,0x3f6b4b0c,0xbec9b953,0x3f676bd8,0xbedae880,0x3f633c5a,0xbeebcbbb,0x3f5ebe05,0xbefc5d27,0x3f59f26a,0xbf064b82,
0x3f710908,0xbeac7cd4,0x3f6d1c1d,0xbec1071e,0x3f68bf3c,0xbed53641,0x3f63f473,0xbee900b7,0x3f5ebe05,0xbefc5d27,0x3f591e6a,0xbf07a136,0x3f531849,0xbf10d3cd,0x3f4cae79,0xbf19c200,
0x3f6c835e,0xbec3ef15,0x3f676bd8,0xbedae880,0x3f61c598,0xbef15aea,0x3f5b941a,0xbf039c3d,0x3f54db31,0xbf0e39da,0x3f4d9f02,0xbf187fc0,0x3f45e403,0xbf226799,0x3f3daef9,0xbf2beb4a,
0x3f676bd8,0xbedae880,0x3f6106f2,0xbef41f07,0x3f59f26a,0xbf064b82,0x3f5233c6,0xbf121eb0,0x3f49d112,0xbf1d7fd1,0x3f40d0da,0xbf286605,0x3f373a23,0xbf32c8c9,0x3f2d1469,0xbf3ca003,
0x3f61c598,0xbef15aea,0x3f59f26a,0xbf064b82,0x3f514d3d,0xbf13682a,0x3f47de65,0xbf1ff6cb,0x3f3daef9,0xbf2beb4a,0x3f32c8c9,0xbf373a23,0x3f273656,0xbf41d870,0x3f1b02c6,0xbf4bbbf8,
0x3f5b941a,0xbf039c3d,0x3f5233c6,0xbf121eb0,0x3f47de65,0xbf1ff6cb,0x3f3ca003,0xbf2d1469,0x3f3085bb,0xbf396842,0x3f239da9,0xbf44e3f5,0x3f15f6d9,0xbf4f7a1f,0x3f07a136,0xbf591e6a,
0x3f54db31,0xbf0e39da,0x3f49d112,0xbf1d7fd1,0x3f3daef9,0xbf2beb4a,0x3f3085bb,0xbf396842,0x3f226799,0xbf45e403,0x3f13682a,0xbf514d3d,0x3f039c3d,0xbf5b941a,0x3ee63375,0xbf64aa59,
0x3f4d9f02,0xbf187fc0,0x3f40d0da,0xbf286605,0x3f32c8c9,0xbf373a23,0x3f239da9,0xbf44e3f5,0x3f13682a,0xbf514d3d,0x3f0242b1,0xbf5c61c7,0x3ee0924f,0xbf660f88,0x3ebb31a0,0xbf6e46be,
0x3f45e403,0xbf226799,0x3f373a23,0xbf32c8c9,0x3f273656,0xbf41d870,0x3f15f6d9,0xbf4f7a1f,0x3f039c3d,0xbf5b941a,0x3ee0924f,0xbf660f88,0x3eb8442a,0xbf6ed89e,0x3e8e9a22,0xbf75dec6,
0x3f3daef9,0xbf2beb4a,0x3f2d1469,0xbf3ca003,0x3f1b02c6,0xbf4bbbf8,0x3f07a136,0xbf591e6a,0x3ee63375,0xbf64aa59,0x3ebb31a0,0xbf6e46be,0x3e8e9a22,0xbf75dec6,0x3e419b37,0xbf7b61fc,
0x3f3504f3,0xbf3504f3,0x3f226799,0xbf45e403,0x3f0e39da,0xbf54db31,0x3ef15aea,0xbf61c598,0x3ec3ef15,0xbf6c835e,0x3e94a031,0xbf74fa0b,0x3e47c5c2,0xbf7b14be,0x3dc8bd36,0xbf7ec46d,
0x3f2beb4a,0xbf3daef9,0x3f173c07,0xbf4e8d90,0x3f00e7e4,0xbf5d2d53,0x3ed25a09,0xbf696591,0x3ea09ae5,0xbf731447,0x3e5a3997,0xbf7a1e84,0x3de1bc2e,0xbf7e70b0,0x3bc90f88,0xbf7ffec4,
0x3f226799,0xbf45e403,0x3f0b9a6b,0xbf5695e5,0x3ee63375,0xbf64aa59,0x3eb263ef,0xbf6ff573,0x3e78cfcc,0xbf7853f8,0x3e09cf86,0xbf7dabcc,0x3cc90ab0,0xbf7fec43,0xbdafb680,0xbf7f0e58,
0x3f187fc0,0xbf4d9f02,0x3eff17b2,0xbf5df6be,0x3ec9b953,0xbf6b4b0c,0x3e919ddd,0xbf756d97,0x3e2f10a2,0xbf7c3b28,0x3d621469,0xbf7f9c18,0xbd7b2b74,0xbf7f84ab,0xbe354098,0xbf7bf531,
0x3f0e39da,0xbf54db31,0x3ee63375,0xbf64aa59,0x3eac7cd4,0xbf710908,0x3e605c13,0xbf79c79d,0x3dc8bd36,0xbf7ec46d,0xbcc90ab0,0xbf7fec43,0xbe164083,0xbf7d3aac,0xbe888e93,0xbf76ba07,
0x3f039c3d,0xbf5b941a,0x3ecc9b8b,0xbf6aab7b,0x3e8e9a22,0xbf75dec6,0x3e1c76de,0xbf7cfe73,0x3cc90ab0,0xbf7fec43,0xbdd53db9,0xbf7e9bc9,0xbe6c9a7f,0xbf791298,0xbeb554ec,0xbf6f6830,
0x3ef15aea,0xbf61c598,0x3eb263ef,0xbf6ff573,0x3e605c13,0xbf79c79d,0x3dafb680,0xbf7f0e58,0xbd48fb30,0xbf7fb10f,0xbe3b6ecf,0xbf7baccd,0xbea09ae5,0xbf731447,0xbee0924f,0xbf660f88,
0x3edae880,0xbf676bd8,0x3e97a117,0xbf748422,0x3e22abb6,0xbf7cbfc9,0x3c96c9b6,0xbf7ff4e6,0xbdfab273,0xbf7e1324,0xbe8586ce,0xbf772417,0xbec9b953,0xbf6b4b0c,0xbf04f484,0xbf5ac450,
0x3ec3ef15,0xbf6c835e,0x3e78cfcc,0xbf7853f8,0x3dc8bd36,0xbf7ec46d,0xbd48fb30,0xbf7fb10f,0xbe47c5c2,0xbf7b14be,0xbeac7cd4,0xbf710908,0xbef15aea,0xbf61c598,0xbf187fc0,0xbf4d9f02,
0x3eac7cd4,0xbf710908,0x3e419b37,0xbf7b61fc,0x3d16c32c,0xbf7fd397,0xbdee3876,0xbf7e4323,0xbe888e93,0xbf76ba07,0xbed25a09,0xbf696591,0xbf0b9a6b,0xbf5695e5,0xbf2ac082,0xbf3ebc1b,
0x3e94a031,0xbf74fa0b,0x3e09cf86,0xbf7dabcc,0xbcc90ab0,0xbf7fec43,0xbe3b6ecf,0xbf7baccd,0xbeac7cd4,0xbf710908,0xbef6e0cb,0xbf604621,0xbf1d7fd1,0xbf49d112,0xbf3b8f3b,0xbf2e3bde,
0x3e78cfcc,0xbf7853f8,0x3da3308c,0xbf7f2f9d,0xbdafb680,0xbf7f0e58,0xbe7ee6e1,0xbf77f110,0xbecf7bca,0xbf6a09a7,0xbf0cead0,0xbf55b993,0xbf2e3bde,0xbf3b8f3b,0xbf4ac77f,0xbf1c420c,
0x3e47c5c2,0xbf7b14be,0x3cc90ab0,0xbf7fec43,0xbe164083,0xbf7d3aac,0xbea09ae5,0xbf731447,0xbef15aea,0xbf61c598,0xbf1d7fd1,0xbf49d112,0xbf3daef9,0xbf2beb4a,0xbf584853,0xbf08f59b,
0x3e164083,0xbf7d3aac,0xbcfb49ba,0xbf7fe129,0xbe541501,0xbf7a7302,0xbec1071e,0xbf6d1c1d,0xbf08f59b,0xbf584853,0xbf2d1469,0xbf3ca003,0xbf4bbbf8,0xbf1b02c6,0xbf63f473,0xbee900b7,
0x3dc8bd36,0xbf7ec46d,0xbdafb680,0xbf7f0e58,0xbe888e93,0xbf76ba07,0xbee0924f,0xbf660f88,0xbf187fc0,0xbf4d9f02,0xbf3b8f3b,0xbf2e3bde,0xbf584853,0xbf08f59b,0xbf6db293,0xbebe1d4a,
0x3d48fb30,0xbf7fb10f,0xbe1008b7,0xbf7d7474,0xbea68f12,0xbf721352,0xbeff17b2,0xbf5df6be,0xbf273656,0xbf41d870,0xbf48d8b3,0xbf1ebc12,0xbf633c5a,0xbeebcbbb,0xbf756d97,0xbe919ddd,
0x3f800000,0x0,0x3f800000,0x0,0x3f800000,0x0,0x3f800000,0x0,0x3f800000,0x0,0x3f800000,0x0,0x3f800000,0x0,0x3f800000,0x0,
0x3f7ec46d,0xbdc8bd36,0x3f7e9bc9,0xbdd53db9,0x3f7e70b0,0xbde1bc2e,0x3f7e4323,0xbdee3876,0x3f7e1324,0xbdfab273,0x3f7de0b1,0xbe039502,0x3f7dabcc,0xbe09cf86,0x3f7d7474,0xbe1008b7,
0x3f7b14be,0xbe47c5c2,0x3f7a7302,0xbe541501,0x3f79c79d,0xbe605c13,0x3f791298,0xbe6c9a7f,0x3f7853f8,0xbe78cfcc,0x3f778bc5,0xbe827dc0,0x3f76ba07,0xbe888e93,0x3f75dec6,0xbe8e9a22,
0x3f74fa0b,0xbe94a031,0x3f73913f,0xbe9d9e78,0x3f721352,0xbea68f12,0x3f708066,0xbeaf713a,0x3f6ed89e,0xbeb8442a,0x3f6d1c1d,0xbec1071e,0x3f6b4b0c,0xbec9b953,0x3f696591,0xbed25a09,
0x3f6c835e,0xbec3ef15,0x3f6a09a7,0xbecf7bca,0x3f676bd8,0xbedae880,0x3f64aa59,0xbee63375,0x3f61c598,0xbef15aea,0x3f5ebe05,0xbefc5d27,0x3f5b941a,0xbf039c3d,0x3f584853,0xbf08f59b,
0x3f61c598,0xbef15aea,0x3f5df6be,0xbeff17b2,0x3f59f26a,0xbf064b82,0x3f55b993,0xbf0cead0,0x3f514d3d,0xbf13682a,0x3f4cae79,0xbf19c200,0x3f47de65,0xbf1ff6cb,0x3f42de29,0xbf26050a,
0x3f54db31,0xbf0e39da,0x3f4f7a1f,0xbf15f6d9,0x3f49d112,0xbf1d7fd1,0x3f43e200,0xbf24d225,0x3f3daef9,0xbf2beb4a,0x3f373a23,0xbf32c8c9,0x3f3085bb,0xbf396842,0x3f299415,0xbf3fc767,
0x3f45e403,0xbf226799,0x3f3ebc1b,0xbf2ac082,0x3f373a23,0xbf32c8c9,0x3f2f61a5,0xbf3a7ca4,0x3f273656,0xbf41d870,0x3f1ebc12,0xbf48d8b3,0x3f15f6d9,0xbf4f7a1f,0x3f0cead0,0xbf55b993,
0x3f3504f3,0xbf3504f3,0x3f2beb4a,0xbf3daef9,0x3f226799,0xbf45e403,0x3f187fc0,0xbf4d9f02,0x3f0e39da,0xbf54db31,0x3f039c3d,0xbf5b941a,0x3ef15aea,0xbf61c598,0x3edae880,0xbf676bd8,
0x3f226799,0xbf45e403,0x3f173c07,0xbf4e8d90,0x3f0b9a6b,0xbf5695e5,0x3eff17b2,0xbf5df6be,0x3ee63375,0xbf64aa59,0x3ecc9b8b,0xbf6aab7b,0x3eb263ef,0xbf6ff573,0x3e97a117,0xbf748422,
0x3f0e39da,0xbf54db31,0x3f00e7e4,0xbf5d2d53,0x3ee63375,0xbf64aa59,0x3ec9b953,0xbf6b4b0c,0x3eac7cd4,0xbf710908,0x3e8e9a22,0xbf75dec6,0x3e605c13,0xbf79c79d,0x3e22abb6,0xbf7cbfc9,
0x3ef15aea,0xbf61c598,0x3ed25a09,0xbf696591,0x3eb263ef,0xbf6ff573,0x3e919ddd,0xbf756d97,0x3e605c13,0xbf79c79d,0x3e1c76de,0xbf7cfe73,0x3dafb680,0xbf7f0e58,0x3c96c9b6,0xbf7ff4e6,
0x3ec3ef15,0xbf6c835e,0x3ea09ae5,0xbf731447,0x3e78cfcc,0xbf7853f8,0x3e2f10a2,0xbf7c3b28,0x3dc8bd36,0xbf7ec46d,0x3cc90ab0,0xbf7fec43,0xbd48fb30,0xbf7fb10f,0xbdfab273,0xbf7e1324,
0x3e94a031,0xbf74fa0b,0x3e5a3997,0xbf7a1e84,0x3e09cf86,0xbf7dabcc,0x3d621469,0xbf7f9c18,0xbcc90ab0,0xbf7fec43,0xbdd53db9,0xbf7e9bc9,0xbe3b6ecf,0xbf7baccd,0xbe8586ce,0xbf772417,
0x3e47c5c2,0xbf7b14be,0x3de1bc2e,0xbf7e70b0,0x3cc90ab0,0xbf7fec43,0xbd7b2b74,0xbf7f84ab,0xbe164083,0xbf7d3aac,0xbe6c9a7f,0xbf791298,0xbea09ae5,0xbf731447,0xbec9b953,0xbf6b4b0c,
0x3dc8bd36,0xbf7ec46d,0x3bc90f88,0xbf7ffec4,0xbdafb680,0xbf7f0e58,0xbe354098,0xbf7bf531,0xbe888e93,0xbf76ba07,0xbeb554ec,0xbf6f6830,0xbee0924f,0xbf660f88,0xbf04f484,0xbf5ac450,
0x0,0xbf800000,0xbdc8bd36,0xbf7ec46d,0xbe47c5c2,0xbf7b14be,0xbe94a031,0xbf74fa0b,0xbec3ef15,0xbf6c835e,0xbef15aea,0xbf61c598,0xbf0e39da,0xbf54db31,0xbf226799,0xbf45e403,
0xbdc8bd36,0xbf7ec46d,0xbe4dee60,0xbf7ac516,0xbe9aa086,0xbf740bdd,0xbecc9b8b,0xbf6aab7b,0xbefc5d27,0xbf5ebe05,0xbf14b039,0xbf5064af,0xbf299415,0xbf3fc767,0xbf3ca003,0xbf2d1469,
0xbe47c5c2,0xbf7b14be,0xbe9aa086,0xbf740bdd,0xbecf7bca,0xbf6a09a7,0xbf00e7e4,0xbf5d2d53,0xbf187fc0,0xbf4d9f02,0xbf2e3bde,0xbf3b8f3b,0xbf41d870,0xbf273656,0xbf531849,0xbf10d3cd,
0xbe94a031,0xbf74fa0b,0xbecc9b8b,0xbf6aab7b,0xbf00e7e4,0xbf5d2d53,0xbf19c200,0xbf4cae79,0xbf3085bb,0xbf396842,0xbf44e3f5,0xbf239da9,0xbf5695e5,0xbf0b9a6b,0xbf655e0b,0xbee363fa,
0xbec3ef15,0xbf6c835e,0xbefc5d27,0xbf5ebe05,0xbf187fc0,0xbf4d9f02,0xbf3085bb,0xbf396842,0xbf45e403,0xbf226799,0xbf584853,0xbf08f59b,0xbf676bd8,0xbedae880,0xbf731447,0xbea09ae5,
0xbef15aea,0xbf61c598,0xbf14b039,0xbf5064af,0xbf2e3bde,0xbf3b8f3b,0xbf44e3f5,0xbf239da9,0xbf584853,0xbf08f59b,0xbf6816a8,0xbed8106b,0xbf740bdd,0xbe9aa086,0xbf7bf531,0xbe354098,
0xbf0e39da,0xbf54db31,0xbf299415,0xbf3fc767,0xbf41d870,0xbf273656,0xbf5695e5,0xbf0b9a6b,0xbf676bd8,0xbedae880,0xbf740bdd,0xbe9aa086,0xbf7c3b28,0xbe2f10a2,0xbf7fd397,0xbd16c32c,
0xbf226799,0xbf45e403,0xbf3ca003,0xbf2d1469,0xbf531849,0xbf10d3cd,0xbf655e0b,0xbee363fa,0xbf731447,0xbea09ae5,0xbf7bf531,0xbe354098,0xbf7fd397,0xbd16c32c,0xbf7e9bc9,0x3dd53db9,
0xbf3504f3,0xbf3504f3,0xbf4d9f02,0xbf187fc0,0xbf61c598,0xbef15aea,0xbf710908,0xbeac7cd4,0xbf7b14be,0xbe47c5c2,0xbf7fb10f,0xbd48fb30,0xbf7ec46d,0x3dc8bd36,0xbf7853f8,0x3e78cfcc,
0xbf45e403,0xbf226799,0xbf5c61c7,0xbf0242b1,0xbf6db293,0xbebe1d4a,0xbf796e4e,0xbe667c66,0xbf7f4e6d,0xbd96a905,0xbf7f2f9d,0x3da3308c,0xbf791298,0x3e6c9a7f,0xbf6d1c1d,0x3ec1071e,
0xbf54db31,0xbf0e39da,0xbf68bf3c,0xbed53641,0xbf76ba07,0xbe888e93,0xbf7e70b0,0xbde1bc2e,0xbf7fb10f,0x3d48fb30,0xbf7a7302,0x3e541501,0xbf6ed89e,0x3eb8442a,0xbf5d2d53,0x3f00e7e4,
0xbf61c598,0xbef15aea,0xbf7294f8,0xbea395c5,0xbf7cbfc9,0xbe22abb6,0xbf7ffec4,0x3bc90f88,0xbf7c3b28,0x3e2f10a2,0xbf718f57,0x3ea986c4,0xbf604621,0x3ef6e0cb,0xbf48d8b3,0x3f1ebc12,
0xbf6c835e,0xbec3ef15,0xbf79c79d,0xbe605c13,0xbf7fb10f,0xbd48fb30,0xbf7e1324,0x3dfab273,0xbf74fa0b,0x3e94a031,0xbf64aa59,0x3ee63375,0xbf4d9f02,0x3f187fc0,0xbf3085bb,0x3f396842,
0xbf74fa0b,0xbe94a031,0xbf7e4323,0xbdee3876,0xbf7f84ab,0x3d7b2b74,0xbf78b47b,0x3e72b651,0xbf6a09a7,0x3ecf7bca,0xbf53fac3,0x3f0f8784,0xbf373a23,0x3f32c8c9,0xbf14b039,0x3f5064af,
0xbf7b14be,0xbe47c5c2,0xbf7ffb11,0xbc490e90,0xbf7c3b28,0x3e2f10a2,0xbf6ff573,0x3eb263ef,0xbf5b941a,0x3f039c3d,0xbf3fc767,0x3f299415,0xbf1d7fd1,0x3f49d112,0xbeebcbbb,0x3f633c5a,
0xbf7ec46d,0xbdc8bd36,0xbf7eea9d,0x3dbc3ac3,0xbf75dec6,0x3e8e9a22,0xbf63f473,0x3ee900b7,0xbf49d112,0x3f1d7fd1,0xbf286605,0x3f40d0da,0xbf00e7e4,0x3f5d2d53,0xbea986c4,0x3f718f57,
0x3f800000,0x0,0x3f800000,0x0,0x3f800000,0x0,0x3f800000,0x0,0x3f800000,0x0,0x3f800000,0x0,0x3f800000,0x0,0x3f800000,0x0,
0x3f7d3aac,0xbe164083,0x3f7cfe73,0xbe1c76de,0x3f7cbfc9,0xbe22abb6,0x3f7c7eb0,0xbe28defc,0x3f7c3b28,0xbe2f10a2,0x3f7bf531,0xbe354098,0x3f7baccd,0xbe3b6ecf,0x3f7b61fc,0xbe419b37,
0x3f74fa0b,0xbe94a031,0x3f740bdd,0xbe9aa086,0x3f731447,0xbea09ae5,0x3f721352,0xbea68f12,0x3f710908,0xbeac7cd4,0x3f6ff573,0xbeb263ef,0x3f6ed89e,0xbeb8442a,0x3f6db293,0xbebe1d4a,
0x3f676bd8,0xbedae880,0x3f655e0b,0xbee363fa,0x3f633c5a,0xbeebcbbb,0x3f6106f2,0xbef41f07,0x3f5ebe05,0xbefc5d27,0x3f5c61c7,0xbf0242b1,0x3f59f26a,0xbf064b82,0x3f577026,0xbf0a48ad,
0x3f54db31,0xbf0e39da,0x3f514d3d,0xbf13682a,0x3f4d9f02,0xbf187fc0,0x3f49d112,0xbf1d7fd1,0x3f45e403,0xbf226799,0x3f41d870,0xbf273656,0x3f3daef9,0xbf2beb4a,0x3f396842,0xbf3085bb,
0x3f3daef9,0xbf2beb4a,0x3f385216,0xbf31a81d,0x3f32c8c9,0xbf373a23,0x3f2d1469,0xbf3ca003,0x3f273656,0xbf41d870,0x3f212ff9,0xbf46e22a,0x3f1b02c6,0xbf4bbbf8,0x3f14b039,0xbf5064af,
0x3f226799,0xbf45e403,0x3f1b02c6,0xbf4bbbf8,0x3f13682a,0xbf514d3d,0x3f0b9a6b,0xbf5695e5,0x3f039c3d,0xbf5b941a,0x3ef6e0cb,0xbf604621,0x3ee63375,0xbf64aa59,0x3ed53641,0xbf68bf3c,
0x3f039c3d,0xbf5b941a,0x3ef41f07,0xbf6106f2,0x3ee0924f,0xbf660f88,0x3ecc9b8b,0xbf6aab7b,0x3eb8442a,0xbf6ed89e,0x3ea395c5,0xbf7294f8,0x3e8e9a22,0xbf75dec6,0x3e72b651,0xbf78b47b,
0x3ec3ef15,0xbf6c835e,0x3eac7cd4,0xbf710908,0x3e94a031,0xbf74fa0b,0x3e78cfcc,0xbf7853f8,0x3e47c5c2,0xbf7b14be,0x3e164083,0xbf7d3aac,0x3dc8bd36,0xbf7ec46d,0x3d48fb30,0xbf7fb10f,
0x3e78cfcc,0xbf7853f8,0x3e419b37,0xbf7b61fc,0x3e09cf86,0xbf7dabcc,0x3da3308c,0xbf7f2f9d,0x3cc90ab0,0xbf7fec43,0xbcfb49ba,0xbf7fe129,0xbdafb680,0xbf7f0e58,0xbe1008b7,0xbf7d7474,
0x3dc8bd36,0xbf7ec46d,0x3d16c32c,0xbf7fd397,0xbcc90ab0,0xbf7fec43,0xbdafb680,0xbf7f0e58,0xbe164083,0xbf7d3aac,0xbe541501,0xbf7a7302,0xbe888e93,0xbf76ba07,0xbea68f12,0xbf721352,
0xbd48fb30,0xbf7fb10f,0xbdee3876,0xbf7e4323,0xbe3b6ecf,0xbf7baccd,0xbe7ee6e1,0xbf77f110,0xbea09ae5,0xbf731447,0xbec1071e,0xbf6d1c1d,0xbee0924f,0xbf660f88,0xbeff17b2,0xbf5df6be,
0xbe47c5c2,0xbf7b14be,0xbe888e93,0xbf76ba07,0xbeac7cd4,0xbf710908,0xbecf7bca,0xbf6a09a7,0xbef15aea,0xbf61c598,0xbf08f59b,0xbf584853,0xbf187fc0,0xbf4d9f02,0xbf273656,0xbf41d870,
0xbeac7cd4,0xbf710908,0xbed25a09,0xbf696591,0xbef6e0cb,0xbf604621,0xbf0cead0,0xbf55b993,0xbf1d7fd1,0xbf49d112,0xbf2d1469,0xbf3ca003,0xbf3b8f3b,0xbf2e3bde,0xbf48d8b3,0xbf1ebc12,
0xbef15aea,0xbf61c598,0xbf0b9a6b,0xbf5695e5,0xbf1d7fd1,0xbf49d112,0xbf2e3bde,0xbf3b8f3b,0xbf3daef9,0xbf2beb4a,0xbf4bbbf8,0xbf1b02c6,0xbf584853,0xbf08f59b,0xbf633c5a,0xbeebcbbb,
0xbf187fc0,0xbf4d9f02,0xbf2ac082,0xbf3ebc1b,0xbf3b8f3b,0xbf2e3bde,0xbf4ac77f,0xbf1c420c,0xbf584853,0xbf08f59b,0xbf63f473,0xbee900b7,0xbf6db293,0xbebe1d4a,0xbf756d97,0xbe919ddd,
0xbf3504f3,0xbf3504f3,0xbf45e403,0xbf226799,0xbf54db31,0xbf0e39da,0xbf61c598,0xbef15aea,0xbf6c835e,0xbec3ef15,0xbf74fa0b,0xbe94a031,0xbf7b14be,0xbe47c5c2,0xbf7ec46d,0xbdc8bd36,
0xbf4d9f02,0xbf187fc0,0xbf5c61c7,0xbf0242b1,0xbf68bf3c,0xbed53641,0xbf7294f8,0xbea395c5,0xbf79c79d,0xbe605c13,0xbf7e4323,0xbdee3876,0xbf7ffb11,0xbc490e90,0xbf7eea9d,0x3dbc3ac3,
0xbf61c598,0xbef15aea,0xbf6db293,0xbebe1d4a,0xbf76ba07,0xbe888e93,0xbf7cbfc9,0xbe22abb6,0xbf7fb10f,0xbd48fb30,0xbf7f84ab,0x3d7b2b74,0xbf7c3b28,0x3e2f10a2,0xbf75dec6,0x3e8e9a22,
0xbf710908,0xbeac7cd4,0xbf796e4e,0xbe667c66,0xbf7e70b0,0xbde1bc2e,0xbf7ffec4,0x3bc90f88,0xbf7e1324,0x3dfab273,0xbf78b47b,0x3e72b651,0xbf6ff573,0x3eb263ef,0xbf63f473,0x3ee900b7,
0xbf7b14be,0xbe47c5c2,0xbf7f4e6d,0xbd96a905,0xbf7fb10f,0x3d48fb30,0xbf7c3b28,0x3e2f10a2,0xbf74fa0b,0x3e94a031,0xbf6a09a7,0x3ecf7bca,0xbf5b941a,0x3f039c3d,0xbf49d112,0x3f1d7fd1,
0xbf7fb10f,0xbd48fb30,0xbf7f2f9d,0x3da3308c,0xbf7a7302,0x3e541501,0xbf718f57,0x3ea986c4,0xbf64aa59,0x3ee63375,0xbf53fac3,0x3f0f8784,0xbf3fc767,0x3f299415,0xbf286605,0x3f40d0da,
0xbf7ec46d,0x3dc8bd36,0xbf791298,0x3e6c9a7f,0xbf6ed89e,0x3eb8442a,0xbf604621,0x3ef6e0cb,0xbf4d9f02,0x3f187fc0,0xbf373a23,0x3f32c8c9,0xbf1d7fd1,0x3f49d112,0xbf00e7e4,0x3f5d2d53,
0xbf7853f8,0x3e78cfcc,0xbf6d1c1d,0x3ec1071e,0xbf5d2d53,0x3f00e7e4,0xbf48d8b3,0x3f1ebc12,0xbf3085bb,0x3f396842,0xbf14b039,0x3f5064af,0xbeebcbbb,0x3f633c5a,0xbea986c4,0x3f718f57,
0xbf6c835e,0x3ec3ef15,0xbf5b941a,0x3f039c3d,0xbf45e403,0x3f226799,0xbf2beb4a,0x3f3daef9,0xbf0e39da,0x3f54db31,0xbedae880,0x3f676bd8,0xbe94a031,0x3f74fa0b,0xbe164083,0x3f7d3aac,
0xbf5b941a,0x3f039c3d,0xbf44e3f5,0x3f239da9,0xbf299415,0x3f3fc767,0xbf0a48ad,0x3f577026,0xbecf7bca,0x3f6a09a7,0xbe8586ce,0x3f772417,0xbde1bc2e,0x3f7e70b0,0x3d2fe007,0x3f7fc38f,
0xbf45e403,0x3f226799,0xbf299415,0x3f3fc767,0xbf08f59b,0x3f584853,0xbec9b953,0x3f6b4b0c,0xbe78cfcc,0x3f7853f8,0xbdafb680,0x3f7f0e58,0x3d96a905,0x3f7f4e6d,0x3e6c9a7f,0x3f791298,
0xbf2beb4a,0x3f3daef9,0xbf0a48ad,0x3f577026,0xbec9b953,0x3f6b4b0c,0xbe72b651,0x3f78b47b,0xbd96a905,0x3f7f4e6d,0x3dbc3ac3,0x3f7eea9d,0x3e827dc0,0x3f778bc5,0x3ed25a09,0x3f696591,
0xbf0e39da,0x3f54db31,0xbecf7bca,0x3f6a09a7,0xbe78cfcc,0x3f7853f8,0xbd96a905,0x3f7f4e6d,0x3dc8bd36,0x3f7ec46d,0x3e888e93,0x3f76ba07,0x3edae880,0x3f676bd8,0x3f13682a,0x3f514d3d,
0xbedae880,0x3f676bd8,0xbe8586ce,0x3f772417,0xbdafb680,0x3f7f0e58,0x3dbc3ac3,0x3f7eea9d,0x3e888e93,0x3f76ba07,0x3eddbe79,0x3f66becc,0x3f15f6d9,0x3f4f7a1f,0x3f385216,0x3f31a81d,
0xbe94a031,0x3f74fa0b,0xbde1bc2e,0x3f7e70b0,0x3d96a905,0x3f7f4e6d,0x3e827dc0,0x3f778bc5,0x3edae880,0x3f676bd8,0x3f15f6d9,0x3f4f7a1f,0x3f396842,0x3f3085bb,0x3f5695e5,0x3f0b9a6b,
0xbe164083,0x3f7d3aac,0x3d2fe007,0x3f7fc38f,0x3e6c9a7f,0x3f791298,0x3ed25a09,0x3f696591,0x3f13682a,0x3f514d3d,0x3f385216,0x3f31a81d,0x3f5695e5,0x3f0b9a6b,0x3f6d1c1d,0x3ec1071e,
0xbd803d80,0x80003e00,0x80003e00,0x80003e00,0x80003e00,0x80003e00,0x80003e00,0x80003e00,0x80003e00,0x80003e00,0x80003e00,0x80003e00,0x80003e00,0x80003e00,0x80003e00,0x80003e00,
0x3d803d80,0x3cc83dfb,0x3e000000,0x3dfbbcc8,0x3d443ded,0x3d8e3dd5,0x3dedbd44,0x3dd5bd8e,0x3db53db5,0x3dd53d8e,0x3db5bdb5,0x3d8ebdd5,0x3ded3d44,0x3dfb3cc8,0x3d44bded,0x3cc8bdfb,
0xbd803d80,0x3d443ded,0x8000be00,0xbd44bded,0x3db53db5,0x3ded3d44,0xbdb5bdb5,0xbdedbd44,0x3e000000,0x3dedbd44,0xbe000000,0xbded3d44,0x3db5bdb5,0x3d44bded,0xbdb53db5,0xbd443ded,
0x3d803d80,0x3d8e3dd5,0xbe000000,0xbdd53d8e,0x3ded3d44,0x3dfbbcc8,0xbd443ded,0x3cc83dfb,0x3db5bdb5,0x3cc8bdfb,0x3db53db5,0x3dfb3cc8,0xbd44bded,0xbdd5bd8e,0x3dedbd44,0x3d8ebdd5,
0xbd803d80,0x3db53db5,0x80003e00,0x3db53db5,0x3e000000,0x3db5bdb5,0x3e000000,0x3db5bdb5,0x8000be00,0xbdb5bdb5,0x8000be00,0xbdb5bdb5,0xbe000000,0xbdb53db5,0xbe000000,0xbdb53db5,
0x3d803d80,0x3dd53d8e,0x3e000000,0x3d8ebdd5,0x3dedbd44,0x3cc8bdfb,0xbd44bded,0xbdfbbcc8,0xbdb5bdb5,0xbdfb3cc8,0xbdb53db5,0x3cc83dfb,0xbd443ded,0x3d8e3dd5,0x3ded3d44,0x3dd5bd8e,
0xbd803d80,0x3ded3d44,0x8000be00,0xbdedbd44,0x3db5bdb5,0xbd44bded,0xbdb53db5,0x3d443ded,0xbe000000,0xbd443ded,0x3e000000,0x3d44bded,0x3db53db5,0x3dedbd44,0xbdb5bdb5,0xbded3d44,
0x3d803d80,0x3dfb3cc8,0xbe000000,0xbcc83dfb,0x3d44bded,0xbdd5bd8e,0x3ded3d44,0x3d8ebdd5,0xbdb53db5,0x3d8e3dd5,0xbdb5bdb5,0xbdd53d8e,0x3dedbd44,0xbcc8bdfb,0x3d443ded,0x3dfbbcc8,
0xbd803d80,0x3e000000,0x80003e00,0x3e000000,0x8000be00,0xbe000000,0x8000be00,0xbe000000,0x80003e00,0x3e000000,0x80003e00,0x3e000000,0x8000be00,0xbe000000,0x8000be00,0xbe000000,
0x3d803d80,0x3dfbbcc8,0x3e000000,0xbcc8bdfb,0xbd44bded,0xbdd53d8e,0xbded3d44,0x3d8e3dd5,0x3db53db5,0x3d8ebdd5,0x3db5bdb5,0xbdd5bd8e,0xbdedbd44,0xbcc83dfb,0xbd443ded,0x3dfb3cc8,
0xbd803d80,0x3dedbd44,0x8000be00,0xbded3d44,0xbdb5bdb5,0xbd443ded,0x3db53db5,0x3d44bded,0x3e000000,0xbd44bded,0xbe000000,0x3d443ded,0xbdb53db5,0x3ded3d44,0x3db5bdb5,0xbdedbd44,
0x3d803d80,0x3dd5bd8e,0xbe000000,0x3d8e3dd5,0xbdedbd44,0x3cc83dfb,0x3d44bded,0xbdfb3cc8,0x3db5bdb5,0xbdfbbcc8,0x3db53db5,0x3cc8bdfb,0x3d443ded,0x3d8ebdd5,0xbded3d44,0x3dd53d8e,
0xbd803d80,0x3db5bdb5,0x80003e00,0x3db5bdb5,0xbe000000,0x3db53db5,0xbe000000,0x3db53db5,0x8000be00,0xbdb53db5,0x8000be00,0xbdb53db5,0x3e000000,0xbdb5bdb5,0x3e000000,0xbdb5bdb5,
0x3d803d80,0x3d8ebdd5,0x3e000000,0xbdd5bd8e,0xbded3d44,0x3dfb3cc8,0x3d443ded,0x3cc8bdfb,0xbdb5bdb5,0x3cc83dfb,0xbdb53db5,0x3dfbbcc8,0x3d44bded,0xbdd53d8e,0xbdedbd44,0x3d8e3dd5,
0xbd803d80,0x3d44bded,0x8000be00,0xbd443ded,0xbdb53db5,0x3dedbd44,0x3db5bdb5,0xbded3d44,0xbe000000,0x3ded3d44,0x3e000000,0xbdedbd44,0xbdb5bdb5,0x3d443ded,0x3db53db5,0xbd44bded,
0x3d803d80,0x3cc8bdfb,0xbe000000,0x3dfb3cc8,0xbd443ded,0x3d8ebdd5,0xbdedbd44,0x3dd53d8e,0xbdb53db5,0x3dd5bd8e,0xbdb5bdb5,0x3d8e3dd5,0xbded3d44,0x3dfbbcc8,0xbd44bded,0x3cc83dfb,
0xbd803d80,0x8000be00,0x80003e00,0x8000be00,0x80003e00,0x8000be00,0x80003e00,0x8000be00,0x80003e00,0x8000be00,0x80003e00,0x8000be00,0x80003e00,0x8000be00,0x80003e00,0x8000be00,
0x3d803d80,0xbcc8bdfb,0x3e000000,0xbdfb3cc8,0x3d443ded,0xbd8ebdd5,0x3dedbd44,0xbdd53d8e,0x3db53db5,0xbdd5bd8e,0x3db5bdb5,0xbd8e3dd5,0x3ded3d44,0xbdfbbcc8,0x3d44bded,0xbcc83dfb,
0xbd803d80,0xbd44bded,0x8000be00,0x3d443ded,0x3db53db5,0xbdedbd44,0xbdb5bdb5,0x3ded3d44,0x3e000000,0xbded3d44,0xbe000000,0x3dedbd44,0x3db5bdb5,0xbd443ded,0xbdb53db5,0x3d44bded,
0x3d803d80,0xbd8ebdd5,0xbe000000,0x3dd5bd8e,0x3ded3d44,0xbdfb3cc8,0xbd443ded,0xbcc8bdfb,0x3db5bdb5,0xbcc83dfb,0x3db53db5,0xbdfbbcc8,0xbd44bded,0x3dd53d8e,0x3dedbd44,0xbd8e3dd5,
0xbd803d80,0xbdb5bdb5,0x80003e00,0xbdb5bdb5,0x3e000000,0xbdb53db5,0x3e000000,0xbdb53db5,0x8000be00,0x3db53db5,0x8000be00,0x3db53db5,0xbe000000,0x3db5bdb5,0xbe000000,0x3db5bdb5,
0x3d803d80,0xbdd5bd8e,0x3e000000,0xbd8e3dd5,0x3dedbd44,0xbcc83dfb,0xbd44bded,0x3dfb3cc8,0xbdb5bdb5,0x3dfbbcc8,0xbdb53db5,0xbcc8bdfb,0xbd443ded,0xbd8ebdd5,0x3ded3d44,0xbdd53d8e,
0xbd803d80,0xbdedbd44,0x8000be00,0x3ded3d44,0x3db5bdb5,0x3d443ded,0xbdb53db5,0xbd44bded,0xbe000000,0x3d44bded,0x3e000000,0xbd443ded,0x3db53db5,0xbded3d44,0xbdb5bdb5,0x3dedbd44,
0x3d803d80,0xbdfbbcc8,0xbe000000,0x3cc8bdfb,0x3d44bded,0x3dd53d8e,0x3ded3d44,0xbd8e3dd5,0xbdb53db5,0xbd8ebdd5,0xbdb5bdb5,0x3dd5bd8e,0x3dedbd44,0x3cc83dfb,0x3d443ded,0xbdfb3cc8,
0xbd803d80,0xbe000000,0x80003e00,0xbe000000,0x8000be00,0x3e000000,0x8000be00,0x3e000000,0x80003e00,0xbe000000,0x80003e00,0xbe000000,0x8000be00,0x3e000000,0x8000be00,0x3e000000,
0x3d803d80,0xbdfb3cc8,0x3e000000,0x3cc83dfb,0xbd44bded,0x3dd5bd8e,0xbded3d44,0xbd8ebdd5,0x3db53db5,0xbd8e3dd5,0x3db5bdb5,0x3dd53d8e,0xbdedbd44,0x3cc8bdfb,0xbd443ded,0xbdfbbcc8,
0xbd803d80,0xbded3d44,0x8000be00,0x3dedbd44,0xbdb5bdb5,0x3d44bded,0x3db53db5,0xbd443ded,0x3e000000,0x3d443ded,0xbe000000,0xbd44bded,0xbdb53db5,0xbdedbd44,0x3db5bdb5,0x3ded3d44,
0x3d803d80,0xbdd53d8e,0xbe000000,0xbd8ebdd5,0xbdedbd44,0xbcc8bdfb,0x3d44bded,0x3dfbbcc8,0x3db5bdb5,0x3dfb3cc8,0x3db53db5,0xbcc83dfb,0x3d443ded,0xbd8e3dd5,0xbded3d44,0xbdd5bd8e,
0xbd803d80,0xbdb53db5,0x80003e00,0xbdb53db5,0xbe000000,0xbdb5bdb5,0xbe000000,0xbdb5bdb5,0x8000be00,0x3db5bdb5,0x8000be00,0x3db5bdb5,0x3e000000,0x3db53db5,0x3e000000,0x3db53db5,
0x3d803d80,0xbd8e3dd5,0x3e000000,0x3dd53d8e,0xbded3d44,0xbdfbbcc8,0x3d443ded,0xbcc83dfb,0xbdb5bdb5,0xbcc8bdfb,0xbdb53db5,0xbdfb3cc8,0x3d44bded,0x3dd5bd8e,0xbdedbd44,0xbd8ebdd5,
0xbd803d80,0xbd443ded,0x8000be00,0x3d44bded,0xbdb53db5,0xbded3d44,0x3db5bdb5,0x3dedbd44,0xbe000000,0xbdedbd44,0x3e000000,0x3ded3d44,0xbdb5bdb5,0xbd44bded,0x3db53db5,0x3d443ded,
0x3d803d80,0xbcc83dfb,0xbe000000,0xbdfbbcc8,0xbd443ded,0xbd8e3dd5,0xbdedbd44,0xbdd5bd8e,0xbdb53db5,0xbdd53d8e,0xbdb5bdb5,0xbd8ebdd5,0xbded3d44,0xbdfb3cc8,0xbd44bded,0xbcc8bdfb,
0x80003e00,0x80003e00,0x80003e00,0x80003e00,0x80003e00,0x80003e00,0x80003e00,0x80003e00,0x80003e00,0x80003e00,0x80003e00,0x80003e00,0x80003e00,0x80003e00,0x80003e00,0x80003e00,
0x3c493dff,0x3d153df5,0x3dffbc49,0x3df5bd15,0x3d713de2,0x3da23dc6,0x3de2bd71,0x3dc6bda2,0x3dc63da2,0x3de23d71,0x3da2bdc6,0x3d71bde2,0x3df53d15,0x3dff3c49,0x3d15bdf5,0x3c49bdff,
0x3cc83dfb,0x3d8e3dd5,0xbcc8bdfb,0xbd8ebdd5,0x3dd53d8e,0x3dfb3cc8,0xbdd5bd8e,0xbdfbbcc8,0x3dfbbcc8,0x3dd5bd8e,0xbdfb3cc8,0xbdd53d8e,0x3d8ebdd5,0x3cc8bdfb,0xbd8e3dd5,0xbcc83dfb,
0x3d153df5,0x3dc63da2,0xbdf53d15,0xbda23dc6,0x3dff3c49,0x3de2bd71,0xbc493dff,0x3d713de2,0x3d71bde2,0xbc49bdff,0x3de23d71,0x3dffbc49,0xbda2bdc6,0xbdf5bd15,0x3dc6bda2,0x3d15bdf5,
0x3d443ded,0x3ded3d44,0x3d443ded,0x3ded3d44,0x3dedbd44,0x3d44bded,0x3dedbd44,0x3d44bded,0xbd44bded,0xbdedbd44,0xbd44bded,0xbdedbd44,0xbded3d44,0xbd443ded,0xbded3d44,0xbd443ded,
0x3d713de2,0x3dff3c49,0x3de2bd71,0x3c49bdff,0x3da2bdc6,0xbd15bdf5,0xbdc6bda2,0xbdf53d15,0xbdf5bd15,0xbdc63da2,0xbd153df5,0x3da23dc6,0x3c493dff,0x3de23d71,0x3dffbc49,0x3d71bde2,
0x3d8e3dd5,0x3dfbbcc8,0xbd8ebdd5,0xbdfb3cc8,0x3cc8bdfb,0xbdd5bd8e,0xbcc83dfb,0x3dd53d8e,0xbdd53d8e,0x3cc83dfb,0x3dd5bd8e,0xbcc8bdfb,0x3dfb3cc8,0x3d8ebdd5,0xbdfbbcc8,0xbd8e3dd5,
0x3da23dc6,0x3de2bd71,0xbdc63da2,0x3d713de2,0xbd15bdf5,0xbdff3c49,0x3df5bd15,0xbc49bdff,0xbc493dff,0x3df53d15,0xbdffbc49,0xbd153df5,0x3d71bde2,0xbdc6bda2,0x3de23d71,0x3da2bdc6,
0x3db53db5,0x3db5bdb5,0x3db53db5,0x3db5bdb5,0xbdb5bdb5,0xbdb53db5,0xbdb5bdb5,0xbdb53db5,0x3db53db5,0x3db5bdb5,0x3db53db5,0x3db5bdb5,0xbdb5bdb5,0xbdb53db5,0xbdb5bdb5,0xbdb53db5,
0x3dc63da2,0x3d71bde2,0x3da2bdc6,0xbde2bd71,0xbdf5bd15,0xbc493dff,0xbd153df5,0x3dff3c49,0x3dffbc49,0xbd15bdf5,0xbc49bdff,0xbdf53d15,0xbde23d71,0x3da23dc6,0x3d713de2,0x3dc6bda2,
0x3dd53d8e,0x3cc8bdfb,0xbdd5bd8e,0xbcc83dfb,0xbdfb3cc8,0x3d8e3dd5,0x3dfbbcc8,0xbd8ebdd5,0x3d8ebdd5,0xbdfbbcc8,0xbd8e3dd5,0x3dfb3cc8,0x3cc83dfb,0x3dd5bd8e,0xbcc8bdfb,0xbdd53d8e,
0x3de23d71,0xbc49bdff,0xbd713de2,0x3dffbc49,0xbdc63da2,0x3df53d15,0xbda2bdc6,0xbd153df5,0xbd15bdf5,0xbda23dc6,0x3df5bd15,0xbdc6bda2,0x3dff3c49,0xbd71bde2,0xbc493dff,0x3de2bd71,
0x3ded3d44,0xbd44bded,0x3ded3d44,0xbd44bded,0xbd443ded,0x3dedbd44,0xbd443ded,0x3dedbd44,0xbdedbd44,0x3d443ded,0xbdedbd44,0x3d443ded,0x3d44bded,0xbded3d44,0x3d44bded,0xbded3d44,
0x3df53d15,0xbda2bdc6,0x3d15bdf5,0xbdc63da2,0x3c493dff,0x3d71bde2,0x3dffbc49,0xbde2bd71,0xbde23d71,0x3dff3c49,0x3d713de2,0x3c49bdff,0xbdc6bda2,0x3d153df5,0xbda23dc6,0x3df5bd15,
0x3dfb3cc8,0xbdd5bd8e,0xbdfbbcc8,0x3dd53d8e,0x3d8e3dd5,0xbcc8bdfb,0xbd8ebdd5,0x3cc83dfb,0xbcc83dfb,0x3d8ebdd5,0x3cc8bdfb,0xbd8e3dd5,0xbdd53d8e,0x3dfbbcc8,0x3dd5bd8e,0xbdfb3cc8,
0x3dff3c49,0xbdf5bd15,0xbc493dff,0x3d15bdf5,0x3de23d71,0xbdc6bda2,0xbd713de2,0x3da2bdc6,0x3da23dc6,0xbd71bde2,0xbdc63da2,0x3de2bd71,0x3d153df5,0xbc49bdff,0xbdf53d15,0x3dffbc49,
0x3e000000,0xbe000000,0x3e000000,0xbe000000,0x3e000000,0xbe000000,0x3e000000,0xbe000000,0x3e000000,0xbe000000,0x3e000000,0xbe000000,0x3e000000,0xbe000000,0x3e000000,0xbe000000,
0x3dffbc49,0xbdf53d15,0xbc49bdff,0x3d153df5,0x3de2bd71,0xbdc63da2,0xbd71bde2,0x3da23dc6,0x3da2bdc6,0xbd713de2,0xbdc6bda2,0x3de23d71,0x3d15bdf5,0xbc493dff,0xbdf5bd15,0x3dff3c49,
0x3dfbbcc8,0xbdd53d8e,0xbdfb3cc8,0x3dd5bd8e,0x3d8ebdd5,0xbcc83dfb,0xbd8e3dd5,0x3cc8bdfb,0xbcc8bdfb,0x3d8e3dd5,0x3cc83dfb,0xbd8ebdd5,0xbdd5bd8e,0x3dfb3cc8,0x3dd53d8e,0xbdfbbcc8,
0x3df5bd15,0xbda23dc6,0x3d153df5,0xbdc6bda2,0x3c49bdff,0x3d713de2,0x3dff3c49,0xbde23d71,0xbde2bd71,0x3dffbc49,0x3d71bde2,0x3c493dff,0xbdc63da2,0x3d15bdf5,0xbda2bdc6,0x3df53d15,
0x3dedbd44,0xbd443ded,0x3dedbd44,0xbd443ded,0xbd44bded,0x3ded3d44,0xbd44bded,0x3ded3d44,0xbded3d44,0x3d44bded,0xbded3d44,0x3d44bded,0x3d443ded,0xbdedbd44,0x3d443ded,0xbdedbd44,
0x3de2bd71,0xbc493dff,0xbd71bde2,0x3dff3c49,0xbdc6bda2,0x3df5bd15,0xbda23dc6,0xbd15bdf5,0xbd153df5,0xbda2bdc6,0x3df53d15,0xbdc63da2,0x3dffbc49,0xbd713de2,0xbc49bdff,0x3de23d71,
0x3dd5bd8e,0x3cc83dfb,0xbdd53d8e,0xbcc8bdfb,0xbdfbbcc8,0x3d8ebdd5,0x3dfb3cc8,0xbd8e3dd5,0x3d8e3dd5,0xbdfb3cc8,0xbd8ebdd5,0x3dfbbcc8,0x3cc8bdfb,0x3dd53d8e,0xbcc83dfb,0xbdd5bd8e,
0x3dc6bda2,0x3d713de2,0x3da23dc6,0xbde23d71,0xbdf53d15,0xbc49bdff,0xbd15bdf5,0x3dffbc49,0x3dff3c49,0xbd153df5,0xbc493dff,0xbdf5bd15,0xbde2bd71,0x3da2bdc6,0x3d71bde2,0x3dc63da2,
0x3db5bdb5,0x3db53db5,0x3db5bdb5,0x3db53db5,0xbdb53db5,0xbdb5bdb5,0xbdb53db5,0xbdb5bdb5,0x3db5bdb5,0x3db53db5,0x3db5bdb5,0x3db53db5,0xbdb53db5,0xbdb5bdb5,0xbdb53db5,0xbdb5bdb5,
0x3da2bdc6,0x3de23d71,0xbdc6bda2,0x3d71bde2,0xbd153df5,0xbdffbc49,0x3df53d15,0xbc493dff,0xbc49bdff,0x3df5bd15,0xbdff3c49,0xbd15bdf5,0x3d713de2,0xbdc63da2,0x3de2bd71,0x3da23dc6,
0x3d8ebdd5,0x3dfb3cc8,0xbd8e3dd5,0xbdfbbcc8,0x3cc83dfb,0xbdd53d8e,0xbcc8bdfb,0x3dd5bd8e,0xbdd5bd8e,0x3cc8bdfb,0x3dd53d8e,0xbcc83dfb,0x3dfbbcc8,0x3d8e3dd5,0xbdfb3cc8,0xbd8ebdd5,
0x3d71bde2,0x3dffbc49,0x3de23d71,0x3c493dff,0x3da23dc6,0xbd153df5,0xbdc63da2,0xbdf5bd15,0xbdf53d15,0xbdc6bda2,0xbd15bdf5,0x3da2bdc6,0x3c49bdff,0x3de2bd71,0x3dff3c49,0x3d713de2,
0x3d44bded,0x3dedbd44,0x3d44bded,0x3dedbd44,0x3ded3d44,0x3d443ded,0x3ded3d44,0x3d443ded,0xbd443ded,0xbded3d44,0xbd443ded,0xbded3d44,0xbdedbd44,0xbd44bded,0xbdedbd44,0xbd44bded,
0x3d15bdf5,0x3dc6bda2,0xbdf5bd15,0xbda2bdc6,0x3dffbc49,0x3de23d71,0xbc49bdff,0x3d71bde2,0x3d713de2,0xbc493dff,0x3de2bd71,0x3dff3c49,0xbda23dc6,0xbdf53d15,0x3dc63da2,0x3d153df5,
0x3cc8bdfb,0x3d8ebdd5,0xbcc83dfb,0xbd8e3dd5,0x3dd5bd8e,0x3dfbbcc8,0xbdd53d8e,0xbdfb3cc8,0x3dfb3cc8,0x3dd53d8e,0xbdfbbcc8,0xbdd5bd8e,0x3d8e3dd5,0x3cc83dfb,0xbd8ebdd5,0xbcc8bdfb,
0x3c49bdff,0x3d15bdf5,0x3dff3c49,0x3df53d15,0x3d71bde2,0x3da2bdc6,0x3de23d71,0x3dc63da2,0x3dc6bda2,0x3de2bd71,0x3da23dc6,0x3d713de2,0x3df5bd15,0x3dffbc49,0x3d153df5,0x3c493dff,
0x3f800000,0x0,0x3f800000,0x0,0x3f800000,0x0,0x3f800000,0x0,0x3f800000,0x0,0x3f800000,0x0,0x3f800000,0x0,0x3f800000,0x0,
0x3f800000,0x0,0x3f7ffb11,0xbc490e90,0x3f7fec43,0xbcc90ab0,0x3f7fd397,0xbd16c32c,0x3f7fb10f,0xbd48fb30,0x3f7f84ab,0xbd7b2b74,0x3f7f4e6d,0xbd96a905,0x3f7f0e58,0xbdafb680,
0x3f800000,0x0,0x3f7fec43,0xbcc90ab0,0x3f7fb10f,0xbd48fb30,0x3f7f4e6d,0xbd96a905,0x3f7ec46d,0xbdc8bd36,0x3f7e1324,0xbdfab273,0x3f7d3aac,0xbe164083,0x3f7c3b28,0xbe2f10a2,
0x3f800000,0x0,0x3f7fd397,0xbd16c32c,0x3f7f4e6d,0xbd96a905,0x3f7e70b0,0xbde1bc2e,0x3f7d3aac,0xbe164083,0x3f7baccd,0xbe3b6ecf,0x3f79c79d,0xbe605c13,0x3f778bc5,0xbe827dc0,
0x3f800000,0x0,0x3f7fb10f,0xbd48fb30,0x3f7ec46d,0xbdc8bd36,0x3f7d3aac,0xbe164083,0x3f7b14be,0xbe47c5c2,0x3f7853f8,0xbe78cfcc,0x3f74fa0b,0xbe94a031,0x3f710908,0xbeac7cd4,
0x3f800000,0x0,0x3f7f84ab,0xbd7b2b74,0x3f7e1324,0xbdfab273,0x3f7baccd,0xbe3b6ecf,0x3f7853f8,0xbe78cfcc,0x3f740bdd,0xbe9aa086,0x3f6ed89e,0xbeb8442a,0x3f68bf3c,0xbed53641,
0x3f800000,0x0,0x3f7f4e6d,0xbd96a905,0x3f7d3aac,0xbe164083,0x3f79c79d,0xbe605c13,0x3f74fa0b,0xbe94a031,0x3f6ed89e,0xbeb8442a,0x3f676bd8,0xbedae880,0x3f5ebe05,0xbefc5d27,
0x3f800000,0x0,0x3f7f0e58,0xbdafb680,0x3f7c3b28,0xbe2f10a2,0x3f778bc5,0xbe827dc0,0x3f710908,0xbeac7cd4,0x3f68bf3c,0xbed53641,0x3f5ebe05,0xbefc5d27,0x3f531849,0xbf10d3cd,
0x3f800000,0x0,0x3f7ec46d,0xbdc8bd36,0x3f7b14be,0xbe47c5c2,0x3f74fa0b,0xbe94a031,0x3f6c835e,0xbec3ef15,0x3f61c598,0xbef15aea,0x3f54db31,0xbf0e39da,0x3f45e403,0xbf226799,
0x3f800000,0x0,0x3f7e70b0,0xbde1bc2e,0x3f79c79d,0xbe605c13,0x3f721352,0xbea68f12,0x3f676bd8,0xbedae880,0x3f59f26a,0xbf064b82,0x3f49d112,0xbf1d7fd1,0x3f373a23,0xbf32c8c9,
0x3f800000,0x0,0x3f7e1324,0xbdfab273,0x3f7853f8,0xbe78cfcc,0x3f6ed89e,0xbeb8442a,0x3f61c598,0xbef15aea,0x3f514d3d,0xbf13682a,0x3f3daef9,0xbf2beb4a,0x3f273656,0xbf41d870,
0x3f800000,0x0,0x3f7dabcc,0xbe09cf86,0x3f76ba07,0xbe888e93,0x3f6b4b0c,0xbec9b953,0x3f5b941a,0xbf039c3d,0x3f47de65,0xbf1ff6cb,0x3f3085bb,0xbf396842,0x3f15f6d9,0xbf4f7a1f,
0x3f800000,0x0,0x3f7d3aac,0xbe164083,0x3f74fa0b,0xbe94a031,0x3f676bd8,0xbedae880,0x3f54db31,0xbf0e39da,0x3f3daef9,0xbf2beb4a,0x3f226799,0xbf45e403,0x3f039c3d,0xbf5b941a,
0x3f800000,0x0,0x3f7cbfc9,0xbe22abb6,0x3f731447,0xbea09ae5,0x3f633c5a,0xbeebcbbb,0x3f4d9f02,0xbf187fc0,0x3f32c8c9,0xbf373a23,0x3f13682a,0xbf514d3d,0x3ee0924f,0xbf660f88,
0x3f800000,0x0,0x3f7c3b28,0xbe2f10a2,0x3f710908,0xbeac7cd4,0x3f5ebe05,0xbefc5d27,0x3f45e403,0xbf226799,0x3f273656,0xbf41d870,0x3f039c3d,0xbf5b941a,0x3eb8442a,0xbf6ed89e,
0x3f800000,0x0,0x3f7baccd,0xbe3b6ecf,0x3f6ed89e,0xbeb8442a,0x3f59f26a,0xbf064b82,0x3f3daef9,0xbf2beb4a,0x3f1b02c6,0xbf4bbbf8,0x3ee63375,0xbf64aa59,0x3e8e9a22,0xbf75dec6,
0x3f800000,0x0,0x3f7b14be,0xbe47c5c2,0x3f6c835e,0xbec3ef15,0x3f54db31,0xbf0e39da,0x3f3504f3,0xbf3504f3,0x3f0e39da,0xbf54db31,0x3ec3ef15,0xbf6c835e,0x3e47c5c2,0xbf7b14be,
0x3f800000,0x0,0x3f7a7302,0xbe541501,0x3f6a09a7,0xbecf7bca,0x3f4f7a1f,0xbf15f6d9,0x3f2beb4a,0xbf3daef9,0x3f00e7e4,0xbf5d2d53,0x3ea09ae5,0xbf731447,0x3de1bc2e,0xbf7e70b0,
0x3f800000,0x0,0x3f79c79d,0xbe605c13,0x3f676bd8,0xbedae880,0x3f49d112,0xbf1d7fd1,0x3f226799,0xbf45e403,0x3ee63375,0xbf64aa59,0x3e78cfcc,0xbf7853f8,0x3cc90ab0,0xbf7fec43,
0x3f800000,0x0,0x3f791298,0xbe6c9a7f,0x3f64aa59,0xbee63375,0x3f43e200,0xbf24d225,0x3f187fc0,0xbf4d9f02,0x3ec9b953,0xbf6b4b0c,0x3e2f10a2,0xbf7c3b28,0xbd7b2b74,0xbf7f84ab,
0x3f800000,0x0,0x3f7853f8,0xbe78cfcc,0x3f61c598,0xbef15aea,0x3f3daef9,0xbf2beb4a,0x3f0e39da,0xbf54db31,0x3eac7cd4,0xbf710908,0x3dc8bd36,0xbf7ec46d,0xbe164083,0xbf7d3aac,
0x3f800000,0x0,0x3f778bc5,0xbe827dc0,0x3f5ebe05,0xbefc5d27,0x3f373a23,0xbf32c8c9,0x3f039c3d,0xbf5b941a,0x3e8e9a22,0xbf75dec6,0x3cc90ab0,0xbf7fec43,0xbe6c9a7f,0xbf791298,
0x3f800000,0x0,0x3f76ba07,0xbe888e93,0x3f5b941a,0xbf039c3d,0x3f3085bb,0xbf396842,0x3ef15aea,0xbf61c598,0x3e605c13,0xbf79c79d,0xbd48fb30,0xbf7fb10f,0xbea09ae5,0xbf731447,
0x3f800000,0x0,0x3f75dec6,0xbe8e9a22,0x3f584853,0xbf08f59b,0x3f299415,0xbf3fc767,0x3edae880,0xbf676bd8,0x3e22abb6,0xbf7cbfc9,0xbdfab273,0xbf7e1324,0xbec9b953,0xbf6b4b0c,
0x3f800000,0x0,0x3f74fa0b,0xbe94a031,0x3f54db31,0xbf0e39da,0x3f226799,0xbf45e403,0x3ec3ef15,0xbf6c835e,0x3dc8bd36,0xbf7ec46d,0xbe47c5c2,0xbf7b14be,0xbef15aea,0xbf61c598,
0x3f800000,0x0,0x3f740bdd,0xbe9aa086,0x3f514d3d,0xbf13682a,0x3f1b02c6,0xbf4bbbf8,0x3eac7cd4,0xbf710908,0x3d16c32c,0xbf7fd397,0xbe888e93,0xbf76ba07,0xbf0b9a6b,0xbf5695e5,
0x3f800000,0x0,0x3f731447,0xbea09ae5,0x3f4d9f02,0xbf187fc0,0x3f13682a,0xbf514d3d,0x3e94a031,0xbf74fa0b,0xbcc90ab0,0xbf7fec43,0xbeac7cd4,0xbf710908,0xbf1d7fd1,0xbf49d112,
0x3f800000,0x0,0x3f721352,0xbea68f12,0x3f49d112,0xbf1d7fd1,0x3f0b9a6b,0xbf5695e5,0x3e78cfcc,0xbf7853f8,0xbdafb680,0xbf7f0e58,0xbecf7bca,0xbf6a09a7,0xbf2e3bde,0xbf3b8f3b,
0x3f800000,0x0,0x3f710908,0xbeac7cd4,0x3f45e403,0xbf226799,0x3f039c3d,0xbf5b941a,0x3e47c5c2,0xbf7b14be,0xbe164083,0xbf7d3aac,0xbef15aea,0xbf61c598,0xbf3daef9,0xbf2beb4a,
0x3f800000,0x0,0x3f6ff573,0xbeb263ef,0x3f41d870,0xbf273656,0x3ef6e0cb,0xbf604621,0x3e164083,0xbf7d3aac,0xbe541501,0xbf7a7302,0xbf08f59b,0xbf584853,0xbf4bbbf8,0xbf1b02c6,
0x3f800000,0x0,0x3f6ed89e,0xbeb8442a,0x3f3daef9,0xbf2beb4a,0x3ee63375,0xbf64aa59,0x3dc8bd36,0xbf7ec46d,0xbe888e93,0xbf76ba07,0xbf187fc0,0xbf4d9f02,0xbf584853,0xbf08f59b,
0x3f800000,0x0,0x3f6db293,0xbebe1d4a,0x3f396842,0xbf3085bb,0x3ed53641,0xbf68bf3c,0x3d48fb30,0xbf7fb10f,0xbea68f12,0xbf721352,0xbf273656,0xbf41d870,0xbf633c5a,0xbeebcbbb,
0x3f800000,0x3f800000,0x3f800000,0x3f800000,0x3f800000,0x3f800000,0x3f800000,0x3f800000,0x3f800000,0xbf800000,0x3f800000,0xbf800000,0x3f800000,0xbf800000,0x3f800000,0xbf800000,
0x3f800000,0x3f3504f3,0x0,0xbf3504f3,0xbf800000,0xbf3504f3,0x0,0x3f3504f3,0x0,0xbf3504f3,0xbf800000,0xbf3504f3,0x0,0x3f3504f3,0x3f800000,0x3f3504f3,
0x3f800000,0x0,0xbf800000,0x0,0x3f800000,0x0,0xbf800000,0x0,0x0,0xbf800000,0x0,0x3f800000,0x0,0xbf800000,0x0,0x3f800000,
0x3f800000,0xbf3504f3,0x0,0x3f3504f3,0xbf800000,0x3f3504f3,0x0,0xbf3504f3,0x0,0xbf3504f3,0x3f800000,0xbf3504f3,0x0,0x3f3504f3,0xbf800000,0x3f3504f3,
0x3f800000,0x3f6c835e,0x3f3504f3,0x3ec3ef15,0x0,0xbec3ef15,0xbf3504f3,0xbf6c835e,0x0,0xbec3ef15,0xbf3504f3,0xbf6c835e,0xbf800000,0xbf6c835e,0xbf3504f3,0xbec3ef15,
0x3f800000,0x3ec3ef15,0xbf3504f3,0xbf6c835e,0x0,0x3f6c835e,0x3f3504f3,0xbec3ef15,0x0,0xbf6c835e,0xbf3504f3,0x3ec3ef15,0x3f800000,0x3ec3ef15,0xbf3504f3,0xbf6c835e,
0x3f800000,0xbec3ef15,0xbf3504f3,0x3f6c835e,0x0,0xbf6c835e,0x3f3504f3,0x3ec3ef15,0x0,0xbf6c835e,0x3f3504f3,0x3ec3ef15,0xbf800000,0x3ec3ef15,0x3f3504f3,0xbf6c835e,
0x3f800000,0xbf6c835e,0x3f3504f3,0xbec3ef15,0x0,0x3ec3ef15,0xbf3504f3,0x3f6c835e,0x0,0xbec3ef15,0x3f3504f3,0xbf6c835e,0x3f800000,0xbf6c835e,0x3f3504f3,0xbec3ef15,
};

struct Params {
    const __nv_bfloat16 *xb, *lre, *lim, *ldt, *dsk;
    float* out;
    int zero[8];
    uint64_t da[4];
    uint32_t unit[258];
};

struct Maps { CUtensorMap m[10]; };

struct cf { float x, y; };
__device__ __forceinline__ uint32_t smem_u32(const void* p) { return (uint32_t)__cvta_generic_to_shared(p); }
__device__ __forceinline__ void mbar_init(uint32_t a, uint32_t c) { asm volatile("mbarrier.init.shared::cta.b64 [%0], %1;" ::"r"(a), "r"(c) : "memory"); }
__device__ __forceinline__ void mbar_expect_tx(uint32_t a, uint32_t b) { asm volatile("mbarrier.arrive.expect_tx.shared::cta.b64 _, [%0], %1;" ::"r"(a), "r"(b) : "memory"); }
__device__ __forceinline__ void mbar_arrive(uint32_t a) { asm volatile("mbarrier.arrive.shared::cta.b64 _, [%0];" ::"r"(a) : "memory"); }
__device__ __forceinline__ void mbar_wait(uint32_t a, uint32_t ph) {
    asm volatile("{.reg .pred p;\nLOOP: mbarrier.try_wait.parity.shared::cta.b64 p, [%0], %1;\n@!p bra LOOP;}" ::"r"(a), "r"(ph) : "memory");
}
__device__ __forceinline__ unsigned ld_rlx(const unsigned* p) { unsigned v; asm volatile("ld.relaxed.gpu.global.u32 %0, [%1];" : "=r"(v) : "l"(p) : "memory"); return v; }
__device__ __forceinline__ void wait_cnt(const unsigned* p, unsigned target) {
    unsigned n = 0;
    while ((int)(ld_rlx(p) - target) < 0 && ++n < SPIN_LIMIT) __nanosleep(20);
}
__device__ __forceinline__ void red_hint(unsigned* p) { asm volatile("red.relaxed.gpu.global.add.u32 [%0], 1;" ::"l"(p) : "memory"); }
__device__ __forceinline__ void fence_async() { asm volatile("fence.proxy.async.global;" ::: "memory"); }
__device__ __forceinline__ void fence_async_sm() { asm volatile("fence.proxy.async.shared::cta;" ::: "memory"); }
#define bar_sync(id, n) asm volatile("bar.sync %0, %1;" ::"n"(id), "n"(n) : "memory")
#define bar_arrive(id, n) asm volatile("bar.arrive %0, %1;" ::"n"(id), "n"(n) : "memory")
__device__ __forceinline__ bool elect_one() {
    uint32_t r;
    asm volatile("{.reg .pred p; elect.sync _|p, 0xffffffff; selp.u32 %0, 1, 0, p;}" : "=r"(r));
    return r != 0;
}

__device__ __forceinline__ void tma2d(uint32_t dst, const CUtensorMap* m, int c0, int c1, uint32_t bar) {
    asm volatile("cp.async.bulk.tensor.2d.shared::cluster.global.mbarrier::complete_tx::bytes [%0], [%1, {%3,%4}], [%2];" ::"r"(dst), "l"(m), "r"(bar), "r"(c0), "r"(c1) : "memory");
}
__device__ __forceinline__ void tma4d(uint32_t dst, const CUtensorMap* m, int c0, int c1, int c2, int c3, uint32_t bar) {
    asm volatile("cp.async.bulk.tensor.4d.shared::cluster.global.mbarrier::complete_tx::bytes [%0], [%1, {%3,%4,%5,%6}], [%2];" ::"r"(dst), "l"(m), "r"(bar), "r"(c0), "r"(c1), "r"(c2), "r"(c3) : "memory");
}
__device__ __forceinline__ void tma4d_mc(uint32_t dst, const CUtensorMap* m, int c0, int c3, uint32_t bar) {
    asm volatile("cp.async.bulk.tensor.4d.shared::cluster.global.mbarrier::complete_tx::bytes.multicast::cluster [%0], [%1, {%3,%6,%6,%4}], [%2], %5;" ::"r"(dst), "l"(m), "r"(bar), "r"(c0), "r"(c3), "h"((uint16_t)3), "r"(0) : "memory");
}
__device__ __forceinline__ void tma2d_st(const CUtensorMap* m, int c0, int c1, uint32_t src) {
    asm volatile("cp.async.bulk.tensor.2d.global.shared::cta.bulk_group [%0, {%2,%3}], [%1];" ::"l"(m), "r"(src), "r"(c0), "r"(c1) : "memory");
}
__device__ __forceinline__ void tma3d_st(const CUtensorMap* m, int c0, int c1, int c2, uint32_t src) {
    asm volatile("cp.async.bulk.tensor.3d.global.shared::cta.bulk_group [%0, {%2,%3,%4}], [%1];" ::"l"(m), "r"(src), "r"(c0), "r"(c1), "r"(c2) : "memory");
}
__device__ __forceinline__ void tma5d(uint32_t dst, const CUtensorMap* m, int c0, int c1, int c2, int c3, int c4, uint32_t bar) {
    asm volatile("cp.async.bulk.tensor.5d.shared::cluster.global.mbarrier::complete_tx::bytes [%0], [%1, {%3,%4,%5,%6,%7}], [%2];" ::"r"(dst), "l"(m), "r"(bar), "r"(c0), "r"(c1), "r"(c2), "r"(c3), "r"(c4) : "memory");
}
__device__ __forceinline__ void bulk_ld(uint32_t dst, const void* src, uint32_t n, uint32_t bar) {
    asm volatile("cp.async.bulk.shared::cluster.global.mbarrier::complete_tx::bytes [%0], [%1], %2, [%3];" ::"r"(dst), "l"(src), "r"(n), "r"(bar) : "memory");
}
__device__ __forceinline__ void bulk_commit() { asm volatile("cp.async.bulk.commit_group;" ::: "memory"); }
template <int N> __device__ __forceinline__ void bulk_wait_read() { asm volatile("cp.async.bulk.wait_group.read %0;" ::"n"(N) : "memory"); }
__device__ __forceinline__ void stsm4(uint32_t a, uint32_t r0, uint32_t r1, uint32_t r2, uint32_t r3) {
    asm volatile("stmatrix.sync.aligned.m8n8.x4.shared.b16 [%0], {%1,%2,%3,%4};" ::"r"(a), "r"(r0), "r"(r1), "r"(r2), "r"(r3) : "memory");
}
__device__ __forceinline__ void sts128f(uint32_t a, cf u, cf v) {
    asm volatile("st.shared.v4.f32 [%0], {%1,%2,%3,%4};" ::"r"(a), "f"(u.x), "f"(u.y), "f"(v.x), "f"(v.y) : "memory");
}
__device__ __forceinline__ void stg128(const void* a, uint32_t r0, uint32_t r1, uint32_t r2, uint32_t r3) {
    asm volatile("st.global.v4.b32 [%0], {%1,%2,%3,%4};" ::"l"(a), "r"(r0), "r"(r1), "r"(r2), "r"(r3) : "memory");
}
__device__ __forceinline__ void lds128f(uint32_t a, float& x, float& y, float& z, float& u) { asm volatile("ld.shared.v4.f32 {%0,%1,%2,%3}, [%4];" : "=f"(x), "=f"(y), "=f"(z), "=f"(u) : "r"(a) : "memory"); }
__device__ __forceinline__ cf lds_cf(uint32_t a) { cf v; asm volatile("ld.shared.v2.f32 {%0,%1}, [%2];" : "=f"(v.x), "=f"(v.y) : "r"(a) : "memory"); return v; }
__device__ __forceinline__ uint4 ldtab(int word) { return __ldg((const uint4*)(g_tab + word)); }
__device__ __forceinline__ void load_tw(cf (&tw)[8], int k1) {
#pragma unroll
    for (int i = 0; i < 4; i++) {
        const uint4 v = ldtab(TAB_TW + k1 * 16 + i * 4);
        tw[2 * i] = {__uint_as_float(v.x), __uint_as_float(v.y)};
        tw[2 * i + 1] = {__uint_as_float(v.z), __uint_as_float(v.w)};
    }
}
__device__ __forceinline__ void load_T(cf (&T)[8], int t7) {
#pragma unroll
    for (int i = 0; i < 4; i++)
        asm volatile("ld.global.nc.v4.f32 {%0,%1,%2,%3}, [%4];" : "=f"(T[2 * i].x), "=f"(T[2 * i].y), "=f"(T[2 * i + 1].x), "=f"(T[2 * i + 1].y) : "l"(g_tab + TAB_T + i * 512 + t7 * 4));
}
__device__ __forceinline__ uint32_t lds_u16(uint32_t a) { uint32_t v; asm volatile("ld.shared.u16 %0, [%1];" : "=r"(v) : "r"(a)); return v; }
__device__ __forceinline__ float up(uint32_t v) { return __uint_as_float(v << 16); }
__device__ __forceinline__ unsigned get_epoch(uint32_t bars) {
    mbar_wait(bars + B_EP, 0);
    unsigned e;
    asm volatile("ld.shared.u32 %0, [%1];" : "=r"(e) : "r"(bars + B_EPOCH) : "memory");
    return e;
}
__device__ __forceinline__ void sts64f(uint32_t a, float x, float y) { asm volatile("st.shared.v2.f32 [%0], {%1,%2};" ::"r"(a), "f"(x), "f"(y) : "memory"); }
__device__ __forceinline__ uint32_t pk(float lo, float hi) { uint32_t r; asm("cvt.rn.bf16x2.f32 %0, %1, %2;" : "=r"(r) : "f"(hi), "f"(lo)); return r; }
__device__ __forceinline__ uint32_t bitsel(uint32_t a, uint32_t m, uint32_t b) {
    uint32_t r;
    asm("lop3.b32 %0, %1, %2, %3, 0xea;" : "=r"(r) : "r"(a), "r"(m), "r"(b));
    return r;
}

__host__ __device__ constexpr uint64_t mkdesc(uint32_t off, uint32_t lbo, uint32_t sbo, uint32_t swz) {
    return (uint64_t)((SB0 + off) >> 4) | ((uint64_t)(lbo >> 4) << 16) | ((uint64_t)(sbo >> 4) << 32) | ((uint64_t)swz << 62);
}
__device__ __forceinline__ void wg_fence() { asm volatile("wgmma.fence.sync.aligned;" ::: "memory"); }
__device__ __forceinline__ void wg_commit() { asm volatile("wgmma.commit_group.sync.aligned;" ::: "memory"); }
template <int N> __device__ __forceinline__ void wg_wait() { asm volatile("wgmma.wait_group.sync.aligned %0;" ::"n"(N) : "memory"); }
template <int N> __device__ __forceinline__ void pin(float (&d)[N]) {
#pragma unroll
    for (int i = 0; i < N; i++) asm volatile("" : "+f"(d[i])::"memory");
}
template <int N> __device__ __forceinline__ void pinu(uint32_t (&d)[N]) {
#pragma unroll
    for (int i = 0; i < N; i++) asm volatile("" : "+r"(d[i])::"memory");
}

#define R8(d, o) "+f"(d[o]), "+f"(d[o + 1]), "+f"(d[o + 2]), "+f"(d[o + 3]), "+f"(d[o + 4]), "+f"(d[o + 5]), "+f"(d[o + 6]), "+f"(d[o + 7])
#define L8 "%0,%1,%2,%3,%4,%5,%6,%7"
#define L24 L8 ",%8,%9,%10,%11,%12,%13,%14,%15,%16,%17,%18,%19,%20,%21,%22,%23"
#define L32 L24 ",%24,%25,%26,%27,%28,%29,%30,%31"
#define L64 L32 ",%32,%33,%34,%35,%36,%37,%38,%39,%40,%41,%42,%43,%44,%45,%46,%47,%48,%49,%50,%51,%52,%53,%54,%55,%56,%57,%58,%59,%60,%61,%62,%63"

template <int O, int TA, int TB, int SC, int N> __device__ __forceinline__ void mma128_ss(float (&d)[N], uint64_t da, uint64_t db) {
    asm volatile("wgmma.mma_async.sync.aligned.m64n128k16.f32.bf16.bf16 {" L64 "}, %64, %65, %66, 1, 1, %67, %68;"
                 : R8(d, O), R8(d, O + 8), R8(d, O + 16), R8(d, O + 24), R8(d, O + 32), R8(d, O + 40), R8(d, O + 48), R8(d, O + 56)
                 : "l"(da), "l"(db), "n"(SC), "n"(TA), "n"(TB));
}
template <int TB, int SC> __device__ __forceinline__ void mma128_rs(float (&d)[64], const uint32_t* a, uint64_t db) {
    asm volatile("wgmma.mma_async.sync.aligned.m64n128k16.f32.bf16.bf16 {" L64 "}, {%64,%65,%66,%67}, %68, %69, 1, 1, %70;"
                 : R8(d, 0), R8(d, 8), R8(d, 16), R8(d, 24), R8(d, 32), R8(d, 40), R8(d, 48), R8(d, 56)
                 : "r"(a[0]), "r"(a[1]), "r"(a[2]), "r"(a[3]), "l"(db), "n"(SC), "n"(TB));
}
template <int TB, int SC> __device__ __forceinline__ void mma64_rs(float (&d)[32], const uint32_t* a, uint64_t db) {
    asm volatile("wgmma.mma_async.sync.aligned.m64n64k16.f32.bf16.bf16 {" L32 "}, {%32,%33,%34,%35}, %36, %37, 1, 1, %38;"
                 : R8(d, 0), R8(d, 8), R8(d, 16), R8(d, 24)
                 : "r"(a[0]), "r"(a[1]), "r"(a[2]), "r"(a[3]), "l"(db), "n"(SC), "n"(TB));
}
template <int SC> __device__ __forceinline__ void mma64_ss(float (&d)[64], uint64_t da, uint64_t db) {
    asm volatile("wgmma.mma_async.sync.aligned.m64n64k16.f32.bf16.bf16 {" L32 "}, %32, %33, %34, 1, 1, 0, 1;"
                 : R8(d, 32), R8(d, 40), R8(d, 48), R8(d, 56)
                 : "l"(da), "l"(db), "n"(SC));
}
template <int SC> __device__ __forceinline__ void mma48_ss(float (&d)[64], uint64_t da, uint64_t db) {
    asm volatile("wgmma.mma_async.sync.aligned.m64n48k16.f32.bf16.bf16 {" L24 "}, %24, %25, %26, 1, 1, 0, 1;"
                 : R8(d, 8), R8(d, 16), R8(d, 24)
                 : "l"(da), "l"(db), "n"(SC));
}
template <int SC> __device__ __forceinline__ void mma16_rs(float (&d)[64], uint32_t a0, uint32_t a1, uint32_t a2, uint32_t a3, uint64_t db) {
    asm volatile("wgmma.mma_async.sync.aligned.m64n16k16.f32.bf16.bf16 {" L8 "}, {%8,%9,%10,%11}, %12, %13, 1, 1, 1;"
                 : R8(d, 0)
                 : "r"(a0), "r"(a1), "r"(a2), "r"(a3), "l"(db), "n"(SC));
}

__device__ __forceinline__ cf cmul(cf a, cf b) { return {fmaf(a.x, b.x, -a.y * b.y), fmaf(a.x, b.y, a.y * b.x)}; }
__device__ __forceinline__ cf csq(cf a) { return {fmaf(a.x, a.x, -a.y * a.y), (a.x + a.x) * a.y}; }
__device__ __forceinline__ cf cmulc(cf a, cf b) { return {fmaf(a.x, b.x, a.y * b.y), fmaf(a.y, b.x, -a.x * b.y)}; }
__device__ __forceinline__ cf cfma(cf a, cf b, cf c) { return {fmaf(a.x, b.x, fmaf(-a.y, b.y, c.x)), fmaf(a.x, b.y, fmaf(a.y, b.x, c.y))}; }
__device__ __forceinline__ cf csel(int c, cf a, cf b) {
    cf r;
    asm("{.reg .pred p; setp.ne.s32 p, %6, 0; selp.f32 %0, %2, %4, p; selp.f32 %1, %3, %5, p;}" : "=f"(r.x), "=f"(r.y) : "f"(a.x), "f"(a.y), "f"(b.x), "f"(b.y), "r"(c));
    return r;
}
__device__ __forceinline__ cf cadd(cf a, cf b) { return {a.x + b.x, a.y + b.y}; }
__device__ __forceinline__ cf csub(cf a, cf b) { return {a.x - b.x, a.y - b.y}; }
__device__ __forceinline__ cf twice_minus(cf a, cf s) { return {fmaf(2.f, a.x, -s.x), fmaf(2.f, a.y, -s.y)}; }
__device__ __forceinline__ cf twid(int m, int M) {
    int r = ((m + M / 2) & (M - 1)) - M / 2;
    float s, c;
    __sincosf((float)r * (-6.283185307179586f / (float)M), &s, &c);
    return {c, s};
}
template <bool TW> __device__ __forceinline__ void dft8(cf (&v)[8], const cf (&tw)[8]) {
    const float s = 0.70710678118654752f;
    cf a0, a1, a2, a3, a4, a5, a6, a7;
    if (TW) {
        a0 = cfma(v[4], tw[4], v[0]); a1 = twice_minus(v[0], a0);
        YIELD2();
        const cf t2 = cmul(v[2], tw[2]);
        a2 = cfma(v[6], tw[6], t2); a3 = twice_minus(t2, a2);
        YIELD();
        const cf t1 = cmul(v[1], tw[1]);
        a4 = cfma(v[5], tw[5], t1); a5 = twice_minus(t1, a4);
        YIELD2();
        const cf t3 = cmul(v[3], tw[3]);
        a6 = cfma(v[7], tw[7], t3); a7 = twice_minus(t3, a6);
    } else {
        a0 = cadd(v[0], v[4]); a1 = csub(v[0], v[4]); a2 = cadd(v[2], v[6]); a3 = csub(v[2], v[6]);
        YIELD2();
        a4 = cadd(v[1], v[5]); a5 = csub(v[1], v[5]); a6 = cadd(v[3], v[7]); a7 = csub(v[3], v[7]);
    }
    YIELD();
    const cf e0 = cadd(a0, a2), e2 = csub(a0, a2), o0 = cadd(a4, a6), o2 = csub(a4, a6);
    YIELD2();
    v[0] = cadd(e0, o0); v[4] = csub(e0, o0);
    v[2] = {e2.x + o2.y, e2.y - o2.x}; v[6] = {e2.x - o2.y, e2.y + o2.x};
    YIELD();
    const cf e1 = {a1.x + a3.y, a1.y - a3.x}, o1 = {a5.x + a7.y, a5.y - a7.x}, t1 = {o1.x + o1.y, o1.y - o1.x};
    v[1] = {fmaf(s, t1.x, e1.x), fmaf(s, t1.y, e1.y)}; v[5] = {fmaf(-s, t1.x, e1.x), fmaf(-s, t1.y, e1.y)};
    YIELD2();
    const cf e3 = {a1.x - a3.y, a1.y + a3.x}, o3 = {a5.x - a7.y, a5.y + a7.x}, t3 = {o3.y - o3.x, -o3.x - o3.y};
    v[3] = {fmaf(s, t3.x, e3.x), fmaf(s, t3.y, e3.y)}; v[7] = {fmaf(-s, t3.x, e3.x), fmaf(-s, t3.y, e3.y)};
    YIELD();
}

__device__ __forceinline__ void bid2tile(int b, int& tc, int& cb) {
    const int c = b >> 1, e = c - 36, t7 = (e * 37) >> 8;
    int g;
    asm("{.reg .pred p, q; setp.lt.s32 p, %2, 4; setp.lt.s32 q, %2, 36; selp.s32 %0, %3, %4, q; selp.s32 %1, %5, %6, q; selp.s32 %0, 0, %0, p; selp.s32 %1, %7, %1, p;}"
        : "=&r"(g), "=&r"(cb) : "r"(c), "r"((c + 4) & 7), "r"(1 + e - 7 * t7), "r"((c - 4) >> 3), "r"(4 + t7), "r"(4 + c));
    tc = 2 * g + (b & 1);
}
__host__ __device__ __forceinline__ int pos_of(int n) { return (n & 24) + 4 * (n & 1) + ((n >> 1) & 3); }
static int kappa_of(int b, int gi) {
    const int r = b >> 4, j = b & 7;
    const int k1 = 2 * (b & 8) + (gi ? (j >= 4 ? j : 9 + j) : (j < 4 ? j : (j == 4 ? 8 : 8 + j)));
    return b >= 128 ? gi * 256 : (k1 || r < 4 ? k1 + 64 * r : 64 * r - 224);
}
static int slot3_of(int kap, int& cj) {
    int m = kap & 15;
    cj = (m > 8) || ((m & 7) == 0 && kap > 256);
    const int kk = cj ? 512 - kap : kap;
    m = kk & 15;
    return kk == 256 ? 0 : (m & 7) * 32 + pos_of((kk >> 4) + 2 * (m & 8));
}

__device__ __forceinline__ uint32_t tag_bad(uint32_t a, uint32_t tag) {
    uint32_t v;
    asm volatile("ld.shared.u32 %0, [%1];" : "=r"(v) : "r"(a) : "memory");
    return (v ^ tag) & 1;
}
__device__ __forceinline__ bool wg_all_ok(uint32_t bad, int id) {
    uint32_t ok;
    asm volatile("{.reg .pred p, q; setp.eq.u32 q, %1, 0; barrier.red.and.aligned.pred p, %2, 128, q; selp.u32 %0, 1, 0, p;}" : "=r"(ok) : "r"(bad), "r"(id) : "memory");
    return __all_sync(~0u, ok);
}

__device__ __forceinline__ uint32_t lines_bad(uint32_t va, uint32_t tag, uint32_t bit) {
    uint32_t bad;
    asm volatile("{.reg .b32 a, b, c, d;\n"
                 "ld.shared.u32 a, [%1]; ld.shared.u32 b, [%1+4096]; ld.shared.u32 c, [%1+8192]; ld.shared.u32 d, [%1+12288];\n"
                 "lop3.b32 a, a, b, %2, 0x7e; lop3.b32 c, c, d, %2, 0x7e; lop3.b32 %0, a, c, %3, 0xa8;}"
                 : "=r"(bad) : "r"(va), "r"(tag), "r"(bit) : "memory");
    return bad;
}
__device__ __forceinline__ void load_w(uint32_t sb, const CUtensorMap* m, int kap, uint32_t more) {
    mbar_expect_tx(sb + OFF_BAR + B_WIN, 16 * WPITCH + more);
#pragma unroll 1
    for (int i = 0; i < 4; i++) {
        if (i) __nanosleep(PACE_W);
        tma2d(sb + OFF_W + i * (4 * WPITCH), m + (i & 1), ((i & 2 ? (512 - kap) & 511 : kap) * 1026 >> 4) * 2, 0, sb + OFF_BAR + B_WIN);
    }
}
__device__ __forceinline__ void carry_poll(unsigned __int128 (&f)[4], const uint4* a, int n, uint32_t tag) {
    f[0] = f[1] = f[2] = f[3] = tag;
    asm volatile("{.reg .pred p<4>;\n"
                 "setp.ge.s32 p0, %5, 0; setp.ge.s32 p1, %5, 4; setp.ge.s32 p2, %5, 8; setp.ge.s32 p3, %5, 12;\n"
                 "@p0 ld.relaxed.gpu.global.b128 %0, [%4];\n"
                 "@p1 ld.relaxed.gpu.global.b128 %1, [%4+-32768];\n"
                 "@p2 ld.relaxed.gpu.global.b128 %2, [%4+-65536];\n"
                 "@p3 ld.relaxed.gpu.global.b128 %3, [%4+-98304];}"
                 : "+q"(f[0]), "+q"(f[1]), "+q"(f[2]), "+q"(f[3]) : "l"(a), "r"(n) : "memory");
}
__device__ __forceinline__ uint32_t carry_sum(const unsigned __int128 (&f)[4], const cf (&m4)[2], uint32_t tag, cf (&P)[2]) {
#pragma unroll
    for (int h = 0; h < 2; h++)
#pragma unroll
        for (int a = 3; a >= 0; a--) {
            const cf v = {__uint_as_float((uint32_t)(f[a] >> (64 * h))), __uint_as_float((uint32_t)(f[a] >> (64 * h + 32)))};
            P[h] = a == 3 ? v : cfma(m4[h], P[h], v);
        }
    return (((uint32_t)f[0] ^ tag) | ((uint32_t)f[1] ^ tag) | ((uint32_t)f[2] ^ tag) | ((uint32_t)f[3] ^ tag)) & 15u;
}

struct Ring {
    uint32_t full, rel;
    uint32_t ph, bh;
    uint64_t da;
    bool sig;
};
__device__ __forceinline__ void ring_release(const Ring& r, int slot) {
    if (r.sig) asm volatile("mbarrier.arrive.shared::cluster.b64 _, [%0];" ::"r"(r.rel + 8 * slot) : "memory");
}
__device__ __forceinline__ void ring_wait(Ring& r, int slot) {
    if (slot == 0) r.ph ^= 1;
    mbar_wait(r.full + 8 * slot, r.ph);
}
template <int SLOT, int TA, int HF, int J> __device__ __forceinline__ void mma_g(float (&d)[128], const Ring& r, int sc) {
    constexpr int O = 64 * HF;
    asm volatile("{.reg .b64 da, db; .reg .b32 l; .reg .pred p; setp.ne.s32 p, %67, 0; add.u64 da, %64, %69; mov.b32 l, %65; mov.b64 db, {l,%66};\n"
                 "wgmma.mma_async.sync.aligned.m64n128k16.f32.bf16.bf16 {" L64 "}, da, db, p, 1, 1, %68, 0;}"
                 : R8(d, O), R8(d, O + 8), R8(d, O + 16), R8(d, O + 24), R8(d, O + 32), R8(d, O + 40), R8(d, O + 48), R8(d, O + 56)
                 : "l"(r.da), "n"((uint32_t)mkdesc(SLOT * 32768 + 16384 + J * 32, 16, 0, 0)), "r"(r.bh), "r"(sc), "n"(TA),
                   "n"(1 + SLOT * 2048 + (TA ? HF * 64 + J * 256 : HF * 512 + J * 2)));
}
template <int SLOT, int TA> __device__ __forceinline__ void gemm_step(float (&d)[128], Ring& r, int sc) {
    ring_wait(r, SLOT);
    if (GRP < 8 && LASTW < 2) wg_wait<WAITN>();
    wg_fence();
    mma_g<SLOT, TA, 0, 0>(d, r, sc); mma_g<SLOT, TA, 1, 0>(d, r, sc);
    if (GRP == 2) { wg_commit(); wg_wait<WAITN>(); if (WAITN == 1 && sc) ring_release(r, (SLOT + NST - 1) % NST); }
    mma_g<SLOT, TA, 0, 1>(d, r, 1); mma_g<SLOT, TA, 1, 1>(d, r, 1);
    if (GRP <= 4) { wg_commit(); wg_wait<WAITN>(); if (GRP * WAITN == 4 && sc) ring_release(r, (SLOT + NST - 1) % NST); }
    mma_g<SLOT, TA, 0, 2>(d, r, 1); mma_g<SLOT, TA, 1, 2>(d, r, 1);
    if (GRP == 2) { wg_commit(); if (LASTW) wg_wait<WAITN>(); }
    mma_g<SLOT, TA, 0, 3>(d, r, 1); mma_g<SLOT, TA, 1, 3>(d, r, 1);
    wg_commit();
    if (GRP == 8) { wg_wait<1>(); if (sc) ring_release(r, (SLOT + NST - 1) % NST); }
    else if (LASTW == 2) wg_wait<WAITN>();
}
template <int K, int HF> __device__ __forceinline__ void gemm_half(float (&d)[128], Ring& r) {
    if (HF == 0) { ring_wait(r, K % NST); wg_fence(); }
    mma_g<K % NST, 1, HF, 0>(d, r, 1); mma_g<K % NST, 1, HF, 1>(d, r, 1); mma_g<K % NST, 1, HF, 2>(d, r, 1); mma_g<K % NST, 1, HF, 3>(d, r, 1);
    if constexpr (K < 63) gemm_half<K + 1, HF>(d, r);
}
struct Prod {
    uint32_t b0, b1, b2, b3, b4, dbase;
    unsigned* prof;
    __device__ __forceinline__ Prod(uint32_t sb, int slot, uint32_t off) {
        const uint32_t bars = sb + OFF_BAR;
        b0 = bars + slot % NST * 8; b1 = bars + (slot + 1) % NST * 8; b2 = bars + (slot + 2) % NST * 8; b3 = bars + (slot + 3) % NST * 8; b4 = bars + (slot + 4) % NST * 8;
        dbase = sb + off - bars * 4096;
    }
    __device__ __forceinline__ uint32_t dst() const { return b0 * 4096 + dbase; }
    __device__ __forceinline__ void next() { const uint32_t t = b0; b0 = b1; b1 = b2; b2 = b3; b3 = b4; b4 = t; }
};
__device__ __forceinline__ void load_shared(Prod& r, uint32_t ph, const CUtensorMap* m, int c0, int c3, int first) {
    mbar_wait(r.b0 + B_EMPTY, ph);
    tma4d_mc(r.dst(), m, c0, c3, r.b0);
    r.next();
}
__host__ __device__ constexpr uint64_t phases_from(int k) {
    uint64_t v = 0;
    for (int i = 0; i < 64; i++) v |= (uint64_t)((k + i) / NST & 1) << i;
    return v;
}
__device__ __forceinline__ uint32_t phases(int k, int n) { return ((uint32_t)(phases_from(0) >> k) & ((1u << n) - 1)) | 1u << n; }

__global__ void __cluster_dims__(2, 1, 1) __launch_bounds__(512, 1)
fused_kernel(const __grid_constant__ Maps tm, const __grid_constant__ Params p) {
    const CUtensorMap &tmX = tm.m[0], &tmBre = tm.m[1], &tmBim = tm.m[2], &tmXA = tm.m[5], &tmUst = tm.m[6], &tmVst = tm.m[7], &tmWr = tm.m[8], &tmWi = tm.m[9];
    extern __shared__ __align__(1024) uint8_t smraw[];
    const uint32_t sb = smem_u32(smraw);
    const uint32_t bars = sb + OFF_BAR;
    const int bid = blockIdx.x;
    const bool extra = bid >= 128;
    int tc, cb;
    bid2tile(bid, tc, cb);
    const int wid = __shfl_sync(~0u, threadIdx.x >> 5, 0), wg = ((wid >> 2) + 3) & 3, w = wid & 3;
    const int fb = bid >> 5, fcb = bid & 31, fpos = pos_of(fcb);
    if (wid < 2) {
        if (elect_one()) {
            if (wid == 0) {
#pragma unroll
                for (int s = 0; s < NST; s++) mbar_init(bars + B_FULL + s * 8, 33);
            } else {
                asm volatile("prefetch.tensormap [%0];" ::"l"(&tmBre) : "memory");
                asm volatile("prefetch.tensormap [%0];" ::"l"(&tmBim) : "memory");
#pragma unroll
                for (int o = B_EMPTY; o < B_END; o += 8) mbar_init(bars + o, o < B_STGU ? 2 : (o == B_STGU ? 8 : (o < B_EP ? 4 : 1)));
            }
            asm volatile("fence.mbarrier_init.release.cluster;" ::: "memory");
            fence_async_sm();
            if (wid == 0 && !extra) {
                mbar_expect_tx(bars + B_FULL, 32768);
                tma5d(sb + 16384, &tmX, 0, 0, 0, 0, tc, bars + B_FULL);
                tma4d(sb, &tmBre, 0, 0, 0, cb * 4, bars + B_FULL);
                tma4d(sb + 8192, &tmBim, 0, 0, 0, cb * 4, bars + B_FULL);
                asm volatile("mbarrier.arrive.shared::cta.b64 _, [%0], 32;" ::"r"(bars + B_FULL) : "memory");
                STAMP(56);
            }
        }
        __syncwarp();
    }
    asm volatile("barrier.cluster.arrive.relaxed.aligned;" ::: "memory");

    if (wg == 3) {
        asm volatile("setmaxnreg.dec.sync.aligned.u32 24;");
        if (w == 0 && !extra) {
            if (elect_one()) {
#pragma unroll 1
                for (int k = 1; k < NST; k++) {
                    mbar_expect_tx(bars + B_FULL + k * 8, 32768);
                    tma5d(sb + k * 32768 + 16384, &tmX, k * 64, 0, 0, 0, tc, bars + B_FULL + k * 8);
                    tma4d(sb + k * 32768, &tmBre, k * 64, 0, 0, cb * 4, bars + B_FULL + k * 8);
                    tma4d(sb + k * 32768 + 8192, &tmBim, k * 64, 0, 0, cb * 4, bars + B_FULL + k * 8);
                    asm volatile("mbarrier.arrive.shared::cta.b64 _, [%0], 32;" ::"r"(bars + B_FULL + k * 8) : "memory");
                }
                STAMP(28);
            }
            __syncwarp();
        }
        asm volatile("barrier.cluster.wait.aligned;" ::: "memory");
        if (bid == 129 || (sb & 0x3FFFF) != SB0) return;
        if (w < 2) {
            if (extra || !elect_one()) return;
            const int rank = bid & 1;
            if (w == 0) {
                Prod r(sb, 0, 16384);
                int c0 = 64 * NST;
#pragma unroll 1
                for (uint32_t pat = phases(0, 32 - NST); pat != 1; pat >>= 1) {
                    mbar_wait(r.b0 + B_EMPTY, pat);
                    tma5d(r.dst(), &tmX, c0, 0, 0, 0, tc, r.b0);
                    mbar_expect_tx(r.b0, 32768);
                    asm volatile("mbarrier.arrive.shared::cta.b64 _, [%0], 32;" ::"r"(r.b0) : "memory");
                    c0 = (c0 + 64) & 1023;
                    r.next();
                }
                r.dbase -= 16384;
                const uint8_t* src = g_H + (size_t)tc * (32 * 16384);
                uint32_t all = (uint32_t)phases_from(32 - NST);
#pragma unroll 1
                for (int hh = 0; hh < 4; hh++) {
                    uint32_t pat = (all & 255) | 256;
                    all >>= 8;
                    mbar_wait(bars + B_HGO + 8 * hh, 0);
                    STAMPR(45 + hh);
#pragma unroll 1
                    do {
                        mbar_wait(r.b0 + B_EMPTY, pat);
                        bulk_ld(r.dst(), src, 16384, r.b0 + B_HLD);
                        mbar_expect_tx(r.b0 + B_HLD, 16384);
                        mbar_expect_tx(r.b0, 16384);
                        src += 16384;
                        r.next();
                        pat >>= 1;
                    } while (pat != 1);
                }
            } else {
                Prod r(sb, 0, rank * 8192);
                int c = 64 * NST;
#pragma unroll 1
                for (uint32_t pat = phases(0, 32 - NST); pat != 1; pat >>= 1) {
                    load_shared(r, pat, &tmBre + rank, c & 1023, cb * 4 + ((c >> 4) & 64), 1);
                    c += 64;
                }
                r.dbase += 16384;
                uint32_t pat = (uint32_t)phases_from(32 - NST);
#pragma unroll 1
                for (c = 0; c != 1024; c += 64) {
                    load_shared(r, pat, &tmBre + 2, c, cb * 8 + rank * 4, 0);
                    if (c == 64 * LDK) mbar_arrive(bars + B_LDONE);
                    load_shared(r, pat >> 1, &tmBre + 3, c, cb * 8 + rank * 4, 0);
                    pat >>= 2;
                }
            }
        } else if (w == 2) {
            if (!elect_one()) return;
            unsigned ep;
            asm volatile("ld.relaxed.gpu.global.u32 %0, [%1];" : "=r"(ep) : "l"(g_epoch + bid * 8) : "memory");
            if (!extra) {
                mbar_expect_tx(bars + B_XIN, 16384);
                mbar_expect_tx(bars + B_XIN + 8, 16384);
#pragma unroll 1
                for (int i = 0; i < 8; i++) {
                    const int k = i - XA_FIRST + XA_AT;
                    if (i >= XA_FIRST) mbar_wait(bars + B_EMPTY + (k < NST ? k : k - NST) * 8, k >= NST);
                    tma4d(sb + OFF_P + i * 2048, &tmXA, fcb * 32, 0, i, fb, bars + B_XIN);
                    tma4d(sb + OFF_P + 16384 + i * 2048, &tmXA, fcb * 32 + 16, 0, i, fb, bars + B_XIN + 8);
                }
            }
            ep++;
            asm volatile("st.relaxed.gpu.global.u32 [%0], %1;" ::"l"(g_epoch + bid * 8), "r"(ep) : "memory");
            asm volatile("st.shared.u32 [%0], %1;" ::"r"(bars + B_EPOCH), "r"(ep) : "memory");
            mbar_arrive(bars + B_EP);
            if (!extra) mbar_wait(bars + B_XIN + 8, 0);
            load_w(sb, &tmWr, p.unit[2 * bid] & 0xffff, 8192);
            if (!extra) mbar_wait(bars + B_STGU, 0);
            STAMP(21);
#pragma unroll 1
            for (int gi = 0; gi < 2; gi++) {
                if (!extra) {
#pragma unroll 1
                    for (int r = 128 * gi; r < 128 * gi + 128; r += UBOX) {
                        if (gi) __nanosleep(PACE_U);
                        tma2d_st(&tmUst, fb * 2048 + fpos * 64, r, sb + OFF_P + r * 128);
                    }
                    bulk_commit();
                    if (HINT_LATE) bulk_wait_read<0>();
                    red_hint(g_cnt + gi * 32);
                }
                if (!gi) bulk_ld(sb + OFF_F, g_tab + TAB_FG, 8192, bars + B_WIN);
                bulk_wait_read<0>();
                STAMPR(40 + gi);
                wait_cnt(g_cnt + 32 * gi, 128 * ep);
                if (gi) __nanosleep(UDELAY);
                else STAMP(42);
                mbar_expect_tx(bars + B_UIN + 8 * gi, 16384);
                bulk_ld(sb + OFF_P + gi * 16384, g_U + (size_t)(extra ? 0 : bid + 128 * gi) * 16384, 16384, bars + B_UIN + 8 * gi);
            }
            mbar_wait(bars + B_WFREE, 0);
            load_w(sb, &tmWr, p.unit[2 * bid + 1] & 0xffff, 0);
#pragma unroll 1
            for (int gi = 0; gi < 2; gi++) {
                const int vc = ((p.unit[2 * bid + gi] >> 16) & 255) * 32, go = vc >> 12;
                const uint32_t src = extra ? sb : sb + OFF_P + gi * 16384;
                mbar_wait(bars + B_STG, gi);
                STAMPR(23 + gi);
                if (extra && !gi) continue;
                if (bid + gi != 0) {
#pragma unroll 1
                    for (int r = 0; r < 256; r += VBOX) {
                        if (r && !gi) __nanosleep(PACE_V);
                        tma3d_st(&tmVst, vc + go * 4096, r & 127, r >> 7, src + r * 64);
                    }
                    bulk_commit();
                }
                if (HINT_LATE) bulk_wait_read<0>();
                red_hint(g_cnt + 64 + 32 * go);
                bulk_wait_read<0>();
                STAMP(49);
                if (extra) break;
                wait_cnt(g_cnt + 64 + 32 * gi, (129 - gi) * ep);
                STAMPR(43 + gi);
#pragma unroll
                for (int h = 0; h < 2; h++) {
                    mbar_expect_tx(bars + B_VIN + gi * 16 + h * 8, 8192);
                    bulk_ld(src + h * 8192, g_V + (uint32_t)((fb * 32 + fpos) * 32768 + gi * 16384 + h * 8192), 8192, bars + B_VIN + gi * 16 + h * 8);
                }
            }
        } else {
            if (extra) return;
            const int lane = (threadIdx.x + p.zero[0]) & 31;
            const uint32_t tag = get_epoch(bars);
            Prod r(sb, 32, 0);
            uint32_t va = (lane & 3) * 516 + (lane >> 4) * 2048 + (lane & 12) * 32 + (lane >> 2) * 16 + r.dbase;
            asm volatile("" : "+r"(va));
            uint32_t n = 0;
#pragma unroll 1
            for (int half = 0; half < 2; half++) {
#pragma unroll 1
                for (uint32_t pat = phases(16 * half, 16); pat != 1; pat >>= 1) {
                    mbar_wait(r.b0 + B_HLD, pat);
                    bool bad = lines_bad(r.b0 * 4096 + va, tag, 1);
                    if (!bad) mbar_arrive(r.b0);
#pragma unroll 1
                    while (__any_sync(~0u, bad)) {
                        const int kk = __shfl_sync(~0u, pat, 0);
                        if (elect_one()) {
                            mbar_expect_tx(bars + B_HRTY, 16384);
                            bulk_ld(r.dst(), g_H + (uint32_t)(tc * 32 + half * 16 + __clz(kk) - 15) * 16384, 16384, bars + B_HRTY);
                        }
                        __syncwarp();
                        mbar_wait(bars + B_HRTY, n++);
                        if (bad && !lines_bad(r.b0 * 4096 + va, tag, n < SPIN_LIMIT)) { bad = false; mbar_arrive(r.b0); }
                        __syncwarp();
                    }
                    if (pat >> 16) STAMPR(6 + 23 * half);
                    r.next();
                }
            }
        }
    } else {
        asm volatile("setmaxnreg.inc.sync.aligned.u32 152;");
        asm volatile("barrier.cluster.wait.aligned;" ::: "memory");
        STAMP(55);
        if ((extra && (wg != 2 || bid == 129)) || (sb & 0x3FFFF) != SB0) return;
        const int hf = wg - 1;
#define INDICES(i) const int t7 = (threadIdx.x + p.zero[i]) & 127, lane = t7 & 31, g = lane >> 2, q = lane & 3, k1 = t7 >> 2, mi = lane >> 3, gl = lane & 7; \
                   const uint32_t tmask = q == 0 ? ~1u : ~0u;
        if (wg == 1) {
            INDICES(1)
            const int ch = (t7 >> 6) * 512 + (t7 & 8) * 32 + cb * 32 + ((t7 >> 1) & 24) + (t7 & 7);
            const float lr = __bfloat162float(p.lre[ch]), li = __bfloat162float(p.lim[ch]);
            const float dt = __bfloat162float(__float2bfloat16(expf(__bfloat162float(p.ldt[ch]))));
            float sn, cs;
            sincospif(dt * li * 0.31830988618379067f, &sn, &cs);
            const float ex = expf(dt * lr), br = ex * cs, bi = ex * sn;
            const float inv = __fdividef(2.0f, lr * lr + li * li);
            const cf lam = {br, -bi}, gam = {((br - 1.f) * lr + bi * li) * inv, -(bi * lr - (br - 1.f) * li) * inv};
            const cf l32 = csq(csq(csq(csq(csq(lam))))), l64 = csq(l32), m1 = csq(l64), m2 = csq(m1), g2 = cmul(gam, l64);
            sts128f(sb + OFF_T1 + t7 * 16, lam, l32);
            sts128f(sb + OFF_TL + t7 * 32, gam, cmul(gam, l32));
            sts128f(sb + OFF_TL + t7 * 32 + 16, g2, cmul(g2, l32));
            sts128f(sb + OFF_TM + t7 * 32, csq(m2), m1);
            sts128f(sb + OFF_TM + t7 * 32 + 16, m2, cmul(m2, m1));
            __syncwarp();
            if (lane == 0) mbar_arrive(bars + B_LAM);
        }
        if (wg != 0 && !extra) {
            INDICES(2)
            uint32_t f1[16];
#pragma unroll
            for (int j = 0; j < 4; j++) { const uint4 v = ldtab(TAB_F1 + j * 512 + t7 * 4); f1[4 * j] = v.x; f1[4 * j + 1] = v.y; f1[4 * j + 2] = v.z; f1[4 * j + 3] = v.w; }
            cf tw[8];
            load_tw(tw, k1);
            const uint32_t tbit = get_epoch(bars) & ~tmask;
            float acc[64];
            const uint64_t dx = mkdesc(OFF_P, 2048, 256, 3) + hf * 1024;
            const int jr = (w & 1) ? (gl == 0 ? 4 : (gl < 5 ? gl - 1 : gl)) : gl, gr = (w & 1) ? (jr < 4) : (jr >> 2);
            const uint32_t a0 = w + gl ? sb + OFF_P + (gr * 128 + 8 * (w >> 1) + jr + 16 * (mi >> 1)) * 128 : sb + OFF_F + 2048;
            const uint32_t rs = w + gl ? 2048 : 0;
            const uint32_t scr = sb + OFF_F + hf * 1024;
            mbar_wait(bars + B_XIN + hf * 8, 0);
            STAMP(20);
            pinu(f1);
            wg_fence();
            mma128_rs<1, 0>(acc, f1, dx);
            mma128_rs<1, 1>(acc, f1 + 4, dx + 32);
            mma128_rs<1, 1>(acc, f1 + 8, dx + 64);
            mma128_rs<1, 1>(acc, f1 + 12, dx + 96);
            wg_commit();
            wg_wait<0>();
            pin(acc);
            pinu(f1);
            if (k1 == 0) {
#pragma unroll
                for (int i = 0; i < 16; i++) sts128f(scr + i * 64 + q * 16, {acc[4 * i], acc[4 * i + 1]}, {acc[4 * i + 2], acc[4 * i + 3]});
            }
            uint4 fx0, fx1;
            asm volatile("ld.global.nc.v4.b32 {%0,%1,%2,%3}, [%4];" : "=r"(fx0.x), "=r"(fx0.y), "=r"(fx0.z), "=r"(fx0.w) : "l"(g_tab + TAB_FX + (t7 & 120)));
            asm volatile("ld.global.nc.v4.b32 {%0,%1,%2,%3}, [%4];" : "=r"(fx1.x), "=r"(fx1.y), "=r"(fx1.z), "=r"(fx1.w) : "l"(g_tab + TAB_FX + (t7 & 120) + 4));
#pragma unroll
            for (int cl = 0; cl < 2; cl++) {
                cf v0[8], v1[8];
#pragma unroll
                for (int n = 0; n < 8; n++) {
                    const int i = 4 * (2 * n + cl);
                    v0[n] = {acc[i], acc[i + 2]};
                    v1[n] = {acc[i + 1], acc[i + 3]};
                }
                dft8<true>(v0, tw);
                dft8<true>(v1, tw);
                cf sx[8];
                if (cl == 0) {
                    bar_sync(6, 256);
#pragma unroll
                    for (int n = 0; n < 8; n++) sx[n] = lds_cf(scr + n * 128 + gl * 16 + (w >> 1) * 8);
                }
                const uint32_t a1 = a0 + (((((mi & 1) << 2) | ((2 * hf + cl) ^ (fpos & 3))) ^ jr) << 4);
#pragma unroll
                for (int r = 0; r < 8; r += 2) {
                    uint32_t o0 = pk(v0[r].x, v1[r].x), o1 = pk(v0[r].y, v1[r].y), o2 = pk(v0[r + 1].x, v1[r + 1].x), o3 = pk(v0[r + 1].y, v1[r + 1].y);
                    if (cl == 0) { o0 = bitsel(o0, tmask, tbit); o1 = bitsel(o1, tmask, tbit); o2 = bitsel(o2, tmask, tbit); o3 = bitsel(o3, tmask, tbit); }
                    stsm4(a1 + r * rs, o0, o1, o2, o3);
                }
                if (cl == 0) {
                    YIELD();
                    float s0 = 0.f, s1 = 0.f;
#pragma unroll
                    for (int n = 0; n < 8; n++) {
                        const float c = __uint_as_float(n < 4 ? (n == 0 ? fx0.x : n == 1 ? fx0.y : n == 2 ? fx0.z : fx0.w) : (n == 4 ? fx1.x : n == 5 ? fx1.y : n == 6 ? fx1.z : fx1.w));
                        s0 = fmaf(c, sx[n].x, s0); s1 = fmaf(c, sx[n].y, s1);
                    }
                    asm volatile("st.shared.b32 [%0], %1;" ::"r"(sb + OFF_P + (t7 >> 4) * 2048 + (((mi & 1) * 4 + ((2 * hf + (g & 1)) ^ (fpos & 3))) << 4) + q * 4), "r"(bitsel(pk(s0, s1), tmask, tbit)) : "memory");
                    YIELD();
                }
            }
            fence_async_sm();
            __syncwarp();
            if (lane == 0) mbar_arrive(bars + B_STGU);
        }
        if (wg != 2) {
        if (wg == 0) bar_sync(4, 128);
        asm volatile("setmaxnreg.inc.sync.aligned.u32 168;");
        float d[128];
        Ring rg;
        rg.full = bars + B_FULL;
        asm("mapa.shared::cluster.u32 %0, %1, %2;" : "=r"(rg.rel) : "r"(bars + B_EMPTY), "r"(w & 1));
        rg.sig = ((threadIdx.x + p.zero[7]) & 95) == 0;
        rg.bh = (uint32_t)(mkdesc(0, 0, 1024, 1) >> 32) + p.zero[0];
        rg.da = p.da[0];
        rg.ph = 1;
        if (wg == 0) {
            STAMP(0);
            gemm_step<0, 0>(d, rg, 0);
        } else {
            bar_sync(1, 256);
            STAMP(10);
        }
        rg.da = p.da[1];
#pragma unroll 1
        for (int i = 0; i < 3; i++) {
            gemm_step<1, 0>(d, rg, i >= wg);
            gemm_step<2, 0>(d, rg, 1);
            gemm_step<3, 0>(d, rg, 1);
            gemm_step<4, 0>(d, rg, 1);
            gemm_step<0, 0>(d, rg, 1);
        }
        if (wg == p.zero[1]) bar_arrive(1, 256);
        else {
            rg.da = p.da[0];
            gemm_step<1, 0>(d, rg, 1);
            bar_arrive(2, 256);
        }
        {
            INDICES(3)
            cf lam[2], l32[2], l2[2];
            const uint32_t ta = sb + (wg * 64 + 16 * w + g) * 16;
            mbar_wait(bars + B_LAM, 0);
            const unsigned ep = get_epoch(bars), tag = ep & 15u;
            lds128f(ta + OFF_T1, lam[0].x, lam[0].y, l32[0].x, l32[0].y);
            lds128f(ta + OFF_T1 + 128, lam[1].x, lam[1].y, l32[1].x, l32[1].y);
            const uint4* cpub = g_carry + (uint32_t)(wg * 256 + cb * 32 + 8 * w + tc * 512 + g);
            l2[0] = csq(lam[0]);
            l2[1] = csq(lam[1]);
            asm volatile("pmevent 0;" : "+l"(cpub), "+f"(l2[0].x), "+f"(l2[0].y), "+f"(l2[1].x), "+f"(l2[1].y));
            wg_wait<0>();
            ring_release(rg, wg);
            pin(d);
            STAMPW(1, 11);
            cf f[2];
#pragma unroll
            for (int h = 0; h < 2; h++) {
                cf e = {d[2 * h], -d[64 + 2 * h]}, o = {d[2 * h + 1], -d[65 + 2 * h]};
#pragma unroll
                for (int i = 1; i < 16; i++) {
                    const int r = 4 * i + 2 * h;
                    const float a0 = fmaf(-l2[h].y, e.y, d[r]), a1 = fmaf(-l2[h].y, o.y, d[r + 1]);
                    const float b0 = fmaf(l2[h].y, e.x, -d[64 + r]), b1 = fmaf(l2[h].y, o.x, -d[65 + r]);
                    e.x = fmaf(l2[h].x, e.x, a0); o.x = fmaf(l2[h].x, o.x, a1); e.y = fmaf(l2[h].x, e.y, b0); o.y = fmaf(l2[h].x, o.y, b1);
                    if (i % YS == 0) YIELD();
                }
                f[h] = cfma(lam[h], e, o);
            }
            cf st[2], gam[2];
            gam[0] = lds_cf(2 * ta - sb + OFF_TL);
            gam[1] = lds_cf(2 * ta - sb + OFF_TL + 256);
            cf v0[2], v1[2], v2[2];
#pragma unroll
            for (int h = 0; h < 2; h++) {
                v0[h] = {__shfl_sync(~0u, f[h].x, 0, 4), __shfl_sync(~0u, f[h].y, 0, 4)};
                v1[h] = {__shfl_sync(~0u, f[h].x, 1, 4), __shfl_sync(~0u, f[h].y, 1, 4)};
                v2[h] = {__shfl_sync(~0u, f[h].x, 2, 4), __shfl_sync(~0u, f[h].y, 2, 4)};
            }
#pragma unroll
            for (int h = 0; h < 2; h++) {
                v1[h] = cfma(l32[h], v0[h], v1[h]);
                v2[h] = cfma(l32[h], v1[h], v2[h]);
                f[h] = cfma(l32[h], v2[h], f[h]);
            }
            asm volatile("{.reg .pred p; .reg .b64 a, b; .reg .b128 v; setp.eq.u32 p, %5, 3; mov.b64 a, {%1,%2}; mov.b64 b, {%3,%4}; mov.b128 v, {a, b};\n"
                         "@p st.relaxed.gpu.global.b128 [%0], v;}" ::"l"(cpub),
                         "r"(bitsel(__float_as_uint(f[0].x), ~15u, tag)), "r"(__float_as_uint(f[0].y)), "r"(__float_as_uint(f[1].x)), "r"(__float_as_uint(f[1].y)), "r"(q) : "memory");
            STAMPX(2, 12);
            YIELD();
#pragma unroll
            for (int h = 0; h < 2; h++) st[h] = cmul(gam[h], csel(q & 2, csel(q & 1, v2[h], v1[h]), csel(q & 1, v0[h], cf{0.f, 0.f})));
            const uint4* cget = cpub + (gl - g) - (1 + mi) * 512;
            const int nget = tc - 1 - mi;
            unsigned __int128 fq[4];
#pragma unroll
            for (int i = 0; i < 32; i++) {
                if (i == POLL_AT) carry_poll(fq, cget, nget, tag);
                if (i % YS == 0) YIELD();
                const int h = i >> 4, r = 4 * (i & 15) + 2 * h;
                asm volatile("{.reg .f32 s0, s1, n; neg.f32 n, %4; mul.f32 s0, %5, %1; mul.f32 s1, %5, %3; mul.f32 %1, n, %1; mul.f32 %3, n, %3;\n"
                             "fma.rn.f32 %1, %5, %0, %1; fma.rn.f32 %3, %5, %2, %3; fma.rn.f32 %0, %4, %0, s0; fma.rn.f32 %2, %4, %2, s1;}"
                             : "+f"(d[r]), "+f"(d[64 + r]), "+f"(d[r + 1]), "+f"(d[65 + r]) : "f"(gam[h].x), "f"(gam[h].y));
            }
            YIELD();
            const uint32_t tm = sb + OFF_TM + (wg * 64 + 16 * w) * 32;
            cf m4[2], mj[2], P[2], lq[2];
#pragma unroll
            for (int h = 0; h < 2; h++) {
                m4[h] = lds_cf(tm + gl * 32 + h * 256);
                mj[h] = lds_cf(tm + gl * 32 + h * 256 + mi * 8);
            }
            uint32_t bad = carry_sum(fq, m4, tag, P);
            unsigned n = 0;
            while (__any_sync(~0u, bad) && ++n < SPIN_LIMIT) {
                unsigned __int128 fr[4];
                carry_poll(fr, cget, nget, tag);
                bad = carry_sum(fr, m4, tag, P);
                YIELD();
                mj[0] = lds_cf(tm + gl * 32 + mi * 8);
                mj[1] = lds_cf(tm + gl * 32 + 256 + mi * 8);
            }
            STAMPX(53, 54);
            P[0] = csel(mi, cmul(P[0], mj[0]), P[0]);
            P[1] = csel(mi, cmul(P[1], mj[1]), P[1]);
            __syncwarp();
            sts128f(tm + lane * 16, P[0], P[1]);
#pragma unroll
            for (int h = 0; h < 2; h++) {
                lq[h] = lds_cf(2 * ta - sb + OFF_TL + h * 256 + q * 8);
                lam[h] = lds_cf(ta + OFF_T1 + h * 128);
            }
            __syncwarp();
            float ps[4][4];
#pragma unroll
            for (int j = 0; j < 4; j++) lds128f(tm + g * 16 + j * 128, ps[j][0], ps[j][1], ps[j][2], ps[j][3]);
            const uint8_t* hp = g_H + (uint32_t)((tc * 32 + wg * 16 + (cb & 6)) * 16384 + ((cb & 1) * 4 + w) * 2048 + g * 64 + ((q ^ (g >> 1)) << 4));
#pragma unroll
            for (int h = 0; h < 2; h++)
                st[h] = cfma(lq[h], {(ps[0][2 * h] + ps[1][2 * h]) + (ps[2][2 * h] + ps[3][2 * h]), (ps[0][2 * h + 1] + ps[1][2 * h + 1]) + (ps[2][2 * h + 1] + ps[3][2 * h + 1])}, st[h]);
            STAMPX(3, 13);
            uint32_t hv[32];
#pragma unroll
            for (int h = 0; h < 2; h++) {
                YIELD();
                cf c = st[h];
#pragma unroll
                for (int i = 0; i < 16; i++) {
                    const int r = 4 * i + 2 * h;
                    const cf a = cfma(lam[h], c, {d[r], d[64 + r]});
                    c = cfma(lam[h], a, {d[r + 1], d[65 + r]});
                    hv[i] = pk(a.x, c.x);
                    hv[16 + i] = pk(a.y, c.y);
                    if ((i & 3) == (i >> 2)) { hv[i] = bitsel(hv[i], ~1u, ep & 1); hv[16 + i] = bitsel(hv[16 + i], ~1u, ep & 1); }
                    if (h == 0 && (i & 3) == 3) {
                        stg128(hp + (i >> 2) * 512, hv[i - 3], hv[i - 2], hv[i - 1], hv[i]);
                        stg128(hp + 16384 + (i >> 2) * 512, hv[13 + i], hv[14 + i], hv[15 + i], hv[16 + i]);
                    }
                }
                if (h == 0) {
                    STAMPW(4, 14);
                    if (lane == 0) red_hint(g_hcnt + tc * 64 + wg * 32);
                }
            }
            YIELD();
            if (w == 0) {
                wait_cnt(g_hcnt + tc * 64 + wg * 32, 32 * ep);
                if (lane < 4) mbar_arrive(bars + B_HGO + 16 * wg);
            } else mbar_wait(bars + B_HGO + 16 * wg, 0);
            if (HDELAY) __nanosleep(HDELAY);
#pragma unroll
            for (int j = 0; j < 8; j++) {
                stg128(hp + (8 + (j >> 2)) * 16384 + (j & 3) * 512, hv[4 * j], hv[4 * j + 1], hv[4 * j + 2], hv[4 * j + 3]);
                if (j < 7) __nanosleep(PACE_H);
            }
            __syncwarp();
            if (lane == 0) mbar_arrive(bars + B_HGO + 16 * wg + 8);
            STAMPW(5, 15);
        }
        if (wg == p.zero[2]) {
            INDICES(1)
            float y[128];
            const uint32_t sa = sb + w * 4096 + g * 512 + q * 8;
            bar_sync(2, 256);
            STAMP(7);
            rg.da = p.da[2];
            rg.ph = 0;
#pragma unroll 1
            for (int i = 0;; i++) {
                gemm_step<2, 1>(y, rg, i);
                gemm_step<3, 1>(y, rg, 1);
                gemm_step<4, 1>(y, rg, 1);
                if (i == 5) break;
                gemm_step<0, 1>(y, rg, 1);
                gemm_step<1, 1>(y, rg, 1);
            }
            rg.da = p.da[3];
            gemm_half<64 - SKEW, 0>(y, rg);
            wg_commit();
            gemm_half<64 - SKEW, 1>(y, rg);
            wg_commit();
#pragma unroll
            for (int r = 0; r < 4; r++) {
                if (r == 0) {
                    wg_wait<1>();
#pragma unroll
                    for (int i = 0; i < 64; i++) asm volatile("" : "+f"(y[i])::"memory");
                    STAMP(16);
                    bar_sync(4, 128);
                }
                if (r == 2) {
                    STAMP(18);
                    wg_wait<0>();
#pragma unroll
                    for (int i = 64; i < 128; i++) asm volatile("" : "+f"(y[i])::"memory");
                    STAMP(8);
                    bar_sync(4, 128);
                }
#pragma unroll
                for (int c = 0; c < 16; c++) {
                    const int yi = 64 * (r >> 1) + 4 * c + 2 * (r & 1);
                    sts64f(sa + (r < 2 ? (NST - 1) * 32768 : 0) + (r & 1) * 16384 + (c >> 2) * 128 + (((c ^ g) & 3) << 5), y[yi], y[yi + 1]);
                }
                if (r == 0) bar_arrive(9, 256);
                if (r == 1) bar_arrive(10, 256);
                if (r == 2) bar_arrive(11, 256);
                if (r == 3) bar_arrive(12, 256);
            }
            STAMP(19);
            return;
        }
        bar_sync(8, 128);
        asm volatile("setmaxnreg.dec.sync.aligned.u32 152;");
        } else {
            INDICES(4)
            cf T[8];
            load_T(T, t7);
            const uint32_t tag = get_epoch(bars) & 1;
#pragma unroll 1
            for (int gi = 0; gi < 2; gi++) {
                const uint32_t un = p.unit[2 * bid + gi];
                const int kap = un & 0xffff;
                const uint32_t buf = sb + OFF_P + gi * 16384;
                STAMP3(39);
                float acc[64], za[32], zb[32], ya[32], yb[32], vv[64];
                constexpr uint64_t dF = mkdesc(OFF_F, 16, 1024, 1);
                const uint64_t dB = mkdesc(OFF_P, 4096, 512, 2) + gi * 1024;
                cf be1, be2, be3;
                uint32_t wad[4];
                mbar_wait(bars + B_WIN, gi);
#pragma unroll 1
                for (int n = 0; n < 4096; n++) {
                    mbar_wait(bars + B_UIN + gi * 8, n & 1);
                    STAMP3(22);
                    wg_fence();
                    mma128_ss<0, 0, 1, 0>(acc, dF, dB);
                    mma128_ss<0, 0, 1, 1>(acc, dF + 2, dB + 64);
                    mma128_ss<0, 0, 1, 1>(acc, dF + 4, dB + 128);
                    mma128_ss<0, 0, 1, 1>(acc, dF + 6, dB + 192);
                    wg_commit();
                    const uint32_t bad = tag_bad(buf + t7 * 128 + (((t7 & 1) ^ (g & 2)) << 4) + (g & 1) * 64, tag);
                    int kq;
                    asm volatile("mad.lo.s32 %0, %1, 512, %2;" : "=r"(kq) : "r"(q), "r"(kap));
                    be1 = twid(kq, 2048); be2 = cmul(be1, be1); be3 = cmul(be1, be2);
#pragma unroll
                    for (int j = 0; j < 4; j++) wad[j] = sb + OFF_W + ((j + (kq >> 9)) & 3) * WPITCH + ((2 * kap) & 15) + 2 * k1 + 128 * q;
                    const bool ok = wg_all_ok(bad, 3);
                    YIELD();
                    wg_wait<0>();
                    pin(acc);
                    if (ok) break;
                    bar_sync(3, 128);
                    if (w == 0 && elect_one()) { mbar_expect_tx(bars + B_UIN + gi * 8, 16384); bulk_ld(buf, g_U + (size_t)(extra ? 0 : bid + gi * 128) * 16384, 16384, bars + B_UIN + gi * 8); }
                }
                STAMP3(30);
                const int im = g & 1, mir = mi & 1;
                const uint32_t ad = sb + OFF_W + (4 * im + q) * WPITCH + ((2 * kap) & 15) + 1024 * mir;
                const uint32_t am = sb + OFF_W + (8 + 4 * im + (((kap ? 3 : 4) - q) & 3)) * WPITCH + ((-2 * kap) & 15) + 1024 * mir;
                uint32_t pa, pb;
                if (w == 2) { pa = lds_u16(mir ? am : ad); pb = lds_u16(mir ? ad : am); }
                uint32_t af[32];
#pragma unroll
                for (int b = 0; b < 4; b++) {
#pragma unroll
                    for (int c = 0; c < 4; c++) {
                        const int i = 4 * (4 * b + c);
                        cf x0 = cmul({acc[i], acc[i + 2]}, T[2 * c]), x1 = cmul({acc[i + 1], acc[i + 3]}, T[2 * c + 1]);
                        af[16 * (b >> 1) + 4 * c + (b & 1)] = pk(x0.x, x0.y);
                        af[16 * (b >> 1) + 4 * c + 2 + (b & 1)] = pk(x1.x, x1.y);
                        if (c & 1) YIELD(); else YIELD2();
                    }
                    if (b == 0 && w == 2 && lane < 16)
                        asm volatile("st.shared.u16 [%0], %1;" ::"r"(mir ? am : ad), "h"((unsigned short)pk(0.5f * (im ? up(pa) - up(pb) : up(pa) + up(pb)), 0.f)) : "memory");
                    if (b == 1) {
                        wg_fence();
                        mma64_rs<0, 0>(za, af, dF); mma64_rs<0, 1>(za, af + 4, dF + 2); mma64_rs<0, 1>(za, af + 8, dF + 4); mma64_rs<0, 1>(za, af + 12, dF + 6);
                        wg_commit();
                    }
                }
                wg_fence();
                mma64_rs<0, 0>(zb, af + 16, dF); mma64_rs<0, 1>(zb, af + 20, dF + 2); mma64_rs<0, 1>(zb, af + 24, dF + 4); mma64_rs<0, 1>(zb, af + 28, dF + 6);
                wg_commit();
                STAMP3(31);
                bar_sync(3, 128);
                uint32_t wn[8];
#pragma unroll
                for (int j = 0; j < 4; j++) { wn[2 * j] = lds_u16(wad[j]); wn[2 * j + 1] = lds_u16(wad[j] + 4 * WPITCH); }
                wg_wait<0>();
                pin(za);
                pin(zb);
                pinu(af);
                STAMP3(32);
#pragma unroll
                for (int jb = 0; jb < 4; jb++) {
                    if (jb == 2) STAMP3(37);
                    if (jb == 3) load_T(T, t7);
                    cf z[2][4];
#pragma unroll
                    for (int e = 0; e < 2; e++) {
                        cf W[4];
#pragma unroll
                        for (int j = 0; j < 4; j++) W[j] = {up(wn[2 * j]), jb < 2 ? up(wn[2 * j + 1]) : -up(wn[2 * j + 1])};
                        YIELD();
                        const int nx = 2 * jb + e + 1;
                        if (nx == 4) {
#pragma unroll
                            for (int j = 0; j < 4; j++)
                                wad[j] = sb + OFF_W + (8 + (((kap ? 3 : 4) - j - q) & 3)) * WPITCH + ((-2 * kap) & 15) + 1024 - 2 * k1 - 128 * q;
                        }
                        if (nx < 8) {
                            const int off = nx < 4 ? 512 * (nx >> 1) + 64 * (nx & 1) : -(512 * ((nx >> 1) - 2) + 64 * (nx & 1));
#pragma unroll
                            for (int j = 0; j < 4; j++) { wn[2 * j] = lds_u16(wad[j] + off); wn[2 * j + 1] = lds_u16(wad[j] + off + 4 * WPITCH); }
                        }
                        const int i = 8 * jb + e;
                        const cf z0 = {za[i], za[i + 4]};
                        cf s0 = cfma({zb[i], zb[i + 4]}, be2, z0), s1 = twice_minus(z0, s0);
                        YIELD2();
                        const cf z1 = cmul({za[i + 2], za[i + 6]}, be1);
                        cf s2 = cfma({zb[i + 2], zb[i + 6]}, be3, z1), s3 = twice_minus(z1, s2);
                        YIELD();
                        const cf y0 = cmul(cadd(s0, s2), W[0]), x2 = csub(s0, s2);
                        YIELD2();
                        const cf y1 = cmul({s1.x + s3.y, s1.y - s3.x}, W[1]), x3 = {s1.x - s3.y, s1.y + s3.x};
                        YIELD();
                        s0 = cfma(x2, W[2], y0); s1 = twice_minus(y0, s0);
                        s2 = cfma(x3, W[3], y1); s3 = twice_minus(y1, s2);
                        YIELD2();
                        z[e][0] = cadd(s0, s2);
                        z[e][2] = cmulc(csub(s0, s2), be2);
                        YIELD();
                        z[e][1] = cmulc({s1.x - s3.y, s1.y + s3.x}, be1);
                        z[e][3] = cmulc({s1.x + s3.y, s1.y - s3.x}, be3);
                        YIELD2();
                    }
#pragma unroll
                    for (int b = 0; b < 4; b++) {
                        af[16 * (b >> 1) + 4 * jb + (b & 1)] = pk(z[0][b].x, z[1][b].x);
                        af[16 * (b >> 1) + 4 * jb + 2 + (b & 1)] = pk(z[0][b].y, z[1][b].y);
                    }
                }
                pinu(af);
                wg_fence();
                mma64_rs<1, 0>(ya, af, dF); mma64_rs<1, 1>(ya, af + 4, dF + 128); mma64_rs<1, 1>(ya, af + 8, dF + 256); mma64_rs<1, 1>(ya, af + 12, dF + 384);
                wg_commit();
                mma64_rs<1, 0>(yb, af + 16, dF); mma64_rs<1, 1>(yb, af + 20, dF + 128); mma64_rs<1, 1>(yb, af + 24, dF + 256); mma64_rs<1, 1>(yb, af + 28, dF + 384);
                wg_commit();
                STAMP3(33);
                if (w == 2) fence_async_sm();
                __syncwarp();
                if (lane == 0) mbar_arrive(bars + B_WFREE);
                {
                    const uint32_t a0 = buf + (mi & 1) * 4096 + (16 * w + 8 * (mi >> 1) + gl) * 64;
#pragma unroll
                    for (int u = 0; u < 2; u++)
#pragma unroll
                        for (int c = 0; c < 4; c++) {
                            if (c == 0) {
                                if (u == 0) { wg_wait<1>(); pin(ya); STAMP3(34); }
                                else { wg_wait<0>(); pin(yb); pinu(af); }
                            }
                            const int i = 8 * c;
                            const float(&yy)[32] = u ? yb : ya;
                            const cf x0 = cmulc({yy[i], yy[i + 1]}, T[2 * c]), x1 = cmulc({yy[i + 4], yy[i + 5]}, T[2 * c + 1]);
                            const uint32_t o0 = pk(x0.x, x1.x), o2 = pk(x0.y, x1.y);
                            YIELD2();
                            const cf y0 = cmulc({yy[i + 2], yy[i + 3]}, T[2 * c]), y1 = cmulc({yy[i + 6], yy[i + 7]}, T[2 * c + 1]);
                            stsm4(a0 + u * 8192 + ((c ^ (gl >> 1)) << 4), o0, pk(y0.x, y1.x), o2, pk(y0.y, y1.y));
                            YIELD();
                        }
                }
                STAMP3(38);
                fence_async_sm();
                bar_sync(3, 128);
                wg_fence();
                mma128_ss<0, 1, 1, 0>(vv, dF, dB);
                mma128_ss<0, 1, 1, 1>(vv, dF + 128, dB + 64);
                mma128_ss<0, 1, 1, 1>(vv, dF + 256, dB + 128);
                mma128_ss<0, 1, 1, 1>(vv, dF + 384, dB + 192);
                wg_commit();
                STAMP3(35);
                const uint32_t flip = ((g & 1) && !(un >> 24)) ? 0x80008000u : 0u, flipt = flip | (tag & ~tmask);
                const int rw = 8 * w + 4 * (mi & 1) + (gl >> 1);
                const uint32_t a0 = (extra ? ((gl & 1) == gi ? sb : sb + 16384) : buf) + rw * 64 +
                                    (((((gl & 1) << 1) | ((mi >> 1) ^ ((un >> 17) & 1))) ^ ((rw >> 1) & 3)) << 4);
                YIELD();
                wg_wait<0>();
                pin(vv);
                STAMP3(36);
                bar_sync(3, 128);
#pragma unroll
                for (int b = 0; b < 4; b++)
#pragma unroll
                    for (int c = 0; c < 4; c += 2) {
                        const int i = 4 * (4 * b + c);
                        stsm4(a0 + b * 2048 + c * 4096, (pk(vv[i], vv[i + 1]) & tmask) ^ flipt, (pk(vv[i + 2], vv[i + 3]) & tmask) ^ flipt,
                              pk(vv[i + 4], vv[i + 5]) ^ flip, pk(vv[i + 6], vv[i + 7]) ^ flip);
                    }
                fence_async_sm();
                __syncwarp();
                if (lane == 0) mbar_arrive(bars + B_STG);
            }
            if (extra) return;
        }
        {
            INDICES(5)
            uint32_t sp[8];
#pragma unroll
            for (int j = 0; j < 2; j++) { const uint4 v = ldtab(TAB_SP + j * 512 + t7 * 4); sp[4 * j] = v.x; sp[4 * j + 1] = v.y; sp[4 * j + 2] = v.z; sp[4 * j + 3] = v.w; }
            cf tw[8];
            load_tw(tw, k1);
            tw[4].x *= 2.f; tw[4].y *= 2.f;
            const uint32_t tag = get_epoch(bars) & 1;
            const uint32_t in = sb + OFF_P + hf * 8192;
            constexpr uint64_t dF = mkdesc(OFF_F, 16, 1024, 1);
            const uint64_t dB = mkdesc(OFF_P, 2048, 256, 3) + hf * 512;
            float acc[64];
#pragma unroll
            for (int rgn = 0; rgn < 2; rgn++) {
#pragma unroll 1
                for (int n = 0; n < 4096; n++) {
                    mbar_wait(bars + B_VIN + rgn * 16 + hf * 8, n & 1);
                    if (rgn) STAMP(25);
                    pinu(sp);
                    wg_fence();
                    if (rgn == 0) {
                        mma48_ss<0>(acc, dF, dB + 128); mma16_rs<0>(acc, sp[0], 0u, sp[1], 0u, dB);
                        mma48_ss<1>(acc, dF + 2, dB + 160); mma16_rs<1>(acc, sp[2], 0u, sp[3], 0u, dB + 32);
                        mma48_ss<1>(acc, dF + 4, dB + 192); mma16_rs<1>(acc, 0u, sp[4], 0u, sp[5], dB + 64);
                        mma48_ss<1>(acc, dF + 6, dB + 224); mma16_rs<1>(acc, 0u, sp[6], 0u, sp[7], dB + 96);
                    } else {
                        mma64_ss<0>(acc, dF, dB + 1024);
                        mma64_ss<1>(acc, dF + 2, dB + 1056);
                        mma64_ss<1>(acc, dF + 4, dB + 1088);
                        mma64_ss<1>(acc, dF + 6, dB + 1120);
                    }
                    wg_commit();
                    const uint32_t bad = tag_bad(in + rgn * 16384 + t7 * 64 + (t7 & 6) * 8, tag);
                    wg_wait<0>();
                    pin(acc);
                    pinu(sp);
                    if (wg_all_ok(bad, hf ? 3 : 8)) break;
                    if (w == 0 && elect_one()) {
                        mbar_expect_tx(bars + B_VIN + rgn * 16 + hf * 8, 8192);
                        bulk_ld(in + rgn * 16384, g_V + (uint32_t)((fb * 32 + fpos) * 32768 + rgn * 16384 + hf * 8192), 8192, bars + B_VIN + rgn * 16 + hf * 8);
                    }
                }
            }
            uint32_t o[2][16];
#pragma unroll
            for (int cl = 0; cl < 2; cl++) {
                cf z[2][8];
#pragma unroll
                for (int e = 0; e < 2; e++) {
                    const float b0 = acc[4 * cl + e], b8 = acc[4 * cl + 2 + e];
                    z[e][0] = {b0 + b8, b0 - b8};
                    z[e][4] = cmul({acc[4 * (8 + cl) + e], acc[4 * (8 + cl) + 2 + e]}, tw[4]);
#pragma unroll
                    for (int n = 1; n < 4; n++) {
                        const cf w16 = n == 1 ? cf{0.92387953251128674f, -0.38268343236508977f}
                                              : (n == 2 ? cf{0.70710678118654752f, -0.70710678118654752f} : cf{0.38268343236508977f, -0.92387953251128674f});
                        YIELD();
                        const cf y = cmul({acc[4 * (2 * n + cl) + e], acc[4 * (2 * n + cl) + 2 + e]}, tw[n]);
                        const cf u = {acc[4 * (2 * (8 - n) + cl) + e], acc[4 * (2 * (8 - n) + cl) + 2 + e]}, t = tw[8 - n];
                        const cf E = {fmaf(u.x, t.x, fmaf(-u.y, t.y, y.x)), fmaf(-u.x, t.y, fmaf(-u.y, t.x, y.y))};
                        YIELD2();
                        const cf D = twice_minus(y, E);
                        z[e][n] = {fmaf(-D.x, w16.y, fmaf(-D.y, w16.x, E.x)), fmaf(D.x, w16.x, fmaf(-D.y, w16.y, E.y))};
                        z[e][8 - n] = {fmaf(2.f, E.x, -z[e][n].x), fmaf(-2.f, E.y, z[e][n].y)};
                    }
                    YIELD();
                    dft8<false>(z[e], tw);
                }
#pragma unroll
                for (int m = 0; m < 8; m++) { o[cl][2 * m] = pk(z[0][m].x, z[1][m].x); o[cl][2 * m + 1] = pk(z[0][m].y, z[1][m].y); }
                YIELD();
            }
            const uint32_t a0 = in + (8 * w + gl + 32 * (mi >> 1)) * 32 + (((mi & 1) ^ (gl >> 2)) << 4);
#pragma unroll
            for (int m = 0; m < 16; m += 2) stsm4(a0 + (m & 7) * 1024 + (m >> 3) * 16384, o[0][m], o[1][m], o[0][m + 1], o[1][m + 1]);
            bar_sync(7, 256);
            STAMP(26);
        }
        INDICES(6)
        const int t0 = tc * 128 + 64 * (w & 1) + 32 * hf + 8 * (w >> 1);
        const uint2* xp = (const uint2*)(p.xb + (size_t)t0 * 1024 + cb * 128) + lane;
        const uint2 dd = __ldg((const uint2*)(p.dsk + cb * 128) + lane);
        uint2 xd[16];
        {
            const int n0 = 16 * hf + 4 * w + mi;
            const uint32_t la = sb + OFF_P + (gl >> 2) * 8192 + n0 * 32 + ((((gl >> 1) & 1) ^ (w & 1)) << 4) + (gl & 1) * 8;
            float* op = p.out + (size_t)(4 * n0 + fb) * 2048 + fcb * 32 + gl * 4;
#pragma unroll
            for (int it = 0; it < 16; it += 4) {
                uint32_t u[8], fast;
                asm volatile("{.reg .pred p; mbarrier.test_wait.parity.shared::cta.b64 p, [%1], 0; selp.u32 %0, 1, 0, p;}" : "=r"(fast) : "r"(bars + B_LDONE) : "memory");
#pragma unroll
                for (int i = 0; i < 4; i++) asm volatile("ld.shared.v2.b32 {%0,%1}, [%2];" : "=r"(u[2 * i]), "=r"(u[2 * i + 1]) : "r"(la + ((it + i) & 7) * 1024 + ((it + i) >> 3) * 16384) : "memory");
#pragma unroll
                for (int i = 0; i < 4; i++) {
                    const int j = it + i;
                    if (!XLATE) asm volatile("ld.global.nc.v2.b32 {%0,%1}, [%2];" : "=r"(xd[j].x), "=r"(xd[j].y) : "l"(xp + ((j >> 3) * 16 + (j & 7)) * 256));
                    stg128(op + (size_t)j * 128 * 2048, u[2 * i] << 16, u[2 * i] & 0xffff0000u, u[2 * i + 1] << 16, u[2 * i + 1] & 0xffff0000u);
                    if (!fast) __nanosleep(PACE_O);
                }
            }
            STAMP(27);
        }
        if (XLATE) {
            mbar_wait(bars + B_LDONE, 0);
#pragma unroll
            for (int j = 0; j < 16; j++) asm volatile("ld.global.nc.v2.b32 {%0,%1}, [%2];" : "=r"(xd[j].x), "=r"(xd[j].y) : "l"(xp + ((j >> 3) * 16 + (j & 7)) * 256));
        }
#pragma unroll
        for (int j = 0; j < 16; j++) {
            asm("fma.rn.bf16x2 %0, %0, %1, %2;" : "+r"(xd[j].x) : "r"(dd.x), "r"(0x80008000u));
            asm("fma.rn.bf16x2 %0, %0, %1, %2;" : "+r"(xd[j].y) : "r"(dd.y), "r"(0x80008000u));
        }
        const uint32_t ra = sb + hf * 16384 + w * 4096;
        float* ob = p.out + (size_t)t0 * 2048 + 1024 + cb * 128 + lane * 4;
#pragma unroll
        for (int mb = 0; mb < 2; mb++) {
            if (hf == 0) { if (mb == 0) bar_sync(9, 256); else bar_sync(11, 256); }
            else { if (mb == 0) bar_sync(10, 256); else bar_sync(12, 256); }
            if (mb == 0) STAMP(17);
            float v[8][4];
#pragma unroll
            for (int j = 0; j < 8; j++) lds128f(ra + (mb ? 0 : (NST - 1) * 32768) + j * 512 + ((lane * 16) ^ ((j & 3) * 32)), v[j][0], v[j][1], v[j][2], v[j][3]);
#pragma unroll
            for (int j = 0; j < 8; j++) {
                const uint2 s = xd[8 * mb + j];
                stg128(ob + (16 * mb + j) * 2048, __float_as_uint(v[j][0] + up(s.x)), __float_as_uint(v[j][1] + __uint_as_float(s.x & 0xffff0000u)),
                       __float_as_uint(v[j][2] + up(s.y)), __float_as_uint(v[j][3] + __uint_as_float(s.y & 0xffff0000u)));
            }
        }
        STAMP(9);
    }
}

typedef CUresult (*EncodeFn)(CUtensorMap*, CUtensorMapDataType, cuuint32_t, void*, const cuuint64_t*, const cuuint64_t*, const cuuint32_t*,
                             const cuuint32_t*, CUtensorMapInterleave, CUtensorMapSwizzle, CUtensorMapL2promotion, CUtensorMapFloatOOBfill);

static CUtensorMap make_map(EncodeFn enc, const void* ptr, int rank, const cuuint64_t* dims, const cuuint64_t* strides, const cuuint32_t* box,
                            CUtensorMapSwizzle swz, CUtensorMapL2promotion promo, CUtensorMapDataType dt = CU_TENSOR_MAP_DATA_TYPE_BFLOAT16) {
    CUtensorMap m;
    const cuuint32_t es[5] = {1, 1, 1, 1, 1};
    enc(&m, dt, rank, const_cast<void*>(ptr), dims, strides, box, es, CU_TENSOR_MAP_INTERLEAVE_NONE, swz, promo,
        CU_TENSOR_MAP_FLOAT_OOB_FILL_NONE);
    return m;
}

extern "C" void kernel_launch(void* const* d_in, const int* in_sizes, int n_in, void* d_out, int out_size) {
    void* fn = nullptr;
    cudaDriverEntryPointQueryResult qr;
    cudaGetDriverEntryPoint("cuTensorMapEncodeTiled", &fn, cudaEnableDefault, &qr);
    EncodeFn enc = (EncodeFn)fn;
    void *pU, *pV;
    cudaGetSymbolAddress(&pU, g_U);
    cudaGetSymbolAddress(&pV, g_V);
    const CUtensorMapL2promotion P256 = CU_TENSOR_MAP_L2_PROMOTION_L2_256B, P0 = CU_TENSOR_MAP_L2_PROMOTION_NONE;

    const cuuint64_t dX[5] = {1024, 2, 4, 16, 16}, sX[4] = {2048, 32 * 2048, 2 * 2048, 128 * 2048};
    const cuuint32_t bX[5] = {64, 2, 4, 16, 1};
    CUtensorMap tmX = make_map(enc, d_in[3], 5, dX, sX, bX, CU_TENSOR_MAP_SWIZZLE_128B, P256);
    const cuuint64_t dB[4] = {1024, 8, 2, 96}, sB[3] = {2048, 256 * 2048, 8 * 2048}, dC[4] = {1024, 8, 2, 64}, sC[3] = {2048, 8 * 2048, 16 * 2048};
    const cuuint32_t bB[4] = {64, 8, 2, 4};
    CUtensorMap tmBre = make_map(enc, d_in[6], 4, dB, sB, bB, CU_TENSOR_MAP_SWIZZLE_128B, P256);
    CUtensorMap tmBim = make_map(enc, d_in[7], 4, dB, sB, bB, CU_TENSOR_MAP_SWIZZLE_128B, P256);
    CUtensorMap tmCre = make_map(enc, d_in[8], 4, dC, sC, bB, CU_TENSOR_MAP_SWIZZLE_128B, P256);
    CUtensorMap tmCim = make_map(enc, d_in[9], 4, dC, sC, bB, CU_TENSOR_MAP_SWIZZLE_128B, P256);

    const cuuint64_t dU[2] = {8192, 256}, sU[1] = {16384};
    const cuuint32_t bS[2] = {64, UBOX};
    CUtensorMap tmUst = make_map(enc, pU, 2, dU, sU, bS, CU_TENSOR_MAP_SWIZZLE_128B, P0);
    const cuuint64_t dV[3] = {12288, 128, 2}, sV[2] = {32768, 8192};
    const cuuint32_t bV[3] = {32, VBOX, 1};
    CUtensorMap tmVst = make_map(enc, pV, 3, dV, sV, bV, CU_TENSOR_MAP_SWIZZLE_64B, P0);
    const cuuint64_t dA[4] = {1024, 64, 8, 4}, sA[3] = {32 * 2048, 4 * 2048, 2048};
    const cuuint32_t bA[4] = {16, 64, 1, 1};
    CUtensorMap tmXA = make_map(enc, d_in[0], 4, dA, sA, bA, CU_TENSOR_MAP_SWIZZLE_32B, CU_TENSOR_MAP_L2_PROMOTION_L2_128B);
    const cuuint64_t dF[2] = {512 * 1026 / 8, 4}, sF[1] = {512 * 1026};
    const cuuint32_t bF[2] = {WPITCH / 8, 4};
    CUtensorMap tmWr = make_map(enc, d_in[1], 2, dF, sF, bF, CU_TENSOR_MAP_SWIZZLE_NONE, P0, CU_TENSOR_MAP_DATA_TYPE_UINT64);
    CUtensorMap tmWi = make_map(enc, d_in[2], 2, dF, sF, bF, CU_TENSOR_MAP_SWIZZLE_NONE, P0, CU_TENSOR_MAP_DATA_TYPE_UINT64);

    Params p = {};
    p.xb = (const __nv_bfloat16*)d_in[3];
    p.lre = (const __nv_bfloat16*)d_in[4];
    p.lim = (const __nv_bfloat16*)d_in[5];
    p.ldt = (const __nv_bfloat16*)d_in[10];
    p.dsk = (const __nv_bfloat16*)d_in[11];
    p.out = (float*)d_out;
    p.da[0] = p.da[1] = mkdesc(0, 16, 1024, 1) - 1;
    p.da[2] = p.da[3] = mkdesc(0, 512, 2048, 2) - 1;
    for (int i = 0; i < 258; i++) {
        int cj;
        const int kap = kappa_of(i >> 1, i & 1), s3 = slot3_of(kap, cj);
        p.unit[i] = kap | s3 << 16 | cj << 24;
    }
    cudaFuncSetAttribute(fused_kernel, cudaFuncAttributeMaxDynamicSharedMemorySize, SMEM_BYTES);
    fused_kernel<<<130, 512, SMEM_BYTES>>>(Maps{{tmX, tmBre, tmBim, tmCre, tmCim, tmXA, tmUst, tmVst, tmWr, tmWi}}, p);
}
```

```cpp
#include <cuda_runtime.h>
#include <cuda.h>
#include <cuda_bf16.h>
#include <stdint.h>

#define NST 5
#define SB0 1024
#define WPITCH 1056
#define OFF_P (NST * 32768)
#define OFF_F (OFF_P + 32768)
#define OFF_W (OFF_F + 8192)
#define OFF_TL (OFF_W + 16 * WPITCH)
#define OFF_TM (OFF_TL + 4096)
#define OFF_T1 (OFF_TM + 4096)
#define OFF_BAR (OFF_T1 + 2048)
#define OFF_STAMP (OFF_BAR + 284)
#define SMEM_BYTES (OFF_BAR + 512)
#define B_FULL 0
#define B_EMPTY 40
#define B_STGU 80
#define B_HGO 88
#define B_LAM 120
#define B_STG 128
#define B_WFREE 136
#define B_EP 144
#define B_LDONE 152
#define B_UIN 160
#define B_WIN 176
#define B_XIN 184
#define B_VIN 200
#define B_HRTY 232
#define B_HLD 240
#define B_END 280
#define B_EPOCH 280

#define PACE_U 250
#define PACE_V 120
#define PACE_O 150
#define PACE_H 120
#define YP 0
#define HAND 3
#define HNOW 0
#define HDELAY 0
#define LDK 15
#define POLL_AT 24
#define XA_FIRST 4
#define XA_AT 0
#define YS 3
#define UDELAY 250
#define PACE_W 120
#define HINT_U 2
#define HINT_V 2
#define WPF 0
#define XAT 1
#define XNA ".L1::no_allocate"
#define PACE_X 0
#define X_GRP 4
#define GRP 0xaa
#define PRO 1
#define PRX 2
#define PRB 3
#define VDEFER 1
#define VSPLIT 0
#define UBOX 32
#define VBOX 64
#define SKEW 4
#define SPIN_LIMIT 32768

#define YIELD() asm volatile("pmevent 0;")
#define YF1 3
#define YF2 2
#define YF3 2
#define YLD(level, n) do { if ((level) >= (n)) YIELD(); } while (0)

__device__ __align__(1024) uint8_t g_U[4 << 20];
__device__ __align__(1024) uint8_t g_V[4 << 20];
__device__ __align__(1024) uint8_t g_H[8 << 20];
__device__ __align__(1024) uint4 g_carry[16 * 512];
__device__ __align__(1024) unsigned g_hcnt[16 * 64];
__device__ __align__(128) unsigned g_cnt[128];
__device__ __align__(128) unsigned g_epoch[129 * 8];

#define STAMP(i) do { } while (0)
#define STAMPR(i) do { } while (0)
#define STAMPW(a, b) do { } while (0)
#define STAMPX(a, b) do { } while (0)
#define STAMP5(i) do { } while (0)
#define STAMP3(i) do { } while (0)

#define TAB_FG 0
#define TAB_F1 2048
#define TAB_T 4096
#define TAB_SP 6144
#define TAB_TW 7168
#define TAB_FX 7680
__device__ __align__(1024) const uint32_t g_tab[7808] = {
0x80003d80,0x80003d80,0x80003d80,0x80003d80,0x80003d80,0x80003d80,0x80003d80,0x80003d80,0x80003d80,0x80003d80,0x80003d80,0x80003d80,0x80003d80,0x80003d80,0x80003d80,0x80003d80,
0x80003d80,0x80003d80,0x80003d80,0x80003d80,0x80003d80,0x80003d80,0x80003d80,0x80003d80,0x80003d80,0x80003d80,0x80003d80,0x80003d80,0x80003d80,0x80003d80,0x80003d80,0x80003d80,
0x3c483d7b,0x3d0e3d55,0x3d553d0e,0x3d7b3c48,0x80003d80,0x3cc43d6d,0x3d353d35,0x3d6d3cc4,0x3d7bbc48,0x3d55bd0e,0x3d0ebd55,0x3c48bd7b,0x3d800000,0x3d6dbcc4,0x3d35bd35,0x3cc4bd6d,
0xbc48bd7b,0xbd0ebd55,0xbd55bd0e,0xbd7bbc48,0x8000bd80,0xbcc4bd6d,0xbd35bd35,0xbd6dbcc4,0xbd7b3c48,0xbd553d0e,0xbd0e3d55,0xbc483d7b,0xbd800000,0xbd6d3cc4,0xbd353d35,0xbcc43d6d,
0x8000bd80,0xbd35bd35,0xbd800000,0xbd353d35,0xbcc4bd6d,0xbd6dbcc4,0xbd6d3cc4,0xbcc43d6d,0x80003d80,0x3d353d35,0x3d800000,0x3d35bd35,0x3cc43d6d,0x3d6d3cc4,0x3d6dbcc4,0x3cc4bd6d,
0x8000bd80,0xbd35bd35,0xbd800000,0xbd353d35,0xbcc4bd6d,0xbd6dbcc4,0xbd6d3cc4,0xbcc43d6d,0x80003d80,0x3d353d35,0x3d800000,0x3d35bd35,0x3cc43d6d,0x3d6d3cc4,0x3d6dbcc4,0x3cc4bd6d,
0xbd553d0e,0x3c483d7b,0x3d7b3c48,0x3d0ebd55,0xbd800000,0xbcc43d6d,0x3d353d35,0x3d6dbcc4,0x3d0e3d55,0x3d7bbc48,0x3c48bd7b,0xbd55bd0e,0x80003d80,0x3d6d3cc4,0x3d35bd35,0xbcc4bd6d,
0x3d55bd0e,0xbc48bd7b,0xbd7bbc48,0xbd0e3d55,0x3d800000,0x3cc4bd6d,0xbd35bd35,0xbd6d3cc4,0xbd0ebd55,0xbd7b3c48,0xbc483d7b,0x3d553d0e,0x8000bd80,0xbd6dbcc4,0xbd353d35,0x3cc43d6d,
0x80003d80,0x3d800000,0x8000bd80,0xbd800000,0x3d353d35,0x3d35bd35,0xbd35bd35,0xbd353d35,0x80003d80,0x3d800000,0x8000bd80,0xbd800000,0x3d353d35,0x3d35bd35,0xbd35bd35,0xbd353d35,
0x80003d80,0x3d800000,0x8000bd80,0xbd800000,0x3d353d35,0x3d35bd35,0xbd35bd35,0xbd353d35,0x80003d80,0x3d800000,0x8000bd80,0xbd800000,0x3d353d35,0x3d35bd35,0xbd35bd35,0xbd353d35,
0xbd55bd0e,0xbc483d7b,0x3d7bbc48,0xbd0ebd55,0x8000bd80,0xbd6d3cc4,0x3d353d35,0x3cc4bd6d,0xbd0e3d55,0x3d7b3c48,0xbc48bd7b,0xbd553d0e,0xbd800000,0x3cc43d6d,0x3d35bd35,0xbd6dbcc4,
0x3d553d0e,0x3c48bd7b,0xbd7b3c48,0x3d0e3d55,0x80003d80,0x3d6dbcc4,0xbd35bd35,0xbcc43d6d,0x3d0ebd55,0xbd7bbc48,0x3c483d7b,0x3d55bd0e,0x3d800000,0xbcc4bd6d,0xbd353d35,0x3d6d3cc4,
0x8000bd80,0xbd353d35,0x3d800000,0xbd35bd35,0xbd6dbcc4,0x3cc43d6d,0x3cc4bd6d,0xbd6d3cc4,0x80003d80,0x3d35bd35,0xbd800000,0x3d353d35,0x3d6d3cc4,0xbcc4bd6d,0xbcc43d6d,0x3d6dbcc4,
0x8000bd80,0xbd353d35,0x3d800000,0xbd35bd35,0xbd6dbcc4,0x3cc43d6d,0x3cc4bd6d,0xbd6d3cc4,0x80003d80,0x3d35bd35,0xbd800000,0x3d353d35,0x3d6d3cc4,0xbcc4bd6d,0xbcc43d6d,0x3d6dbcc4,
0x3c48bd7b,0xbd0e3d55,0x3d55bd0e,0xbd7b3c48,0x3d800000,0xbd6dbcc4,0x3d353d35,0xbcc4bd6d,0xbd7bbc48,0x3d553d0e,0xbd0ebd55,0x3c483d7b,0x8000bd80,0xbcc43d6d,0x3d35bd35,0xbd6d3cc4,
0xbc483d7b,0x3d0ebd55,0xbd553d0e,0x3d7bbc48,0xbd800000,0x3d6d3cc4,0xbd35bd35,0x3cc43d6d,0x3d7b3c48,0xbd55bd0e,0x3d0e3d55,0xbc48bd7b,0x80003d80,0x3cc4bd6d,0xbd353d35,0x3d6dbcc4,
0x3d800000,0x3d800000,0x3d800000,0x3d800000,0x3d800000,0x3d800000,0x3d800000,0x3d800000,0x3d800000,0x3d800000,0x3d800000,0x3d800000,0x3d800000,0x3d800000,0x3d800000,0x3d800000,
0x3d800000,0x3d800000,0x3d800000,0x3d800000,0x3d800000,0x3d800000,0x3d800000,0x3d800000,0x3d800000,0x3d800000,0x3d800000,0x3d800000,0x3d800000,0x3d800000,0x3d800000,0x3d800000,
0x3d7bbc48,0x3d55bd0e,0x3d0ebd55,0x3c48bd7b,0x3d800000,0x3d6dbcc4,0x3d35bd35,0x3cc4bd6d,0xbc48bd7b,0xbd0ebd55,0xbd55bd0e,0xbd7bbc48,0xbd80,0xbcc4bd6d,0xbd35bd35,0xbd6dbcc4,
0xbd7b3c48,0xbd553d0e,0xbd0e3d55,0xbc483d7b,0xbd800000,0xbd6d3cc4,0xbd353d35,0xbcc43d6d,0x3c483d7b,0x3d0e3d55,0x3d553d0e,0x3d7b3c48,0x3d80,0x3cc43d6d,0x3d353d35,0x3d6d3cc4,
0xbd800000,0xbd353d35,0x3d80,0x3d353d35,0xbd6d3cc4,0xbcc43d6d,0x3cc43d6d,0x3d6d3cc4,0x3d800000,0x3d35bd35,0xbd80,0xbd35bd35,0x3d6dbcc4,0x3cc4bd6d,0xbcc4bd6d,0xbd6dbcc4,
0xbd800000,0xbd353d35,0x3d80,0x3d353d35,0xbd6d3cc4,0xbcc43d6d,0x3cc43d6d,0x3d6d3cc4,0x3d800000,0x3d35bd35,0xbd80,0xbd35bd35,0x3d6dbcc4,0x3cc4bd6d,0xbcc4bd6d,0xbd6dbcc4,
0x3d0e3d55,0x3d7bbc48,0x3c48bd7b,0xbd55bd0e,0x3d80,0x3d6d3cc4,0x3d35bd35,0xbcc4bd6d,0x3d55bd0e,0xbc48bd7b,0xbd7bbc48,0xbd0e3d55,0x3d800000,0x3cc4bd6d,0xbd35bd35,0xbd6d3cc4,
0xbd0ebd55,0xbd7b3c48,0xbc483d7b,0x3d553d0e,0xbd80,0xbd6dbcc4,0xbd353d35,0x3cc43d6d,0xbd553d0e,0x3c483d7b,0x3d7b3c48,0x3d0ebd55,0xbd800000,0xbcc43d6d,0x3d353d35,0x3d6dbcc4,
0x3d800000,0xbd80,0xbd800000,0x3d80,0x3d35bd35,0xbd35bd35,0xbd353d35,0x3d353d35,0x3d800000,0xbd80,0xbd800000,0x3d80,0x3d35bd35,0xbd35bd35,0xbd353d35,0x3d353d35,
0x3d800000,0xbd80,0xbd800000,0x3d80,0x3d35bd35,0xbd35bd35,0xbd353d35,0x3d353d35,0x3d800000,0xbd80,0xbd800000,0x3d80,0x3d35bd35,0xbd35bd35,0xbd353d35,0x3d353d35,
0xbd0e3d55,0x3d7b3c48,0xbc48bd7b,0xbd553d0e,0xbd800000,0x3cc43d6d,0x3d35bd35,0xbd6dbcc4,0x3d553d0e,0x3c48bd7b,0xbd7b3c48,0x3d0e3d55,0x3d80,0x3d6dbcc4,0xbd35bd35,0xbcc43d6d,
0x3d0ebd55,0xbd7bbc48,0x3c483d7b,0x3d55bd0e,0x3d800000,0xbcc4bd6d,0xbd353d35,0x3d6d3cc4,0xbd55bd0e,0xbc483d7b,0x3d7bbc48,0xbd0ebd55,0xbd80,0xbd6d3cc4,0x3d353d35,0x3cc4bd6d,
0xbd800000,0x3d353d35,0xbd80,0xbd353d35,0xbcc43d6d,0x3d6dbcc4,0xbd6dbcc4,0x3cc43d6d,0x3d800000,0xbd35bd35,0x3d80,0x3d35bd35,0x3cc4bd6d,0xbd6d3cc4,0x3d6d3cc4,0xbcc4bd6d,
0xbd800000,0x3d353d35,0xbd80,0xbd353d35,0xbcc43d6d,0x3d6dbcc4,0xbd6dbcc4,0x3cc43d6d,0x3d800000,0xbd35bd35,0x3d80,0x3d35bd35,0x3cc4bd6d,0xbd6d3cc4,0x3d6d3cc4,0xbcc4bd6d,
0xbd7bbc48,0x3d553d0e,0xbd0ebd55,0x3c483d7b,0xbd80,0xbcc43d6d,0x3d35bd35,0xbd6d3cc4,0xbc483d7b,0x3d0ebd55,0xbd553d0e,0x3d7bbc48,0xbd800000,0x3d6d3cc4,0xbd35bd35,0x3cc43d6d,
0x3d7b3c48,0xbd55bd0e,0x3d0e3d55,0xbc48bd7b,0x3d80,0x3cc4bd6d,0xbd353d35,0x3d6dbcc4,0x3c48bd7b,0xbd0e3d55,0x3d55bd0e,0xbd7b3c48,0x3d800000,0xbd6dbcc4,0x3d353d35,0xbcc4bd6d,
0x80003d80,0x8000bd80,0x80003d80,0x8000bd80,0x3d800000,0xbd800000,0x3d800000,0xbd800000,0x80003d80,0x8000bd80,0x80003d80,0x8000bd80,0x3d800000,0xbd800000,0x3d800000,0xbd800000,
0x80003d80,0x8000bd80,0x80003d80,0x8000bd80,0x3d800000,0xbd800000,0x3d800000,0xbd800000,0x80003d80,0x8000bd80,0x80003d80,0x8000bd80,0x3d800000,0xbd800000,0x3d800000,0xbd800000,
0x3d7bbc48,0xbd553d0e,0x3d0ebd55,0xbc483d7b,0x80003d80,0xbcc4bd6d,0x3d353d35,0xbd6dbcc4,0xbc48bd7b,0x3d0e3d55,0xbd55bd0e,0x3d7b3c48,0x3d800000,0xbd6d3cc4,0x3d35bd35,0xbcc43d6d,
0xbd7b3c48,0x3d55bd0e,0xbd0e3d55,0x3c48bd7b,0x8000bd80,0x3cc43d6d,0xbd35bd35,0x3d6d3cc4,0x3c483d7b,0xbd0ebd55,0x3d553d0e,0xbd7bbc48,0xbd800000,0x3d6dbcc4,0xbd353d35,0x3cc4bd6d,
0x8000bd80,0x3d353d35,0xbd800000,0x3d35bd35,0xbd6d3cc4,0x3cc4bd6d,0x3cc43d6d,0xbd6dbcc4,0x80003d80,0xbd35bd35,0x3d800000,0xbd353d35,0x3d6dbcc4,0xbcc43d6d,0xbcc4bd6d,0x3d6d3cc4,
0x8000bd80,0x3d353d35,0xbd800000,0x3d35bd35,0xbd6d3cc4,0x3cc4bd6d,0x3cc43d6d,0xbd6dbcc4,0x80003d80,0xbd35bd35,0x3d800000,0xbd353d35,0x3d6dbcc4,0xbcc43d6d,0xbcc4bd6d,0x3d6d3cc4,
0x3d0e3d55,0xbd7b3c48,0x3c48bd7b,0x3d553d0e,0xbd800000,0x3cc4bd6d,0x3d353d35,0xbd6d3cc4,0x3d55bd0e,0x3c483d7b,0xbd7bbc48,0x3d0ebd55,0x80003d80,0xbd6dbcc4,0x3d35bd35,0x3cc43d6d,
0xbd0ebd55,0x3d7bbc48,0xbc483d7b,0xbd55bd0e,0x3d800000,0xbcc43d6d,0xbd35bd35,0x3d6dbcc4,0xbd553d0e,0xbc48bd7b,0x3d7b3c48,0xbd0e3d55,0x8000bd80,0x3d6d3cc4,0xbd353d35,0xbcc4bd6d,
0x80003d80,0xbd800000,0x8000bd80,0x3d800000,0x3d35bd35,0x3d353d35,0xbd353d35,0xbd35bd35,0x80003d80,0xbd800000,0x8000bd80,0x3d800000,0x3d35bd35,0x3d353d35,0xbd353d35,0xbd35bd35,
0x80003d80,0xbd800000,0x8000bd80,0x3d800000,0x3d35bd35,0x3d353d35,0xbd353d35,0xbd35bd35,0x80003d80,0xbd800000,0x8000bd80,0x3d800000,0x3d35bd35,0x3d353d35,0xbd353d35,0xbd35bd35,
0xbd0e3d55,0xbd7bbc48,0xbc48bd7b,0x3d55bd0e,0x8000bd80,0x3d6dbcc4,0x3d353d35,0xbcc43d6d,0x3d553d0e,0xbc483d7b,0xbd7b3c48,0xbd0ebd55,0xbd800000,0xbcc4bd6d,0x3d35bd35,0x3d6d3cc4,
0x3d0ebd55,0x3d7b3c48,0x3c483d7b,0xbd553d0e,0x80003d80,0xbd6d3cc4,0xbd35bd35,0x3cc4bd6d,0xbd55bd0e,0x3c48bd7b,0x3d7bbc48,0x3d0e3d55,0x3d800000,0x3cc43d6d,0xbd353d35,0xbd6dbcc4,
0x8000bd80,0x3d35bd35,0x3d800000,0x3d353d35,0xbcc43d6d,0xbd6d3cc4,0xbd6dbcc4,0xbcc4bd6d,0x80003d80,0xbd353d35,0xbd800000,0xbd35bd35,0x3cc4bd6d,0x3d6dbcc4,0x3d6d3cc4,0x3cc43d6d,
0x8000bd80,0x3d35bd35,0x3d800000,0x3d353d35,0xbcc43d6d,0xbd6d3cc4,0xbd6dbcc4,0xbcc4bd6d,0x80003d80,0xbd353d35,0xbd800000,0xbd35bd35,0x3cc4bd6d,0x3d6dbcc4,0x3d6d3cc4,0x3cc43d6d,
0xbd7bbc48,0xbd55bd0e,0xbd0ebd55,0xbc48bd7b,0x3d800000,0x3d6d3cc4,0x3d353d35,0x3cc43d6d,0xbc483d7b,0xbd0e3d55,0xbd553d0e,0xbd7b3c48,0x8000bd80,0x3cc4bd6d,0x3d35bd35,0x3d6dbcc4,
0x3d7b3c48,0x3d553d0e,0x3d0e3d55,0x3c483d7b,0xbd800000,0xbd6dbcc4,0xbd35bd35,0xbcc4bd6d,0x3c48bd7b,0x3d0ebd55,0x3d55bd0e,0x3d7bbc48,0x80003d80,0xbcc43d6d,0xbd353d35,0xbd6d3cc4,
0x3d800000,0xbd800000,0x3d800000,0xbd800000,0xbd80,0x3d80,0xbd80,0x3d80,0x3d800000,0xbd800000,0x3d800000,0xbd800000,0xbd80,0x3d80,0xbd80,0x3d80,
0x3d800000,0xbd800000,0x3d800000,0xbd800000,0xbd80,0x3d80,0xbd80,0x3d80,0x3d800000,0xbd800000,0x3d800000,0xbd800000,0xbd80,0x3d80,0xbd80,0x3d80,
0xbc48bd7b,0x3d0e3d55,0xbd55bd0e,0x3d7b3c48,0x3d800000,0xbd6d3cc4,0x3d35bd35,0xbcc43d6d,0xbd7b3c48,0x3d55bd0e,0xbd0e3d55,0x3c48bd7b,0xbd80,0x3cc43d6d,0xbd35bd35,0x3d6d3cc4,
0x3c483d7b,0xbd0ebd55,0x3d553d0e,0xbd7bbc48,0xbd800000,0x3d6dbcc4,0xbd353d35,0x3cc4bd6d,0x3d7bbc48,0xbd553d0e,0x3d0ebd55,0xbc483d7b,0x3d80,0xbcc4bd6d,0x3d353d35,0xbd6dbcc4,
0xbd800000,0x3d35bd35,0x3d80,0xbd35bd35,0x3cc43d6d,0xbd6dbcc4,0x3d6dbcc4,0xbcc43d6d,0x3d800000,0xbd353d35,0xbd80,0x3d353d35,0xbcc4bd6d,0x3d6d3cc4,0xbd6d3cc4,0x3cc4bd6d,
0xbd800000,0x3d35bd35,0x3d80,0xbd35bd35,0x3cc43d6d,0xbd6dbcc4,0x3d6dbcc4,0xbcc43d6d,0x3d800000,0xbd353d35,0xbd80,0x3d353d35,0xbcc4bd6d,0x3d6d3cc4,0xbd6d3cc4,0x3cc4bd6d,
0x3d55bd0e,0x3c483d7b,0xbd7bbc48,0x3d0ebd55,0x3d80,0xbd6dbcc4,0x3d35bd35,0x3cc43d6d,0xbd0ebd55,0x3d7bbc48,0xbc483d7b,0xbd55bd0e,0x3d800000,0xbcc43d6d,0xbd35bd35,0x3d6dbcc4,
0xbd553d0e,0xbc48bd7b,0x3d7b3c48,0xbd0e3d55,0xbd80,0x3d6d3cc4,0xbd353d35,0xbcc4bd6d,0x3d0e3d55,0xbd7b3c48,0x3c48bd7b,0x3d553d0e,0xbd800000,0x3cc4bd6d,0x3d353d35,0xbd6d3cc4,
0x3d800000,0x3d80,0xbd800000,0xbd80,0xbd35bd35,0x3d35bd35,0x3d353d35,0xbd353d35,0x3d800000,0x3d80,0xbd800000,0xbd80,0xbd35bd35,0x3d35bd35,0x3d353d35,0xbd353d35,
0x3d800000,0x3d80,0xbd800000,0xbd80,0xbd35bd35,0x3d35bd35,0x3d353d35,0xbd353d35,0x3d800000,0x3d80,0xbd800000,0xbd80,0xbd35bd35,0x3d35bd35,0x3d353d35,0xbd353d35,
0x3d553d0e,0xbc483d7b,0xbd7b3c48,0xbd0ebd55,0xbd800000,0xbcc4bd6d,0x3d35bd35,0x3d6d3cc4,0x3d0ebd55,0x3d7b3c48,0x3c483d7b,0xbd553d0e,0x3d80,0xbd6d3cc4,0xbd35bd35,0x3cc4bd6d,
0xbd55bd0e,0x3c48bd7b,0x3d7bbc48,0x3d0e3d55,0x3d800000,0x3cc43d6d,0xbd353d35,0xbd6dbcc4,0xbd0e3d55,0xbd7bbc48,0xbc48bd7b,0x3d55bd0e,0xbd80,0x3d6dbcc4,0x3d353d35,0xbcc43d6d,
0xbd800000,0xbd35bd35,0xbd80,0x3d35bd35,0x3d6d3cc4,0x3cc43d6d,0xbcc43d6d,0xbd6d3cc4,0x3d800000,0x3d353d35,0x3d80,0xbd353d35,0xbd6dbcc4,0xbcc4bd6d,0x3cc4bd6d,0x3d6dbcc4,
0xbd800000,0xbd35bd35,0xbd80,0x3d35bd35,0x3d6d3cc4,0x3cc43d6d,0xbcc43d6d,0xbd6d3cc4,0x3d800000,0x3d353d35,0x3d80,0xbd353d35,0xbd6dbcc4,0xbcc4bd6d,0x3cc4bd6d,0x3d6dbcc4,
0xbc483d7b,0xbd0e3d55,0xbd553d0e,0xbd7b3c48,0xbd80,0x3cc4bd6d,0x3d35bd35,0x3d6dbcc4,0x3d7b3c48,0x3d553d0e,0x3d0e3d55,0x3c483d7b,0xbd800000,0xbd6dbcc4,0xbd35bd35,0xbcc4bd6d,
0x3c48bd7b,0x3d0ebd55,0x3d55bd0e,0x3d7bbc48,0x3d80,0xbcc43d6d,0xbd353d35,0xbd6d3cc4,0xbd7bbc48,0xbd55bd0e,0xbd0ebd55,0xbc48bd7b,0x3d800000,0x3d6d3cc4,0x3d353d35,0x3cc43d6d,
0x80003d80,0x80003d80,0x80003d80,0x80003d80,0x8000bd80,0x8000bd80,0x8000bd80,0x8000bd80,0x80003d80,0x80003d80,0x80003d80,0x80003d80,0x8000bd80,0x8000bd80,0x8000bd80,0x8000bd80,
0x80003d80,0x80003d80,0x80003d80,0x80003d80,0x8000bd80,0x8000bd80,0x8000bd80,0x8000bd80,0x80003d80,0x80003d80,0x80003d80,0x80003d80,0x8000bd80,0x8000bd80,0x8000bd80,0x8000bd80,
0xbc48bd7b,0xbd0ebd55,0xbd55bd0e,0xbd7bbc48,0x80003d80,0x3cc43d6d,0x3d353d35,0x3d6d3cc4,0xbd7b3c48,0xbd553d0e,0xbd0e3d55,0xbc483d7b,0x3d800000,0x3d6dbcc4,0x3d35bd35,0x3cc4bd6d,
0x3c483d7b,0x3d0e3d55,0x3d553d0e,0x3d7b3c48,0x8000bd80,0xbcc4bd6d,0xbd35bd35,0xbd6dbcc4,0x3d7bbc48,0x3d55bd0e,0x3d0ebd55,0x3c48bd7b,0xbd800000,0xbd6d3cc4,0xbd353d35,0xbcc43d6d,
0x8000bd80,0xbd35bd35,0xbd800000,0xbd353d35,0x3cc43d6d,0x3d6d3cc4,0x3d6dbcc4,0x3cc4bd6d,0x80003d80,0x3d353d35,0x3d800000,0x3d35bd35,0xbcc4bd6d,0xbd6dbcc4,0xbd6d3cc4,0xbcc43d6d,
0x8000bd80,0xbd35bd35,0xbd800000,0xbd353d35,0x3cc43d6d,0x3d6d3cc4,0x3d6dbcc4,0x3cc4bd6d,0x80003d80,0x3d353d35,0x3d800000,0x3d35bd35,0xbcc4bd6d,0xbd6dbcc4,0xbd6d3cc4,0xbcc43d6d,
0x3d55bd0e,0xbc48bd7b,0xbd7bbc48,0xbd0e3d55,0xbd800000,0xbcc43d6d,0x3d353d35,0x3d6dbcc4,0xbd0ebd55,0xbd7b3c48,0xbc483d7b,0x3d553d0e,0x80003d80,0x3d6d3cc4,0x3d35bd35,0xbcc4bd6d,
0xbd553d0e,0x3c483d7b,0x3d7b3c48,0x3d0ebd55,0x3d800000,0x3cc4bd6d,0xbd35bd35,0xbd6d3cc4,0x3d0e3d55,0x3d7bbc48,0x3c48bd7b,0xbd55bd0e,0x8000bd80,0xbd6dbcc4,0xbd353d35,0x3cc43d6d,
0x80003d80,0x3d800000,0x8000bd80,0xbd800000,0xbd35bd35,0xbd353d35,0x3d353d35,0x3d35bd35,0x80003d80,0x3d800000,0x8000bd80,0xbd800000,0xbd35bd35,0xbd353d35,0x3d353d35,0x3d35bd35,
0x80003d80,0x3d800000,0x8000bd80,0xbd800000,0xbd35bd35,0xbd353d35,0x3d353d35,0x3d35bd35,0x80003d80,0x3d800000,0x8000bd80,0xbd800000,0xbd35bd35,0xbd353d35,0x3d353d35,0x3d35bd35,
0x3d553d0e,0x3c48bd7b,0xbd7b3c48,0x3d0e3d55,0x8000bd80,0xbd6d3cc4,0x3d353d35,0x3cc4bd6d,0x3d0ebd55,0xbd7bbc48,0x3c483d7b,0x3d55bd0e,0xbd800000,0x3cc43d6d,0x3d35bd35,0xbd6dbcc4,
0xbd55bd0e,0xbc483d7b,0x3d7bbc48,0xbd0ebd55,0x80003d80,0x3d6dbcc4,0xbd35bd35,0xbcc43d6d,0xbd0e3d55,0x3d7b3c48,0xbc48bd7b,0xbd553d0e,0x3d800000,0xbcc4bd6d,0xbd353d35,0x3d6d3cc4,
0x8000bd80,0xbd353d35,0x3d800000,0xbd35bd35,0x3d6d3cc4,0xbcc4bd6d,0xbcc43d6d,0x3d6dbcc4,0x80003d80,0x3d35bd35,0xbd800000,0x3d353d35,0xbd6dbcc4,0x3cc43d6d,0x3cc4bd6d,0xbd6d3cc4,
0x8000bd80,0xbd353d35,0x3d800000,0xbd35bd35,0x3d6d3cc4,0xbcc4bd6d,0xbcc43d6d,0x3d6dbcc4,0x80003d80,0x3d35bd35,0xbd800000,0x3d353d35,0xbd6dbcc4,0x3cc43d6d,0x3cc4bd6d,0xbd6d3cc4,
0xbc483d7b,0x3d0ebd55,0xbd553d0e,0x3d7bbc48,0x3d800000,0xbd6dbcc4,0x3d353d35,0xbcc4bd6d,0x3d7b3c48,0xbd55bd0e,0x3d0e3d55,0xbc48bd7b,0x8000bd80,0xbcc43d6d,0x3d35bd35,0xbd6d3cc4,
0x3c48bd7b,0xbd0e3d55,0x3d55bd0e,0xbd7b3c48,0xbd800000,0x3d6d3cc4,0xbd35bd35,0x3cc43d6d,0xbd7bbc48,0x3d553d0e,0xbd0ebd55,0x3c483d7b,0x80003d80,0x3cc4bd6d,0xbd353d35,0x3d6dbcc4,
0x3d800000,0x3d800000,0x3d800000,0x3d800000,0xbd800000,0xbd800000,0xbd800000,0xbd800000,0x3d800000,0x3d800000,0x3d800000,0x3d800000,0xbd800000,0xbd800000,0xbd800000,0xbd800000,
0x3d800000,0x3d800000,0x3d800000,0x3d800000,0xbd800000,0xbd800000,0xbd800000,0xbd800000,0x3d800000,0x3d800000,0x3d800000,0x3d800000,0xbd800000,0xbd800000,0xbd800000,0xbd800000,
0xbd7b3c48,0xbd553d0e,0xbd0e3d55,0xbc483d7b,0x3d800000,0x3d6dbcc4,0x3d35bd35,0x3cc4bd6d,0x3c483d7b,0x3d0e3d55,0x3d553d0e,0x3d7b3c48,0xbd80,0xbcc4bd6d,0xbd35bd35,0xbd6dbcc4,
0x3d7bbc48,0x3d55bd0e,0x3d0ebd55,0x3c48bd7b,0xbd800000,0xbd6d3cc4,0xbd353d35,0xbcc43d6d,0xbc48bd7b,0xbd0ebd55,0xbd55bd0e,0xbd7bbc48,0x3d80,0x3cc43d6d,0x3d353d35,0x3d6d3cc4,
0xbd800000,0xbd353d35,0x3d80,0x3d353d35,0x3d6dbcc4,0x3cc4bd6d,0xbcc4bd6d,0xbd6dbcc4,0x3d800000,0x3d35bd35,0xbd80,0xbd35bd35,0xbd6d3cc4,0xbcc43d6d,0x3cc43d6d,0x3d6d3cc4,
0xbd800000,0xbd353d35,0x3d80,0x3d353d35,0x3d6dbcc4,0x3cc4bd6d,0xbcc4bd6d,0xbd6dbcc4,0x3d800000,0x3d35bd35,0xbd80,0xbd35bd35,0xbd6d3cc4,0xbcc43d6d,0x3cc43d6d,0x3d6d3cc4,
0xbd0ebd55,0xbd7b3c48,0xbc483d7b,0x3d553d0e,0x3d80,0x3d6d3cc4,0x3d35bd35,0xbcc4bd6d,0xbd553d0e,0x3c483d7b,0x3d7b3c48,0x3d0ebd55,0x3d800000,0x3cc4bd6d,0xbd35bd35,0xbd6d3cc4,
0x3d0e3d55,0x3d7bbc48,0x3c48bd7b,0xbd55bd0e,0xbd80,0xbd6dbcc4,0xbd353d35,0x3cc43d6d,0x3d55bd0e,0xbc48bd7b,0xbd7bbc48,0xbd0e3d55,0xbd800000,0xbcc43d6d,0x3d353d35,0x3d6dbcc4,
0x3d800000,0xbd80,0xbd800000,0x3d80,0xbd353d35,0x3d353d35,0x3d35bd35,0xbd35bd35,0x3d800000,0xbd80,0xbd800000,0x3d80,0xbd353d35,0x3d353d35,0x3d35bd35,0xbd35bd35,
0x3d800000,0xbd80,0xbd800000,0x3d80,0xbd353d35,0x3d353d35,0x3d35bd35,0xbd35bd35,0x3d800000,0xbd80,0xbd800000,0x3d80,0xbd353d35,0x3d353d35,0x3d35bd35,0xbd35bd35,
0x3d0ebd55,0xbd7bbc48,0x3c483d7b,0x3d55bd0e,0xbd800000,0x3cc43d6d,0x3d35bd35,0xbd6dbcc4,0xbd55bd0e,0xbc483d7b,0x3d7bbc48,0xbd0ebd55,0x3d80,0x3d6dbcc4,0xbd35bd35,0xbcc43d6d,
0xbd0e3d55,0x3d7b3c48,0xbc48bd7b,0xbd553d0e,0x3d800000,0xbcc4bd6d,0xbd353d35,0x3d6d3cc4,0x3d553d0e,0x3c48bd7b,0xbd7b3c48,0x3d0e3d55,0xbd80,0xbd6d3cc4,0x3d353d35,0x3cc4bd6d,
0xbd800000,0x3d353d35,0xbd80,0xbd353d35,0x3cc4bd6d,0xbd6d3cc4,0x3d6d3cc4,0xbcc4bd6d,0x3d800000,0xbd35bd35,0x3d80,0x3d35bd35,0xbcc43d6d,0x3d6dbcc4,0xbd6dbcc4,0x3cc43d6d,
0xbd800000,0x3d353d35,0xbd80,0xbd353d35,0x3cc4bd6d,0xbd6d3cc4,0x3d6d3cc4,0xbcc4bd6d,0x3d800000,0xbd35bd35,0x3d80,0x3d35bd35,0xbcc43d6d,0x3d6dbcc4,0xbd6dbcc4,0x3cc43d6d,
0x3d7b3c48,0xbd55bd0e,0x3d0e3d55,0xbc48bd7b,0xbd80,0xbcc43d6d,0x3d35bd35,0xbd6d3cc4,0x3c48bd7b,0xbd0e3d55,0x3d55bd0e,0xbd7b3c48,0xbd800000,0x3d6d3cc4,0xbd35bd35,0x3cc43d6d,
0xbd7bbc48,0x3d553d0e,0xbd0ebd55,0x3c483d7b,0x3d80,0x3cc4bd6d,0xbd353d35,0x3d6dbcc4,0xbc483d7b,0x3d0ebd55,0xbd553d0e,0x3d7bbc48,0x3d800000,0xbd6dbcc4,0x3d353d35,0xbcc4bd6d,
0x80003d80,0x8000bd80,0x80003d80,0x8000bd80,0xbd800000,0x3d800000,0xbd800000,0x3d800000,0x80003d80,0x8000bd80,0x80003d80,0x8000bd80,0xbd800000,0x3d800000,0xbd800000,0x3d800000,
0x80003d80,0x8000bd80,0x80003d80,0x8000bd80,0xbd800000,0x3d800000,0xbd800000,0x3d800000,0x80003d80,0x8000bd80,0x80003d80,0x8000bd80,0xbd800000,0x3d800000,0xbd800000,0x3d800000,
0xbd7b3c48,0x3d55bd0e,0xbd0e3d55,0x3c48bd7b,0x80003d80,0xbcc4bd6d,0x3d353d35,0xbd6dbcc4,0x3c483d7b,0xbd0ebd55,0x3d553d0e,0xbd7bbc48,0x3d800000,0xbd6d3cc4,0x3d35bd35,0xbcc43d6d,
0x3d7bbc48,0xbd553d0e,0x3d0ebd55,0xbc483d7b,0x8000bd80,0x3cc43d6d,0xbd35bd35,0x3d6d3cc4,0xbc48bd7b,0x3d0e3d55,0xbd55bd0e,0x3d7b3c48,0xbd800000,0x3d6dbcc4,0xbd353d35,0x3cc4bd6d,
0x8000bd80,0x3d353d35,0xbd800000,0x3d35bd35,0x3d6dbcc4,0xbcc43d6d,0xbcc4bd6d,0x3d6d3cc4,0x80003d80,0xbd35bd35,0x3d800000,0xbd353d35,0xbd6d3cc4,0x3cc4bd6d,0x3cc43d6d,0xbd6dbcc4,
0x8000bd80,0x3d353d35,0xbd800000,0x3d35bd35,0x3d6dbcc4,0xbcc43d6d,0xbcc4bd6d,0x3d6d3cc4,0x80003d80,0xbd35bd35,0x3d800000,0xbd353d35,0xbd6d3cc4,0x3cc4bd6d,0x3cc43d6d,0xbd6dbcc4,
0xbd0ebd55,0x3d7bbc48,0xbc483d7b,0xbd55bd0e,0xbd800000,0x3cc4bd6d,0x3d353d35,0xbd6d3cc4,0xbd553d0e,0xbc48bd7b,0x3d7b3c48,0xbd0e3d55,0x80003d80,0xbd6dbcc4,0x3d35bd35,0x3cc43d6d,
0x3d0e3d55,0xbd7b3c48,0x3c48bd7b,0x3d553d0e,0x3d800000,0xbcc43d6d,0xbd35bd35,0x3d6dbcc4,0x3d55bd0e,0x3c483d7b,0xbd7bbc48,0x3d0ebd55,0x8000bd80,0x3d6d3cc4,0xbd353d35,0xbcc4bd6d,
0x80003d80,0xbd800000,0x8000bd80,0x3d800000,0xbd353d35,0xbd35bd35,0x3d35bd35,0x3d353d35,0x80003d80,0xbd800000,0x8000bd80,0x3d800000,0xbd353d35,0xbd35bd35,0x3d35bd35,0x3d353d35,
0x80003d80,0xbd800000,0x8000bd80,0x3d800000,0xbd353d35,0xbd35bd35,0x3d35bd35,0x3d353d35,0x80003d80,0xbd800000,0x8000bd80,0x3d800000,0xbd353d35,0xbd35bd35,0x3d35bd35,0x3d353d35,
0x3d0ebd55,0x3d7b3c48,0x3c483d7b,0xbd553d0e,0x8000bd80,0x3d6dbcc4,0x3d353d35,0xbcc43d6d,0xbd55bd0e,0x3c48bd7b,0x3d7bbc48,0x3d0e3d55,0xbd800000,0xbcc4bd6d,0x3d35bd35,0x3d6d3cc4,
0xbd0e3d55,0xbd7bbc48,0xbc48bd7b,0x3d55bd0e,0x80003d80,0xbd6d3cc4,0xbd35bd35,0x3cc4bd6d,0x3d553d0e,0xbc483d7b,0xbd7b3c48,0xbd0ebd55,0x3d800000,0x3cc43d6d,0xbd353d35,0xbd6dbcc4,
0x8000bd80,0x3d35bd35,0x3d800000,0x3d353d35,0x3cc4bd6d,0x3d6dbcc4,0x3d6d3cc4,0x3cc43d6d,0x80003d80,0xbd353d35,0xbd800000,0xbd35bd35,0xbcc43d6d,0xbd6d3cc4,0xbd6dbcc4,0xbcc4bd6d,
0x8000bd80,0x3d35bd35,0x3d800000,0x3d353d35,0x3cc4bd6d,0x3d6dbcc4,0x3d6d3cc4,0x3cc43d6d,0x80003d80,0xbd353d35,0xbd800000,0xbd35bd35,0xbcc43d6d,0xbd6d3cc4,0xbd6dbcc4,0xbcc4bd6d,
0x3d7b3c48,0x3d553d0e,0x3d0e3d55,0x3c483d7b,0x3d800000,0x3d6d3cc4,0x3d353d35,0x3cc43d6d,0x3c48bd7b,0x3d0ebd55,0x3d55bd0e,0x3d7bbc48,0x8000bd80,0x3cc4bd6d,0x3d35bd35,0x3d6dbcc4,
0xbd7bbc48,0xbd55bd0e,0xbd0ebd55,0xbc48bd7b,0xbd800000,0xbd6dbcc4,0xbd35bd35,0xbcc4bd6d,0xbc483d7b,0xbd0e3d55,0xbd553d0e,0xbd7b3c48,0x80003d80,0xbcc43d6d,0xbd353d35,0xbd6d3cc4,
0x3d800000,0xbd800000,0x3d800000,0xbd800000,0x3d80,0xbd80,0x3d80,0xbd80,0x3d800000,0xbd800000,0x3d800000,0xbd800000,0x3d80,0xbd80,0x3d80,0xbd80,
0x3d800000,0xbd800000,0x3d800000,0xbd800000,0x3d80,0xbd80,0x3d80,0xbd80,0x3d800000,0xbd800000,0x3d800000,0xbd800000,0x3d80,0xbd80,0x3d80,0xbd80,
0x3c483d7b,0xbd0ebd55,0x3d553d0e,0xbd7bbc48,0x3d800000,0xbd6d3cc4,0x3d35bd35,0xbcc43d6d,0x3d7bbc48,0xbd553d0e,0x3d0ebd55,0xbc483d7b,0xbd80,0x3cc43d6d,0xbd35bd35,0x3d6d3cc4,
0xbc48bd7b,0x3d0e3d55,0xbd55bd0e,0x3d7b3c48,0xbd800000,0x3d6dbcc4,0xbd353d35,0x3cc4bd6d,0xbd7b3c48,0x3d55bd0e,0xbd0e3d55,0x3c48bd7b,0x3d80,0xbcc4bd6d,0x3d353d35,0xbd6dbcc4,
0xbd800000,0x3d35bd35,0x3d80,0xbd35bd35,0xbcc4bd6d,0x3d6d3cc4,0xbd6d3cc4,0x3cc4bd6d,0x3d800000,0xbd353d35,0xbd80,0x3d353d35,0x3cc43d6d,0xbd6dbcc4,0x3d6dbcc4,0xbcc43d6d,
0xbd800000,0x3d35bd35,0x3d80,0xbd35bd35,0xbcc4bd6d,0x3d6d3cc4,0xbd6d3cc4,0x3cc4bd6d,0x3d800000,0xbd353d35,0xbd80,0x3d353d35,0x3cc43d6d,0xbd6dbcc4,0x3d6dbcc4,0xbcc43d6d,
0xbd553d0e,0xbc48bd7b,0x3d7b3c48,0xbd0e3d55,0x3d80,0xbd6dbcc4,0x3d35bd35,0x3cc43d6d,0x3d0e3d55,0xbd7b3c48,0x3c48bd7b,0x3d553d0e,0x3d800000,0xbcc43d6d,0xbd35bd35,0x3d6dbcc4,
0x3d55bd0e,0x3c483d7b,0xbd7bbc48,0x3d0ebd55,0xbd80,0x3d6d3cc4,0xbd353d35,0xbcc4bd6d,0xbd0ebd55,0x3d7bbc48,0xbc483d7b,0xbd55bd0e,0xbd800000,0x3cc4bd6d,0x3d353d35,0xbd6d3cc4,
0x3d800000,0x3d80,0xbd800000,0xbd80,0x3d353d35,0xbd353d35,0xbd35bd35,0x3d35bd35,0x3d800000,0x3d80,0xbd800000,0xbd80,0x3d353d35,0xbd353d35,0xbd35bd35,0x3d35bd35,
0x3d800000,0x3d80,0xbd800000,0xbd80,0x3d353d35,0xbd353d35,0xbd35bd35,0x3d35bd35,0x3d800000,0x3d80,0xbd800000,0xbd80,0x3d353d35,0xbd353d35,0xbd35bd35,0x3d35bd35,
0xbd55bd0e,0x3c48bd7b,0x3d7bbc48,0x3d0e3d55,0xbd800000,0xbcc4bd6d,0x3d35bd35,0x3d6d3cc4,0xbd0e3d55,0xbd7bbc48,0xbc48bd7b,0x3d55bd0e,0x3d80,0xbd6d3cc4,0xbd35bd35,0x3cc4bd6d,
0x3d553d0e,0xbc483d7b,0xbd7b3c48,0xbd0ebd55,0x3d800000,0x3cc43d6d,0xbd353d35,0xbd6dbcc4,0x3d0ebd55,0x3d7b3c48,0x3c483d7b,0xbd553d0e,0xbd80,0x3d6dbcc4,0x3d353d35,0xbcc43d6d,
0xbd800000,0xbd35bd35,0xbd80,0x3d35bd35,0xbd6dbcc4,0xbcc4bd6d,0x3cc4bd6d,0x3d6dbcc4,0x3d800000,0x3d353d35,0x3d80,0xbd353d35,0x3d6d3cc4,0x3cc43d6d,0xbcc43d6d,0xbd6d3cc4,
0xbd800000,0xbd35bd35,0xbd80,0x3d35bd35,0xbd6dbcc4,0xbcc4bd6d,0x3cc4bd6d,0x3d6dbcc4,0x3d800000,0x3d353d35,0x3d80,0xbd353d35,0x3d6d3cc4,0x3cc43d6d,0xbcc43d6d,0xbd6d3cc4,
0x3c48bd7b,0x3d0ebd55,0x3d55bd0e,0x3d7bbc48,0xbd80,0x3cc4bd6d,0x3d35bd35,0x3d6dbcc4,0xbd7bbc48,0xbd55bd0e,0xbd0ebd55,0xbc48bd7b,0xbd800000,0xbd6dbcc4,0xbd35bd35,0xbcc4bd6d,
0xbc483d7b,0xbd0e3d55,0xbd553d0e,0xbd7b3c48,0x3d80,0xbcc43d6d,0xbd353d35,0xbd6d3cc4,0x3d7b3c48,0x3d553d0e,0x3d0e3d55,0x3c483d7b,0x3d800000,0x3d6d3cc4,0x3d353d35,0x3cc43d6d,
0x3f003f00,0xbf003f00,0x3f003f00,0xbf003f00,0x3f003f00,0xbf003f00,0x3f003f00,0xbf003f00,0x3f003f00,0xbf003f00,0x3f003f00,0xbf003f00,0x3f003f00,0xbf003f00,0x3f003f00,0xbf003f00,
0x3eff3f00,0xbd490000,0x3ea23eb5,0xbec6beb5,0x3ef53efb,0xbe15bdc8,0x3e713e8e,0xbee2bed5,0x3ee23eed,0xbe71be44,0x3e153e44,0xbef5beed,0x3ec63ed5,0xbea2be8e,0x3d493dc8,0xbeffbefb,
0x3efb3f00,0xbdc80000,0xbdc80000,0xbefbbf00,0x3ed53eed,0xbe8ebe44,0xbe8ebe44,0xbed5beed,0x3e8e3eb5,0xbed5beb5,0xbed5beb5,0xbe8ebeb5,0x3dc83e44,0xbefbbeed,0xbefbbeed,0xbdc8be44,
0x3ef53f00,0xbe150000,0xbee2beb5,0xbe71beb5,0x3ea23ed5,0xbec6be8e,0xbeffbefb,0x3d49bdc8,0x3d493e44,0xbeffbeed,0xbec6beed,0x3ea23e44,0xbe71bdc8,0xbee2befb,0xbe15be8e,0x3ef53ed5,
0x3eed3f00,0xbe440000,0xbeedbf00,0x3e440000,0x3e443eb5,0xbeedbeb5,0xbe44beb5,0x3eed3eb5,0xbe440000,0xbeedbf00,0x3e440000,0x3eed3f00,0xbeedbeb5,0xbe44beb5,0x3eed3eb5,0x3e443eb5,
0x3ee23f00,0xbe710000,0xbe15beb5,0x3ef53eb5,0x3d493e8e,0xbeffbed5,0x3ea23dc8,0x3ec63efb,0xbec6be44,0xbea2beed,0x3eff3eed,0xbd493e44,0xbef5befb,0x3e15bdc8,0x3e713ed5,0xbee2be8e,
0x3ed53f00,0xbe8e0000,0x3e8e0000,0x3ed53f00,0xbdc83e44,0xbefbbeed,0x3efb3eed,0xbdc83e44,0xbefbbeb5,0xbdc8beb5,0x3dc83eb5,0xbefbbeb5,0xbe8ebeed,0x3ed53e44,0xbed5be44,0xbe8ebeed,
0x3ec63f00,0xbea20000,0x3eff3eb5,0x3d493eb5,0xbe713dc8,0xbee2befb,0x3e153ed5,0xbef5be8e,0xbef5beed,0x3e15be44,0xbee2be44,0xbe71beed,0x3d49be8e,0x3eff3ed5,0xbea2befb,0x3ec63dc8,
0x3eb53f00,0xbeb50000,0x3eb53f00,0xbeb50000,0xbeb50000,0xbeb5bf00,0xbeb50000,0xbeb5bf00,0xbeb5bf00,0x3eb50000,0xbeb5bf00,0x3eb50000,0x3eb50000,0x3eb53f00,0x3eb50000,0x3eb53f00,
0x3ea23f00,0xbec60000,0xbd493eb5,0xbeffbeb5,0xbee2bdc8,0xbe71befb,0xbef5bed5,0x3e15be8e,0xbe15beed,0x3ef53e44,0x3e71be44,0x3ee23eed,0x3eff3e8e,0x3d493ed5,0x3ec63efb,0xbea23dc8,
0x3e8e3f00,0xbed50000,0xbed50000,0xbe8ebf00,0xbefbbe44,0xbdc8beed,0xbdc8beed,0x3efb3e44,0x3dc8beb5,0x3efb3eb5,0x3efb3eb5,0xbdc83eb5,0x3ed53eed,0xbe8e3e44,0xbe8e3e44,0xbed5beed,
0x3e713f00,0xbee20000,0xbef5beb5,0x3e15beb5,0xbeffbe8e,0x3d49bed5,0x3ec6bdc8,0x3ea23efb,0x3ea2be44,0x3ec63eed,0x3d493eed,0xbeffbe44,0x3e153efb,0xbef5bdc8,0xbee2bed5,0x3e71be8e,
0x3e443f00,0xbeed0000,0xbe44bf00,0x3eed0000,0xbeedbeb5,0x3e44beb5,0x3eed3eb5,0xbe443eb5,0x3eed0000,0x3e443f00,0xbeed0000,0xbe44bf00,0xbe443eb5,0xbeedbeb5,0x3e44beb5,0x3eed3eb5,
0x3e153f00,0xbef50000,0x3e71beb5,0x3ee23eb5,0xbec6bed5,0x3ea2be8e,0x3d493efb,0xbeffbdc8,0x3eff3e44,0xbd493eed,0xbea2beed,0x3ec6be44,0xbee23dc8,0xbe71befb,0x3ef53e8e,0xbe153ed5,
0x3dc83f00,0xbefb0000,0x3efb0000,0x3dc83f00,0xbe8ebeed,0x3ed5be44,0xbed53e44,0xbe8ebeed,0x3ed53eb5,0xbe8e3eb5,0x3e8ebeb5,0x3ed53eb5,0xbefbbe44,0x3dc8beed,0xbdc83eed,0xbefbbe44,
0x3d493f00,0xbeff0000,0x3ec63eb5,0xbea23eb5,0xbe15befb,0x3ef5bdc8,0xbee2be8e,0x3e71bed5,0x3e713eed,0xbee23e44,0x3ef53e44,0xbe153eed,0xbea2bed5,0x3ec6be8e,0xbeffbdc8,0x3d49befb,
0x3f00,0xbf000000,0x3f00,0xbf000000,0xbf00,0x3f000000,0xbf00,0x3f000000,0x3f00,0xbf000000,0x3f00,0xbf000000,0xbf00,0x3f000000,0xbf00,0x3f000000,
0xbd493f00,0xbeff0000,0xbec63eb5,0xbea2beb5,0x3e15befb,0x3ef53dc8,0x3ee2be8e,0x3e713ed5,0xbe713eed,0xbee2be44,0xbef53e44,0xbe15beed,0x3ea2bed5,0x3ec63e8e,0x3effbdc8,0x3d493efb,
0xbdc83f00,0xbefb0000,0xbefb0000,0x3dc8bf00,0x3e8ebeed,0x3ed53e44,0x3ed53e44,0xbe8e3eed,0xbed53eb5,0xbe8ebeb5,0xbe8ebeb5,0x3ed5beb5,0x3efbbe44,0x3dc83eed,0x3dc83eed,0xbefb3e44,
0xbe153f00,0xbef50000,0xbe71beb5,0x3ee2beb5,0x3ec6bed5,0x3ea23e8e,0xbd493efb,0xbeff3dc8,0xbeff3e44,0xbd49beed,0x3ea2beed,0x3ec63e44,0x3ee23dc8,0xbe713efb,0xbef53e8e,0xbe15bed5,
0xbe443f00,0xbeed0000,0x3e44bf00,0x3eed0000,0x3eedbeb5,0x3e443eb5,0xbeed3eb5,0xbe44beb5,0xbeed0000,0x3e44bf00,0x3eed0000,0xbe443f00,0x3e443eb5,0xbeed3eb5,0xbe44beb5,0x3eedbeb5,
0xbe713f00,0xbee20000,0x3ef5beb5,0x3e153eb5,0x3effbe8e,0x3d493ed5,0xbec6bdc8,0x3ea2befb,0xbea2be44,0x3ec6beed,0xbd493eed,0xbeff3e44,0xbe153efb,0xbef53dc8,0x3ee2bed5,0x3e713e8e,
0xbe8e3f00,0xbed50000,0x3ed50000,0xbe8e3f00,0x3efbbe44,0xbdc83eed,0x3dc8beed,0x3efbbe44,0xbdc8beb5,0x3efbbeb5,0xbefb3eb5,0xbdc8beb5,0xbed53eed,0xbe8ebe44,0x3e8e3e44,0xbed53eed,
0xbea23f00,0xbec60000,0x3d493eb5,0xbeff3eb5,0x3ee2bdc8,0xbe713efb,0x3ef5bed5,0x3e153e8e,0x3e15beed,0x3ef5be44,0xbe71be44,0x3ee2beed,0xbeff3e8e,0x3d49bed5,0xbec63efb,0xbea2bdc8,
0xbeb53f00,0xbeb50000,0xbeb53f00,0xbeb50000,0x3eb50000,0xbeb53f00,0x3eb50000,0xbeb53f00,0x3eb5bf00,0x3eb50000,0x3eb5bf00,0x3eb50000,0xbeb50000,0x3eb5bf00,0xbeb50000,0x3eb5bf00,
0xbec63f00,0xbea20000,0xbeff3eb5,0x3d49beb5,0x3e713dc8,0xbee23efb,0xbe153ed5,0xbef53e8e,0x3ef5beed,0x3e153e44,0x3ee2be44,0xbe713eed,0xbd49be8e,0x3effbed5,0x3ea2befb,0x3ec6bdc8,
0xbed53f00,0xbe8e0000,0xbe8e0000,0x3ed5bf00,0x3dc83e44,0xbefb3eed,0xbefb3eed,0xbdc8be44,0x3efbbeb5,0xbdc83eb5,0xbdc83eb5,0xbefb3eb5,0x3e8ebeed,0x3ed5be44,0x3ed5be44,0xbe8e3eed,
0xbee23f00,0xbe710000,0x3e15beb5,0x3ef5beb5,0xbd493e8e,0xbeff3ed5,0xbea23dc8,0x3ec6befb,0x3ec6be44,0xbea23eed,0xbeff3eed,0xbd49be44,0x3ef5befb,0x3e153dc8,0xbe713ed5,0xbee23e8e,
0xbeed3f00,0xbe440000,0x3eedbf00,0x3e440000,0xbe443eb5,0xbeed3eb5,0x3e44beb5,0x3eedbeb5,0x3e440000,0xbeed3f00,0xbe440000,0x3eedbf00,0x3eedbeb5,0xbe443eb5,0xbeed3eb5,0x3e44beb5,
0xbef53f00,0xbe150000,0x3ee2beb5,0xbe713eb5,0xbea23ed5,0xbec63e8e,0x3effbefb,0x3d493dc8,0xbd493e44,0xbeff3eed,0x3ec6beed,0x3ea2be44,0x3e71bdc8,0xbee23efb,0x3e15be8e,0x3ef5bed5,
0xbefb3f00,0xbdc80000,0x3dc80000,0xbefb3f00,0xbed53eed,0xbe8e3e44,0x3e8ebe44,0xbed53eed,0xbe8e3eb5,0xbed53eb5,0x3ed5beb5,0xbe8e3eb5,0xbdc83e44,0xbefb3eed,0x3efbbeed,0xbdc83e44,
0xbeff3f00,0xbd490000,0xbea23eb5,0xbec63eb5,0xbef53efb,0xbe153dc8,0xbe713e8e,0xbee23ed5,0xbee23eed,0xbe713e44,0xbe153e44,0xbef53eed,0xbec63ed5,0xbea23e8e,0xbd493dc8,0xbeff3efb,
0x3f003f00,0xbf003f00,0x3f003f00,0xbf003f00,0x3f003f00,0xbf003f00,0x3f003f00,0xbf003f00,0x3f003f00,0xbf003f00,0x3f003f00,0xbf003f00,0x3f003f00,0xbf003f00,0x3f003f00,0xbf003f00,
0xbd490000,0xbeffbf00,0xbec6beb5,0xbea2beb5,0xbe15bdc8,0xbef5befb,0xbee2bed5,0xbe71be8e,0xbe71be44,0xbee2beed,0xbef5beed,0xbe15be44,0xbea2be8e,0xbec6bed5,0xbeffbefb,0xbd49bdc8,
0xbefbbf00,0x3dc80000,0x3dc80000,0x3efb3f00,0xbed5beed,0x3e8e3e44,0x3e8e3e44,0x3ed53eed,0xbe8ebeb5,0x3ed53eb5,0x3ed53eb5,0x3e8e3eb5,0xbdc8be44,0x3efb3eed,0x3efb3eed,0x3dc83e44,
0x3e150000,0x3ef53f00,0x3e713eb5,0xbee2beb5,0x3ec63e8e,0x3ea23ed5,0xbd493dc8,0xbeffbefb,0x3eff3eed,0x3d493e44,0xbea2be44,0xbec6beed,0x3ee23efb,0xbe71bdc8,0xbef5bed5,0xbe15be8e,
0x3eed3f00,0xbe440000,0xbeedbf00,0x3e440000,0x3e443eb5,0xbeedbeb5,0xbe44beb5,0x3eed3eb5,0xbe440000,0xbeedbf00,0x3e440000,0x3eed3f00,0xbeedbeb5,0xbe44beb5,0x3eed3eb5,0x3e443eb5,
0xbe710000,0xbee2bf00,0x3ef53eb5,0x3e153eb5,0xbeffbed5,0xbd49be8e,0x3ec63efb,0xbea2bdc8,0xbea2beed,0x3ec63e44,0xbd493e44,0xbeffbeed,0x3e15bdc8,0x3ef53efb,0xbee2be8e,0xbe71bed5,
0xbed5bf00,0x3e8e0000,0xbe8e0000,0xbed5bf00,0x3dc8be44,0x3efb3eed,0xbefbbeed,0x3dc8be44,0x3efb3eb5,0x3dc83eb5,0xbdc8beb5,0x3efb3eb5,0x3e8e3eed,0xbed5be44,0x3ed53e44,0x3e8e3eed,
0x3ea20000,0x3ec63f00,0xbd49beb5,0x3eff3eb5,0x3ee23efb,0xbe713dc8,0x3ef53e8e,0x3e153ed5,0xbe153e44,0xbef5beed,0x3e713eed,0xbee2be44,0xbeffbed5,0x3d49be8e,0xbec6bdc8,0xbea2befb,
0x3eb53f00,0xbeb50000,0x3eb53f00,0xbeb50000,0xbeb50000,0xbeb5bf00,0xbeb50000,0xbeb5bf00,0xbeb5bf00,0x3eb50000,0xbeb5bf00,0x3eb50000,0x3eb50000,0x3eb53f00,0x3eb50000,0x3eb53f00,
0xbec60000,0xbea2bf00,0xbeffbeb5,0x3d49beb5,0xbe71befb,0x3ee23dc8,0x3e15be8e,0x3ef53ed5,0x3ef53e44,0x3e153eed,0x3ee23eed,0xbe713e44,0x3d493ed5,0xbeffbe8e,0xbea23dc8,0xbec6befb,
0xbe8ebf00,0x3ed50000,0x3ed50000,0x3e8e3f00,0x3efb3e44,0x3dc83eed,0x3dc83eed,0xbefbbe44,0xbdc83eb5,0xbefbbeb5,0xbefbbeb5,0x3dc8beb5,0xbed5beed,0x3e8ebe44,0x3e8ebe44,0x3ed53eed,
0x3ee20000,0x3e713f00,0xbe153eb5,0xbef5beb5,0xbd493ed5,0xbeffbe8e,0xbea2befb,0x3ec6bdc8,0xbec6beed,0x3ea2be44,0x3eff3e44,0x3d493eed,0x3ef53dc8,0x3e153efb,0xbe713e8e,0xbee2bed5,
0x3e443f00,0xbeed0000,0xbe44bf00,0x3eed0000,0xbeedbeb5,0x3e44beb5,0x3eed3eb5,0xbe443eb5,0x3eed0000,0x3e443f00,0xbeed0000,0xbe44bf00,0xbe443eb5,0xbeedbeb5,0x3e44beb5,0x3eed3eb5,
0xbef50000,0xbe15bf00,0x3ee23eb5,0xbe713eb5,0x3ea2be8e,0x3ec63ed5,0xbeffbdc8,0xbd49befb,0xbd493eed,0xbeffbe44,0x3ec6be44,0x3ea23eed,0xbe71befb,0x3ee2bdc8,0xbe153ed5,0xbef5be8e,
0xbdc8bf00,0x3efb0000,0xbefb0000,0xbdc8bf00,0x3e8e3eed,0xbed53e44,0x3ed5be44,0x3e8e3eed,0xbed5beb5,0x3e8ebeb5,0xbe8e3eb5,0xbed5beb5,0x3efb3e44,0xbdc83eed,0x3dc8beed,0x3efb3e44,
0x3eff0000,0x3d493f00,0x3ea2beb5,0x3ec63eb5,0xbef53dc8,0xbe15befb,0xbe713ed5,0xbee2be8e,0x3ee2be44,0x3e713eed,0x3e15beed,0x3ef53e44,0xbec63e8e,0xbea2bed5,0xbd493efb,0xbeffbdc8,
0x3f00,0xbf000000,0x3f00,0xbf000000,0xbf00,0x3f000000,0xbf00,0x3f000000,0x3f00,0xbf000000,0x3f00,0xbf000000,0xbf00,0x3f000000,0xbf00,0x3f000000,
0xbeff0000,0x3d49bf00,0xbea2beb5,0x3ec6beb5,0x3ef53dc8,0xbe153efb,0x3e713ed5,0xbee23e8e,0xbee2be44,0x3e71beed,0xbe15beed,0x3ef5be44,0x3ec63e8e,0xbea23ed5,0x3d493efb,0xbeff3dc8,
0x3dc8bf00,0x3efb0000,0x3efb0000,0xbdc83f00,0xbe8e3eed,0xbed5be44,0xbed5be44,0x3e8ebeed,0x3ed5beb5,0x3e8e3eb5,0x3e8e3eb5,0xbed53eb5,0xbefb3e44,0xbdc8beed,0xbdc8beed,0x3efbbe44,
0x3ef50000,0xbe153f00,0xbee23eb5,0xbe71beb5,0xbea2be8e,0x3ec6bed5,0x3effbdc8,0xbd493efb,0x3d493eed,0xbeff3e44,0xbec6be44,0x3ea2beed,0x3e71befb,0x3ee23dc8,0x3e153ed5,0xbef53e8e,
0xbe443f00,0xbeed0000,0x3e44bf00,0x3eed0000,0x3eedbeb5,0x3e443eb5,0xbeed3eb5,0xbe44beb5,0xbeed0000,0x3e44bf00,0x3eed0000,0xbe443f00,0x3e443eb5,0xbeed3eb5,0xbe44beb5,0x3eedbeb5,
0xbee20000,0x3e71bf00,0x3e153eb5,0xbef53eb5,0x3d493ed5,0xbeff3e8e,0x3ea2befb,0x3ec63dc8,0x3ec6beed,0x3ea23e44,0xbeff3e44,0x3d49beed,0xbef53dc8,0x3e15befb,0x3e713e8e,0xbee23ed5,
0x3e8ebf00,0x3ed50000,0xbed50000,0x3e8ebf00,0xbefb3e44,0x3dc8beed,0xbdc83eed,0xbefb3e44,0x3dc83eb5,0xbefb3eb5,0x3efbbeb5,0x3dc83eb5,0x3ed5beed,0x3e8e3e44,0xbe8ebe44,0x3ed5beed,
0x3ec60000,0xbea23f00,0x3effbeb5,0x3d493eb5,0x3e71befb,0x3ee2bdc8,0xbe15be8e,0x3ef5bed5,0xbef53e44,0x3e15beed,0xbee23eed,0xbe71be44,0xbd493ed5,0xbeff3e8e,0x3ea23dc8,0xbec63efb,
0xbeb53f00,0xbeb50000,0xbeb53f00,0xbeb50000,0x3eb50000,0xbeb53f00,0x3eb50000,0xbeb53f00,0x3eb5bf00,0x3eb50000,0x3eb5bf00,0x3eb50000,0xbeb50000,0x3eb5bf00,0xbeb50000,0x3eb5bf00,
0xbea20000,0x3ec6bf00,0x3d49beb5,0x3effbeb5,0xbee23efb,0xbe71bdc8,0xbef53e8e,0x3e15bed5,0x3e153e44,0xbef53eed,0xbe713eed,0xbee23e44,0x3effbed5,0x3d493e8e,0x3ec6bdc8,0xbea23efb,
0x3ed5bf00,0x3e8e0000,0x3e8e0000,0xbed53f00,0xbdc8be44,0x3efbbeed,0x3efbbeed,0x3dc83e44,0xbefb3eb5,0x3dc8beb5,0x3dc8beb5,0x3efbbeb5,0xbe8e3eed,0xbed53e44,0xbed53e44,0x3e8ebeed,
0x3e710000,0xbee23f00,0xbef53eb5,0x3e15beb5,0x3effbed5,0xbd493e8e,0xbec63efb,0xbea23dc8,0x3ea2beed,0x3ec6be44,0x3d493e44,0xbeff3eed,0xbe15bdc8,0x3ef5befb,0x3ee2be8e,0xbe713ed5,
0xbeed3f00,0xbe440000,0x3eedbf00,0x3e440000,0xbe443eb5,0xbeed3eb5,0x3e44beb5,0x3eedbeb5,0x3e440000,0xbeed3f00,0xbe440000,0x3eedbf00,0x3eedbeb5,0xbe443eb5,0xbeed3eb5,0x3e44beb5,
0xbe150000,0x3ef5bf00,0xbe713eb5,0xbee23eb5,0xbec63e8e,0x3ea2bed5,0x3d493dc8,0xbeff3efb,0xbeff3eed,0x3d49be44,0x3ea2be44,0xbec63eed,0xbee23efb,0xbe713dc8,0x3ef5bed5,0xbe153e8e,
0x3efbbf00,0x3dc80000,0xbdc80000,0x3efbbf00,0x3ed5beed,0x3e8ebe44,0xbe8e3e44,0x3ed5beed,0x3e8ebeb5,0x3ed5beb5,0xbed53eb5,0x3e8ebeb5,0x3dc8be44,0x3efbbeed,0xbefb3eed,0x3dc8be44,
0x3d490000,0xbeff3f00,0x3ec6beb5,0xbea23eb5,0x3e15bdc8,0xbef53efb,0x3ee2bed5,0xbe713e8e,0x3e71be44,0xbee23eed,0x3ef5beed,0xbe153e44,0x3ea2be8e,0xbec63ed5,0x3effbefb,0xbd493dc8,
0x3f003f00,0xbf003f00,0x3f003f00,0xbf003f00,0x3f003f00,0xbf003f00,0x3f003f00,0xbf003f00,0x3f003f00,0xbf003f00,0x3f003f00,0xbf003f00,0x3f003f00,0xbf003f00,0x3f003f00,0xbf003f00,
0xbeffbf00,0x3d490000,0xbea2beb5,0x3ec63eb5,0xbef5befb,0x3e153dc8,0xbe71be8e,0x3ee23ed5,0xbee2beed,0x3e713e44,0xbe15be44,0x3ef53eed,0xbec6bed5,0x3ea23e8e,0xbd49bdc8,0x3eff3efb,
0x3efb3f00,0xbdc80000,0xbdc80000,0xbefbbf00,0x3ed53eed,0xbe8ebe44,0xbe8ebe44,0xbed5beed,0x3e8e3eb5,0xbed5beb5,0xbed5beb5,0xbe8ebeb5,0x3dc83e44,0xbefbbeed,0xbefbbeed,0xbdc8be44,
0xbef5bf00,0x3e150000,0x3ee23eb5,0x3e713eb5,0xbea2bed5,0x3ec63e8e,0x3eff3efb,0xbd493dc8,0xbd49be44,0x3eff3eed,0x3ec63eed,0xbea2be44,0x3e713dc8,0x3ee23efb,0x3e153e8e,0xbef5bed5,
0x3eed3f00,0xbe440000,0xbeedbf00,0x3e440000,0x3e443eb5,0xbeedbeb5,0xbe44beb5,0x3eed3eb5,0xbe440000,0xbeedbf00,0x3e440000,0x3eed3f00,0xbeedbeb5,0xbe44beb5,0x3eed3eb5,0x3e443eb5,
0xbee2bf00,0x3e710000,0x3e153eb5,0xbef5beb5,0xbd49be8e,0x3eff3ed5,0xbea2bdc8,0xbec6befb,0x3ec63e44,0x3ea23eed,0xbeffbeed,0x3d49be44,0x3ef53efb,0xbe153dc8,0xbe71bed5,0x3ee23e8e,
0x3ed53f00,0xbe8e0000,0x3e8e0000,0x3ed53f00,0xbdc83e44,0xbefbbeed,0x3efb3eed,0xbdc83e44,0xbefbbeb5,0xbdc8beb5,0x3dc83eb5,0xbefbbeb5,0xbe8ebeed,0x3ed53e44,0xbed5be44,0xbe8ebeed,
0xbec6bf00,0x3ea20000,0xbeffbeb5,0xbd49beb5,0x3e71bdc8,0x3ee23efb,0xbe15bed5,0x3ef53e8e,0x3ef53eed,0xbe153e44,0x3ee23e44,0x3e713eed,0xbd493e8e,0xbeffbed5,0x3ea23efb,0xbec6bdc8,
0x3eb53f00,0xbeb50000,0x3eb53f00,0xbeb50000,0xbeb50000,0xbeb5bf00,0xbeb50000,0xbeb5bf00,0xbeb5bf00,0x3eb50000,0xbeb5bf00,0x3eb50000,0x3eb50000,0x3eb53f00,0x3eb50000,0x3eb53f00,
0xbea2bf00,0x3ec60000,0x3d49beb5,0x3eff3eb5,0x3ee23dc8,0x3e713efb,0x3ef53ed5,0xbe153e8e,0x3e153eed,0xbef5be44,0xbe713e44,0xbee2beed,0xbeffbe8e,0xbd49bed5,0xbec6befb,0x3ea2bdc8,
0x3e8e3f00,0xbed50000,0xbed50000,0xbe8ebf00,0xbefbbe44,0xbdc8beed,0xbdc8beed,0x3efb3e44,0x3dc8beb5,0x3efb3eb5,0x3efb3eb5,0xbdc83eb5,0x3ed53eed,0xbe8e3e44,0xbe8e3e44,0xbed5beed,
0xbe71bf00,0x3ee20000,0x3ef53eb5,0xbe153eb5,0x3eff3e8e,0xbd493ed5,0xbec63dc8,0xbea2befb,0xbea23e44,0xbec6beed,0xbd49beed,0x3eff3e44,0xbe15befb,0x3ef53dc8,0x3ee23ed5,0xbe713e8e,
0x3e443f00,0xbeed0000,0xbe44bf00,0x3eed0000,0xbeedbeb5,0x3e44beb5,0x3eed3eb5,0xbe443eb5,0x3eed0000,0x3e443f00,0xbeed0000,0xbe44bf00,0xbe443eb5,0xbeedbeb5,0x3e44beb5,0x3eed3eb5,
0xbe15bf00,0x3ef50000,0xbe713eb5,0xbee2beb5,0x3ec63ed5,0xbea23e8e,0xbd49befb,0x3eff3dc8,0xbeffbe44,0x3d49beed,0x3ea23eed,0xbec63e44,0x3ee2bdc8,0x3e713efb,0xbef5be8e,0x3e15bed5,
0x3dc83f00,0xbefb0000,0x3efb0000,0x3dc83f00,0xbe8ebeed,0x3ed5be44,0xbed53e44,0xbe8ebeed,0x3ed53eb5,0xbe8e3eb5,0x3e8ebeb5,0x3ed53eb5,0xbefbbe44,0x3dc8beed,0xbdc83eed,0xbefbbe44,
0xbd49bf00,0x3eff0000,0xbec6beb5,0x3ea2beb5,0x3e153efb,0xbef53dc8,0x3ee23e8e,0xbe713ed5,0xbe71beed,0x3ee2be44,0xbef5be44,0x3e15beed,0x3ea23ed5,0xbec63e8e,0x3eff3dc8,0xbd493efb,
0x3f00,0xbf000000,0x3f00,0xbf000000,0xbf00,0x3f000000,0xbf00,0x3f000000,0x3f00,0xbf000000,0x3f00,0xbf000000,0xbf00,0x3f000000,0xbf00,0x3f000000,
0x3d49bf00,0x3eff0000,0x3ec6beb5,0x3ea23eb5,0xbe153efb,0xbef5bdc8,0xbee23e8e,0xbe71bed5,0x3e71beed,0x3ee23e44,0x3ef5be44,0x3e153eed,0xbea23ed5,0xbec6be8e,0xbeff3dc8,0xbd49befb,
0xbdc83f00,0xbefb0000,0xbefb0000,0x3dc8bf00,0x3e8ebeed,0x3ed53e44,0x3ed53e44,0xbe8e3eed,0xbed53eb5,0xbe8ebeb5,0xbe8ebeb5,0x3ed5beb5,0x3efbbe44,0x3dc83eed,0x3dc83eed,0xbefb3e44,
0x3e15bf00,0x3ef50000,0x3e713eb5,0xbee23eb5,0xbec63ed5,0xbea2be8e,0x3d49befb,0x3effbdc8,0x3effbe44,0x3d493eed,0xbea23eed,0xbec6be44,0xbee2bdc8,0x3e71befb,0x3ef5be8e,0x3e153ed5,
0xbe443f00,0xbeed0000,0x3e44bf00,0x3eed0000,0x3eedbeb5,0x3e443eb5,0xbeed3eb5,0xbe44beb5,0xbeed0000,0x3e44bf00,0x3eed0000,0xbe443f00,0x3e443eb5,0xbeed3eb5,0xbe44beb5,0x3eedbeb5,
0x3e71bf00,0x3ee20000,0xbef53eb5,0xbe15beb5,0xbeff3e8e,0xbd49bed5,0x3ec63dc8,0xbea23efb,0x3ea23e44,0xbec63eed,0x3d49beed,0x3effbe44,0x3e15befb,0x3ef5bdc8,0xbee23ed5,0xbe71be8e,
0xbe8e3f00,0xbed50000,0x3ed50000,0xbe8e3f00,0x3efbbe44,0xbdc83eed,0x3dc8beed,0x3efbbe44,0xbdc8beb5,0x3efbbeb5,0xbefb3eb5,0xbdc8beb5,0xbed53eed,0xbe8ebe44,0x3e8e3e44,0xbed53eed,
0x3ea2bf00,0x3ec60000,0xbd49beb5,0x3effbeb5,0xbee23dc8,0x3e71befb,0xbef53ed5,0xbe15be8e,0xbe153eed,0xbef53e44,0x3e713e44,0xbee23eed,0x3effbe8e,0xbd493ed5,0x3ec6befb,0x3ea23dc8,
0xbeb53f00,0xbeb50000,0xbeb53f00,0xbeb50000,0x3eb50000,0xbeb53f00,0x3eb50000,0xbeb53f00,0x3eb5bf00,0x3eb50000,0x3eb5bf00,0x3eb50000,0xbeb50000,0x3eb5bf00,0xbeb50000,0x3eb5bf00,
0x3ec6bf00,0x3ea20000,0x3effbeb5,0xbd493eb5,0xbe71bdc8,0x3ee2befb,0x3e15bed5,0x3ef5be8e,0xbef53eed,0xbe15be44,0xbee23e44,0x3e71beed,0x3d493e8e,0xbeff3ed5,0xbea23efb,0xbec63dc8,
0xbed53f00,0xbe8e0000,0xbe8e0000,0x3ed5bf00,0x3dc83e44,0xbefb3eed,0xbefb3eed,0xbdc8be44,0x3efbbeb5,0xbdc83eb5,0xbdc83eb5,0xbefb3eb5,0x3e8ebeed,0x3ed5be44,0x3ed5be44,0xbe8e3eed,
0x3ee2bf00,0x3e710000,0xbe153eb5,0xbef53eb5,0x3d49be8e,0x3effbed5,0x3ea2bdc8,0xbec63efb,0xbec63e44,0x3ea2beed,0x3effbeed,0x3d493e44,0xbef53efb,0xbe15bdc8,0x3e71bed5,0x3ee2be8e,
0xbeed3f00,0xbe440000,0x3eedbf00,0x3e440000,0xbe443eb5,0xbeed3eb5,0x3e44beb5,0x3eedbeb5,0x3e440000,0xbeed3f00,0xbe440000,0x3eedbf00,0x3eedbeb5,0xbe443eb5,0xbeed3eb5,0x3e44beb5,
0x3ef5bf00,0x3e150000,0xbee23eb5,0x3e71beb5,0x3ea2bed5,0x3ec6be8e,0xbeff3efb,0xbd49bdc8,0x3d49be44,0x3effbeed,0xbec63eed,0xbea23e44,0xbe713dc8,0x3ee2befb,0xbe153e8e,0xbef53ed5,
0xbefb3f00,0xbdc80000,0x3dc80000,0xbefb3f00,0xbed53eed,0xbe8e3e44,0x3e8ebe44,0xbed53eed,0xbe8e3eb5,0xbed53eb5,0x3ed5beb5,0xbe8e3eb5,0xbdc83e44,0xbefb3eed,0x3efbbeed,0xbdc83e44,
0x3effbf00,0x3d490000,0x3ea2beb5,0x3ec6beb5,0x3ef5befb,0x3e15bdc8,0x3e71be8e,0x3ee2bed5,0x3ee2beed,0x3e71be44,0x3e15be44,0x3ef5beed,0x3ec6bed5,0x3ea2be8e,0x3d49bdc8,0x3effbefb,
0x3f003f00,0xbf003f00,0x3f003f00,0xbf003f00,0x3f003f00,0xbf003f00,0x3f003f00,0xbf003f00,0x3f003f00,0xbf003f00,0x3f003f00,0xbf003f00,0x3f003f00,0xbf003f00,0x3f003f00,0xbf003f00,
0x3d490000,0x3eff3f00,0x3ec63eb5,0x3ea23eb5,0x3e153dc8,0x3ef53efb,0x3ee23ed5,0x3e713e8e,0x3e713e44,0x3ee23eed,0x3ef53eed,0x3e153e44,0x3ea23e8e,0x3ec63ed5,0x3eff3efb,0x3d493dc8,
0xbefbbf00,0x3dc80000,0x3dc80000,0x3efb3f00,0xbed5beed,0x3e8e3e44,0x3e8e3e44,0x3ed53eed,0xbe8ebeb5,0x3ed53eb5,0x3ed53eb5,0x3e8e3eb5,0xbdc8be44,0x3efb3eed,0x3efb3eed,0x3dc83e44,
0xbe150000,0xbef5bf00,0xbe71beb5,0x3ee23eb5,0xbec6be8e,0xbea2bed5,0x3d49bdc8,0x3eff3efb,0xbeffbeed,0xbd49be44,0x3ea23e44,0x3ec63eed,0xbee2befb,0x3e713dc8,0x3ef53ed5,0x3e153e8e,
0x3eed3f00,0xbe440000,0xbeedbf00,0x3e440000,0x3e443eb5,0xbeedbeb5,0xbe44beb5,0x3eed3eb5,0xbe440000,0xbeedbf00,0x3e440000,0x3eed3f00,0xbeedbeb5,0xbe44beb5,0x3eed3eb5,0x3e443eb5,
0x3e710000,0x3ee23f00,0xbef5beb5,0xbe15beb5,0x3eff3ed5,0x3d493e8e,0xbec6befb,0x3ea23dc8,0x3ea23eed,0xbec6be44,0x3d49be44,0x3eff3eed,0xbe153dc8,0xbef5befb,0x3ee23e8e,0x3e713ed5,
0xbed5bf00,0x3e8e0000,0xbe8e0000,0xbed5bf00,0x3dc8be44,0x3efb3eed,0xbefbbeed,0x3dc8be44,0x3efb3eb5,0x3dc83eb5,0xbdc8beb5,0x3efb3eb5,0x3e8e3eed,0xbed5be44,0x3ed53e44,0x3e8e3eed,
0xbea20000,0xbec6bf00,0x3d493eb5,0xbeffbeb5,0xbee2befb,0x3e71bdc8,0xbef5be8e,0xbe15bed5,0x3e15be44,0x3ef53eed,0xbe71beed,0x3ee23e44,0x3eff3ed5,0xbd493e8e,0x3ec63dc8,0x3ea23efb,
0x3eb53f00,0xbeb50000,0x3eb53f00,0xbeb50000,0xbeb50000,0xbeb5bf00,0xbeb50000,0xbeb5bf00,0xbeb5bf00,0x3eb50000,0xbeb5bf00,0x3eb50000,0x3eb50000,0x3eb53f00,0x3eb50000,0x3eb53f00,
0x3ec60000,0x3ea23f00,0x3eff3eb5,0xbd493eb5,0x3e713efb,0xbee2bdc8,0xbe153e8e,0xbef5bed5,0xbef5be44,0xbe15beed,0xbee2beed,0x3e71be44,0xbd49bed5,0x3eff3e8e,0x3ea2bdc8,0x3ec63efb,
0xbe8ebf00,0x3ed50000,0x3ed50000,0x3e8e3f00,0x3efb3e44,0x3dc83eed,0x3dc83eed,0xbefbbe44,0xbdc83eb5,0xbefbbeb5,0xbefbbeb5,0x3dc8beb5,0xbed5beed,0x3e8ebe44,0x3e8ebe44,0x3ed53eed,
0xbee20000,0xbe71bf00,0x3e15beb5,0x3ef53eb5,0x3d49bed5,0x3eff3e8e,0x3ea23efb,0xbec63dc8,0x3ec63eed,0xbea23e44,0xbeffbe44,0xbd49beed,0xbef5bdc8,0xbe15befb,0x3e71be8e,0x3ee23ed5,
0x3e443f00,0xbeed0000,0xbe44bf00,0x3eed0000,0xbeedbeb5,0x3e44beb5,0x3eed3eb5,0xbe443eb5,0x3eed0000,0x3e443f00,0xbeed0000,0xbe44bf00,0xbe443eb5,0xbeedbeb5,0x3e44beb5,0x3eed3eb5,
0x3ef50000,0x3e153f00,0xbee2beb5,0x3e71beb5,0xbea23e8e,0xbec6bed5,0x3eff3dc8,0x3d493efb,0x3d49beed,0x3eff3e44,0xbec63e44,0xbea2beed,0x3e713efb,0xbee23dc8,0x3e15bed5,0x3ef53e8e,
0xbdc8bf00,0x3efb0000,0xbefb0000,0xbdc8bf00,0x3e8e3eed,0xbed53e44,0x3ed5be44,0x3e8e3eed,0xbed5beb5,0x3e8ebeb5,0xbe8e3eb5,0xbed5beb5,0x3efb3e44,0xbdc83eed,0x3dc8beed,0x3efb3e44,
0xbeff0000,0xbd49bf00,0xbea23eb5,0xbec6beb5,0x3ef5bdc8,0x3e153efb,0x3e71bed5,0x3ee23e8e,0xbee23e44,0xbe71beed,0xbe153eed,0xbef5be44,0x3ec6be8e,0x3ea23ed5,0x3d49befb,0x3eff3dc8,
0x3f00,0xbf000000,0x3f00,0xbf000000,0xbf00,0x3f000000,0xbf00,0x3f000000,0x3f00,0xbf000000,0x3f00,0xbf000000,0xbf00,0x3f000000,0xbf00,0x3f000000,
0x3eff0000,0xbd493f00,0x3ea23eb5,0xbec63eb5,0xbef5bdc8,0x3e15befb,0xbe71bed5,0x3ee2be8e,0x3ee23e44,0xbe713eed,0x3e153eed,0xbef53e44,0xbec6be8e,0x3ea2bed5,0xbd49befb,0x3effbdc8,
0x3dc8bf00,0x3efb0000,0x3efb0000,0xbdc83f00,0xbe8e3eed,0xbed5be44,0xbed5be44,0x3e8ebeed,0x3ed5beb5,0x3e8e3eb5,0x3e8e3eb5,0xbed53eb5,0xbefb3e44,0xbdc8beed,0xbdc8beed,0x3efbbe44,
0xbef50000,0x3e15bf00,0x3ee2beb5,0x3e713eb5,0x3ea23e8e,0xbec63ed5,0xbeff3dc8,0x3d49befb,0xbd49beed,0x3effbe44,0x3ec63e44,0xbea23eed,0xbe713efb,0xbee2bdc8,0xbe15bed5,0x3ef5be8e,
0xbe443f00,0xbeed0000,0x3e44bf00,0x3eed0000,0x3eedbeb5,0x3e443eb5,0xbeed3eb5,0xbe44beb5,0xbeed0000,0x3e44bf00,0x3eed0000,0xbe443f00,0x3e443eb5,0xbeed3eb5,0xbe44beb5,0x3eedbeb5,
0x3ee20000,0xbe713f00,0xbe15beb5,0x3ef5beb5,0xbd49bed5,0x3effbe8e,0xbea23efb,0xbec6bdc8,0xbec63eed,0xbea2be44,0x3effbe44,0xbd493eed,0x3ef5bdc8,0xbe153efb,0xbe71be8e,0x3ee2bed5,
0x3e8ebf00,0x3ed50000,0xbed50000,0x3e8ebf00,0xbefb3e44,0x3dc8beed,0xbdc83eed,0xbefb3e44,0x3dc83eb5,0xbefb3eb5,0x3efbbeb5,0x3dc83eb5,0x3ed5beed,0x3e8e3e44,0xbe8ebe44,0x3ed5beed,
0xbec60000,0x3ea2bf00,0xbeff3eb5,0xbd49beb5,0xbe713efb,0xbee23dc8,0x3e153e8e,0xbef53ed5,0x3ef5be44,0xbe153eed,0x3ee2beed,0x3e713e44,0x3d49bed5,0x3effbe8e,0xbea2bdc8,0x3ec6befb,
0xbeb53f00,0xbeb50000,0xbeb53f00,0xbeb50000,0x3eb50000,0xbeb53f00,0x3eb50000,0xbeb53f00,0x3eb5bf00,0x3eb50000,0x3eb5bf00,0x3eb50000,0xbeb50000,0x3eb5bf00,0xbeb50000,0x3eb5bf00,
0x3ea20000,0xbec63f00,0xbd493eb5,0xbeff3eb5,0x3ee2befb,0x3e713dc8,0x3ef5be8e,0xbe153ed5,0xbe15be44,0x3ef5beed,0x3e71beed,0x3ee2be44,0xbeff3ed5,0xbd49be8e,0xbec63dc8,0x3ea2befb,
0x3ed5bf00,0x3e8e0000,0x3e8e0000,0xbed53f00,0xbdc8be44,0x3efbbeed,0x3efbbeed,0x3dc83e44,0xbefb3eb5,0x3dc8beb5,0x3dc8beb5,0x3efbbeb5,0xbe8e3eed,0xbed53e44,0xbed53e44,0x3e8ebeed,
0xbe710000,0x3ee2bf00,0x3ef5beb5,0xbe153eb5,0xbeff3ed5,0x3d49be8e,0x3ec6befb,0x3ea2bdc8,0xbea23eed,0xbec63e44,0xbd49be44,0x3effbeed,0x3e153dc8,0xbef53efb,0xbee23e8e,0x3e71bed5,
0xbeed3f00,0xbe440000,0x3eedbf00,0x3e440000,0xbe443eb5,0xbeed3eb5,0x3e44beb5,0x3eedbeb5,0x3e440000,0xbeed3f00,0xbe440000,0x3eedbf00,0x3eedbeb5,0xbe443eb5,0xbeed3eb5,0x3e44beb5,
0x3e150000,0xbef53f00,0x3e71beb5,0x3ee2beb5,0x3ec6be8e,0xbea23ed5,0xbd49bdc8,0x3effbefb,0x3effbeed,0xbd493e44,0xbea23e44,0x3ec6beed,0x3ee2befb,0x3e71bdc8,0xbef53ed5,0x3e15be8e,
0x3efbbf00,0x3dc80000,0xbdc80000,0x3efbbf00,0x3ed5beed,0x3e8ebe44,0xbe8e3e44,0x3ed5beed,0x3e8ebeb5,0x3ed5beb5,0xbed53eb5,0x3e8ebeb5,0x3dc8be44,0x3efbbeed,0xbefb3eed,0x3dc8be44,
0xbd490000,0x3effbf00,0xbec63eb5,0x3ea2beb5,0xbe153dc8,0x3ef5befb,0xbee23ed5,0x3e71be8e,0xbe713e44,0x3ee2beed,0xbef53eed,0x3e15be44,0xbea23e8e,0x3ec6bed5,0xbeff3efb,0x3d49bdc8,
0x3f800000,0x0,0x3f800000,0x0,0x3f800000,0x0,0x3f800000,0x0,0x3f800000,0x0,0x3f800000,0x0,0x3f800000,0x0,0x3f800000,0x0,
0x3f800000,0x0,0x3f7ffec4,0xbbc90f88,0x3f7ffb11,0xbc490e90,0x3f7ff4e6,0xbc96c9b6,0x3f7fec43,0xbcc90ab0,0x3f7fe129,0xbcfb49ba,0x3f7fd397,0xbd16c32c,0x3f7fc38f,0xbd2fe007,
0x3f800000,0x0,0x3f7ffb11,0xbc490e90,0x3f7fec43,0xbcc90ab0,0x3f7fd397,0xbd16c32c,0x3f7fb10f,0xbd48fb30,0x3f7f84ab,0xbd7b2b74,0x3f7f4e6d,0xbd96a905,0x3f7f0e58,0xbdafb680,
0x3f800000,0x0,0x3f7ff4e6,0xbc96c9b6,0x3f7fd397,0xbd16c32c,0x3f7f9c18,0xbd621469,0x3f7f4e6d,0xbd96a905,0x3f7eea9d,0xbdbc3ac3,0x3f7e70b0,0xbde1bc2e,0x3f7de0b1,0xbe039502,
0x3f800000,0x0,0x3f7fec43,0xbcc90ab0,0x3f7fb10f,0xbd48fb30,0x3f7f4e6d,0xbd96a905,0x3f7ec46d,0xbdc8bd36,0x3f7e1324,0xbdfab273,0x3f7d3aac,0xbe164083,0x3f7c3b28,0xbe2f10a2,
0x3f800000,0x0,0x3f7fe129,0xbcfb49ba,0x3f7f84ab,0xbd7b2b74,0x3f7eea9d,0xbdbc3ac3,0x3f7e1324,0xbdfab273,0x3f7cfe73,0xbe1c76de,0x3f7baccd,0xbe3b6ecf,0x3f7a1e84,0xbe5a3997,
0x3f800000,0x0,0x3f7fd397,0xbd16c32c,0x3f7f4e6d,0xbd96a905,0x3f7e70b0,0xbde1bc2e,0x3f7d3aac,0xbe164083,0x3f7baccd,0xbe3b6ecf,0x3f79c79d,0xbe605c13,0x3f778bc5,0xbe827dc0,
0x3f800000,0x0,0x3f7fc38f,0xbd2fe007,0x3f7f0e58,0xbdafb680,0x3f7de0b1,0xbe039502,0x3f7c3b28,0xbe2f10a2,0x3f7a1e84,0xbe5a3997,0x3f778bc5,0xbe827dc0,0x3f748422,0xbe97a117,
0x3f800000,0x0,0x3f7fb10f,0xbd48fb30,0x3f7ec46d,0xbdc8bd36,0x3f7d3aac,0xbe164083,0x3f7b14be,0xbe47c5c2,0x3f7853f8,0xbe78cfcc,0x3f74fa0b,0xbe94a031,0x3f710908,0xbeac7cd4,
0x3f800000,0x0,0x3f7f9c18,0xbd621469,0x3f7e70b0,0xbde1bc2e,0x3f7c7eb0,0xbe28defc,0x3f79c79d,0xbe605c13,0x3f764d97,0xbe8b9507,0x3f721352,0xbea68f12,0x3f6d1c1d,0xbec1071e,
0x3f800000,0x0,0x3f7f84ab,0xbd7b2b74,0x3f7e1324,0xbdfab273,0x3f7baccd,0xbe3b6ecf,0x3f7853f8,0xbe78cfcc,0x3f740bdd,0xbe9aa086,0x3f6ed89e,0xbeb8442a,0x3f68bf3c,0xbed53641,
0x3f800000,0x0,0x3f7f6ac7,0xbd8a200a,0x3f7dabcc,0xbe09cf86,0x3f7ac516,0xbe4dee60,0x3f76ba07,0xbe888e93,0x3f718f57,0xbea986c4,0x3f6b4b0c,0xbec9b953,0x3f63f473,0xbee900b7,
0x3f800000,0x0,0x3f7f4e6d,0xbd96a905,0x3f7d3aac,0xbe164083,0x3f79c79d,0xbe605c13,0x3f74fa0b,0xbe94a031,0x3f6ed89e,0xbeb8442a,0x3f676bd8,0xbedae880,0x3f5ebe05,0xbefc5d27,
0x3f800000,0x0,0x3f7f2f9d,0xbda3308c,0x3f7cbfc9,0xbe22abb6,0x3f78b47b,0xbe72b651,0x3f731447,0xbea09ae5,0x3f6be858,0xbec6d529,0x3f633c5a,0xbeebcbbb,0x3f591e6a,0xbf07a136,
0x3f800000,0x0,0x3f7f0e58,0xbdafb680,0x3f7c3b28,0xbe2f10a2,0x3f778bc5,0xbe827dc0,0x3f710908,0xbeac7cd4,0x3f68bf3c,0xbed53641,0x3f5ebe05,0xbefc5d27,0x3f531849,0xbf10d3cd,
0x3f800000,0x0,0x3f7eea9d,0xbdbc3ac3,0x3f7baccd,0xbe3b6ecf,0x3f764d97,0xbe8b9507,0x3f6ed89e,0xbeb8442a,0x3f655e0b,0xbee363fa,0x3f59f26a,0xbf064b82,0x3f4cae79,0xbf19c200,
0x3f800000,0x0,0x3f7ec46d,0xbdc8bd36,0x3f7b14be,0xbe47c5c2,0x3f74fa0b,0xbe94a031,0x3f6c835e,0xbec3ef15,0x3f61c598,0xbef15aea,0x3f54db31,0xbf0e39da,0x3f45e403,0xbf226799,
0x3f800000,0x0,0x3f7e9bc9,0xbdd53db9,0x3f7a7302,0xbe541501,0x3f73913f,0xbe9d9e78,0x3f6a09a7,0xbecf7bca,0x3f5df6be,0xbeff17b2,0x3f4f7a1f,0xbf15f6d9,0x3f3ebc1b,0xbf2ac082,
0x3f800000,0x0,0x3f7e70b0,0xbde1bc2e,0x3f79c79d,0xbe605c13,0x3f721352,0xbea68f12,0x3f676bd8,0xbedae880,0x3f59f26a,0xbf064b82,0x3f49d112,0xbf1d7fd1,0x3f373a23,0xbf32c8c9,
0x3f800000,0x0,0x3f7e4323,0xbdee3876,0x3f791298,0xbe6c9a7f,0x3f708066,0xbeaf713a,0x3f64aa59,0xbee63375,0x3f55b993,0xbf0cead0,0x3f43e200,0xbf24d225,0x3f2f61a5,0xbf3a7ca4,
0x3f800000,0x0,0x3f7e1324,0xbdfab273,0x3f7853f8,0xbe78cfcc,0x3f6ed89e,0xbeb8442a,0x3f61c598,0xbef15aea,0x3f514d3d,0xbf13682a,0x3f3daef9,0xbf2beb4a,0x3f273656,0xbf41d870,
0x3f800000,0x0,0x3f7de0b1,0xbe039502,0x3f778bc5,0xbe827dc0,0x3f6d1c1d,0xbec1071e,0x3f5ebe05,0xbefc5d27,0x3f4cae79,0xbf19c200,0x3f373a23,0xbf32c8c9,0x3f1ebc12,0xbf48d8b3,
0x3f800000,0x0,0x3f7dabcc,0xbe09cf86,0x3f76ba07,0xbe888e93,0x3f6b4b0c,0xbec9b953,0x3f5b941a,0xbf039c3d,0x3f47de65,0xbf1ff6cb,0x3f3085bb,0xbf396842,0x3f15f6d9,0xbf4f7a1f,
0x3f800000,0x0,0x3f7d7474,0xbe1008b7,0x3f75dec6,0xbe8e9a22,0x3f696591,0xbed25a09,0x3f584853,0xbf08f59b,0x3f42de29,0xbf26050a,0x3f299415,0xbf3fc767,0x3f0cead0,0xbf55b993,
0x3f800000,0x0,0x3f7d3aac,0xbe164083,0x3f74fa0b,0xbe94a031,0x3f676bd8,0xbedae880,0x3f54db31,0xbf0e39da,0x3f3daef9,0xbf2beb4a,0x3f226799,0xbf45e403,0x3f039c3d,0xbf5b941a,
0x3f800000,0x0,0x3f7cfe73,0xbe1c76de,0x3f740bdd,0xbe9aa086,0x3f655e0b,0xbee363fa,0x3f514d3d,0xbf13682a,0x3f385216,0xbf31a81d,0x3f1b02c6,0xbf4bbbf8,0x3ef41f07,0xbf6106f2,
0x3f800000,0x0,0x3f7cbfc9,0xbe22abb6,0x3f731447,0xbea09ae5,0x3f633c5a,0xbeebcbbb,0x3f4d9f02,0xbf187fc0,0x3f32c8c9,0xbf373a23,0x3f13682a,0xbf514d3d,0x3ee0924f,0xbf660f88,
0x3f800000,0x0,0x3f7c7eb0,0xbe28defc,0x3f721352,0xbea68f12,0x3f6106f2,0xbef41f07,0x3f49d112,0xbf1d7fd1,0x3f2d1469,0xbf3ca003,0x3f0b9a6b,0xbf5695e5,0x3ecc9b8b,0xbf6aab7b,
0x3f800000,0x0,0x3f7c3b28,0xbe2f10a2,0x3f710908,0xbeac7cd4,0x3f5ebe05,0xbefc5d27,0x3f45e403,0xbf226799,0x3f273656,0xbf41d870,0x3f039c3d,0xbf5b941a,0x3eb8442a,0xbf6ed89e,
0x3f800000,0x0,0x3f7bf531,0xbe354098,0x3f6ff573,0xbeb263ef,0x3f5c61c7,0xbf0242b1,0x3f41d870,0xbf273656,0x3f212ff9,0xbf46e22a,0x3ef6e0cb,0xbf604621,0x3ea395c5,0xbf7294f8,
0x3f800000,0x0,0x3f7baccd,0xbe3b6ecf,0x3f6ed89e,0xbeb8442a,0x3f59f26a,0xbf064b82,0x3f3daef9,0xbf2beb4a,0x3f1b02c6,0xbf4bbbf8,0x3ee63375,0xbf64aa59,0x3e8e9a22,0xbf75dec6,
0x3f800000,0x0,0x3f7b61fc,0xbe419b37,0x3f6db293,0xbebe1d4a,0x3f577026,0xbf0a48ad,0x3f396842,0xbf3085bb,0x3f14b039,0xbf5064af,0x3ed53641,0xbf68bf3c,0x3e72b651,0xbf78b47b,
0x3f800000,0x0,0x3f800000,0x0,0x3f800000,0x0,0x3f800000,0x0,0x3f800000,0x0,0x3f800000,0x0,0x3f800000,0x0,0x3f800000,0x0,
0x3f7fb10f,0xbd48fb30,0x3f7f9c18,0xbd621469,0x3f7f84ab,0xbd7b2b74,0x3f7f6ac7,0xbd8a200a,0x3f7f4e6d,0xbd96a905,0x3f7f2f9d,0xbda3308c,0x3f7f0e58,0xbdafb680,0x3f7eea9d,0xbdbc3ac3,
0x3f7ec46d,0xbdc8bd36,0x3f7e70b0,0xbde1bc2e,0x3f7e1324,0xbdfab273,0x3f7dabcc,0xbe09cf86,0x3f7d3aac,0xbe164083,0x3f7cbfc9,0xbe22abb6,0x3f7c3b28,0xbe2f10a2,0x3f7baccd,0xbe3b6ecf,
0x3f7d3aac,0xbe164083,0x3f7c7eb0,0xbe28defc,0x3f7baccd,0xbe3b6ecf,0x3f7ac516,0xbe4dee60,0x3f79c79d,0xbe605c13,0x3f78b47b,0xbe72b651,0x3f778bc5,0xbe827dc0,0x3f764d97,0xbe8b9507,
0x3f7b14be,0xbe47c5c2,0x3f79c79d,0xbe605c13,0x3f7853f8,0xbe78cfcc,0x3f76ba07,0xbe888e93,0x3f74fa0b,0xbe94a031,0x3f731447,0xbea09ae5,0x3f710908,0xbeac7cd4,0x3f6ed89e,0xbeb8442a,
0x3f7853f8,0xbe78cfcc,0x3f764d97,0xbe8b9507,0x3f740bdd,0xbe9aa086,0x3f718f57,0xbea986c4,0x3f6ed89e,0xbeb8442a,0x3f6be858,0xbec6d529,0x3f68bf3c,0xbed53641,0x3f655e0b,0xbee363fa,
0x3f74fa0b,0xbe94a031,0x3f721352,0xbea68f12,0x3f6ed89e,0xbeb8442a,0x3f6b4b0c,0xbec9b953,0x3f676bd8,0xbedae880,0x3f633c5a,0xbeebcbbb,0x3f5ebe05,0xbefc5d27,0x3f59f26a,0xbf064b82,
0x3f710908,0xbeac7cd4,0x3f6d1c1d,0xbec1071e,0x3f68bf3c,0xbed53641,0x3f63f473,0xbee900b7,0x3f5ebe05,0xbefc5d27,0x3f591e6a,0xbf07a136,0x3f531849,0xbf10d3cd,0x3f4cae79,0xbf19c200,
0x3f6c835e,0xbec3ef15,0x3f676bd8,0xbedae880,0x3f61c598,0xbef15aea,0x3f5b941a,0xbf039c3d,0x3f54db31,0xbf0e39da,0x3f4d9f02,0xbf187fc0,0x3f45e403,0xbf226799,0x3f3daef9,0xbf2beb4a,
0x3f676bd8,0xbedae880,0x3f6106f2,0xbef41f07,0x3f59f26a,0xbf064b82,0x3f5233c6,0xbf121eb0,0x3f49d112,0xbf1d7fd1,0x3f40d0da,0xbf286605,0x3f373a23,0xbf32c8c9,0x3f2d1469,0xbf3ca003,
0x3f61c598,0xbef15aea,0x3f59f26a,0xbf064b82,0x3f514d3d,0xbf13682a,0x3f47de65,0xbf1ff6cb,0x3f3daef9,0xbf2beb4a,0x3f32c8c9,0xbf373a23,0x3f273656,0xbf41d870,0x3f1b02c6,0xbf4bbbf8,
0x3f5b941a,0xbf039c3d,0x3f5233c6,0xbf121eb0,0x3f47de65,0xbf1ff6cb,0x3f3ca003,0xbf2d1469,0x3f3085bb,0xbf396842,0x3f239da9,0xbf44e3f5,0x3f15f6d9,0xbf4f7a1f,0x3f07a136,0xbf591e6a,
0x3f54db31,0xbf0e39da,0x3f49d112,0xbf1d7fd1,0x3f3daef9,0xbf2beb4a,0x3f3085bb,0xbf396842,0x3f226799,0xbf45e403,0x3f13682a,0xbf514d3d,0x3f039c3d,0xbf5b941a,0x3ee63375,0xbf64aa59,
0x3f4d9f02,0xbf187fc0,0x3f40d0da,0xbf286605,0x3f32c8c9,0xbf373a23,0x3f239da9,0xbf44e3f5,0x3f13682a,0xbf514d3d,0x3f0242b1,0xbf5c61c7,0x3ee0924f,0xbf660f88,0x3ebb31a0,0xbf6e46be,
0x3f45e403,0xbf226799,0x3f373a23,0xbf32c8c9,0x3f273656,0xbf41d870,0x3f15f6d9,0xbf4f7a1f,0x3f039c3d,0xbf5b941a,0x3ee0924f,0xbf660f88,0x3eb8442a,0xbf6ed89e,0x3e8e9a22,0xbf75dec6,
0x3f3daef9,0xbf2beb4a,0x3f2d1469,0xbf3ca003,0x3f1b02c6,0xbf4bbbf8,0x3f07a136,0xbf591e6a,0x3ee63375,0xbf64aa59,0x3ebb31a0,0xbf6e46be,0x3e8e9a22,0xbf75dec6,0x3e419b37,0xbf7b61fc,
0x3f3504f3,0xbf3504f3,0x3f226799,0xbf45e403,0x3f0e39da,0xbf54db31,0x3ef15aea,0xbf61c598,0x3ec3ef15,0xbf6c835e,0x3e94a031,0xbf74fa0b,0x3e47c5c2,0xbf7b14be,0x3dc8bd36,0xbf7ec46d,
0x3f2beb4a,0xbf3daef9,0x3f173c07,0xbf4e8d90,0x3f00e7e4,0xbf5d2d53,0x3ed25a09,0xbf696591,0x3ea09ae5,0xbf731447,0x3e5a3997,0xbf7a1e84,0x3de1bc2e,0xbf7e70b0,0x3bc90f88,0xbf7ffec4,
0x3f226799,0xbf45e403,0x3f0b9a6b,0xbf5695e5,0x3ee63375,0xbf64aa59,0x3eb263ef,0xbf6ff573,0x3e78cfcc,0xbf7853f8,0x3e09cf86,0xbf7dabcc,0x3cc90ab0,0xbf7fec43,0xbdafb680,0xbf7f0e58,
0x3f187fc0,0xbf4d9f02,0x3eff17b2,0xbf5df6be,0x3ec9b953,0xbf6b4b0c,0x3e919ddd,0xbf756d97,0x3e2f10a2,0xbf7c3b28,0x3d621469,0xbf7f9c18,0xbd7b2b74,0xbf7f84ab,0xbe354098,0xbf7bf531,
0x3f0e39da,0xbf54db31,0x3ee63375,0xbf64aa59,0x3eac7cd4,0xbf710908,0x3e605c13,0xbf79c79d,0x3dc8bd36,0xbf7ec46d,0xbcc90ab0,0xbf7fec43,0xbe164083,0xbf7d3aac,0xbe888e93,0xbf76ba07,
0x3f039c3d,0xbf5b941a,0x3ecc9b8b,0xbf6aab7b,0x3e8e9a22,0xbf75dec6,0x3e1c76de,0xbf7cfe73,0x3cc90ab0,0xbf7fec43,0xbdd53db9,0xbf7e9bc9,0xbe6c9a7f,0xbf791298,0xbeb554ec,0xbf6f6830,
0x3ef15aea,0xbf61c598,0x3eb263ef,0xbf6ff573,0x3e605c13,0xbf79c79d,0x3dafb680,0xbf7f0e58,0xbd48fb30,0xbf7fb10f,0xbe3b6ecf,0xbf7baccd,0xbea09ae5,0xbf731447,0xbee0924f,0xbf660f88,
0x3edae880,0xbf676bd8,0x3e97a117,0xbf748422,0x3e22abb6,0xbf7cbfc9,0x3c96c9b6,0xbf7ff4e6,0xbdfab273,0xbf7e1324,0xbe8586ce,0xbf772417,0xbec9b953,0xbf6b4b0c,0xbf04f484,0xbf5ac450,
0x3ec3ef15,0xbf6c835e,0x3e78cfcc,0xbf7853f8,0x3dc8bd36,0xbf7ec46d,0xbd48fb30,0xbf7fb10f,0xbe47c5c2,0xbf7b14be,0xbeac7cd4,0xbf710908,0xbef15aea,0xbf61c598,0xbf187fc0,0xbf4d9f02,
0x3eac7cd4,0xbf710908,0x3e419b37,0xbf7b61fc,0x3d16c32c,0xbf7fd397,0xbdee3876,0xbf7e4323,0xbe888e93,0xbf76ba07,0xbed25a09,0xbf696591,0xbf0b9a6b,0xbf5695e5,0xbf2ac082,0xbf3ebc1b,
0x3e94a031,0xbf74fa0b,0x3e09cf86,0xbf7dabcc,0xbcc90ab0,0xbf7fec43,0xbe3b6ecf,0xbf7baccd,0xbeac7cd4,0xbf710908,0xbef6e0cb,0xbf604621,0xbf1d7fd1,0xbf49d112,0xbf3b8f3b,0xbf2e3bde,
0x3e78cfcc,0xbf7853f8,0x3da3308c,0xbf7f2f9d,0xbdafb680,0xbf7f0e58,0xbe7ee6e1,0xbf77f110,0xbecf7bca,0xbf6a09a7,0xbf0cead0,0xbf55b993,0xbf2e3bde,0xbf3b8f3b,0xbf4ac77f,0xbf1c420c,
0x3e47c5c2,0xbf7b14be,0x3cc90ab0,0xbf7fec43,0xbe164083,0xbf7d3aac,0xbea09ae5,0xbf731447,0xbef15aea,0xbf61c598,0xbf1d7fd1,0xbf49d112,0xbf3daef9,0xbf2beb4a,0xbf584853,0xbf08f59b,
0x3e164083,0xbf7d3aac,0xbcfb49ba,0xbf7fe129,0xbe541501,0xbf7a7302,0xbec1071e,0xbf6d1c1d,0xbf08f59b,0xbf584853,0xbf2d1469,0xbf3ca003,0xbf4bbbf8,0xbf1b02c6,0xbf63f473,0xbee900b7,
0x3dc8bd36,0xbf7ec46d,0xbdafb680,0xbf7f0e58,0xbe888e93,0xbf76ba07,0xbee0924f,0xbf660f88,0xbf187fc0,0xbf4d9f02,0xbf3b8f3b,0xbf2e3bde,0xbf584853,0xbf08f59b,0xbf6db293,0xbebe1d4a,
0x3d48fb30,0xbf7fb10f,0xbe1008b7,0xbf7d7474,0xbea68f12,0xbf721352,0xbeff17b2,0xbf5df6be,0xbf273656,0xbf41d870,0xbf48d8b3,0xbf1ebc12,0xbf633c5a,0xbeebcbbb,0xbf756d97,0xbe919ddd,
0x3f800000,0x0,0x3f800000,0x0,0x3f800000,0x0,0x3f800000,0x0,0x3f800000,0x0,0x3f800000,0x0,0x3f800000,0x0,0x3f800000,0x0,
0x3f7ec46d,0xbdc8bd36,0x3f7e9bc9,0xbdd53db9,0x3f7e70b0,0xbde1bc2e,0x3f7e4323,0xbdee3876,0x3f7e1324,0xbdfab273,0x3f7de0b1,0xbe039502,0x3f7dabcc,0xbe09cf86,0x3f7d7474,0xbe1008b7,
0x3f7b14be,0xbe47c5c2,0x3f7a7302,0xbe541501,0x3f79c79d,0xbe605c13,0x3f791298,0xbe6c9a7f,0x3f7853f8,0xbe78cfcc,0x3f778bc5,0xbe827dc0,0x3f76ba07,0xbe888e93,0x3f75dec6,0xbe8e9a22,
0x3f74fa0b,0xbe94a031,0x3f73913f,0xbe9d9e78,0x3f721352,0xbea68f12,0x3f708066,0xbeaf713a,0x3f6ed89e,0xbeb8442a,0x3f6d1c1d,0xbec1071e,0x3f6b4b0c,0xbec9b953,0x3f696591,0xbed25a09,
0x3f6c835e,0xbec3ef15,0x3f6a09a7,0xbecf7bca,0x3f676bd8,0xbedae880,0x3f64aa59,0xbee63375,0x3f61c598,0xbef15aea,0x3f5ebe05,0xbefc5d27,0x3f5b941a,0xbf039c3d,0x3f584853,0xbf08f59b,
0x3f61c598,0xbef15aea,0x3f5df6be,0xbeff17b2,0x3f59f26a,0xbf064b82,0x3f55b993,0xbf0cead0,0x3f514d3d,0xbf13682a,0x3f4cae79,0xbf19c200,0x3f47de65,0xbf1ff6cb,0x3f42de29,0xbf26050a,
0x3f54db31,0xbf0e39da,0x3f4f7a1f,0xbf15f6d9,0x3f49d112,0xbf1d7fd1,0x3f43e200,0xbf24d225,0x3f3daef9,0xbf2beb4a,0x3f373a23,0xbf32c8c9,0x3f3085bb,0xbf396842,0x3f299415,0xbf3fc767,
0x3f45e403,0xbf226799,0x3f3ebc1b,0xbf2ac082,0x3f373a23,0xbf32c8c9,0x3f2f61a5,0xbf3a7ca4,0x3f273656,0xbf41d870,0x3f1ebc12,0xbf48d8b3,0x3f15f6d9,0xbf4f7a1f,0x3f0cead0,0xbf55b993,
0x3f3504f3,0xbf3504f3,0x3f2beb4a,0xbf3daef9,0x3f226799,0xbf45e403,0x3f187fc0,0xbf4d9f02,0x3f0e39da,0xbf54db31,0x3f039c3d,0xbf5b941a,0x3ef15aea,0xbf61c598,0x3edae880,0xbf676bd8,
0x3f226799,0xbf45e403,0x3f173c07,0xbf4e8d90,0x3f0b9a6b,0xbf5695e5,0x3eff17b2,0xbf5df6be,0x3ee63375,0xbf64aa59,0x3ecc9b8b,0xbf6aab7b,0x3eb263ef,0xbf6ff573,0x3e97a117,0xbf748422,
0x3f0e39da,0xbf54db31,0x3f00e7e4,0xbf5d2d53,0x3ee63375,0xbf64aa59,0x3ec9b953,0xbf6b4b0c,0x3eac7cd4,0xbf710908,0x3e8e9a22,0xbf75dec6,0x3e605c13,0xbf79c79d,0x3e22abb6,0xbf7cbfc9,
0x3ef15aea,0xbf61c598,0x3ed25a09,0xbf696591,0x3eb263ef,0xbf6ff573,0x3e919ddd,0xbf756d97,0x3e605c13,0xbf79c79d,0x3e1c76de,0xbf7cfe73,0x3dafb680,0xbf7f0e58,0x3c96c9b6,0xbf7ff4e6,
0x3ec3ef15,0xbf6c835e,0x3ea09ae5,0xbf731447,0x3e78cfcc,0xbf7853f8,0x3e2f10a2,0xbf7c3b28,0x3dc8bd36,0xbf7ec46d,0x3cc90ab0,0xbf7fec43,0xbd48fb30,0xbf7fb10f,0xbdfab273,0xbf7e1324,
0x3e94a031,0xbf74fa0b,0x3e5a3997,0xbf7a1e84,0x3e09cf86,0xbf7dabcc,0x3d621469,0xbf7f9c18,0xbcc90ab0,0xbf7fec43,0xbdd53db9,0xbf7e9bc9,0xbe3b6ecf,0xbf7baccd,0xbe8586ce,0xbf772417,
0x3e47c5c2,0xbf7b14be,0x3de1bc2e,0xbf7e70b0,0x3cc90ab0,0xbf7fec43,0xbd7b2b74,0xbf7f84ab,0xbe164083,0xbf7d3aac,0xbe6c9a7f,0xbf791298,0xbea09ae5,0xbf731447,0xbec9b953,0xbf6b4b0c,
0x3dc8bd36,0xbf7ec46d,0x3bc90f88,0xbf7ffec4,0xbdafb680,0xbf7f0e58,0xbe354098,0xbf7bf531,0xbe888e93,0xbf76ba07,0xbeb554ec,0xbf6f6830,0xbee0924f,0xbf660f88,0xbf04f484,0xbf5ac450,
0x0,0xbf800000,0xbdc8bd36,0xbf7ec46d,0xbe47c5c2,0xbf7b14be,0xbe94a031,0xbf74fa0b,0xbec3ef15,0xbf6c835e,0xbef15aea,0xbf61c598,0xbf0e39da,0xbf54db31,0xbf226799,0xbf45e403,
0xbdc8bd36,0xbf7ec46d,0xbe4dee60,0xbf7ac516,0xbe9aa086,0xbf740bdd,0xbecc9b8b,0xbf6aab7b,0xbefc5d27,0xbf5ebe05,0xbf14b039,0xbf5064af,0xbf299415,0xbf3fc767,0xbf3ca003,0xbf2d1469,
0xbe47c5c2,0xbf7b14be,0xbe9aa086,0xbf740bdd,0xbecf7bca,0xbf6a09a7,0xbf00e7e4,0xbf5d2d53,0xbf187fc0,0xbf4d9f02,0xbf2e3bde,0xbf3b8f3b,0xbf41d870,0xbf273656,0xbf531849,0xbf10d3cd,
0xbe94a031,0xbf74fa0b,0xbecc9b8b,0xbf6aab7b,0xbf00e7e4,0xbf5d2d53,0xbf19c200,0xbf4cae79,0xbf3085bb,0xbf396842,0xbf44e3f5,0xbf239da9,0xbf5695e5,0xbf0b9a6b,0xbf655e0b,0xbee363fa,
0xbec3ef15,0xbf6c835e,0xbefc5d27,0xbf5ebe05,0xbf187fc0,0xbf4d9f02,0xbf3085bb,0xbf396842,0xbf45e403,0xbf226799,0xbf584853,0xbf08f59b,0xbf676bd8,0xbedae880,0xbf731447,0xbea09ae5,
0xbef15aea,0xbf61c598,0xbf14b039,0xbf5064af,0xbf2e3bde,0xbf3b8f3b,0xbf44e3f5,0xbf239da9,0xbf584853,0xbf08f59b,0xbf6816a8,0xbed8106b,0xbf740bdd,0xbe9aa086,0xbf7bf531,0xbe354098,
0xbf0e39da,0xbf54db31,0xbf299415,0xbf3fc767,0xbf41d870,0xbf273656,0xbf5695e5,0xbf0b9a6b,0xbf676bd8,0xbedae880,0xbf740bdd,0xbe9aa086,0xbf7c3b28,0xbe2f10a2,0xbf7fd397,0xbd16c32c,
0xbf226799,0xbf45e403,0xbf3ca003,0xbf2d1469,0xbf531849,0xbf10d3cd,0xbf655e0b,0xbee363fa,0xbf731447,0xbea09ae5,0xbf7bf531,0xbe354098,0xbf7fd397,0xbd16c32c,0xbf7e9bc9,0x3dd53db9,
0xbf3504f3,0xbf3504f3,0xbf4d9f02,0xbf187fc0,0xbf61c598,0xbef15aea,0xbf710908,0xbeac7cd4,0xbf7b14be,0xbe47c5c2,0xbf7fb10f,0xbd48fb30,0xbf7ec46d,0x3dc8bd36,0xbf7853f8,0x3e78cfcc,
0xbf45e403,0xbf226799,0xbf5c61c7,0xbf0242b1,0xbf6db293,0xbebe1d4a,0xbf796e4e,0xbe667c66,0xbf7f4e6d,0xbd96a905,0xbf7f2f9d,0x3da3308c,0xbf791298,0x3e6c9a7f,0xbf6d1c1d,0x3ec1071e,
0xbf54db31,0xbf0e39da,0xbf68bf3c,0xbed53641,0xbf76ba07,0xbe888e93,0xbf7e70b0,0xbde1bc2e,0xbf7fb10f,0x3d48fb30,0xbf7a7302,0x3e541501,0xbf6ed89e,0x3eb8442a,0xbf5d2d53,0x3f00e7e4,
0xbf61c598,0xbef15aea,0xbf7294f8,0xbea395c5,0xbf7cbfc9,0xbe22abb6,0xbf7ffec4,0x3bc90f88,0xbf7c3b28,0x3e2f10a2,0xbf718f57,0x3ea986c4,0xbf604621,0x3ef6e0cb,0xbf48d8b3,0x3f1ebc12,
0xbf6c835e,0xbec3ef15,0xbf79c79d,0xbe605c13,0xbf7fb10f,0xbd48fb30,0xbf7e1324,0x3dfab273,0xbf74fa0b,0x3e94a031,0xbf64aa59,0x3ee63375,0xbf4d9f02,0x3f187fc0,0xbf3085bb,0x3f396842,
0xbf74fa0b,0xbe94a031,0xbf7e4323,0xbdee3876,0xbf7f84ab,0x3d7b2b74,0xbf78b47b,0x3e72b651,0xbf6a09a7,0x3ecf7bca,0xbf53fac3,0x3f0f8784,0xbf373a23,0x3f32c8c9,0xbf14b039,0x3f5064af,
0xbf7b14be,0xbe47c5c2,0xbf7ffb11,0xbc490e90,0xbf7c3b28,0x3e2f10a2,0xbf6ff573,0x3eb263ef,0xbf5b941a,0x3f039c3d,0xbf3fc767,0x3f299415,0xbf1d7fd1,0x3f49d112,0xbeebcbbb,0x3f633c5a,
0xbf7ec46d,0xbdc8bd36,0xbf7eea9d,0x3dbc3ac3,0xbf75dec6,0x3e8e9a22,0xbf63f473,0x3ee900b7,0xbf49d112,0x3f1d7fd1,0xbf286605,0x3f40d0da,0xbf00e7e4,0x3f5d2d53,0xbea986c4,0x3f718f57,
0x3f800000,0x0,0x3f800000,0x0,0x3f800000,0x0,0x3f800000,0x0,0x3f800000,0x0,0x3f800000,0x0,0x3f800000,0x0,0x3f800000,0x0,
0x3f7d3aac,0xbe164083,0x3f7cfe73,0xbe1c76de,0x3f7cbfc9,0xbe22abb6,0x3f7c7eb0,0xbe28defc,0x3f7c3b28,0xbe2f10a2,0x3f7bf531,0xbe354098,0x3f7baccd,0xbe3b6ecf,0x3f7b61fc,0xbe419b37,
0x3f74fa0b,0xbe94a031,0x3f740bdd,0xbe9aa086,0x3f731447,0xbea09ae5,0x3f721352,0xbea68f12,0x3f710908,0xbeac7cd4,0x3f6ff573,0xbeb263ef,0x3f6ed89e,0xbeb8442a,0x3f6db293,0xbebe1d4a,
0x3f676bd8,0xbedae880,0x3f655e0b,0xbee363fa,0x3f633c5a,0xbeebcbbb,0x3f6106f2,0xbef41f07,0x3f5ebe05,0xbefc5d27,0x3f5c61c7,0xbf0242b1,0x3f59f26a,0xbf064b82,0x3f577026,0xbf0a48ad,
0x3f54db31,0xbf0e39da,0x3f514d3d,0xbf13682a,0x3f4d9f02,0xbf187fc0,0x3f49d112,0xbf1d7fd1,0x3f45e403,0xbf226799,0x3f41d870,0xbf273656,0x3f3daef9,0xbf2beb4a,0x3f396842,0xbf3085bb,
0x3f3daef9,0xbf2beb4a,0x3f385216,0xbf31a81d,0x3f32c8c9,0xbf373a23,0x3f2d1469,0xbf3ca003,0x3f273656,0xbf41d870,0x3f212ff9,0xbf46e22a,0x3f1b02c6,0xbf4bbbf8,0x3f14b039,0xbf5064af,
0x3f226799,0xbf45e403,0x3f1b02c6,0xbf4bbbf8,0x3f13682a,0xbf514d3d,0x3f0b9a6b,0xbf5695e5,0x3f039c3d,0xbf5b941a,0x3ef6e0cb,0xbf604621,0x3ee63375,0xbf64aa59,0x3ed53641,0xbf68bf3c,
0x3f039c3d,0xbf5b941a,0x3ef41f07,0xbf6106f2,0x3ee0924f,0xbf660f88,0x3ecc9b8b,0xbf6aab7b,0x3eb8442a,0xbf6ed89e,0x3ea395c5,0xbf7294f8,0x3e8e9a22,0xbf75dec6,0x3e72b651,0xbf78b47b,
0x3ec3ef15,0xbf6c835e,0x3eac7cd4,0xbf710908,0x3e94a031,0xbf74fa0b,0x3e78cfcc,0xbf7853f8,0x3e47c5c2,0xbf7b14be,0x3e164083,0xbf7d3aac,0x3dc8bd36,0xbf7ec46d,0x3d48fb30,0xbf7fb10f,
0x3e78cfcc,0xbf7853f8,0x3e419b37,0xbf7b61fc,0x3e09cf86,0xbf7dabcc,0x3da3308c,0xbf7f2f9d,0x3cc90ab0,0xbf7fec43,0xbcfb49ba,0xbf7fe129,0xbdafb680,0xbf7f0e58,0xbe1008b7,0xbf7d7474,
0x3dc8bd36,0xbf7ec46d,0x3d16c32c,0xbf7fd397,0xbcc90ab0,0xbf7fec43,0xbdafb680,0xbf7f0e58,0xbe164083,0xbf7d3aac,0xbe541501,0xbf7a7302,0xbe888e93,0xbf76ba07,0xbea68f12,0xbf721352,
0xbd48fb30,0xbf7fb10f,0xbdee3876,0xbf7e4323,0xbe3b6ecf,0xbf7baccd,0xbe7ee6e1,0xbf77f110,0xbea09ae5,0xbf731447,0xbec1071e,0xbf6d1c1d,0xbee0924f,0xbf660f88,0xbeff17b2,0xbf5df6be,
0xbe47c5c2,0xbf7b14be,0xbe888e93,0xbf76ba07,0xbeac7cd4,0xbf710908,0xbecf7bca,0xbf6a09a7,0xbef15aea,0xbf61c598,0xbf08f59b,0xbf584853,0xbf187fc0,0xbf4d9f02,0xbf273656,0xbf41d870,
0xbeac7cd4,0xbf710908,0xbed25a09,0xbf696591,0xbef6e0cb,0xbf604621,0xbf0cead0,0xbf55b993,0xbf1d7fd1,0xbf49d112,0xbf2d1469,0xbf3ca003,0xbf3b8f3b,0xbf2e3bde,0xbf48d8b3,0xbf1ebc12,
0xbef15aea,0xbf61c598,0xbf0b9a6b,0xbf5695e5,0xbf1d7fd1,0xbf49d112,0xbf2e3bde,0xbf3b8f3b,0xbf3daef9,0xbf2beb4a,0xbf4bbbf8,0xbf1b02c6,0xbf584853,0xbf08f59b,0xbf633c5a,0xbeebcbbb,
0xbf187fc0,0xbf4d9f02,0xbf2ac082,0xbf3ebc1b,0xbf3b8f3b,0xbf2e3bde,0xbf4ac77f,0xbf1c420c,0xbf584853,0xbf08f59b,0xbf63f473,0xbee900b7,0xbf6db293,0xbebe1d4a,0xbf756d97,0xbe919ddd,
0xbf3504f3,0xbf3504f3,0xbf45e403,0xbf226799,0xbf54db31,0xbf0e39da,0xbf61c598,0xbef15aea,0xbf6c835e,0xbec3ef15,0xbf74fa0b,0xbe94a031,0xbf7b14be,0xbe47c5c2,0xbf7ec46d,0xbdc8bd36,
0xbf4d9f02,0xbf187fc0,0xbf5c61c7,0xbf0242b1,0xbf68bf3c,0xbed53641,0xbf7294f8,0xbea395c5,0xbf79c79d,0xbe605c13,0xbf7e4323,0xbdee3876,0xbf7ffb11,0xbc490e90,0xbf7eea9d,0x3dbc3ac3,
0xbf61c598,0xbef15aea,0xbf6db293,0xbebe1d4a,0xbf76ba07,0xbe888e93,0xbf7cbfc9,0xbe22abb6,0xbf7fb10f,0xbd48fb30,0xbf7f84ab,0x3d7b2b74,0xbf7c3b28,0x3e2f10a2,0xbf75dec6,0x3e8e9a22,
0xbf710908,0xbeac7cd4,0xbf796e4e,0xbe667c66,0xbf7e70b0,0xbde1bc2e,0xbf7ffec4,0x3bc90f88,0xbf7e1324,0x3dfab273,0xbf78b47b,0x3e72b651,0xbf6ff573,0x3eb263ef,0xbf63f473,0x3ee900b7,
0xbf7b14be,0xbe47c5c2,0xbf7f4e6d,0xbd96a905,0xbf7fb10f,0x3d48fb30,0xbf7c3b28,0x3e2f10a2,0xbf74fa0b,0x3e94a031,0xbf6a09a7,0x3ecf7bca,0xbf5b941a,0x3f039c3d,0xbf49d112,0x3f1d7fd1,
0xbf7fb10f,0xbd48fb30,0xbf7f2f9d,0x3da3308c,0xbf7a7302,0x3e541501,0xbf718f57,0x3ea986c4,0xbf64aa59,0x3ee63375,0xbf53fac3,0x3f0f8784,0xbf3fc767,0x3f299415,0xbf286605,0x3f40d0da,
0xbf7ec46d,0x3dc8bd36,0xbf791298,0x3e6c9a7f,0xbf6ed89e,0x3eb8442a,0xbf604621,0x3ef6e0cb,0xbf4d9f02,0x3f187fc0,0xbf373a23,0x3f32c8c9,0xbf1d7fd1,0x3f49d112,0xbf00e7e4,0x3f5d2d53,
0xbf7853f8,0x3e78cfcc,0xbf6d1c1d,0x3ec1071e,0xbf5d2d53,0x3f00e7e4,0xbf48d8b3,0x3f1ebc12,0xbf3085bb,0x3f396842,0xbf14b039,0x3f5064af,0xbeebcbbb,0x3f633c5a,0xbea986c4,0x3f718f57,
0xbf6c835e,0x3ec3ef15,0xbf5b941a,0x3f039c3d,0xbf45e403,0x3f226799,0xbf2beb4a,0x3f3daef9,0xbf0e39da,0x3f54db31,0xbedae880,0x3f676bd8,0xbe94a031,0x3f74fa0b,0xbe164083,0x3f7d3aac,
0xbf5b941a,0x3f039c3d,0xbf44e3f5,0x3f239da9,0xbf299415,0x3f3fc767,0xbf0a48ad,0x3f577026,0xbecf7bca,0x3f6a09a7,0xbe8586ce,0x3f772417,0xbde1bc2e,0x3f7e70b0,0x3d2fe007,0x3f7fc38f,
0xbf45e403,0x3f226799,0xbf299415,0x3f3fc767,0xbf08f59b,0x3f584853,0xbec9b953,0x3f6b4b0c,0xbe78cfcc,0x3f7853f8,0xbdafb680,0x3f7f0e58,0x3d96a905,0x3f7f4e6d,0x3e6c9a7f,0x3f791298,
0xbf2beb4a,0x3f3daef9,0xbf0a48ad,0x3f577026,0xbec9b953,0x3f6b4b0c,0xbe72b651,0x3f78b47b,0xbd96a905,0x3f7f4e6d,0x3dbc3ac3,0x3f7eea9d,0x3e827dc0,0x3f778bc5,0x3ed25a09,0x3f696591,
0xbf0e39da,0x3f54db31,0xbecf7bca,0x3f6a09a7,0xbe78cfcc,0x3f7853f8,0xbd96a905,0x3f7f4e6d,0x3dc8bd36,0x3f7ec46d,0x3e888e93,0x3f76ba07,0x3edae880,0x3f676bd8,0x3f13682a,0x3f514d3d,
0xbedae880,0x3f676bd8,0xbe8586ce,0x3f772417,0xbdafb680,0x3f7f0e58,0x3dbc3ac3,0x3f7eea9d,0x3e888e93,0x3f76ba07,0x3eddbe79,0x3f66becc,0x3f15f6d9,0x3f4f7a1f,0x3f385216,0x3f31a81d,
0xbe94a031,0x3f74fa0b,0xbde1bc2e,0x3f7e70b0,0x3d96a905,0x3f7f4e6d,0x3e827dc0,0x3f778bc5,0x3edae880,0x3f676bd8,0x3f15f6d9,0x3f4f7a1f,0x3f396842,0x3f3085bb,0x3f5695e5,0x3f0b9a6b,
0xbe164083,0x3f7d3aac,0x3d2fe007,0x3f7fc38f,0x3e6c9a7f,0x3f791298,0x3ed25a09,0x3f696591,0x3f13682a,0x3f514d3d,0x3f385216,0x3f31a81d,0x3f5695e5,0x3f0b9a6b,0x3f6d1c1d,0x3ec1071e,
0xbd803d80,0x80003e00,0x80003e00,0x80003e00,0x80003e00,0x80003e00,0x80003e00,0x80003e00,0x80003e00,0x80003e00,0x80003e00,0x80003e00,0x80003e00,0x80003e00,0x80003e00,0x80003e00,
0x3d803d80,0x3cc83dfb,0x3e000000,0x3dfbbcc8,0x3d443ded,0x3d8e3dd5,0x3dedbd44,0x3dd5bd8e,0x3db53db5,0x3dd53d8e,0x3db5bdb5,0x3d8ebdd5,0x3ded3d44,0x3dfb3cc8,0x3d44bded,0x3cc8bdfb,
0xbd803d80,0x3d443ded,0x8000be00,0xbd44bded,0x3db53db5,0x3ded3d44,0xbdb5bdb5,0xbdedbd44,0x3e000000,0x3dedbd44,0xbe000000,0xbded3d44,0x3db5bdb5,0x3d44bded,0xbdb53db5,0xbd443ded,
0x3d803d80,0x3d8e3dd5,0xbe000000,0xbdd53d8e,0x3ded3d44,0x3dfbbcc8,0xbd443ded,0x3cc83dfb,0x3db5bdb5,0x3cc8bdfb,0x3db53db5,0x3dfb3cc8,0xbd44bded,0xbdd5bd8e,0x3dedbd44,0x3d8ebdd5,
0xbd803d80,0x3db53db5,0x80003e00,0x3db53db5,0x3e000000,0x3db5bdb5,0x3e000000,0x3db5bdb5,0x8000be00,0xbdb5bdb5,0x8000be00,0xbdb5bdb5,0xbe000000,0xbdb53db5,0xbe000000,0xbdb53db5,
0x3d803d80,0x3dd53d8e,0x3e000000,0x3d8ebdd5,0x3dedbd44,0x3cc8bdfb,0xbd44bded,0xbdfbbcc8,0xbdb5bdb5,0xbdfb3cc8,0xbdb53db5,0x3cc83dfb,0xbd443ded,0x3d8e3dd5,0x3ded3d44,0x3dd5bd8e,
0xbd803d80,0x3ded3d44,0x8000be00,0xbdedbd44,0x3db5bdb5,0xbd44bded,0xbdb53db5,0x3d443ded,0xbe000000,0xbd443ded,0x3e000000,0x3d44bded,0x3db53db5,0x3dedbd44,0xbdb5bdb5,0xbded3d44,
0x3d803d80,0x3dfb3cc8,0xbe000000,0xbcc83dfb,0x3d44bded,0xbdd5bd8e,0x3ded3d44,0x3d8ebdd5,0xbdb53db5,0x3d8e3dd5,0xbdb5bdb5,0xbdd53d8e,0x3dedbd44,0xbcc8bdfb,0x3d443ded,0x3dfbbcc8,
0xbd803d80,0x3e000000,0x80003e00,0x3e000000,0x8000be00,0xbe000000,0x8000be00,0xbe000000,0x80003e00,0x3e000000,0x80003e00,0x3e000000,0x8000be00,0xbe000000,0x8000be00,0xbe000000,
0x3d803d80,0x3dfbbcc8,0x3e000000,0xbcc8bdfb,0xbd44bded,0xbdd53d8e,0xbded3d44,0x3d8e3dd5,0x3db53db5,0x3d8ebdd5,0x3db5bdb5,0xbdd5bd8e,0xbdedbd44,0xbcc83dfb,0xbd443ded,0x3dfb3cc8,
0xbd803d80,0x3dedbd44,0x8000be00,0xbded3d44,0xbdb5bdb5,0xbd443ded,0x3db53db5,0x3d44bded,0x3e000000,0xbd44bded,0xbe000000,0x3d443ded,0xbdb53db5,0x3ded3d44,0x3db5bdb5,0xbdedbd44,
0x3d803d80,0x3dd5bd8e,0xbe000000,0x3d8e3dd5,0xbdedbd44,0x3cc83dfb,0x3d44bded,0xbdfb3cc8,0x3db5bdb5,0xbdfbbcc8,0x3db53db5,0x3cc8bdfb,0x3d443ded,0x3d8ebdd5,0xbded3d44,0x3dd53d8e,
0xbd803d80,0x3db5bdb5,0x80003e00,0x3db5bdb5,0xbe000000,0x3db53db5,0xbe000000,0x3db53db5,0x8000be00,0xbdb53db5,0x8000be00,0xbdb53db5,0x3e000000,0xbdb5bdb5,0x3e000000,0xbdb5bdb5,
0x3d803d80,0x3d8ebdd5,0x3e000000,0xbdd5bd8e,0xbded3d44,0x3dfb3cc8,0x3d443ded,0x3cc8bdfb,0xbdb5bdb5,0x3cc83dfb,0xbdb53db5,0x3dfbbcc8,0x3d44bded,0xbdd53d8e,0xbdedbd44,0x3d8e3dd5,
0xbd803d80,0x3d44bded,0x8000be00,0xbd443ded,0xbdb53db5,0x3dedbd44,0x3db5bdb5,0xbded3d44,0xbe000000,0x3ded3d44,0x3e000000,0xbdedbd44,0xbdb5bdb5,0x3d443ded,0x3db53db5,0xbd44bded,
0x3d803d80,0x3cc8bdfb,0xbe000000,0x3dfb3cc8,0xbd443ded,0x3d8ebdd5,0xbdedbd44,0x3dd53d8e,0xbdb53db5,0x3dd5bd8e,0xbdb5bdb5,0x3d8e3dd5,0xbded3d44,0x3dfbbcc8,0xbd44bded,0x3cc83dfb,
0xbd803d80,0x8000be00,0x80003e00,0x8000be00,0x80003e00,0x8000be00,0x80003e00,0x8000be00,0x80003e00,0x8000be00,0x80003e00,0x8000be00,0x80003e00,0x8000be00,0x80003e00,0x8000be00,
0x3d803d80,0xbcc8bdfb,0x3e000000,0xbdfb3cc8,0x3d443ded,0xbd8ebdd5,0x3dedbd44,0xbdd53d8e,0x3db53db5,0xbdd5bd8e,0x3db5bdb5,0xbd8e3dd5,0x3ded3d44,0xbdfbbcc8,0x3d44bded,0xbcc83dfb,
0xbd803d80,0xbd44bded,0x8000be00,0x3d443ded,0x3db53db5,0xbdedbd44,0xbdb5bdb5,0x3ded3d44,0x3e000000,0xbded3d44,0xbe000000,0x3dedbd44,0x3db5bdb5,0xbd443ded,0xbdb53db5,0x3d44bded,
0x3d803d80,0xbd8ebdd5,0xbe000000,0x3dd5bd8e,0x3ded3d44,0xbdfb3cc8,0xbd443ded,0xbcc8bdfb,0x3db5bdb5,0xbcc83dfb,0x3db53db5,0xbdfbbcc8,0xbd44bded,0x3dd53d8e,0x3dedbd44,0xbd8e3dd5,
0xbd803d80,0xbdb5bdb5,0x80003e00,0xbdb5bdb5,0x3e000000,0xbdb53db5,0x3e000000,0xbdb53db5,0x8000be00,0x3db53db5,0x8000be00,0x3db53db5,0xbe000000,0x3db5bdb5,0xbe000000,0x3db5bdb5,
0x3d803d80,0xbdd5bd8e,0x3e000000,0xbd8e3dd5,0x3dedbd44,0xbcc83dfb,0xbd44bded,0x3dfb3cc8,0xbdb5bdb5,0x3dfbbcc8,0xbdb53db5,0xbcc8bdfb,0xbd443ded,0xbd8ebdd5,0x3ded3d44,0xbdd53d8e,
0xbd803d80,0xbdedbd44,0x8000be00,0x3ded3d44,0x3db5bdb5,0x3d443ded,0xbdb53db5,0xbd44bded,0xbe000000,0x3d44bded,0x3e000000,0xbd443ded,0x3db53db5,0xbded3d44,0xbdb5bdb5,0x3dedbd44,
0x3d803d80,0xbdfbbcc8,0xbe000000,0x3cc8bdfb,0x3d44bded,0x3dd53d8e,0x3ded3d44,0xbd8e3dd5,0xbdb53db5,0xbd8ebdd5,0xbdb5bdb5,0x3dd5bd8e,0x3dedbd44,0x3cc83dfb,0x3d443ded,0xbdfb3cc8,
0xbd803d80,0xbe000000,0x80003e00,0xbe000000,0x8000be00,0x3e000000,0x8000be00,0x3e000000,0x80003e00,0xbe000000,0x80003e00,0xbe000000,0x8000be00,0x3e000000,0x8000be00,0x3e000000,
0x3d803d80,0xbdfb3cc8,0x3e000000,0x3cc83dfb,0xbd44bded,0x3dd5bd8e,0xbded3d44,0xbd8ebdd5,0x3db53db5,0xbd8e3dd5,0x3db5bdb5,0x3dd53d8e,0xbdedbd44,0x3cc8bdfb,0xbd443ded,0xbdfbbcc8,
0xbd803d80,0xbded3d44,0x8000be00,0x3dedbd44,0xbdb5bdb5,0x3d44bded,0x3db53db5,0xbd443ded,0x3e000000,0x3d443ded,0xbe000000,0xbd44bded,0xbdb53db5,0xbdedbd44,0x3db5bdb5,0x3ded3d44,
0x3d803d80,0xbdd53d8e,0xbe000000,0xbd8ebdd5,0xbdedbd44,0xbcc8bdfb,0x3d44bded,0x3dfbbcc8,0x3db5bdb5,0x3dfb3cc8,0x3db53db5,0xbcc83dfb,0x3d443ded,0xbd8e3dd5,0xbded3d44,0xbdd5bd8e,
0xbd803d80,0xbdb53db5,0x80003e00,0xbdb53db5,0xbe000000,0xbdb5bdb5,0xbe000000,0xbdb5bdb5,0x8000be00,0x3db5bdb5,0x8000be00,0x3db5bdb5,0x3e000000,0x3db53db5,0x3e000000,0x3db53db5,
0x3d803d80,0xbd8e3dd5,0x3e000000,0x3dd53d8e,0xbded3d44,0xbdfbbcc8,0x3d443ded,0xbcc83dfb,0xbdb5bdb5,0xbcc8bdfb,0xbdb53db5,0xbdfb3cc8,0x3d44bded,0x3dd5bd8e,0xbdedbd44,0xbd8ebdd5,
0xbd803d80,0xbd443ded,0x8000be00,0x3d44bded,0xbdb53db5,0xbded3d44,0x3db5bdb5,0x3dedbd44,0xbe000000,0xbdedbd44,0x3e000000,0x3ded3d44,0xbdb5bdb5,0xbd44bded,0x3db53db5,0x3d443ded,
0x3d803d80,0xbcc83dfb,0xbe000000,0xbdfbbcc8,0xbd443ded,0xbd8e3dd5,0xbdedbd44,0xbdd5bd8e,0xbdb53db5,0xbdd53d8e,0xbdb5bdb5,0xbd8ebdd5,0xbded3d44,0xbdfb3cc8,0xbd44bded,0xbcc8bdfb,
0x80003e00,0x80003e00,0x80003e00,0x80003e00,0x80003e00,0x80003e00,0x80003e00,0x80003e00,0x80003e00,0x80003e00,0x80003e00,0x80003e00,0x80003e00,0x80003e00,0x80003e00,0x80003e00,
0x3c493dff,0x3d153df5,0x3dffbc49,0x3df5bd15,0x3d713de2,0x3da23dc6,0x3de2bd71,0x3dc6bda2,0x3dc63da2,0x3de23d71,0x3da2bdc6,0x3d71bde2,0x3df53d15,0x3dff3c49,0x3d15bdf5,0x3c49bdff,
0x3cc83dfb,0x3d8e3dd5,0xbcc8bdfb,0xbd8ebdd5,0x3dd53d8e,0x3dfb3cc8,0xbdd5bd8e,0xbdfbbcc8,0x3dfbbcc8,0x3dd5bd8e,0xbdfb3cc8,0xbdd53d8e,0x3d8ebdd5,0x3cc8bdfb,0xbd8e3dd5,0xbcc83dfb,
0x3d153df5,0x3dc63da2,0xbdf53d15,0xbda23dc6,0x3dff3c49,0x3de2bd71,0xbc493dff,0x3d713de2,0x3d71bde2,0xbc49bdff,0x3de23d71,0x3dffbc49,0xbda2bdc6,0xbdf5bd15,0x3dc6bda2,0x3d15bdf5,
0x3d443ded,0x3ded3d44,0x3d443ded,0x3ded3d44,0x3dedbd44,0x3d44bded,0x3dedbd44,0x3d44bded,0xbd44bded,0xbdedbd44,0xbd44bded,0xbdedbd44,0xbded3d44,0xbd443ded,0xbded3d44,0xbd443ded,
0x3d713de2,0x3dff3c49,0x3de2bd71,0x3c49bdff,0x3da2bdc6,0xbd15bdf5,0xbdc6bda2,0xbdf53d15,0xbdf5bd15,0xbdc63da2,0xbd153df5,0x3da23dc6,0x3c493dff,0x3de23d71,0x3dffbc49,0x3d71bde2,
0x3d8e3dd5,0x3dfbbcc8,0xbd8ebdd5,0xbdfb3cc8,0x3cc8bdfb,0xbdd5bd8e,0xbcc83dfb,0x3dd53d8e,0xbdd53d8e,0x3cc83dfb,0x3dd5bd8e,0xbcc8bdfb,0x3dfb3cc8,0x3d8ebdd5,0xbdfbbcc8,0xbd8e3dd5,
0x3da23dc6,0x3de2bd71,0xbdc63da2,0x3d713de2,0xbd15bdf5,0xbdff3c49,0x3df5bd15,0xbc49bdff,0xbc493dff,0x3df53d15,0xbdffbc49,0xbd153df5,0x3d71bde2,0xbdc6bda2,0x3de23d71,0x3da2bdc6,
0x3db53db5,0x3db5bdb5,0x3db53db5,0x3db5bdb5,0xbdb5bdb5,0xbdb53db5,0xbdb5bdb5,0xbdb53db5,0x3db53db5,0x3db5bdb5,0x3db53db5,0x3db5bdb5,0xbdb5bdb5,0xbdb53db5,0xbdb5bdb5,0xbdb53db5,
0x3dc63da2,0x3d71bde2,0x3da2bdc6,0xbde2bd71,0xbdf5bd15,0xbc493dff,0xbd153df5,0x3dff3c49,0x3dffbc49,0xbd15bdf5,0xbc49bdff,0xbdf53d15,0xbde23d71,0x3da23dc6,0x3d713de2,0x3dc6bda2,
0x3dd53d8e,0x3cc8bdfb,0xbdd5bd8e,0xbcc83dfb,0xbdfb3cc8,0x3d8e3dd5,0x3dfbbcc8,0xbd8ebdd5,0x3d8ebdd5,0xbdfbbcc8,0xbd8e3dd5,0x3dfb3cc8,0x3cc83dfb,0x3dd5bd8e,0xbcc8bdfb,0xbdd53d8e,
0x3de23d71,0xbc49bdff,0xbd713de2,0x3dffbc49,0xbdc63da2,0x3df53d15,0xbda2bdc6,0xbd153df5,0xbd15bdf5,0xbda23dc6,0x3df5bd15,0xbdc6bda2,0x3dff3c49,0xbd71bde2,0xbc493dff,0x3de2bd71,
0x3ded3d44,0xbd44bded,0x3ded3d44,0xbd44bded,0xbd443ded,0x3dedbd44,0xbd443ded,0x3dedbd44,0xbdedbd44,0x3d443ded,0xbdedbd44,0x3d443ded,0x3d44bded,0xbded3d44,0x3d44bded,0xbded3d44,
0x3df53d15,0xbda2bdc6,0x3d15bdf5,0xbdc63da2,0x3c493dff,0x3d71bde2,0x3dffbc49,0xbde2bd71,0xbde23d71,0x3dff3c49,0x3d713de2,0x3c49bdff,0xbdc6bda2,0x3d153df5,0xbda23dc6,0x3df5bd15,
0x3dfb3cc8,0xbdd5bd8e,0xbdfbbcc8,0x3dd53d8e,0x3d8e3dd5,0xbcc8bdfb,0xbd8ebdd5,0x3cc83dfb,0xbcc83dfb,0x3d8ebdd5,0x3cc8bdfb,0xbd8e3dd5,0xbdd53d8e,0x3dfbbcc8,0x3dd5bd8e,0xbdfb3cc8,
0x3dff3c49,0xbdf5bd15,0xbc493dff,0x3d15bdf5,0x3de23d71,0xbdc6bda2,0xbd713de2,0x3da2bdc6,0x3da23dc6,0xbd71bde2,0xbdc63da2,0x3de2bd71,0x3d153df5,0xbc49bdff,0xbdf53d15,0x3dffbc49,
0x3e000000,0xbe000000,0x3e000000,0xbe000000,0x3e000000,0xbe000000,0x3e000000,0xbe000000,0x3e000000,0xbe000000,0x3e000000,0xbe000000,0x3e000000,0xbe000000,0x3e000000,0xbe000000,
0x3dffbc49,0xbdf53d15,0xbc49bdff,0x3d153df5,0x3de2bd71,0xbdc63da2,0xbd71bde2,0x3da23dc6,0x3da2bdc6,0xbd713de2,0xbdc6bda2,0x3de23d71,0x3d15bdf5,0xbc493dff,0xbdf5bd15,0x3dff3c49,
0x3dfbbcc8,0xbdd53d8e,0xbdfb3cc8,0x3dd5bd8e,0x3d8ebdd5,0xbcc83dfb,0xbd8e3dd5,0x3cc8bdfb,0xbcc8bdfb,0x3d8e3dd5,0x3cc83dfb,0xbd8ebdd5,0xbdd5bd8e,0x3dfb3cc8,0x3dd53d8e,0xbdfbbcc8,
0x3df5bd15,0xbda23dc6,0x3d153df5,0xbdc6bda2,0x3c49bdff,0x3d713de2,0x3dff3c49,0xbde23d71,0xbde2bd71,0x3dffbc49,0x3d71bde2,0x3c493dff,0xbdc63da2,0x3d15bdf5,0xbda2bdc6,0x3df53d15,
0x3dedbd44,0xbd443ded,0x3dedbd44,0xbd443ded,0xbd44bded,0x3ded3d44,0xbd44bded,0x3ded3d44,0xbded3d44,0x3d44bded,0xbded3d44,0x3d44bded,0x3d443ded,0xbdedbd44,0x3d443ded,0xbdedbd44,
0x3de2bd71,0xbc493dff,0xbd71bde2,0x3dff3c49,0xbdc6bda2,0x3df5bd15,0xbda23dc6,0xbd15bdf5,0xbd153df5,0xbda2bdc6,0x3df53d15,0xbdc63da2,0x3dffbc49,0xbd713de2,0xbc49bdff,0x3de23d71,
0x3dd5bd8e,0x3cc83dfb,0xbdd53d8e,0xbcc8bdfb,0xbdfbbcc8,0x3d8ebdd5,0x3dfb3cc8,0xbd8e3dd5,0x3d8e3dd5,0xbdfb3cc8,0xbd8ebdd5,0x3dfbbcc8,0x3cc8bdfb,0x3dd53d8e,0xbcc83dfb,0xbdd5bd8e,
0x3dc6bda2,0x3d713de2,0x3da23dc6,0xbde23d71,0xbdf53d15,0xbc49bdff,0xbd15bdf5,0x3dffbc49,0x3dff3c49,0xbd153df5,0xbc493dff,0xbdf5bd15,0xbde2bd71,0x3da2bdc6,0x3d71bde2,0x3dc63da2,
0x3db5bdb5,0x3db53db5,0x3db5bdb5,0x3db53db5,0xbdb53db5,0xbdb5bdb5,0xbdb53db5,0xbdb5bdb5,0x3db5bdb5,0x3db53db5,0x3db5bdb5,0x3db53db5,0xbdb53db5,0xbdb5bdb5,0xbdb53db5,0xbdb5bdb5,
0x3da2bdc6,0x3de23d71,0xbdc6bda2,0x3d71bde2,0xbd153df5,0xbdffbc49,0x3df53d15,0xbc493dff,0xbc49bdff,0x3df5bd15,0xbdff3c49,0xbd15bdf5,0x3d713de2,0xbdc63da2,0x3de2bd71,0x3da23dc6,
0x3d8ebdd5,0x3dfb3cc8,0xbd8e3dd5,0xbdfbbcc8,0x3cc83dfb,0xbdd53d8e,0xbcc8bdfb,0x3dd5bd8e,0xbdd5bd8e,0x3cc8bdfb,0x3dd53d8e,0xbcc83dfb,0x3dfbbcc8,0x3d8e3dd5,0xbdfb3cc8,0xbd8ebdd5,
0x3d71bde2,0x3dffbc49,0x3de23d71,0x3c493dff,0x3da23dc6,0xbd153df5,0xbdc63da2,0xbdf5bd15,0xbdf53d15,0xbdc6bda2,0xbd15bdf5,0x3da2bdc6,0x3c49bdff,0x3de2bd71,0x3dff3c49,0x3d713de2,
0x3d44bded,0x3dedbd44,0x3d44bded,0x3dedbd44,0x3ded3d44,0x3d443ded,0x3ded3d44,0x3d443ded,0xbd443ded,0xbded3d44,0xbd443ded,0xbded3d44,0xbdedbd44,0xbd44bded,0xbdedbd44,0xbd44bded,
0x3d15bdf5,0x3dc6bda2,0xbdf5bd15,0xbda2bdc6,0x3dffbc49,0x3de23d71,0xbc49bdff,0x3d71bde2,0x3d713de2,0xbc493dff,0x3de2bd71,0x3dff3c49,0xbda23dc6,0xbdf53d15,0x3dc63da2,0x3d153df5,
0x3cc8bdfb,0x3d8ebdd5,0xbcc83dfb,0xbd8e3dd5,0x3dd5bd8e,0x3dfbbcc8,0xbdd53d8e,0xbdfb3cc8,0x3dfb3cc8,0x3dd53d8e,0xbdfbbcc8,0xbdd5bd8e,0x3d8e3dd5,0x3cc83dfb,0xbd8ebdd5,0xbcc8bdfb,
0x3c49bdff,0x3d15bdf5,0x3dff3c49,0x3df53d15,0x3d71bde2,0x3da2bdc6,0x3de23d71,0x3dc63da2,0x3dc6bda2,0x3de2bd71,0x3da23dc6,0x3d713de2,0x3df5bd15,0x3dffbc49,0x3d153df5,0x3c493dff,
0x3f800000,0x0,0x3f800000,0x0,0x3f800000,0x0,0x3f800000,0x0,0x3f800000,0x0,0x3f800000,0x0,0x3f800000,0x0,0x3f800000,0x0,
0x3f800000,0x0,0x3f7ffb11,0xbc490e90,0x3f7fec43,0xbcc90ab0,0x3f7fd397,0xbd16c32c,0x3f7fb10f,0xbd48fb30,0x3f7f84ab,0xbd7b2b74,0x3f7f4e6d,0xbd96a905,0x3f7f0e58,0xbdafb680,
0x3f800000,0x0,0x3f7fec43,0xbcc90ab0,0x3f7fb10f,0xbd48fb30,0x3f7f4e6d,0xbd96a905,0x3f7ec46d,0xbdc8bd36,0x3f7e1324,0xbdfab273,0x3f7d3aac,0xbe164083,0x3f7c3b28,0xbe2f10a2,
0x3f800000,0x0,0x3f7fd397,0xbd16c32c,0x3f7f4e6d,0xbd96a905,0x3f7e70b0,0xbde1bc2e,0x3f7d3aac,0xbe164083,0x3f7baccd,0xbe3b6ecf,0x3f79c79d,0xbe605c13,0x3f778bc5,0xbe827dc0,
0x3f800000,0x0,0x3f7fb10f,0xbd48fb30,0x3f7ec46d,0xbdc8bd36,0x3f7d3aac,0xbe164083,0x3f7b14be,0xbe47c5c2,0x3f7853f8,0xbe78cfcc,0x3f74fa0b,0xbe94a031,0x3f710908,0xbeac7cd4,
0x3f800000,0x0,0x3f7f84ab,0xbd7b2b74,0x3f7e1324,0xbdfab273,0x3f7baccd,0xbe3b6ecf,0x3f7853f8,0xbe78cfcc,0x3f740bdd,0xbe9aa086,0x3f6ed89e,0xbeb8442a,0x3f68bf3c,0xbed53641,
0x3f800000,0x0,0x3f7f4e6d,0xbd96a905,0x3f7d3aac,0xbe164083,0x3f79c79d,0xbe605c13,0x3f74fa0b,0xbe94a031,0x3f6ed89e,0xbeb8442a,0x3f676bd8,0xbedae880,0x3f5ebe05,0xbefc5d27,
0x3f800000,0x0,0x3f7f0e58,0xbdafb680,0x3f7c3b28,0xbe2f10a2,0x3f778bc5,0xbe827dc0,0x3f710908,0xbeac7cd4,0x3f68bf3c,0xbed53641,0x3f5ebe05,0xbefc5d27,0x3f531849,0xbf10d3cd,
0x3f800000,0x0,0x3f7ec46d,0xbdc8bd36,0x3f7b14be,0xbe47c5c2,0x3f74fa0b,0xbe94a031,0x3f6c835e,0xbec3ef15,0x3f61c598,0xbef15aea,0x3f54db31,0xbf0e39da,0x3f45e403,0xbf226799,
0x3f800000,0x0,0x3f7e70b0,0xbde1bc2e,0x3f79c79d,0xbe605c13,0x3f721352,0xbea68f12,0x3f676bd8,0xbedae880,0x3f59f26a,0xbf064b82,0x3f49d112,0xbf1d7fd1,0x3f373a23,0xbf32c8c9,
0x3f800000,0x0,0x3f7e1324,0xbdfab273,0x3f7853f8,0xbe78cfcc,0x3f6ed89e,0xbeb8442a,0x3f61c598,0xbef15aea,0x3f514d3d,0xbf13682a,0x3f3daef9,0xbf2beb4a,0x3f273656,0xbf41d870,
0x3f800000,0x0,0x3f7dabcc,0xbe09cf86,0x3f76ba07,0xbe888e93,0x3f6b4b0c,0xbec9b953,0x3f5b941a,0xbf039c3d,0x3f47de65,0xbf1ff6cb,0x3f3085bb,0xbf396842,0x3f15f6d9,0xbf4f7a1f,
0x3f800000,0x0,0x3f7d3aac,0xbe164083,0x3f74fa0b,0xbe94a031,0x3f676bd8,0xbedae880,0x3f54db31,0xbf0e39da,0x3f3daef9,0xbf2beb4a,0x3f226799,0xbf45e403,0x3f039c3d,0xbf5b941a,
0x3f800000,0x0,0x3f7cbfc9,0xbe22abb6,0x3f731447,0xbea09ae5,0x3f633c5a,0xbeebcbbb,0x3f4d9f02,0xbf187fc0,0x3f32c8c9,0xbf373a23,0x3f13682a,0xbf514d3d,0x3ee0924f,0xbf660f88,
0x3f800000,0x0,0x3f7c3b28,0xbe2f10a2,0x3f710908,0xbeac7cd4,0x3f5ebe05,0xbefc5d27,0x3f45e403,0xbf226799,0x3f273656,0xbf41d870,0x3f039c3d,0xbf5b941a,0x3eb8442a,0xbf6ed89e,
0x3f800000,0x0,0x3f7baccd,0xbe3b6ecf,0x3f6ed89e,0xbeb8442a,0x3f59f26a,0xbf064b82,0x3f3daef9,0xbf2beb4a,0x3f1b02c6,0xbf4bbbf8,0x3ee63375,0xbf64aa59,0x3e8e9a22,0xbf75dec6,
0x3f800000,0x0,0x3f7b14be,0xbe47c5c2,0x3f6c835e,0xbec3ef15,0x3f54db31,0xbf0e39da,0x3f3504f3,0xbf3504f3,0x3f0e39da,0xbf54db31,0x3ec3ef15,0xbf6c835e,0x3e47c5c2,0xbf7b14be,
0x3f800000,0x0,0x3f7a7302,0xbe541501,0x3f6a09a7,0xbecf7bca,0x3f4f7a1f,0xbf15f6d9,0x3f2beb4a,0xbf3daef9,0x3f00e7e4,0xbf5d2d53,0x3ea09ae5,0xbf731447,0x3de1bc2e,0xbf7e70b0,
0x3f800000,0x0,0x3f79c79d,0xbe605c13,0x3f676bd8,0xbedae880,0x3f49d112,0xbf1d7fd1,0x3f226799,0xbf45e403,0x3ee63375,0xbf64aa59,0x3e78cfcc,0xbf7853f8,0x3cc90ab0,0xbf7fec43,
0x3f800000,0x0,0x3f791298,0xbe6c9a7f,0x3f64aa59,0xbee63375,0x3f43e200,0xbf24d225,0x3f187fc0,0xbf4d9f02,0x3ec9b953,0xbf6b4b0c,0x3e2f10a2,0xbf7c3b28,0xbd7b2b74,0xbf7f84ab,
0x3f800000,0x0,0x3f7853f8,0xbe78cfcc,0x3f61c598,0xbef15aea,0x3f3daef9,0xbf2beb4a,0x3f0e39da,0xbf54db31,0x3eac7cd4,0xbf710908,0x3dc8bd36,0xbf7ec46d,0xbe164083,0xbf7d3aac,
0x3f800000,0x0,0x3f778bc5,0xbe827dc0,0x3f5ebe05,0xbefc5d27,0x3f373a23,0xbf32c8c9,0x3f039c3d,0xbf5b941a,0x3e8e9a22,0xbf75dec6,0x3cc90ab0,0xbf7fec43,0xbe6c9a7f,0xbf791298,
0x3f800000,0x0,0x3f76ba07,0xbe888e93,0x3f5b941a,0xbf039c3d,0x3f3085bb,0xbf396842,0x3ef15aea,0xbf61c598,0x3e605c13,0xbf79c79d,0xbd48fb30,0xbf7fb10f,0xbea09ae5,0xbf731447,
0x3f800000,0x0,0x3f75dec6,0xbe8e9a22,0x3f584853,0xbf08f59b,0x3f299415,0xbf3fc767,0x3edae880,0xbf676bd8,0x3e22abb6,0xbf7cbfc9,0xbdfab273,0xbf7e1324,0xbec9b953,0xbf6b4b0c,
0x3f800000,0x0,0x3f74fa0b,0xbe94a031,0x3f54db31,0xbf0e39da,0x3f226799,0xbf45e403,0x3ec3ef15,0xbf6c835e,0x3dc8bd36,0xbf7ec46d,0xbe47c5c2,0xbf7b14be,0xbef15aea,0xbf61c598,
0x3f800000,0x0,0x3f740bdd,0xbe9aa086,0x3f514d3d,0xbf13682a,0x3f1b02c6,0xbf4bbbf8,0x3eac7cd4,0xbf710908,0x3d16c32c,0xbf7fd397,0xbe888e93,0xbf76ba07,0xbf0b9a6b,0xbf5695e5,
0x3f800000,0x0,0x3f731447,0xbea09ae5,0x3f4d9f02,0xbf187fc0,0x3f13682a,0xbf514d3d,0x3e94a031,0xbf74fa0b,0xbcc90ab0,0xbf7fec43,0xbeac7cd4,0xbf710908,0xbf1d7fd1,0xbf49d112,
0x3f800000,0x0,0x3f721352,0xbea68f12,0x3f49d112,0xbf1d7fd1,0x3f0b9a6b,0xbf5695e5,0x3e78cfcc,0xbf7853f8,0xbdafb680,0xbf7f0e58,0xbecf7bca,0xbf6a09a7,0xbf2e3bde,0xbf3b8f3b,
0x3f800000,0x0,0x3f710908,0xbeac7cd4,0x3f45e403,0xbf226799,0x3f039c3d,0xbf5b941a,0x3e47c5c2,0xbf7b14be,0xbe164083,0xbf7d3aac,0xbef15aea,0xbf61c598,0xbf3daef9,0xbf2beb4a,
0x3f800000,0x0,0x3f6ff573,0xbeb263ef,0x3f41d870,0xbf273656,0x3ef6e0cb,0xbf604621,0x3e164083,0xbf7d3aac,0xbe541501,0xbf7a7302,0xbf08f59b,0xbf584853,0xbf4bbbf8,0xbf1b02c6,
0x3f800000,0x0,0x3f6ed89e,0xbeb8442a,0x3f3daef9,0xbf2beb4a,0x3ee63375,0xbf64aa59,0x3dc8bd36,0xbf7ec46d,0xbe888e93,0xbf76ba07,0xbf187fc0,0xbf4d9f02,0xbf584853,0xbf08f59b,
0x3f800000,0x0,0x3f6db293,0xbebe1d4a,0x3f396842,0xbf3085bb,0x3ed53641,0xbf68bf3c,0x3d48fb30,0xbf7fb10f,0xbea68f12,0xbf721352,0xbf273656,0xbf41d870,0xbf633c5a,0xbeebcbbb,
0x3f800000,0x3f800000,0x3f800000,0x3f800000,0x3f800000,0x3f800000,0x3f800000,0x3f800000,0x3f800000,0xbf800000,0x3f800000,0xbf800000,0x3f800000,0xbf800000,0x3f800000,0xbf800000,
0x3f800000,0x3f3504f3,0x0,0xbf3504f3,0xbf800000,0xbf3504f3,0x0,0x3f3504f3,0x0,0xbf3504f3,0xbf800000,0xbf3504f3,0x0,0x3f3504f3,0x3f800000,0x3f3504f3,
0x3f800000,0x0,0xbf800000,0x0,0x3f800000,0x0,0xbf800000,0x0,0x0,0xbf800000,0x0,0x3f800000,0x0,0xbf800000,0x0,0x3f800000,
0x3f800000,0xbf3504f3,0x0,0x3f3504f3,0xbf800000,0x3f3504f3,0x0,0xbf3504f3,0x0,0xbf3504f3,0x3f800000,0xbf3504f3,0x0,0x3f3504f3,0xbf800000,0x3f3504f3,
0x3f800000,0x3f6c835e,0x3f3504f3,0x3ec3ef15,0x0,0xbec3ef15,0xbf3504f3,0xbf6c835e,0x0,0xbec3ef15,0xbf3504f3,0xbf6c835e,0xbf800000,0xbf6c835e,0xbf3504f3,0xbec3ef15,
0x3f800000,0x3ec3ef15,0xbf3504f3,0xbf6c835e,0x0,0x3f6c835e,0x3f3504f3,0xbec3ef15,0x0,0xbf6c835e,0xbf3504f3,0x3ec3ef15,0x3f800000,0x3ec3ef15,0xbf3504f3,0xbf6c835e,
0x3f800000,0xbec3ef15,0xbf3504f3,0x3f6c835e,0x0,0xbf6c835e,0x3f3504f3,0x3ec3ef15,0x0,0xbf6c835e,0x3f3504f3,0x3ec3ef15,0xbf800000,0x3ec3ef15,0x3f3504f3,0xbf6c835e,
0x3f800000,0xbf6c835e,0x3f3504f3,0xbec3ef15,0x0,0x3ec3ef15,0xbf3504f3,0x3f6c835e,0x0,0xbec3ef15,0x3f3504f3,0xbf6c835e,0x3f800000,0xbf6c835e,0x3f3504f3,0xbec3ef15,
};

struct Params {
    const __nv_bfloat16 *xb, *lre, *lim, *ldt, *dsk;
    float* out;
    int zero[8];
    uint64_t da[4];
    uint32_t unit[258];
};

struct Maps { CUtensorMap m[10]; };

struct cf { float x, y; };
__device__ __forceinline__ uint32_t smem_u32(const void* p) { return (uint32_t)__cvta_generic_to_shared(p); }
__device__ __forceinline__ void mbar_init(uint32_t a, uint32_t c) { asm volatile("mbarrier.init.shared::cta.b64 [%0], %1;" ::"r"(a), "r"(c) : "memory"); }
__device__ __forceinline__ void mbar_expect_tx(uint32_t a, uint32_t b) { asm volatile("mbarrier.arrive.expect_tx.shared::cta.b64 _, [%0], %1;" ::"r"(a), "r"(b) : "memory"); }
__device__ __forceinline__ void mbar_arrive(uint32_t a) { asm volatile("mbarrier.arrive.shared::cta.b64 _, [%0];" ::"r"(a) : "memory"); }
__device__ __forceinline__ void mbar_wait(uint32_t a, uint32_t ph) {
    asm volatile("{.reg .pred p; .reg .u32 n;\n"
                 "mov.u32 n, 0;\n"
                 "LOOP: mbarrier.try_wait.parity.shared::cta.b64 p, [%0], %1;\n"
                 "@p bra DONE;\n"
                 "add.u32 n, n, 1;\n"
                 "setp.lt.u32 p, n, %2;\n"
                 "@p bra LOOP;\n"
                 "DONE: }" ::"r"(a), "r"(ph), "n"(SPIN_LIMIT) : "memory");
}
__device__ __forceinline__ unsigned ld_rlx(const unsigned* p) { unsigned v; asm volatile("ld.relaxed.gpu.global.u32 %0, [%1];" : "=r"(v) : "l"(p) : "memory"); return v; }
__device__ __forceinline__ void wait_cnt(const unsigned* p, unsigned target) {
    unsigned n = 0;
    while ((int)(ld_rlx(p) - target) < 0 && ++n < SPIN_LIMIT) __nanosleep(20);
}
__device__ __forceinline__ void red_hint(unsigned* p) { asm volatile("red.relaxed.gpu.global.add.u32 [%0], 1;" ::"l"(p) : "memory"); }
__device__ __forceinline__ void fence_async() { asm volatile("fence.proxy.async.global;" ::: "memory"); }
__device__ __forceinline__ void fence_async_sm() { asm volatile("fence.proxy.async.shared::cta;" ::: "memory"); }
#define bar_sync(id, n) asm volatile("bar.sync %0, %1;" ::"n"(id), "n"(n) : "memory")
#define bar_arrive(id, n) asm volatile("bar.arrive %0, %1;" ::"n"(id), "n"(n) : "memory")
__device__ __forceinline__ bool elect_one() {
    uint32_t r;
    asm volatile("{.reg .pred p; elect.sync _|p, 0xffffffff; selp.u32 %0, 1, 0, p;}" : "=r"(r));
    return r != 0;
}

__device__ __forceinline__ void tma2d(uint32_t dst, const CUtensorMap* m, int c0, int c1, uint32_t bar) {
    asm volatile("cp.async.bulk.tensor.2d.shared::cluster.global.mbarrier::complete_tx::bytes [%0], [%1, {%3,%4}], [%2];" ::"r"(dst), "l"(m), "r"(bar), "r"(c0), "r"(c1) : "memory");
}
__device__ __forceinline__ void tma4d(uint32_t dst, const CUtensorMap* m, int c0, int c1, int c2, int c3, uint32_t bar) {
    asm volatile("cp.async.bulk.tensor.4d.shared::cluster.global.mbarrier::complete_tx::bytes [%0], [%1, {%3,%4,%5,%6}], [%2];" ::"r"(dst), "l"(m), "r"(bar), "r"(c0), "r"(c1), "r"(c2), "r"(c3) : "memory");
}
__device__ __forceinline__ void tma4d_mc(uint32_t dst, const CUtensorMap* m, int c0, int c3, uint32_t bar) {
    asm volatile("cp.async.bulk.tensor.4d.shared::cluster.global.mbarrier::complete_tx::bytes.multicast::cluster [%0], [%1, {%3,%6,%6,%4}], [%2], %5;" ::"r"(dst), "l"(m), "r"(bar), "r"(c0), "r"(c3), "h"((uint16_t)3), "r"(0) : "memory");
}
__device__ __forceinline__ void tma2d_st(const CUtensorMap* m, int c0, int c1, uint32_t src) {
    asm volatile("cp.async.bulk.tensor.2d.global.shared::cta.bulk_group [%0, {%2,%3}], [%1];" ::"l"(m), "r"(src), "r"(c0), "r"(c1) : "memory");
}
__device__ __forceinline__ void tma3d_st(const CUtensorMap* m, int c0, int c1, int c2, uint32_t src) {
    asm volatile("cp.async.bulk.tensor.3d.global.shared::cta.bulk_group [%0, {%2,%3,%4}], [%1];" ::"l"(m), "r"(src), "r"(c0), "r"(c1), "r"(c2) : "memory");
}
__device__ __forceinline__ void tma5d(uint32_t dst, const CUtensorMap* m, int c0, int c1, int c2, int c3, int c4, uint32_t bar) {
    asm volatile("cp.async.bulk.tensor.5d.shared::cluster.global.mbarrier::complete_tx::bytes [%0], [%1, {%3,%4,%5,%6,%7}], [%2];" ::"r"(dst), "l"(m), "r"(bar), "r"(c0), "r"(c1), "r"(c2), "r"(c3), "r"(c4) : "memory");
}
__device__ __forceinline__ void bulk_ld(uint32_t dst, const void* src, uint32_t n, uint32_t bar) {
    asm volatile("cp.async.bulk.shared::cluster.global.mbarrier::complete_tx::bytes [%0], [%1], %2, [%3];" ::"r"(dst), "l"(src), "r"(n), "r"(bar) : "memory");
}
__device__ __forceinline__ void bulk_commit() { asm volatile("cp.async.bulk.commit_group;" ::: "memory"); }
template <int N> __device__ __forceinline__ void bulk_wait_read() { asm volatile("cp.async.bulk.wait_group.read %0;" ::"n"(N) : "memory"); }
__device__ __forceinline__ void stsm4(uint32_t a, uint32_t r0, uint32_t r1, uint32_t r2, uint32_t r3) {
    asm volatile("stmatrix.sync.aligned.m8n8.x4.shared.b16 [%0], {%1,%2,%3,%4};" ::"r"(a), "r"(r0), "r"(r1), "r"(r2), "r"(r3) : "memory");
}
__device__ __forceinline__ void sts128f(uint32_t a, cf u, cf v) {
    asm volatile("st.shared.v4.f32 [%0], {%1,%2,%3,%4};" ::"r"(a), "f"(u.x), "f"(u.y), "f"(v.x), "f"(v.y) : "memory");
}
__device__ __forceinline__ void stg128(const void* a, uint32_t r0, uint32_t r1, uint32_t r2, uint32_t r3) {
    asm volatile("st.global.v4.b32 [%0], {%1,%2,%3,%4};" ::"l"(a), "r"(r0), "r"(r1), "r"(r2), "r"(r3) : "memory");
}
__device__ __forceinline__ void lds128f(uint32_t a, float& x, float& y, float& z, float& u) { asm volatile("ld.shared.v4.f32 {%0,%1,%2,%3}, [%4];" : "=f"(x), "=f"(y), "=f"(z), "=f"(u) : "r"(a) : "memory"); }
__device__ __forceinline__ cf lds_cf(uint32_t a) { cf v; asm volatile("ld.shared.v2.f32 {%0,%1}, [%2];" : "=f"(v.x), "=f"(v.y) : "r"(a) : "memory"); return v; }
__device__ __forceinline__ uint4 ldtab(int word) { return __ldg((const uint4*)(g_tab + word)); }
__device__ __forceinline__ void load_tw(cf (&tw)[8], int k1) {
#pragma unroll
    for (int i = 0; i < 4; i++) {
        const uint4 v = ldtab(TAB_TW + k1 * 16 + i * 4);
        tw[2 * i] = {__uint_as_float(v.x), __uint_as_float(v.y)};
        tw[2 * i + 1] = {__uint_as_float(v.z), __uint_as_float(v.w)};
    }
}
__device__ __forceinline__ void load_T(cf (&T)[8], int t7) {
#pragma unroll
    for (int i = 0; i < 4; i++)
        asm volatile("ld.global.nc.v4.f32 {%0,%1,%2,%3}, [%4];" : "=f"(T[2 * i].x), "=f"(T[2 * i].y), "=f"(T[2 * i + 1].x), "=f"(T[2 * i + 1].y) : "l"(g_tab + TAB_T + i * 512 + t7 * 4));
}
__device__ __forceinline__ uint32_t lds_u16(uint32_t a) { uint32_t v; asm volatile("ld.shared.u16 %0, [%1];" : "=r"(v) : "r"(a)); return v; }
__device__ __forceinline__ float up(uint32_t v) { return __uint_as_float(v << 16); }
__device__ __forceinline__ unsigned get_epoch(uint32_t bars) {
    mbar_wait(bars + B_EP, 0);
    unsigned e;
    asm volatile("ld.shared.u32 %0, [%1];" : "=r"(e) : "r"(bars + B_EPOCH) : "memory");
    return e;
}
__device__ __forceinline__ void sts64f(uint32_t a, float x, float y) { asm volatile("st.shared.v2.f32 [%0], {%1,%2};" ::"r"(a), "f"(x), "f"(y) : "memory"); }
__device__ __forceinline__ uint32_t pk(float lo, float hi) { uint32_t r; asm("cvt.rn.bf16x2.f32 %0, %1, %2;" : "=r"(r) : "f"(hi), "f"(lo)); return r; }
__device__ __forceinline__ uint32_t bitsel(uint32_t a, uint32_t m, uint32_t b) {
    uint32_t r;
    asm("lop3.b32 %0, %1, %2, %3, 0xea;" : "=r"(r) : "r"(a), "r"(m), "r"(b));
    return r;
}

__host__ __device__ constexpr uint64_t mkdesc(uint32_t off, uint32_t lbo, uint32_t sbo, uint32_t swz) {
    return (uint64_t)((SB0 + off) >> 4) | ((uint64_t)(lbo >> 4) << 16) | ((uint64_t)(sbo >> 4) << 32) | ((uint64_t)swz << 62);
}
__device__ __forceinline__ void wg_fence() { asm volatile("wgmma.fence.sync.aligned;" ::: "memory"); }
__device__ __forceinline__ void wg_commit() { asm volatile("wgmma.commit_group.sync.aligned;" ::: "memory"); }
template <int N> __device__ __forceinline__ void wg_wait() { asm volatile("wgmma.wait_group.sync.aligned %0;" ::"n"(N) : "memory"); }
template <int N> __device__ __forceinline__ void pin(float (&d)[N]) {
#pragma unroll
    for (int i = 0; i < N; i++) asm volatile("" : "+f"(d[i])::"memory");
}
template <int N> __device__ __forceinline__ void pinu(uint32_t (&d)[N]) {
#pragma unroll
    for (int i = 0; i < N; i++) asm volatile("" : "+r"(d[i])::"memory");
}

#define R8(d, o) "+f"(d[o]), "+f"(d[o + 1]), "+f"(d[o + 2]), "+f"(d[o + 3]), "+f"(d[o + 4]), "+f"(d[o + 5]), "+f"(d[o + 6]), "+f"(d[o + 7])
#define L8 "%0,%1,%2,%3,%4,%5,%6,%7"
#define L24 L8 ",%8,%9,%10,%11,%12,%13,%14,%15,%16,%17,%18,%19,%20,%21,%22,%23"
#define L32 L24 ",%24,%25,%26,%27,%28,%29,%30,%31"
#define L64 L32 ",%32,%33,%34,%35,%36,%37,%38,%39,%40,%41,%42,%43,%44,%45,%46,%47,%48,%49,%50,%51,%52,%53,%54,%55,%56,%57,%58,%59,%60,%61,%62,%63"

template <int O, int TA, int TB, int SC, int N> __device__ __forceinline__ void mma128_ss(float (&d)[N], uint64_t da, uint64_t db) {
    asm volatile("wgmma.mma_async.sync.aligned.m64n128k16.f32.bf16.bf16 {" L64 "}, %64, %65, %66, 1, 1, %67, %68;"
                 : R8(d, O), R8(d, O + 8), R8(d, O + 16), R8(d, O + 24), R8(d, O + 32), R8(d, O + 40), R8(d, O + 48), R8(d, O + 56)
                 : "l"(da), "l"(db), "n"(SC), "n"(TA), "n"(TB));
}
#define W8(d, o) "=f"(d[o]), "=f"(d[o + 1]), "=f"(d[o + 2]), "=f"(d[o + 3]), "=f"(d[o + 4]), "=f"(d[o + 5]), "=f"(d[o + 6]), "=f"(d[o + 7])
__device__ __forceinline__ void mma128_first(float (&d)[64], uint64_t da, uint64_t db) {
    asm volatile("wgmma.mma_async.sync.aligned.m64n128k16.f32.bf16.bf16 {" L64 "}, %64, %65, 0, 1, 1, 0, 1;"
                 : W8(d, 0), W8(d, 8), W8(d, 16), W8(d, 24), W8(d, 32), W8(d, 40), W8(d, 48), W8(d, 56) : "l"(da), "l"(db));
}
template <int TB, int SC> __device__ __forceinline__ void mma128_rs(float (&d)[64], const uint32_t* a, uint64_t db) {
    asm volatile("wgmma.mma_async.sync.aligned.m64n128k16.f32.bf16.bf16 {" L64 "}, {%64,%65,%66,%67}, %68, %69, 1, 1, %70;"
                 : R8(d, 0), R8(d, 8), R8(d, 16), R8(d, 24), R8(d, 32), R8(d, 40), R8(d, 48), R8(d, 56)
                 : "r"(a[0]), "r"(a[1]), "r"(a[2]), "r"(a[3]), "l"(db), "n"(SC), "n"(TB));
}
template <int TB, int SC> __device__ __forceinline__ void mma64_rs(float (&d)[32], const uint32_t* a, uint64_t db) {
    asm volatile("wgmma.mma_async.sync.aligned.m64n64k16.f32.bf16.bf16 {" L32 "}, {%32,%33,%34,%35}, %36, %37, 1, 1, %38;"
                 : R8(d, 0), R8(d, 8), R8(d, 16), R8(d, 24)
                 : "r"(a[0]), "r"(a[1]), "r"(a[2]), "r"(a[3]), "l"(db), "n"(SC), "n"(TB));
}
template <int TA, int SC> __device__ __forceinline__ void mma64_ss(float (&d)[32], uint64_t da, uint64_t db) {
    asm volatile("wgmma.mma_async.sync.aligned.m64n64k16.f32.bf16.bf16 {" L32 "}, %32, %33, %34, 1, 1, %35, 1;"
                 : R8(d, 0), R8(d, 8), R8(d, 16), R8(d, 24)
                 : "l"(da), "l"(db), "n"(SC), "n"(TA));
}
template <int SC> __device__ __forceinline__ void mma48_ss(float (&d)[32], uint64_t da, uint64_t db) {
    asm volatile("wgmma.mma_async.sync.aligned.m64n48k16.f32.bf16.bf16 {" L24 "}, %24, %25, %26, 1, 1, 0, 1;"
                 : R8(d, 8), R8(d, 16), R8(d, 24)
                 : "l"(da), "l"(db), "n"(SC));
}
template <int SC> __device__ __forceinline__ void mma16_rs(float (&d)[32], uint32_t a0, uint32_t a1, uint32_t a2, uint32_t a3, uint64_t db) {
    asm volatile("wgmma.mma_async.sync.aligned.m64n16k16.f32.bf16.bf16 {" L8 "}, {%8,%9,%10,%11}, %12, %13, 1, 1, 1;"
                 : R8(d, 0)
                 : "r"(a0), "r"(a1), "r"(a2), "r"(a3), "l"(db), "n"(SC));
}

__device__ __forceinline__ cf cmul(cf a, cf b) { return {fmaf(a.x, b.x, -a.y * b.y), fmaf(a.x, b.y, a.y * b.x)}; }
__device__ __forceinline__ cf csq(cf a) { return {fmaf(a.x, a.x, -a.y * a.y), (a.x + a.x) * a.y}; }
__device__ __forceinline__ cf cmulc(cf a, cf b) { return {fmaf(a.x, b.x, a.y * b.y), fmaf(a.y, b.x, -a.x * b.y)}; }
__device__ __forceinline__ cf cfma(cf a, cf b, cf c) { return {fmaf(a.x, b.x, fmaf(-a.y, b.y, c.x)), fmaf(a.x, b.y, fmaf(a.y, b.x, c.y))}; }
__device__ __forceinline__ cf csel(int c, cf a, cf b) {
    cf r;
    asm("{.reg .pred p; setp.ne.s32 p, %6, 0; selp.f32 %0, %2, %4, p; selp.f32 %1, %3, %5, p;}" : "=f"(r.x), "=f"(r.y) : "f"(a.x), "f"(a.y), "f"(b.x), "f"(b.y), "r"(c));
    return r;
}
__device__ __forceinline__ cf cadd(cf a, cf b) { return {a.x + b.x, a.y + b.y}; }
__device__ __forceinline__ cf csub(cf a, cf b) { return {a.x - b.x, a.y - b.y}; }
__device__ __forceinline__ cf twice_minus(cf a, cf s) { return {fmaf(2.f, a.x, -s.x), fmaf(2.f, a.y, -s.y)}; }
struct v2 { float a, b; };
struct c2 { v2 x, y; };
#define OP2(name, args, txt, ...) \
    __device__ __forceinline__ v2 name args { v2 r; asm volatile(txt : "=f"(r.a) : __VA_ARGS__(a)); asm volatile(txt : "=f"(r.b) : __VA_ARGS__(b)); return r; }
#define A_XY(e) "f"(x.e), "f"(y.e)
#define A_XYZ(e) "f"(x.e), "f"(y.e), "f"(z.e)
OP2(add2, (v2 x, v2 y), "add.rn.f32 %0, %1, %2;", A_XY)
OP2(sub2, (v2 x, v2 y), "sub.rn.f32 %0, %1, %2;", A_XY)
OP2(mul2, (v2 x, v2 y), "mul.rn.f32 %0, %1, %2;", A_XY)
OP2(tw2, (v2 x, v2 y), "{.reg .f32 n; neg.f32 n, %2; fma.rn.f32 %0, %1, 0f40000000, n;}", A_XY)
OP2(fma2, (v2 x, v2 y, v2 z), "fma.rn.f32 %0, %1, %2, %3;", A_XYZ)
OP2(fms2, (v2 x, v2 y, v2 z), "{.reg .f32 n; neg.f32 n, %3; fma.rn.f32 %0, %1, %2, n;}", A_XYZ)
OP2(fnm2, (v2 x, v2 y, v2 z), "{.reg .f32 n; neg.f32 n, %1; fma.rn.f32 %0, n, %2, %3;}", A_XYZ)
__device__ __forceinline__ c2 both(cf a) { return {{a.x, a.x}, {a.y, a.y}}; }
__device__ __forceinline__ c2 tw2(c2 a, c2 s) { c2 r; r.x = tw2(a.x, s.x); r.y = tw2(a.y, s.y); return r; }
template <bool CJ> __device__ __forceinline__ c2 cmul2(c2 a, c2 t) {
    const v2 p = mul2(a.y, t.y), q = mul2(a.x, t.y);
    c2 r;
    r.x = CJ ? fma2(a.x, t.x, p) : fms2(a.x, t.x, p);
    r.y = CJ ? fms2(a.y, t.x, q) : fma2(a.y, t.x, q);
    return r;
}
template <bool CJ> __device__ __forceinline__ c2 cfma2(c2 a, c2 t, c2 c) {
    const v2 p = CJ ? fma2(a.y, t.y, c.x) : fnm2(a.y, t.y, c.x), q = CJ ? fnm2(a.x, t.y, c.y) : fma2(a.x, t.y, c.y);
    c2 r;
    r.x = fma2(a.x, t.x, p);
    r.y = fma2(a.y, t.x, q);
    return r;
}
__device__ __forceinline__ void bfly2(c2 a, c2 b, c2& s, c2& d) { s.x = add2(a.x, b.x); d.x = sub2(a.x, b.x); s.y = add2(a.y, b.y); d.y = sub2(a.y, b.y); }
__device__ __forceinline__ void bflyi2(c2 a, c2 b, c2& s, c2& d) { s.x = add2(a.x, b.y); d.x = sub2(a.x, b.y); s.y = sub2(a.y, b.x); d.y = add2(a.y, b.x); }
__device__ __forceinline__ uint32_t pkv(float lo, float hi) { uint32_t r; asm volatile("cvt.rn.bf16x2.f32 %0, %1, %2;" : "=r"(r) : "f"(hi), "f"(lo)); return r; }
__device__ __forceinline__ uint32_t pkv(v2 v) { return pkv(v.a, v.b); }
__device__ __forceinline__ float upv(uint32_t v) { float r; asm volatile("shl.b32 %0, %1, 16;" : "=f"(r) : "r"(v)); return r; }
__device__ __forceinline__ cf twid(int m, int M) {
    int r = ((m + M / 2) & (M - 1)) - M / 2;
    float s, c;
    __sincosf((float)r * (-6.283185307179586f / (float)M), &s, &c);
    return {c, s};
}
template <int YL, class F> __device__ __forceinline__ void dft8_end(const c2 (&e)[4], c2 a4, c2 a5, c2 a6, c2 a7, F out) {
    const v2 s = {0.70710678118654752f, 0.70710678118654752f};
    c2 o0, o1, o2, o3, u, v;
    bfly2(a4, a6, o0, o2);
    bfly2(e[0], o0, u, v);
    out(0, u, v);
    YLD(YL, 2);
    bflyi2(e[2], o2, u, v);
    out(2, u, v);
    bflyi2(a5, a7, o1, o3);
    YLD(YL, 1);
    o0.x = add2(o1.y, o1.x); o0.y = sub2(o1.y, o1.x);
    u.x = fma2(o0.x, s, e[1].x); v.x = fnm2(o0.x, s, e[1].x); u.y = fma2(o0.y, s, e[1].y); v.y = fnm2(o0.y, s, e[1].y);
    out(1, u, v);
    YLD(YL, 2);
    o2.x = sub2(o3.y, o3.x); o2.y = add2(o3.y, o3.x);
    u.x = fma2(o2.x, s, e[3].x); v.x = fnm2(o2.x, s, e[3].x); u.y = fnm2(o2.y, s, e[3].y); v.y = fma2(o2.y, s, e[3].y);
    out(3, u, v);
    YLD(YL, 1);
}

__device__ __forceinline__ void bid2tile(int b, int& tc, int& cb) {
    const int c = b >> 1, e = c - 36, t7 = (e * 37) >> 8;
    int g;
    asm("{.reg .pred p, q; setp.lt.s32 p, %2, 4; setp.lt.s32 q, %2, 36; selp.s32 %0, %3, %4, q; selp.s32 %1, %5, %6, q; selp.s32 %0, 0, %0, p; selp.s32 %1, %7, %1, p;}"
        : "=&r"(g), "=&r"(cb) : "r"(c), "r"((c + 4) & 7), "r"(1 + e - 7 * t7), "r"((c - 4) >> 3), "r"(4 + t7), "r"(4 + c));
    tc = 2 * g + (b & 1);
}
__host__ __device__ __forceinline__ int pos_of(int n) { return (n & 24) + 4 * (n & 1) + ((n >> 1) & 3); }
static int kappa_of(int b, int gi) {
    const int r = b >> 4, k1 = 2 * ((b & 15) ^ (4 * gi)) + gi;
    return b >= 128 ? gi * 256 : (k1 || r < 4 ? k1 + 64 * r : 64 * r - 224);
}
static int slot3_of(int kap, int& cj) {
    int m = kap & 15;
    cj = (m > 8) || ((m & 7) == 0 && kap > 256);
    const int kk = cj ? 512 - kap : kap;
    m = kk & 15;
    return kk == 256 ? 0 : (m & 1) * 128 + (m & 6) * 16 + pos_of((kk >> 4) + 2 * (m & 8));
}

__device__ __forceinline__ uint32_t tag_bad(uint32_t a, uint32_t tag) {
    uint32_t v;
    asm volatile("ld.shared.u32 %0, [%1];" : "=r"(v) : "r"(a) : "memory");
    return (v ^ tag) & 1;
}
__device__ __forceinline__ bool wg_all_ok(uint32_t bad, int id) {
    uint32_t ok;
    asm volatile("{.reg .pred p, q; setp.eq.u32 q, %1, 0; barrier.red.and.aligned.pred p, %2, 128, q; selp.u32 %0, 1, 0, p;}" : "=r"(ok) : "r"(bad), "r"(id) : "memory");
    return __all_sync(~0u, ok);
}

__device__ __forceinline__ uint32_t lines_bad(uint32_t va, uint32_t tag, uint32_t bit) {
    uint32_t bad;
    asm volatile("{.reg .b32 a, b, c, d;\n"
                 "ld.shared.u32 a, [%1]; ld.shared.u32 b, [%1+4096]; ld.shared.u32 c, [%1+8192]; ld.shared.u32 d, [%1+12288];\n"
                 "lop3.b32 a, a, b, %2, 0x7e; lop3.b32 c, c, d, %2, 0x7e; lop3.b32 %0, a, c, %3, 0xa8;}"
                 : "=r"(bad) : "r"(va), "r"(tag), "r"(bit) : "memory");
    return bad;
}
__device__ __forceinline__ void load_w(uint32_t sb, const CUtensorMap* m, int kap, uint32_t more) {
    mbar_expect_tx(sb + OFF_BAR + B_WIN, 16 * WPITCH + more);
#pragma unroll 1
    for (int i = 0; i < 4; i++) {
        if (i) __nanosleep(PACE_W);
        tma2d(sb + OFF_W + i * (4 * WPITCH), m + (i & 1), ((i & 2 ? (512 - kap) & 511 : kap) * 1026 >> 4) * 2, 0, sb + OFF_BAR + B_WIN);
    }
}
__device__ __forceinline__ void carry_poll(unsigned __int128 (&f)[4], const uint4* a, int n, uint32_t tag) {
    f[0] = f[1] = f[2] = f[3] = tag;
    asm volatile("{.reg .pred p<4>;\n"
                 "setp.ge.s32 p0, %5, 0; setp.ge.s32 p1, %5, 4; setp.ge.s32 p2, %5, 8; setp.ge.s32 p3, %5, 12;\n"
                 "@p0 ld.relaxed.gpu.global.b128 %0, [%4];\n"
                 "@p1 ld.relaxed.gpu.global.b128 %1, [%4+-32768];\n"
                 "@p2 ld.relaxed.gpu.global.b128 %2, [%4+-65536];\n"
                 "@p3 ld.relaxed.gpu.global.b128 %3, [%4+-98304];}"
                 : "+q"(f[0]), "+q"(f[1]), "+q"(f[2]), "+q"(f[3]) : "l"(a), "r"(n) : "memory");
}
__device__ __forceinline__ uint32_t carry_sum(const unsigned __int128 (&f)[4], const cf (&m4)[2], uint32_t tag, cf (&P)[2]) {
#pragma unroll
    for (int h = 0; h < 2; h++)
#pragma unroll
        for (int a = 3; a >= 0; a--) {
            const cf v = {__uint_as_float((uint32_t)(f[a] >> (64 * h))), __uint_as_float((uint32_t)(f[a] >> (64 * h + 32)))};
            P[h] = a == 3 ? v : cfma(m4[h], P[h], v);
        }
    return (((uint32_t)f[0] ^ tag) | ((uint32_t)f[1] ^ tag) | ((uint32_t)f[2] ^ tag) | ((uint32_t)f[3] ^ tag)) & 15u;
}

struct Ring {
    uint32_t full, rel;
    uint32_t ph, bh;
    uint64_t da;
    bool sig;
    uint32_t k;
};
__device__ __forceinline__ void ring_release(const Ring& r, int slot) {
    if (r.sig) asm volatile("mbarrier.arrive.shared::cluster.b64 _, [%0];" ::"r"(r.rel + 8 * slot) : "memory");
}
__device__ __forceinline__ void ring_wait(Ring& r, int slot) {
    if (slot == 0) r.ph ^= 1;
    mbar_wait(r.full + 8 * slot, r.ph);
}
template <int SLOT, int TA, int HF, int J> __device__ __forceinline__ void mma_g(float (&d)[128], const Ring& r, int sc) {
    constexpr int O = 64 * HF;
    asm volatile("{.reg .b64 da, db; .reg .b32 l; .reg .pred p; setp.ne.s32 p, %67, 0; add.u64 da, %64, %69; mov.b32 l, %65; mov.b64 db, {l,%66};\n"
                 "wgmma.mma_async.sync.aligned.m64n128k16.f32.bf16.bf16 {" L64 "}, da, db, p, 1, 1, %68, 0;}"
                 : R8(d, O), R8(d, O + 8), R8(d, O + 16), R8(d, O + 24), R8(d, O + 32), R8(d, O + 40), R8(d, O + 48), R8(d, O + 56)
                 : "l"(r.da), "n"((uint32_t)mkdesc(SLOT * 32768 + 16384 + J * 32, 16, 0, 0)), "r"(r.bh), "r"(sc), "n"(TA),
                   "n"(1 + SLOT * 2048 + (TA ? HF * 64 + J * 256 : HF * 512 + J * 2)));
}
static_assert((GRP >> HAND & 1) && (GRP >> 7 & 1), "hand-over at the end of a group");
template <int SLOT, int TA, int I, int BAR> __device__ __forceinline__ void gemm_mmas(float (&d)[128], Ring& r, int sc, bool last) {
    mma_g<SLOT, TA, I & 1, I / 2>(d, r, I < 2 ? sc : 1);
    if (GRP >> I & 1) {
        wg_commit();
        if (BAR && I == HAND) asm volatile("{.reg .pred p; setp.ne.s32 p, %1, 0; @p bar.arrive %0, 256;}" ::"n"(BAR), "r"((int)last) : "memory");
        wg_wait<1>();
        if ((GRP & (1 << I) - 1) == 0 && sc) ring_release(r, (SLOT + NST - 1) % NST);
    }
    if constexpr (I < 7) gemm_mmas<SLOT, TA, I + 1, BAR>(d, r, sc, last);
}
template <int SLOT, int TA, int BAR = 0> __device__ __forceinline__ void gemm_step(float (&d)[128], Ring& r, int sc, bool last = false) {
    ring_wait(r, SLOT);
    wg_fence();
    gemm_mmas<SLOT, TA, 0, BAR>(d, r, sc, last);
}
template <int K, int HF> __device__ __forceinline__ void gemm_half(float (&d)[128], Ring& r) {
    if (HF == 0) { ring_wait(r, K % NST); wg_fence(); }
    mma_g<K % NST, 1, HF, 0>(d, r, 1); mma_g<K % NST, 1, HF, 1>(d, r, 1); mma_g<K % NST, 1, HF, 2>(d, r, 1); mma_g<K % NST, 1, HF, 3>(d, r, 1);
    if constexpr (HF == 0 && K < 64 - SKEW) { mma_g<K % NST, 1, 1, 0>(d, r, 1); mma_g<K % NST, 1, 1, 1>(d, r, 1); mma_g<K % NST, 1, 1, 2>(d, r, 1); mma_g<K % NST, 1, 1, 3>(d, r, 1); }
    if constexpr (K < 63) gemm_half<K + 1, HF>(d, r);
}
struct Prod {
    uint32_t b0, b1, b2, b3, b4, dbase;
    unsigned* prof;
    __device__ __forceinline__ Prod(uint32_t sb, int slot, uint32_t off) {
        const uint32_t bars = sb + OFF_BAR;
        b0 = bars + slot % NST * 8; b1 = bars + (slot + 1) % NST * 8; b2 = bars + (slot + 2) % NST * 8; b3 = bars + (slot + 3) % NST * 8; b4 = bars + (slot + 4) % NST * 8;
        dbase = sb + off - bars * 4096;
    }
    __device__ __forceinline__ uint32_t dst() const { return b0 * 4096 + dbase; }
    __device__ __forceinline__ void next() { const uint32_t t = b0; b0 = b1; b1 = b2; b2 = b3; b3 = b4; b4 = t; }
};
__device__ __forceinline__ void load_shared(Prod& r, uint32_t ph, const CUtensorMap* m, int c0, int c3, int first) {
    mbar_wait(r.b0 + B_EMPTY, ph);
    tma4d_mc(r.dst(), m, c0, c3, r.b0);
    r.next();
}
__host__ __device__ constexpr uint64_t phases_from(int k) {
    uint64_t v = 0;
    for (int i = 0; i < 64; i++) v |= (uint64_t)((k + i) / NST & 1) << i;
    return v;
}
__device__ __forceinline__ uint32_t phases(int k, int n) { return ((uint32_t)(phases_from(0) >> k) & ((1u << n) - 1)) | 1u << n; }

__global__ void __cluster_dims__(2, 1, 1) __launch_bounds__(512, 1)
fused_kernel(const __grid_constant__ Maps tm, const __grid_constant__ Params p) {
    const CUtensorMap &tmX = tm.m[0], &tmBre = tm.m[1], &tmBim = tm.m[2], &tmXA = tm.m[5], &tmUst = tm.m[6], &tmVst = tm.m[7], &tmWr = tm.m[8], &tmWi = tm.m[9];
    extern __shared__ __align__(1024) uint8_t smraw[];
    const uint32_t sb = smem_u32(smraw);
    const uint32_t bars = sb + OFF_BAR;
    const int bid = blockIdx.x;
    const bool extra = bid >= 128;
    int tc, cb;
    if (threadIdx.x < 32) {
        if (elect_one()) {
            asm volatile("prefetch.tensormap [%0];" ::"l"(&tmX) : "memory");
            asm volatile("prefetch.tensormap [%0];" ::"l"(&tmBre) : "memory");
            asm volatile("prefetch.tensormap [%0];" ::"l"(&tmBim) : "memory");
#pragma unroll
            for (int s = 0; s < NST; s++) mbar_init(bars + B_FULL + s * 8, 33);
            asm volatile("fence.mbarrier_init.release.cluster;" ::: "memory");
            bid2tile(bid, tc, cb);
            mbar_expect_tx(bars + B_FULL, 32768);
            tma5d(sb + 16384, &tmX, 0, 0, 0, 0, tc, bars + B_FULL);
            tma4d(sb, &tmBre, 0, 0, 0, cb * 4, bars + B_FULL);
            tma4d(sb + 8192, &tmBim, 0, 0, 0, cb * 4, bars + B_FULL);
            asm volatile("mbarrier.arrive.shared::cta.b64 _, [%0], 32;" ::"r"(bars + B_FULL) : "memory");
            STAMP(56);
        }
        __syncwarp();
    }
    const int wid = __shfl_sync(~0u, threadIdx.x >> 5, 0);
    if (wid == 1) {
        if (elect_one()) {
#pragma unroll
            for (int o = B_EMPTY; o < B_END; o += 8) mbar_init(bars + o, o < B_STGU ? 2 : (o == B_STGU ? 8 : (o < B_EP ? 4 : 1)));
            asm volatile("fence.mbarrier_init.release.cluster;" ::: "memory");
        }
        __syncwarp();
    }
    const int wg = ((wid >> 2) + 3) & 3, w = wid & 3;
    const int fb = bid >> 5, fcb = bid & 31, fpos = pos_of(fcb);
    bid2tile(bid, tc, cb);
    asm volatile("barrier.cluster.arrive.relaxed.aligned;" ::: "memory");

    if (wg == 3) {
        asm volatile("setmaxnreg.dec.sync.aligned.u32 24;");
        if (w == 0) {
            if (extra) mbar_wait(bars + B_FULL, 0);
            else if (elect_one()) {
#pragma unroll 1
                for (int k = 1; k < NST; k++) {
                    mbar_expect_tx(bars + B_FULL + k * 8, 32768);
                    tma5d(sb + k * 32768 + 16384, &tmX, k * 64, 0, 0, 0, tc, bars + B_FULL + k * 8);
                    tma4d(sb + k * 32768, &tmBre, k * 64, 0, 0, cb * 4, bars + B_FULL + k * 8);
                    tma4d(sb + k * 32768 + 8192, &tmBim, k * 64, 0, 0, cb * 4, bars + B_FULL + k * 8);
                    asm volatile("mbarrier.arrive.shared::cta.b64 _, [%0], 32;" ::"r"(bars + B_FULL + k * 8) : "memory");
                }
                STAMP(28);
            }
            __syncwarp();
        }
        asm volatile("barrier.cluster.wait.aligned;" ::: "memory");
        if (bid == 129 || (sb & 0x3FFFF) != SB0) return;
        if (w < 2) {
            if (extra || !elect_one()) return;
            const int rank = bid & 1;
            if (w == 0) {
                Prod r(sb, 0, 16384);
                int c0 = 64 * NST;
#pragma unroll 1
                for (uint32_t pat = phases(0, 32 - NST); pat != 1; pat >>= 1) {
                    mbar_wait(r.b0 + B_EMPTY, pat);
                    tma5d(r.dst(), &tmX, c0, 0, 0, 0, tc, r.b0);
                    mbar_expect_tx(r.b0, 32768);
                    asm volatile("mbarrier.arrive.shared::cta.b64 _, [%0], 32;" ::"r"(r.b0) : "memory");
                    c0 = (c0 + 64) & 1023;
                    r.next();
                }
                r.dbase -= 16384;
                const uint8_t* src = g_H + (size_t)tc * (32 * 16384);
                uint32_t all = (uint32_t)phases_from(32 - NST);
#pragma unroll 1
                for (int hh = 0; hh < 4; hh++) {
                    uint32_t pat = (all & 255) | 256;
                    all >>= 8;
                    mbar_wait(bars + B_HGO + 8 * hh, 0);
                    STAMPR(45 + hh);
#pragma unroll 1
                    do {
                        mbar_wait(r.b0 + B_EMPTY, pat);
                        bulk_ld(r.dst(), src, 16384, r.b0 + B_HLD);
                        mbar_expect_tx(r.b0 + B_HLD, 16384);
                        mbar_expect_tx(r.b0, 16384);
                        src += 16384;
                        r.next();
                        pat >>= 1;
                    } while (pat != 1);
                }
            } else {
                Prod r(sb, 0, rank * 8192);
                int c = 64 * NST;
#pragma unroll 1
                for (uint32_t pat = phases(0, 32 - NST); pat != 1; pat >>= 1) {
                    load_shared(r, pat, &tmBre + rank, c & 1023, cb * 4 + ((c >> 4) & 64), 1);
                    c += 64;
                }
                r.dbase += 16384;
                uint32_t pat = (uint32_t)phases_from(32 - NST);
#pragma unroll 1
                for (c = 0; c != 1024; c += 64) {
                    load_shared(r, pat, &tmBre + 2, c, cb * 8 + rank * 4, 0);
                    if (c == 64 * LDK) mbar_arrive(bars + B_LDONE);
                    load_shared(r, pat >> 1, &tmBre + 3, c, cb * 8 + rank * 4, 0);
                    pat >>= 2;
                }
            }
        } else if (w == 2) {
            if (!elect_one()) return;
            STAMP5(39);
            if (!extra) {
                mbar_expect_tx(bars + B_XIN, 16384);
                mbar_expect_tx(bars + B_XIN + 8, 16384);
#pragma unroll 1
                for (int i = 0; i < 8; i++) {
                    const int k = i - XA_FIRST + XA_AT;
                    if (i >= XA_FIRST) mbar_wait(bars + B_EMPTY + (k < NST ? k : k - NST) * 8, k >= NST);
                    tma4d(sb + OFF_P + i * 2048, &tmXA, fcb * 32, 0, i, fb, bars + B_XIN);
                    tma4d(sb + OFF_P + 16384 + i * 2048, &tmXA, fcb * 32 + 16, 0, i, fb, bars + B_XIN + 8);
                    if (!i) STAMP5(30);
                    STAMP5(31);
                }
            }
            const unsigned ep = get_epoch(bars);
            if (!extra) mbar_wait(bars + B_XIN + 8, 0);
            STAMP5(32);
            load_w(sb, &tmWr, p.unit[2 * bid] & 0xffff, 8192);
            if (!extra) mbar_wait(bars + B_STGU, 0);
            STAMP(21);
#pragma unroll 1
            for (int gi = 0; gi < 2; gi++) {
                if (!extra) {
#pragma unroll 1
                    for (int r = 128 * gi; r < 128 * gi + 128; r += UBOX) {
                        if (gi) __nanosleep(PACE_U);
                        tma2d_st(&tmUst, fb * 2048 + fpos * 64, r, sb + OFF_P + r * 128);
                        bulk_commit();
                    }
                    bulk_wait_read<HINT_U>();
                    red_hint(g_cnt + gi * 32);
                }
                if (!gi) bulk_ld(sb + OFF_F, g_tab + TAB_FG, 8192, bars + B_WIN);
                bulk_wait_read<0>();
                STAMPR(40 + gi);
                wait_cnt(g_cnt + 32 * gi, 128 * ep);
                if (gi) __nanosleep(UDELAY);
                else STAMP(42);
                mbar_expect_tx(bars + B_UIN + 8 * gi, 16384);
                bulk_ld(sb + OFF_P + gi * 16384, g_U + (size_t)(extra ? 0 : bid + 128 * gi) * 16384, 16384, bars + B_UIN + 8 * gi);
            }
            if (WPF) {
                const int kap = p.unit[2 * bid + 1] & 0xffff;
#pragma unroll 1
                for (int i = 0; i < 4; i++)
                    asm volatile("cp.async.bulk.prefetch.tensor.2d.L2.global [%0, {%1,%2}];" ::"l"(&tmWr + (i & 1)), "r"(((i & 2 ? 512 - kap : kap) * 1026 >> 4) * 2), "r"(0) : "memory");
            }
            mbar_wait(bars + B_WFREE, 0);
            load_w(sb, &tmWr, p.unit[2 * bid + 1] & 0xffff, 0);
#pragma unroll 1
            for (int gi = 0; gi < 2; gi++) {
                const int vc = ((p.unit[2 * bid + gi] >> 16) & 255) * 32, go = vc >> 12;
                const uint32_t src = extra ? sb + 32768 : sb + OFF_P + gi * 16384;
                mbar_wait(bars + B_STG, gi);
                STAMPR(23 + gi);
                if (extra && !gi) continue;
                if (bid + gi != 0) {
#pragma unroll 1
                    for (int r = 0; r < 256; r += VBOX) {
                        if (r && !gi) __nanosleep(PACE_V);
                        if (VSPLIT && gi && r == 128) mbar_wait(bars + B_STGU, !extra);
                        tma3d_st(&tmVst, vc + go * 4096, (r >> 1) & 64, (r >> 6) & 1, src + (r & 64) * 128 + (r & 128) * 32);
                        bulk_commit();
                    }
                }
                bulk_wait_read<HINT_V>();
                red_hint(g_cnt + 64 + 32 * go);
                bulk_wait_read<0>();
                STAMP(49);
                if (extra) break;
                wait_cnt(g_cnt + 64 + 32 * gi, (129 - gi) * ep);
                STAMPR(43 + gi);
#pragma unroll
                for (int h = 0; h < 2; h++) {
                    mbar_expect_tx(bars + B_VIN + gi * 16 + h * 8, 8192);
                    bulk_ld(src + h * 8192, g_V + (uint32_t)((fb * 32 + fpos) * 32768 + gi * 16384 + h * 8192), 8192, bars + B_VIN + gi * 16 + h * 8);
                }
            }
        } else {
            const uint32_t tag = ld_rlx(g_epoch + bid * 8) + 1;
            __syncwarp();
            if (elect_one()) {
                asm volatile("st.shared.u32 [%0], %1;" ::"r"(bars + B_EPOCH), "r"(tag) : "memory");
                mbar_arrive(bars + B_EP);
                asm volatile("st.relaxed.gpu.global.u32 [%0], %1;" ::"l"(g_epoch + bid * 8), "r"(tag) : "memory");
            }
            __syncwarp();
            if (extra) return;
            const int lane = (threadIdx.x + p.zero[0]) & 31;
            Prod r(sb, 32, 0);
            uint32_t va = (lane & 3) * 516 + (lane >> 4) * 2048 + (lane & 12) * 32 + (lane >> 2) * 16 + r.dbase;
            asm volatile("" : "+r"(va));
            uint32_t n = 0;
#pragma unroll 1
            for (int half = 0; half < 2; half++) {
#pragma unroll 1
                for (uint32_t pat = phases(16 * half, 16); pat != 1; pat >>= 1) {
                    mbar_wait(r.b0 + B_HLD, pat);
                    bool bad = lines_bad(r.b0 * 4096 + va, tag, 1);
                    if (!bad) mbar_arrive(r.b0);
#pragma unroll 1
                    while (__any_sync(~0u, bad)) {
                        const int kk = __shfl_sync(~0u, pat, 0);
                        if (elect_one()) {
                            mbar_expect_tx(bars + B_HRTY, 16384);
                            bulk_ld(r.dst(), g_H + (uint32_t)(tc * 32 + half * 16 + __clz(kk) - 15) * 16384, 16384, bars + B_HRTY);
                        }
                        __syncwarp();
                        mbar_wait(bars + B_HRTY, n++);
                        if (bad && !lines_bad(r.b0 * 4096 + va, tag, n < SPIN_LIMIT)) { bad = false; mbar_arrive(r.b0); }
                        __syncwarp();
                    }
                    if (pat >> 16) STAMPR(6 + 23 * half);
                    r.next();
                }
            }
        }
    } else {
        asm volatile("setmaxnreg.inc.sync.aligned.u32 152;");
        asm volatile("barrier.cluster.wait.aligned;" ::: "memory");
        STAMP(55);
        if ((extra && (wg != 2 || bid == 129)) || (sb & 0x3FFFF) != SB0) return;
        const int hf = wg - 1;
#define INDICES(i) const int t7 = (threadIdx.x + p.zero[i]) & 127, lane = t7 & 31, g = lane >> 2, q = lane & 3, k1 = t7 >> 2, mi = lane >> 3, gl = lane & 7; \
                   const uint32_t tmask = q == 0 ? ~1u : ~0u;
        if (wg == 1) {
            INDICES(1)
            const int ch = (t7 >> 6) * 512 + (t7 & 8) * 32 + cb * 32 + ((t7 >> 1) & 24) + (t7 & 7);
            const float lr = __bfloat162float(p.lre[ch]), li = __bfloat162float(p.lim[ch]);
            const float dt = __bfloat162float(__float2bfloat16(expf(__bfloat162float(p.ldt[ch]))));
            float sn, cs;
            sincospif(dt * li * 0.31830988618379067f, &sn, &cs);
            const float ex = expf(dt * lr), br = ex * cs, bi = ex * sn;
            const float inv = __fdividef(2.0f, lr * lr + li * li);
            const cf lam = {br, -bi}, gam = {((br - 1.f) * lr + bi * li) * inv, -(bi * lr - (br - 1.f) * li) * inv};
            const cf l32 = csq(csq(csq(csq(csq(lam))))), l64 = csq(l32), m1 = csq(l64), m2 = csq(m1), g2 = cmul(gam, l64);
            sts128f(sb + OFF_T1 + t7 * 16, lam, l32);
            sts128f(sb + OFF_TL + t7 * 32, gam, cmul(gam, l32));
            sts128f(sb + OFF_TL + t7 * 32 + 16, g2, cmul(g2, l32));
            sts128f(sb + OFF_TM + t7 * 32, csq(m2), m1);
            sts128f(sb + OFF_TM + t7 * 32 + 16, m2, cmul(m2, m1));
            __syncwarp();
            if (lane == 0) mbar_arrive(bars + B_LAM);
        }
        if (wg != 0 && !extra) {
            INDICES(2)
            uint32_t f1[16];
#pragma unroll
            for (int j = 0; j < 4; j++) { const uint4 v = ldtab(TAB_F1 + j * 512 + t7 * 4); f1[4 * j] = v.x; f1[4 * j + 1] = v.y; f1[4 * j + 2] = v.z; f1[4 * j + 3] = v.w; }
            cf tw[8];
            load_tw(tw, k1);
            const uint32_t tbit = get_epoch(bars) & ~tmask;
            float acc[64];
            const uint64_t dx = mkdesc(OFF_P, 2048, 256, 3) + hf * 1024;
            const int gr = gl & 1, jr = (gl >> 1) + 4 * ((w ^ gl) & 1);
            const uint32_t a0 = w + gl ? sb + OFF_P + (gr * 128 + 8 * (w >> 1) + jr + 64 * (mi >> 1)) * 128 : sb + OFF_F + 2048;
            const uint32_t rs = w + gl ? 2048 : 0;
            const uint32_t scr = sb + OFF_F + hf * 1024;
            STAMP5(33 + hf);
            mbar_wait(bars + B_XIN + hf * 8, 0);
            STAMP(20);
            pinu(f1);
            wg_fence();
            mma128_rs<1, 0>(acc, f1, dx);
            mma128_rs<1, 1>(acc, f1 + 4, dx + 32);
            mma128_rs<1, 1>(acc, f1 + 8, dx + 64);
            mma128_rs<1, 1>(acc, f1 + 12, dx + 96);
            wg_commit();
            wg_wait<0>();
            pin(acc);
            pinu(f1);
            STAMP5(35);
            if (k1 == 0) {
#pragma unroll
                for (int i = 0; i < 16; i++) sts128f(scr + i * 64 + q * 16, {acc[4 * i], acc[4 * i + 1]}, {acc[4 * i + 2], acc[4 * i + 3]});
            }
            uint4 fx0, fx1;
            asm volatile("ld.global.nc.v4.b32 {%0,%1,%2,%3}, [%4];" : "=r"(fx0.x), "=r"(fx0.y), "=r"(fx0.z), "=r"(fx0.w) : "l"(g_tab + TAB_FX + (t7 & 120)));
            asm volatile("ld.global.nc.v4.b32 {%0,%1,%2,%3}, [%4];" : "=r"(fx1.x), "=r"(fx1.y), "=r"(fx1.z), "=r"(fx1.w) : "l"(g_tab + TAB_FX + (t7 & 120) + 4));
#pragma unroll
            for (int cl = 0; cl < 2; cl++) {
                auto in = [&](int n) { const int i = 4 * (2 * n + cl); return c2{{acc[i], acc[i + 1]}, {acc[i + 2], acc[i + 3]}}; };
                c2 e[4];
                {
                    const c2 a0 = cfma2<false>(in(4), both(tw[4]), in(0)), a1 = tw2(in(0), a0);
                    YLD(YF1, 3);
                    const c2 t2 = cmul2<false>(in(2), both(tw[2]));
                    YLD(YF1, 2);
                    const c2 a2 = cfma2<false>(in(6), both(tw[6]), t2), a3 = tw2(t2, a2);
                    YLD(YF1, 3);
                    bfly2(a0, a2, e[0], e[2]);
                    YLD(YF1, 1);
                    bflyi2(a1, a3, e[1], e[3]);
                }
                cf sx[8];
                if (cl == 0) {
                    bar_sync(6, 256);
                    STAMP5(36);
#pragma unroll
                    for (int n = 0; n < 8; n++) sx[n] = lds_cf(scr + n * 128 + gl * 16 + (w >> 1) * 8);
                }
                const c2 t1 = cmul2<false>(in(1), both(tw[1]));
                YLD(YF1, 2);
                const c2 a4 = cfma2<false>(in(5), both(tw[5]), t1), a5 = tw2(t1, a4);
                YLD(YF1, 3);
                const c2 t3 = cmul2<false>(in(3), both(tw[3]));
                YLD(YF1, 1);
                const c2 a6 = cfma2<false>(in(7), both(tw[7]), t3), a7 = tw2(t3, a6);
                YLD(YF1, 2);
                const uint32_t a1 = a0 + (((((mi & 1) << 2) | ((2 * hf + cl) ^ (fpos & 3))) ^ jr) << 4);
                dft8_end<YF1>(e, a4, a5, a6, a7, [&](int r, c2 u, c2 v) {
                    uint32_t o0 = pkv(u.x), o1 = pkv(u.y), o2 = pkv(v.x), o3 = pkv(v.y);
                    if (cl == 0) { o0 = bitsel(o0, tmask, tbit); o1 = bitsel(o1, tmask, tbit); o2 = bitsel(o2, tmask, tbit); o3 = bitsel(o3, tmask, tbit); }
                    stsm4(a1 + r * rs, o0, o1, o2, o3);
                });
                if (cl == 0) {
                    YLD(YF1, 2);
                    float s0 = 0.f, s1 = 0.f;
#pragma unroll
                    for (int n = 0; n < 8; n++) {
                        const float c = __uint_as_float(n < 4 ? (n == 0 ? fx0.x : n == 1 ? fx0.y : n == 2 ? fx0.z : fx0.w) : (n == 4 ? fx1.x : n == 5 ? fx1.y : n == 6 ? fx1.z : fx1.w));
                        s0 = fmaf(c, sx[n].x, s0); s1 = fmaf(c, sx[n].y, s1);
                    }
                    asm volatile("st.shared.b32 [%0], %1;" ::"r"(sb + OFF_P + (t7 >> 4) * 2048 + (((mi & 1) * 4 + ((2 * hf + (g & 1)) ^ (fpos & 3))) << 4) + q * 4), "r"(bitsel(pk(s0, s1), tmask, tbit)) : "memory");
                    YLD(YF1, 1);
                }
            }
            fence_async_sm();
            __syncwarp();
            if (lane == 0) mbar_arrive(bars + B_STGU);
        }
        if (wg != 2) {
        if (wg == 0) bar_sync(4, 128);
        asm volatile("setmaxnreg.inc.sync.aligned.u32 168;");
        float d[128];
        Ring rg;
        rg.full = bars + B_FULL;
        asm("mapa.shared::cluster.u32 %0, %1, %2;" : "=r"(rg.rel) : "r"(bars + B_EMPTY), "r"(w & 1));
        rg.sig = ((threadIdx.x + p.zero[7]) & 95) == 0;
        rg.bh = (uint32_t)(mkdesc(0, 0, 1024, 1) >> 32) + p.zero[0];
        rg.da = p.da[0];
        rg.ph = 1;
        rg.k = 130 * 66 + bid * 66 + 16 * wg;
        if (wg == 0) {
            STAMP(0);
            gemm_step<0, 0>(d, rg, 0);
        } else {
            bar_sync(1, 256);
            STAMP(10);
        }
        rg.da = p.da[1];
#pragma unroll 1
        for (int i = 0; i < 3; i++) {
            gemm_step<1, 0>(d, rg, i >= wg);
            gemm_step<2, 0>(d, rg, 1);
            gemm_step<3, 0>(d, rg, 1);
            gemm_step<4, 0>(d, rg, 1);
            gemm_step<0, 0, 1>(d, rg, 1, i - wg == 2);
        }
        if (wg != p.zero[1]) {
            rg.da = p.da[0];
            gemm_step<1, 0, 2>(d, rg, 1, true);
        }
        {
            INDICES(3)
            cf lam[2], l32[2], l2[2];
            const uint32_t ta = sb + (wg * 64 + 16 * w + g) * 16;
            mbar_wait(bars + B_LAM, 0);
            const unsigned ep = get_epoch(bars), tag = ep & 15u;
            lds128f(ta + OFF_T1, lam[0].x, lam[0].y, l32[0].x, l32[0].y);
            lds128f(ta + OFF_T1 + 128, lam[1].x, lam[1].y, l32[1].x, l32[1].y);
            const uint4* cpub = g_carry + (uint32_t)(wg * 256 + cb * 32 + 8 * w + tc * 512 + g);
            l2[0] = csq(lam[0]);
            l2[1] = csq(lam[1]);
            asm volatile("pmevent 0;" : "+l"(cpub), "+f"(l2[0].x), "+f"(l2[0].y), "+f"(l2[1].x), "+f"(l2[1].y));
            wg_wait<0>();
            ring_release(rg, wg);
            pin(d);
            STAMPW(1, 11);
            cf f[2];
#pragma unroll
            for (int h = 0; h < 2; h++) {
                cf e = {d[2 * h], -d[64 + 2 * h]}, o = {d[2 * h + 1], -d[65 + 2 * h]};
#pragma unroll
                for (int i = 1; i < 16; i++) {
                    const int r = 4 * i + 2 * h;
                    const float a0 = fmaf(-l2[h].y, e.y, d[r]), a1 = fmaf(-l2[h].y, o.y, d[r + 1]);
                    const float b0 = fmaf(l2[h].y, e.x, -d[64 + r]), b1 = fmaf(l2[h].y, o.x, -d[65 + r]);
                    e.x = fmaf(l2[h].x, e.x, a0); o.x = fmaf(l2[h].x, o.x, a1); e.y = fmaf(l2[h].x, e.y, b0); o.y = fmaf(l2[h].x, o.y, b1);
                    if (i % YS == 0) YIELD();
                }
                f[h] = cfma(lam[h], e, o);
            }
            cf st[2], gam[2];
            gam[0] = lds_cf(2 * ta - sb + OFF_TL);
            gam[1] = lds_cf(2 * ta - sb + OFF_TL + 256);
            cf v0[2], v1[2], v2[2];
#pragma unroll
            for (int h = 0; h < 2; h++) {
                v0[h] = {__shfl_sync(~0u, f[h].x, 0, 4), __shfl_sync(~0u, f[h].y, 0, 4)};
                v1[h] = {__shfl_sync(~0u, f[h].x, 1, 4), __shfl_sync(~0u, f[h].y, 1, 4)};
                v2[h] = {__shfl_sync(~0u, f[h].x, 2, 4), __shfl_sync(~0u, f[h].y, 2, 4)};
            }
#pragma unroll
            for (int h = 0; h < 2; h++) {
                v1[h] = cfma(l32[h], v0[h], v1[h]);
                v2[h] = cfma(l32[h], v1[h], v2[h]);
                f[h] = cfma(l32[h], v2[h], f[h]);
            }
            asm volatile("{.reg .pred p; .reg .b64 a, b; .reg .b128 v; setp.eq.u32 p, %5, 3; mov.b64 a, {%1,%2}; mov.b64 b, {%3,%4}; mov.b128 v, {a, b};\n"
                         "@p st.relaxed.gpu.global.b128 [%0], v;}" ::"l"(cpub),
                         "r"(bitsel(__float_as_uint(f[0].x), ~15u, tag)), "r"(__float_as_uint(f[0].y)), "r"(__float_as_uint(f[1].x)), "r"(__float_as_uint(f[1].y)), "r"(q) : "memory");
            STAMPX(2, 12);
            YIELD();
#pragma unroll
            for (int h = 0; h < 2; h++) st[h] = cmul(gam[h], csel(q & 2, csel(q & 1, v2[h], v1[h]), csel(q & 1, v0[h], cf{0.f, 0.f})));
            const uint4* cget = cpub + (gl - g) - (1 + mi) * 512;
            const int nget = tc - 1 - mi;
            unsigned __int128 fq[4];
#pragma unroll
            for (int i = 0; i < 32; i++) {
                if (i == POLL_AT) carry_poll(fq, cget, nget, tag);
                if (i % YS == 0) YIELD();
                const int h = i >> 4, r = 4 * (i & 15) + 2 * h;
                asm volatile("{.reg .f32 s0, s1, n; neg.f32 n, %4; mul.f32 s0, %5, %1; mul.f32 s1, %5, %3; mul.f32 %1, n, %1; mul.f32 %3, n, %3;\n"
                             "fma.rn.f32 %1, %5, %0, %1; fma.rn.f32 %3, %5, %2, %3; fma.rn.f32 %0, %4, %0, s0; fma.rn.f32 %2, %4, %2, s1;}"
                             : "+f"(d[r]), "+f"(d[64 + r]), "+f"(d[r + 1]), "+f"(d[65 + r]) : "f"(gam[h].x), "f"(gam[h].y));
            }
            YIELD();
            const uint32_t tm = sb + OFF_TM + (wg * 64 + 16 * w) * 32;
            cf m4[2], mj[2], P[2], lq[2];
#pragma unroll
            for (int h = 0; h < 2; h++) {
                m4[h] = lds_cf(tm + gl * 32 + h * 256);
                mj[h] = lds_cf(tm + gl * 32 + h * 256 + mi * 8);
            }
            uint32_t bad = carry_sum(fq, m4, tag, P);
            unsigned n = 0;
            while (__any_sync(~0u, bad) && ++n < SPIN_LIMIT) {
                unsigned __int128 fr[4];
                carry_poll(fr, cget, nget, tag);
                bad = carry_sum(fr, m4, tag, P);
                YIELD();
                mj[0] = lds_cf(tm + gl * 32 + mi * 8);
                mj[1] = lds_cf(tm + gl * 32 + 256 + mi * 8);
            }
            STAMPX(53, 54);
            P[0] = csel(mi, cmul(P[0], mj[0]), P[0]);
            P[1] = csel(mi, cmul(P[1], mj[1]), P[1]);
            __syncwarp();
            sts128f(tm + lane * 16, P[0], P[1]);
#pragma unroll
            for (int h = 0; h < 2; h++) {
                lq[h] = lds_cf(2 * ta - sb + OFF_TL + h * 256 + q * 8);
                lam[h] = lds_cf(ta + OFF_T1 + h * 128);
            }
            __syncwarp();
            float ps[4][4];
#pragma unroll
            for (int j = 0; j < 4; j++) lds128f(tm + g * 16 + j * 128, ps[j][0], ps[j][1], ps[j][2], ps[j][3]);
            const uint8_t* hp = g_H + (uint32_t)((tc * 32 + wg * 16 + (cb & 6)) * 16384 + ((cb & 1) * 4 + w) * 2048 + g * 64 + ((q ^ (g >> 1)) << 4));
#pragma unroll
            for (int h = 0; h < 2; h++)
                st[h] = cfma(lq[h], {(ps[0][2 * h] + ps[1][2 * h]) + (ps[2][2 * h] + ps[3][2 * h]), (ps[0][2 * h + 1] + ps[1][2 * h + 1]) + (ps[2][2 * h + 1] + ps[3][2 * h + 1])}, st[h]);
            STAMPX(3, 13);
            uint32_t hv[32];
#pragma unroll
            for (int h = 0; h < 2; h++) {
                YIELD();
                cf c = st[h];
#pragma unroll
                for (int i = 0; i < 16; i++) {
                    const int r = 4 * i + 2 * h;
                    const cf a = cfma(lam[h], c, {d[r], d[64 + r]});
                    c = cfma(lam[h], a, {d[r + 1], d[65 + r]});
                    hv[i] = pk(a.x, c.x);
                    hv[16 + i] = pk(a.y, c.y);
                    if ((i & 3) == (i >> 2)) { hv[i] = bitsel(hv[i], ~1u, ep & 1); hv[16 + i] = bitsel(hv[16 + i], ~1u, ep & 1); }
                    if (h == 0 && (i & 3) == 3) {
                        stg128(hp + (i >> 2) * 512, hv[i - 3], hv[i - 2], hv[i - 1], hv[i]);
                        stg128(hp + 16384 + (i >> 2) * 512, hv[13 + i], hv[14 + i], hv[15 + i], hv[16 + i]);
                    }
                }
                if (h == 0) {
                    STAMPW(4, 14);
                    if (lane == 0) red_hint(g_hcnt + tc * 64 + wg * 32);
                }
            }
            YIELD();
            if (w == 0) {
                wait_cnt(g_hcnt + tc * 64 + wg * 32, 32 * ep);
                if (lane < 4) mbar_arrive(bars + B_HGO + 16 * wg);
            } else if (!(HNOW >> wg & 1)) mbar_wait(bars + B_HGO + 16 * wg, 0);
            if (HDELAY) __nanosleep(wg * HDELAY);
#pragma unroll
            for (int j = 0; j < 8; j++) {
                stg128(hp + (8 + (j >> 2)) * 16384 + (j & 3) * 512, hv[4 * j], hv[4 * j + 1], hv[4 * j + 2], hv[4 * j + 3]);
                if (j < 7) __nanosleep(PACE_H);
            }
            __syncwarp();
            if (lane == 0) mbar_arrive(bars + B_HGO + 16 * wg + 8);
            STAMPW(5, 15);
        }
        if (wg == p.zero[2]) {
            INDICES(1)
            float y[128];
            const uint32_t sa = sb + w * 4096 + g * 512 + q * 8;
            bar_sync(2, 256);
            STAMP(7);
            rg.da = p.da[2];
            rg.ph = 0;
            rg.k = 130 * 66 + bid * 66 + 32;
#pragma unroll 1
            for (int i = 0;; i++) {
                gemm_step<2, 1>(y, rg, i);
                gemm_step<3, 1>(y, rg, 1);
                gemm_step<4, 1>(y, rg, 1);
                if (i == 5) break;
                gemm_step<0, 1>(y, rg, 1);
                gemm_step<1, 1>(y, rg, 1);
            }
            rg.da = p.da[3];
            gemm_half<60, 0>(y, rg);
            if (LDK > 15 && t7 == 0) mbar_arrive(bars + B_LDONE);
            wg_commit();
            gemm_half<64 - SKEW, 1>(y, rg);
            wg_commit();
#pragma unroll
            for (int r = 0; r < 4; r++) {
                if (r == 0) {
                    wg_wait<1>();
#pragma unroll
                    for (int i = 0; i < 64; i++) asm volatile("" : "+f"(y[i])::"memory");
                    STAMP(16);
                    bar_sync(4, 128);
                }
                if (r == 2) {
                    STAMP(18);
                    wg_wait<0>();
#pragma unroll
                    for (int i = 64; i < 128; i++) asm volatile("" : "+f"(y[i])::"memory");
                    STAMP(8);
                    bar_sync(4, 128);
                }
#pragma unroll
                for (int c = 0; c < 16; c++) {
                    const int yi = 64 * (r >> 1) + 4 * c + 2 * (r & 1);
                    sts64f(sa + (r < 2 ? (NST - 1) * 32768 : 0) + (r & 1) * 16384 + (c >> 2) * 128 + (((c ^ g) & 3) << 5), y[yi], y[yi + 1]);
                }
                if (r == 0) bar_arrive(9, 256);
                if (r == 1) bar_arrive(10, 256);
                if (r == 2) bar_arrive(11, 256);
                if (r == 3) bar_arrive(12, 256);
            }
            STAMP(19);
            return;
        }
        bar_sync(8, 128);
        asm volatile("setmaxnreg.dec.sync.aligned.u32 152;");
        } else {
            INDICES(4)
            cf T[8];
            load_T(T, t7);
            const uint32_t tag = get_epoch(bars) & 1;
            float acc[64];
            constexpr uint64_t dF = mkdesc(OFF_F, 16, 1024, 1);
            const uint32_t tga = sb + OFF_P + t7 * 128 + (((t7 & 1) ^ (g & 2)) << 4) + (g & 1) * 64;
            bool ok = false;
            mbar_wait(bars + B_WIN, 0);
#pragma unroll 1
            for (int gi = 0;; gi++) {
                const uint32_t un = p.unit[2 * bid + gi];
                const int kap = un & 0xffff;
                const uint32_t buf = sb + OFF_P + gi * 16384;
                STAMP3(39);
                float za[32], zb[32], ya[32], yb[32];
                const uint64_t dB = mkdesc(OFF_P, 4096, 512, 2) + gi * 1024;
                uint32_t ad, am, pa, pb;
                if (w == 2) {
                    ad = sb + OFF_W + (lane & 8) * 128;
                    am = ad + ((lane & 4) | (((kap ? 3 : 4) - lane) & 3)) * WPITCH + (8 * WPITCH + ((-2 * kap) & 15));
                    ad += gl * WPITCH + ((2 * kap) & 15);
                    asm volatile("" : "+r"(ad), "+r"(am));
                    mbar_wait(bars + B_WIN, gi);
                    pa = lds_u16(ad);
                    pb = lds_u16(am);
                }
#pragma unroll 1
                for (int n = gi; !ok && n < 4096; n++) {
                    if (n) bar_sync(3, 128);
                    if (n && w == 0 && elect_one()) { mbar_expect_tx(bars + B_UIN + gi * 8, 16384); bulk_ld(buf, g_U + (size_t)(extra ? 0 : bid + gi * 128) * 16384, 16384, bars + B_UIN + gi * 8); }
                    mbar_wait(bars + B_UIN + gi * 8, n & 1);
                    STAMP3(22);
                    wg_fence();
                    mma128_first(acc, dF, dB);
                    mma128_ss<0, 0, 1, 1>(acc, dF + 2, dB + 64);
                    mma128_ss<0, 0, 1, 1>(acc, dF + 4, dB + 128);
                    mma128_ss<0, 0, 1, 1>(acc, dF + 6, dB + 192);
                    wg_commit();
                    YIELD();
                    ok = wg_all_ok(tag_bad(tga + gi * 16384, tag), 3);
                    wg_wait<0>();
                    pin(acc);
                }
                STAMP3(30);
                uint32_t af[32];
#pragma unroll
                for (int b = 0; b < 4; b++) {
#pragma unroll
                    for (int c = 0; c < 4; c++) {
                        const int i = 4 * (4 * b + c);
                        cf x0 = cmul({acc[i], acc[i + 2]}, T[2 * c]), x1 = cmul({acc[i + 1], acc[i + 3]}, T[2 * c + 1]);
                        af[16 * (b >> 1) + 4 * c + (b & 1)] = pk(x0.x, x0.y);
                        af[16 * (b >> 1) + 4 * c + 2 + (b & 1)] = pk(x1.x, x1.y);
                        YLD(YF2, c == 3 ? 1 : (c == 1 ? 2 : 3));
                    }
                    if (b == 0 && w == 2) {
                        const uint32_t sg = (lane & 4) << 13, v = pk(0.5f * (up(pa) + up(pb ^ sg)), 0.f);
                        asm volatile("st.shared.u16 [%0], %1;" ::"r"(ad), "r"(v) : "memory");
                        asm volatile("st.shared.u16 [%0], %1;" ::"r"(am), "r"(v ^ sg) : "memory");
                    }
                    if (b == 1) {
                        wg_fence();
                        mma64_rs<0, 0>(za, af, dF); mma64_rs<0, 1>(za, af + 4, dF + 2); mma64_rs<0, 1>(za, af + 8, dF + 4); mma64_rs<0, 1>(za, af + 12, dF + 6);
                        wg_commit();
                    }
                }
                wg_fence();
                mma64_rs<0, 0>(zb, af + 16, dF); mma64_rs<0, 1>(zb, af + 20, dF + 2); mma64_rs<0, 1>(zb, af + 24, dF + 4); mma64_rs<0, 1>(zb, af + 28, dF + 6);
                wg_commit();
                STAMP3(31);
                int kq;
                asm volatile("mad.lo.s32 %0, %1, 512, %2;" : "=r"(kq) : "r"(q), "r"(kap));
                uint32_t wad[4];
#pragma unroll
                for (int j = 0; j < 4; j++) wad[j] = sb + OFF_W + ((j + (kq >> 9)) & 3) * WPITCH + ((2 * kap) & 15) + 2 * k1 + 128 * q;
                if (VDEFER && gi) fence_async_sm();
                bar_sync(3, 128);
                if (VDEFER && lane < gi) mbar_arrive(bars + B_STG);
                uint32_t wn[16];
#pragma unroll
                for (int j = 0; j < 16; j++) wn[j] = lds_u16(wad[j >> 2] + (j & 1) * 64 + (j & 2) * (2 * WPITCH));
                const cf be1 = twid(kq, 2048), be2 = cmul(be1, be1), be3 = cmul(be1, be2);
                YLD(YF2, 1);
                wg_wait<0>();
                pin(za);
                pin(zb);
                pinu(af);
                STAMP3(32);
                c2 z[4];
                auto pack = [&](int jb, int b) {
                    af[16 * (b >> 1) + 4 * jb + (b & 1)] = pkv(z[b].x);
                    af[16 * (b >> 1) + 4 * jb + 2 + (b & 1)] = pkv(z[b].y);
                };
#pragma unroll
                for (int jb = 0; jb < 4; jb++) {
                    if (jb == 2) STAMP3(37);
                    if (jb == 1) {
#pragma unroll
                        for (int j = 0; j < 4; j++)
                            wad[j] = sb + OFF_W + (8 + (((kap ? 3 : 4) - j - q) & 3)) * WPITCH + ((-2 * kap) & 15) + 1024 - 2 * k1 - 128 * q;
                    }
                    c2 W[4];
                    auto next = [&](int j) {
                        W[j] = {{upv(wn[4 * j]), upv(wn[4 * j + 1])}, {upv(wn[4 * j + 2]), upv(wn[4 * j + 3])}};
                        if (jb < 3) {
#pragma unroll
                            for (int n = 0; n < 4; n++) wn[4 * j + n] = lds_u16(wad[j] + (jb ? 512 - 512 * jb - (n & 1) * 64 : 512 + (n & 1) * 64) + (n & 2) * (2 * WPITCH));
                        }
                    };
                    const int i = 8 * jb;
                    const c2 z0 = {{za[i], za[i + 1]}, {za[i + 4], za[i + 5]}};
                    if (jb) pack(jb - 1, 1);
                    next(0);
                    c2 s0 = cfma2<false>({{zb[i], zb[i + 1]}, {zb[i + 4], zb[i + 5]}}, both(be2), z0), s1 = tw2(z0, s0);
                    YLD(YF2, 2);
                    if (jb) pack(jb - 1, 3);
                    if (jb == 3) load_T(T, t7);
                    next(1);
                    const c2 z1 = cmul2<false>({{za[i + 2], za[i + 3]}, {za[i + 6], za[i + 7]}}, both(be1));
                    YLD(YF2, 3);
                    c2 s2 = cfma2<false>({{zb[i + 2], zb[i + 3]}, {zb[i + 6], zb[i + 7]}}, both(be3), z1), s3 = tw2(z1, s2);
                    YLD(YF2, 1);
                    c2 x0, x1, x2, x3;
                    next(2);
                    bfly2(s0, s2, x0, x2);
                    const c2 y0 = jb < 2 ? cmul2<false>(x0, W[0]) : cmul2<true>(x0, W[0]);
                    YLD(YF2, 2);
                    next(3);
                    bflyi2(s1, s3, x1, x3);
                    const c2 y1 = jb < 2 ? cmul2<false>(x1, W[1]) : cmul2<true>(x1, W[1]);
                    YLD(YF2, 1);
                    s0 = jb < 2 ? cfma2<false>(x2, W[2], y0) : cfma2<true>(x2, W[2], y0);
                    s1 = tw2(y0, s0);
                    YLD(YF2, 3);
                    s2 = jb < 2 ? cfma2<false>(x3, W[3], y1) : cfma2<true>(x3, W[3], y1);
                    s3 = tw2(y1, s2);
                    YLD(YF2, 2);
                    bfly2(s0, s2, z[0], x2);
                    z[2] = cmul2<true>(x2, both(be2));
                    pack(jb, 0);
                    YLD(YF2, 1);
                    bflyi2(s1, s3, x3, x1);
                    pack(jb, 2);
                    z[1] = cmul2<true>(x1, both(be1));
                    YLD(YF2, 3);
                    z[3] = cmul2<true>(x3, both(be3));
                    YLD(YF2, 1);
                }
                pack(3, 1);
                pack(3, 3);
                pinu(af);
                wg_fence();
                mma64_rs<1, 0>(ya, af, dF); mma64_rs<1, 1>(ya, af + 4, dF + 128); mma64_rs<1, 1>(ya, af + 8, dF + 256); mma64_rs<1, 1>(ya, af + 12, dF + 384);
                wg_commit();
                mma64_rs<1, 0>(yb, af + 16, dF); mma64_rs<1, 1>(yb, af + 20, dF + 128); mma64_rs<1, 1>(yb, af + 24, dF + 256); mma64_rs<1, 1>(yb, af + 28, dF + 384);
                wg_commit();
                STAMP3(33);
                if (w == 2) fence_async_sm();
                __syncwarp();
                if (lane == 0) mbar_arrive(bars + B_WFREE);
                {
                    const uint32_t a0 = buf + (mi & 1) * 4096 + (16 * w + 8 * (mi >> 1) + gl) * 64;
#pragma unroll
                    for (int u = 0; u < 2; u++)
#pragma unroll
                        for (int c = 0; c < 4; c++) {
                            if (c == 0) {
                                if (u == 0) { wg_wait<1>(); pin(ya); STAMP3(34); }
                                else { wg_wait<0>(); pin(yb); pinu(af); }
                            }
                            const int i = 8 * c;
                            const float(&yy)[32] = u ? yb : ya;
                            const cf x0 = cmulc({yy[i], yy[i + 1]}, T[2 * c]), x1 = cmulc({yy[i + 4], yy[i + 5]}, T[2 * c + 1]);
                            const uint32_t o0 = pk(x0.x, x1.x), o2 = pk(x0.y, x1.y);
                            YLD(YF2, 3);
                            const cf y0 = cmulc({yy[i + 2], yy[i + 3]}, T[2 * c]), y1 = cmulc({yy[i + 6], yy[i + 7]}, T[2 * c + 1]);
                            stsm4(a0 + u * 8192 + ((c ^ (gl >> 1)) << 4), o0, pk(y0.x, y1.x), o2, pk(y0.y, y1.y));
                            YLD(YF2, 2 - (c & 1));
                        }
                }
                STAMP3(38);
                const uint32_t flip = ((g & 1) && !(un >> 24)) ? 0x80008000u : 0u, flipt = flip | (tag & ~tmask);
                const int rw = 8 * w + 4 * (mi & 1) + (gl >> 1);
                const uint32_t a0 = (extra ? ((gl & 1) == gi ? sb + 32768 : sb + 65536) : buf) + rw * 64 +
                                    (((((gl & 1) << 1) | ((mi >> 1) ^ ((un >> 17) & 1))) ^ ((rw >> 1) & 3)) << 4);
                auto put = [&](const float (&v)[32], uint32_t a) {
#pragma unroll
                    for (int i = 0; i < 32; i += 8)
                        stsm4(a + (i >> 4) * 2048 + (i & 8) * 1024, (pk(v[i], v[i + 1]) & tmask) ^ flipt, (pk(v[i + 2], v[i + 3]) & tmask) ^ flipt,
                              pk(v[i + 4], v[i + 5]) ^ flip, pk(v[i + 6], v[i + 7]) ^ flip);
                };
                auto staged = [&](int b, int n) {
                    fence_async_sm();
                    __syncwarp();
                    if (lane < n) mbar_arrive(bars + b);
                };
                fence_async_sm();
                bar_sync(3, 128);
                float va[32], vb[32];
                wg_fence();
                mma64_ss<1, 0>(va, dF, dB); mma64_ss<1, 0>(vb, dF, dB + 512);
                mma64_ss<1, 1>(va, dF + 128, dB + 64); mma64_ss<1, 1>(vb, dF + 128, dB + 576);
                mma64_ss<1, 1>(va, dF + 256, dB + 128); mma64_ss<1, 1>(vb, dF + 256, dB + 640);
                mma64_ss<1, 1>(va, dF + 384, dB + 192); mma64_ss<1, 1>(vb, dF + 384, dB + 704);
                wg_commit();
                STAMP3(35);
                uint32_t bad = 0;
                if (!gi) {
                    mbar_wait(bars + B_UIN + 8, 0);
                    bad = tag_bad(tga + 16384, tag);
                }
                wg_wait<0>();
                pin(va);
                pin(vb);
                STAMP3(36);
                ok = wg_all_ok(bad, 3);
                put(va, a0);
                if (gi) {
                    if (VSPLIT) staged(B_STG, 1);
                    put(vb, a0 + 4096);
                    staged(VSPLIT ? B_STGU : B_STG, 1 + VSPLIT);
                    break;
                }
                constexpr uint64_t dN = mkdesc(OFF_P + 16384, 4096, 512, 2);
                wg_fence();
                mma128_first(acc, dF, dN);
                mma128_ss<0, 0, 1, 1>(acc, dF + 2, dN + 64);
                mma128_ss<0, 0, 1, 1>(acc, dF + 4, dN + 128);
                mma128_ss<0, 0, 1, 1>(acc, dF + 6, dN + 192);
                wg_commit();
                put(vb, a0 + 4096);
                if (!VDEFER) staged(B_STG, 1);
                wg_wait<0>();
                pin(acc);
            }
            if (extra) return;
        }
        uint2 xd[16], dd;
        auto skip = [&]() {
            const int lane = (threadIdx.x + p.zero[2]) & 31;
            const uint2* xp = (const uint2*)(p.xb + (uint32_t)((tc * 128 + 64 * (w & 1) + 32 * hf + 8 * (w >> 1)) * 1024 + cb * 128)) + lane;
            dd = __ldg((const uint2*)(p.dsk + cb * 128) + lane);
#pragma unroll
            for (int j = 0; j < 16; j++) {
                if (PACE_X && j && j % X_GRP == 0) __nanosleep(PACE_X);
                asm volatile("ld.global.nc" XNA ".v2.b32 {%0,%1}, [%2];" : "=r"(xd[j].x), "=r"(xd[j].y) : "l"(xp + ((j >> 3) * 16 + (j & 7)) * 256));
            }
        };
        auto skip2 = [&]() {
#pragma unroll
            for (int j = 0; j < 16; j++) {
                if (j % 4 == 0) YIELD();
                asm volatile("fma.rn.bf16x2 %0, %0, %1, %2;" : "+r"(xd[j].x) : "r"(dd.x), "r"(0x80008000u));
                asm volatile("fma.rn.bf16x2 %0, %0, %1, %2;" : "+r"(xd[j].y) : "r"(dd.y), "r"(0x80008000u));
            }
            YIELD();
        };
        {
            INDICES(5)
            uint32_t sp[8];
#pragma unroll
            for (int j = 0; j < 2; j++) { const uint4 v = ldtab(TAB_SP + j * 512 + t7 * 4); sp[4 * j] = v.x; sp[4 * j + 1] = v.y; sp[4 * j + 2] = v.z; sp[4 * j + 3] = v.w; }
            cf tw[8];
            load_tw(tw, k1);
            tw[4].x *= 2.f; tw[4].y *= 2.f;
            const uint32_t tag = get_epoch(bars) & 1;
            const uint32_t in = sb + OFF_P + hf * 8192;
            constexpr uint64_t dF = mkdesc(OFF_F, 16, 1024, 1);
            const uint64_t dB = mkdesc(OFF_P, 2048, 256, 3) + hf * 512;
            float ae[32], ao[32];
            if (XAT < 0) skip();
            c2 ev[2][4];
            auto blk = [&](const float (&a)[32], int i) { return c2{{a[i], a[i + 1]}, {a[i + 2], a[i + 3]}}; };
            auto unfold = [&](c2 a, c2 u, int n, c2& zn, c2& zm, int yl) {
                const float wc = n == 1 ? 0.92387953251128674f : (n == 2 ? 0.70710678118654752f : 0.38268343236508977f);
                const float ws = n == 3 ? 0.92387953251128674f : (n == 2 ? 0.70710678118654752f : 0.38268343236508977f);
                const v2 c = {wc, wc}, s = {ws, ws}, two = {2.f, 2.f};
                const c2 y = cmul2<false>(a, both(tw[n])), t = both(tw[8 - n]);
                c2 E;
                E.x = fnm2(u.y, t.y, y.x); E.y = fnm2(u.x, t.y, y.y); E.x = fma2(u.x, t.x, E.x); E.y = fnm2(u.y, t.x, E.y);
                YLD(yl, 2);
                const c2 D = tw2(y, E);
                zn.x = fnm2(D.y, c, E.x); zn.y = fma2(D.y, s, E.y); zn.x = fma2(D.x, s, zn.x); zn.y = fma2(D.x, c, zn.y);
                zm.x = tw2(E.x, zn.x); zm.y = fnm2(E.y, two, zn.y);
                YLD(yl, 1);
            };
#pragma unroll
            for (int rgn = 0; rgn < 2; rgn++) {
#pragma unroll 1
                for (int n = 0; n < 4096; n++) {
                    mbar_wait(bars + B_VIN + rgn * 16 + hf * 8, n & 1);
                    if (rgn) STAMP(25);
                    if (rgn == 0) {
                        pinu(sp);
                        wg_fence();
                        mma48_ss<0>(ae, dF, dB + 128); mma16_rs<0>(ae, sp[0], 0u, sp[1], 0u, dB);
                        mma48_ss<1>(ae, dF + 2, dB + 160); mma16_rs<1>(ae, sp[2], 0u, sp[3], 0u, dB + 32);
                        mma48_ss<1>(ae, dF + 4, dB + 192); mma16_rs<1>(ae, 0u, sp[4], 0u, sp[5], dB + 64);
                        mma48_ss<1>(ae, dF + 6, dB + 224); mma16_rs<1>(ae, 0u, sp[6], 0u, sp[7], dB + 96);
                    } else {
                        wg_fence();
                        mma64_ss<0, 0>(ao, dF, dB + 1024);
                        mma64_ss<0, 1>(ao, dF + 2, dB + 1056);
                        mma64_ss<0, 1>(ao, dF + 4, dB + 1088);
                        mma64_ss<0, 1>(ao, dF + 6, dB + 1120);
                    }
                    wg_commit();
                    const bool ok = wg_all_ok(tag_bad(in + rgn * 16384 + t7 * 64 + (t7 & 6) * 8, tag), hf ? 3 : 8);
                    wg_wait<0>();
                    if (rgn) pin(ao);
                    else { pin(ae); pinu(sp); }
                    if (ok) break;
                    wg_all_ok(0, hf ? 3 : 8);
                    if (w == 0 && elect_one()) {
                        mbar_expect_tx(bars + B_VIN + rgn * 16 + hf * 8, 8192);
                        bulk_ld(in + rgn * 16384, g_V + (uint32_t)((fb * 32 + fpos) * 32768 + rgn * 16384 + hf * 8192), 8192, bars + B_VIN + rgn * 16 + hf * 8);
                    }
                }
                if (rgn == 0) {
#pragma unroll
                    for (int cl = 0; cl < 2; cl++) {
                        const c2 b = blk(ae, 4 * cl), z0 = {add2(b.x, b.y), sub2(b.x, b.y)};
                        const c2 a0 = cfma2<false>(blk(ae, 16 + 4 * cl), both(tw[4]), z0), a1 = tw2(z0, a0);
                        YIELD();
                        c2 z2, z6, a2, a3;
                        unfold(blk(ae, 8 + 4 * cl), blk(ae, 24 + 4 * cl), 2, z2, z6, 2);
                        bfly2(z2, z6, a2, a3);
                        bfly2(a0, a2, ev[cl][0], ev[cl][2]);
                        YIELD();
                        bflyi2(a1, a3, ev[cl][1], ev[cl][3]);
                    }
                    YIELD();
                    if (XAT == 0) skip();
                    if (XAT <= 0) skip2();
                }
            }
            if (XAT == 1) skip();
            const uint32_t a0 = in + (8 * w + gl + 32 * (mi & 1)) * 32 + (mi >> 1) * 16384 + (gl & 4) * 4;
#pragma unroll
            for (int cl = 0; cl < 2; cl++) {
                c2 z1, z3, z5, z7, a4, a5, a6, a7;
                unfold(blk(ao, 4 * cl), blk(ao, 24 + 4 * cl), 1, z1, z7, YF3);
                if (cl == 0) wg_all_ok(0, hf ? 3 : 8);
                unfold(blk(ao, 8 + 4 * cl), blk(ao, 16 + 4 * cl), 3, z3, z5, YF3);
                bfly2(z1, z5, a4, a5);
                bfly2(z3, z7, a6, a7);
                YLD(YF3, 2);
                dft8_end<YF3>(ev[cl], a4, a5, a6, a7, [&](int r, c2 u, c2 v) { stsm4((a0 ^ (cl * 16)) + r * 2048, pkv(u.x), pkv(u.y), pkv(v.x), pkv(v.y)); });
            }
            if (XAT == 2) skip();
            bar_sync(7, 256);
            STAMP(26);
        }
        INDICES(6)
        const int t0 = tc * 128 + 64 * (w & 1) + 32 * hf + 8 * (w >> 1);
        {
            const int n0 = 16 * hf + 4 * w + mi;
            const uint32_t la = sb + OFF_P + (gl >> 2) * 8192 + n0 * 32 + ((((gl >> 1) & 1) ^ (w & 1)) << 4) + (gl & 1) * 8;
            float* op = p.out + (size_t)(4 * n0 + fb) * 2048 + fcb * 32 + gl * 4;
#pragma unroll
            for (int it = 0; it < 16; it += 4) {
                uint32_t u[8], fast;
                asm volatile("{.reg .pred p; mbarrier.test_wait.parity.shared::cta.b64 p, [%1], 0; selp.u32 %0, 1, 0, p;}" : "=r"(fast) : "r"(bars + B_LDONE) : "memory");
#pragma unroll
                for (int i = 0; i < 4; i++) asm volatile("ld.shared.v2.b32 {%0,%1}, [%2];" : "=r"(u[2 * i]), "=r"(u[2 * i + 1]) : "r"(la + ((it + i) & 7) * 1024 + ((it + i) >> 3) * 16384) : "memory");
#pragma unroll
                for (int i = 0; i < 4; i++) {
                    const int j = it + i;
                    stg128(op + (size_t)j * 128 * 2048, u[2 * i] << 16, u[2 * i] & 0xffff0000u, u[2 * i + 1] << 16, u[2 * i + 1] & 0xffff0000u);
                    if (!fast) __nanosleep(PACE_O);
                }
            }
            STAMP(27);
        }
        if (XAT > 0) skip2();
        const uint32_t ra = sb + hf * 16384 + w * 4096;
        float* ob = p.out + (size_t)t0 * 2048 + 1024 + cb * 128 + lane * 4;
#pragma unroll
        for (int mb = 0; mb < 2; mb++) {
            if (hf == 0) { if (mb == 0) bar_sync(9, 256); else bar_sync(11, 256); }
            else { if (mb == 0) bar_sync(10, 256); else bar_sync(12, 256); }
            if (mb == 0) STAMP(17);
            float v[8][4];
#pragma unroll
            for (int j = 0; j < 8; j++) lds128f(ra + (mb ? 0 : (NST - 1) * 32768) + j * 512 + ((lane * 16) ^ ((j & 3) * 32)), v[j][0], v[j][1], v[j][2], v[j][3]);
#pragma unroll
            for (int j = 0; j < 8; j++) {
                const uint2 s = xd[8 * mb + j];
                stg128(ob + (16 * mb + j) * 2048, __float_as_uint(v[j][0] + up(s.x)), __float_as_uint(v[j][1] + __uint_as_float(s.x & 0xffff0000u)),
                       __float_as_uint(v[j][2] + up(s.y)), __float_as_uint(v[j][3] + __uint_as_float(s.y & 0xffff0000u)));
            }
        }
        STAMP(9);
    }
}

typedef CUresult (*EncodeFn)(CUtensorMap*, CUtensorMapDataType, cuuint32_t, void*, const cuuint64_t*, const cuuint64_t*, const cuuint32_t*,
                             const cuuint32_t*, CUtensorMapInterleave, CUtensorMapSwizzle, CUtensorMapL2promotion, CUtensorMapFloatOOBfill);

static CUtensorMap make_map(EncodeFn enc, const void* ptr, int rank, const cuuint64_t* dims, const cuuint64_t* strides, const cuuint32_t* box,
                            CUtensorMapSwizzle swz, CUtensorMapL2promotion promo, CUtensorMapDataType dt = CU_TENSOR_MAP_DATA_TYPE_BFLOAT16) {
    CUtensorMap m;
    const cuuint32_t es[5] = {1, 1, 1, 1, 1};
    enc(&m, dt, rank, const_cast<void*>(ptr), dims, strides, box, es, CU_TENSOR_MAP_INTERLEAVE_NONE, swz, promo,
        CU_TENSOR_MAP_FLOAT_OOB_FILL_NONE);
    return m;
}

extern "C" void kernel_launch(void* const* d_in, const int* in_sizes, int n_in, void* d_out, int out_size) {
    void* fn = nullptr;
    cudaDriverEntryPointQueryResult qr;
    cudaGetDriverEntryPoint("cuTensorMapEncodeTiled", &fn, cudaEnableDefault, &qr);
    EncodeFn enc = (EncodeFn)fn;
    void *pU, *pV;
    cudaGetSymbolAddress(&pU, g_U);
    cudaGetSymbolAddress(&pV, g_V);
    const CUtensorMapL2promotion P256 = CU_TENSOR_MAP_L2_PROMOTION_L2_256B, P0 = CU_TENSOR_MAP_L2_PROMOTION_NONE;

    const cuuint64_t dX[5] = {1024, 2, 4, 16, 16}, sX[4] = {2048, 32 * 2048, 2 * 2048, 128 * 2048};
    const cuuint32_t bX[5] = {64, 2, 4, 16, 1};
    CUtensorMap tmX = make_map(enc, d_in[3], 5, dX, sX, bX, CU_TENSOR_MAP_SWIZZLE_128B, (CUtensorMapL2promotion)PRX);
    const cuuint64_t dB[4] = {1024, 8, 2, 96}, sB[3] = {2048, 256 * 2048, 8 * 2048}, dC[4] = {1024, 8, 2, 64}, sC[3] = {2048, 8 * 2048, 16 * 2048};
    const cuuint32_t bB[4] = {64, 8, 2, 4};
    CUtensorMap tmBre = make_map(enc, d_in[6], 4, dB, sB, bB, CU_TENSOR_MAP_SWIZZLE_128B, (CUtensorMapL2promotion)PRB);
    CUtensorMap tmBim = make_map(enc, d_in[7], 4, dB, sB, bB, CU_TENSOR_MAP_SWIZZLE_128B, (CUtensorMapL2promotion)PRB);
    CUtensorMap tmCre = make_map(enc, d_in[8], 4, dC, sC, bB, CU_TENSOR_MAP_SWIZZLE_128B, P256);
    CUtensorMap tmCim = make_map(enc, d_in[9], 4, dC, sC, bB, CU_TENSOR_MAP_SWIZZLE_128B, P256);

    const cuuint64_t dU[2] = {8192, 256}, sU[1] = {16384};
    const cuuint32_t bS[2] = {64, UBOX};
    CUtensorMap tmUst = make_map(enc, pU, 2, dU, sU, bS, CU_TENSOR_MAP_SWIZZLE_128B, P0);
    const cuuint64_t dV[3] = {12288, 128, 2}, sV[2] = {32768, 8192};
    const cuuint32_t bV[3] = {32, VBOX, 1};
    CUtensorMap tmVst = make_map(enc, pV, 3, dV, sV, bV, CU_TENSOR_MAP_SWIZZLE_64B, P0);
    const cuuint64_t dA[4] = {1024, 64, 8, 4}, sA[3] = {32 * 2048, 4 * 2048, 2048};
    const cuuint32_t bA[4] = {16, 64, 1, 1};
    CUtensorMap tmXA = make_map(enc, d_in[0], 4, dA, sA, bA, CU_TENSOR_MAP_SWIZZLE_32B, CU_TENSOR_MAP_L2_PROMOTION_L2_128B);
    const cuuint64_t dF[2] = {512 * 1026 / 8, 4}, sF[1] = {512 * 1026};
    const cuuint32_t bF[2] = {WPITCH / 8, 4};
    CUtensorMap tmWr = make_map(enc, d_in[1], 2, dF, sF, bF, CU_TENSOR_MAP_SWIZZLE_NONE, P0, CU_TENSOR_MAP_DATA_TYPE_UINT64);
    CUtensorMap tmWi = make_map(enc, d_in[2], 2, dF, sF, bF, CU_TENSOR_MAP_SWIZZLE_NONE, P0, CU_TENSOR_MAP_DATA_TYPE_UINT64);

    Params p = {};
    p.xb = (const __nv_bfloat16*)d_in[3];
    p.lre = (const __nv_bfloat16*)d_in[4];
    p.lim = (const __nv_bfloat16*)d_in[5];
    p.ldt = (const __nv_bfloat16*)d_in[10];
    p.dsk = (const __nv_bfloat16*)d_in[11];
    p.out = (float*)d_out;
    p.da[0] = p.da[1] = mkdesc(0, 16, 1024, 1) - 1;
    p.da[2] = p.da[3] = mkdesc(0, 512, 2048, 2) - 1;
    for (int i = 0; i < 258; i++) {
        int cj;
        const int kap = kappa_of(i >> 1, i & 1), s3 = slot3_of(kap, cj);
        p.unit[i] = kap | s3 << 16 | cj << 24;
    }
    cudaFuncSetAttribute(fused_kernel, cudaFuncAttributeMaxDynamicSharedMemorySize, SMEM_BYTES);
    fused_kernel<<<130, 512, SMEM_BYTES>>>(Maps{{tmX, tmBre, tmBim, tmCre, tmCim, tmXA, tmUst, tmVst, tmWr, tmWi}}, p);
}
```

```cpp
#include <cuda_runtime.h>
#include <cuda.h>
#include <cuda_bf16.h>
#include <stdint.h>

#define NST 5
#define SB0 1024
#define WPITCH 1056
#define OFF_P (NST * 32768)
#define OFF_F (OFF_P + 32768)
#define OFF_W (OFF_F + 8192)
#define OFF_TL (OFF_W + 16 * WPITCH)
#define OFF_TM (OFF_TL + 4096)
#define OFF_T1 (OFF_TM + 4096)
#define OFF_BAR (OFF_T1 + 2048)
#define OFF_STAMP (OFF_BAR + 384)
#define SMEM_BYTES (OFF_BAR + 512)
#define B_FULL 0
#define B_EMPTY 40
#define B_STGU 80
#define B_HGO 88
#define B_LAM 120
#define B_STG 128
#define B_WFREE 136
#define B_EP 144
#define B_LDONE 152
#define B_UIN 160
#define B_WIN 176
#define B_XIN 184
#define B_VIN 200
#define B_HRTY 232
#define B_HLD 240
#define B_IDLE 280
#define B_END 288
#define B_EPOCH 288

#define PACE_U 250
#define PACE_V 120
#define PACE_O 150
#define PACE_H 120
#define HAND 1
#define HNOW 0
#define HDELAY 0
#define LDK 15
#define POLL_AT (DEFER ? 16 : 24)
#define XA_FIRST 3
#define XA_AT 0
#define YS 3
#define UDELAY 250
#define PACE_W 120
#define HINT_U 2
#define HINT_V 2
#define WPF 0
#define XAT 1
#define XNA ".L1::no_allocate"
#define PACE_X 0
#define X_GRP 4
#define GRP 0x92
#define PRO 1
#define PRX 2
#define PRB 3
#define KEEP NST
#define EARLY_U 48
#define EARLY_V 16
#define EARLY_H 4
#define WARM 0
#define WARM_NS 0
#define DEFER 0
#define YD 1
#define KMC 4
#define PFIRST 0
#define PFM 0
#define PFJ 15
#define VDEFER 1
#define VSPLIT 0
#define UBOX 32
#define SKEW 4
#define SPIN_LIMIT 32768

#define YIELD() asm volatile("pmevent 0;")
#define YF1 3
#define YF2 2
#define YF3 2
#define YLD(level, n) do { if ((level) >= (n)) YIELD(); } while (0)

__device__ __align__(1024) uint8_t g_U[4 << 20];
__device__ __align__(1024) uint8_t g_V[4 << 20];
__device__ __align__(1024) uint8_t g_H[8 << 20];
__device__ __align__(1024) uint4 g_carry[16 * 512];
__device__ __align__(1024) unsigned g_hcnt[16 * 64];
__device__ __align__(128) unsigned g_cnt[128];
__device__ __align__(128) unsigned g_epoch[129 * 8];

#define RECL(i) do { } while (0)
#define STAMP(i) do { } while (0)
#define STAMPR(i) do { } while (0)
#define STAMPW(a, b) do { } while (0)
#define STAMPX(a, b) do { } while (0)
#define STAMP5(i) do { } while (0)
#define STAMP3(i) do { } while (0)

#define TAB_FG 0
#define TAB_F1 2048
#define TAB_T 4096
#define TAB_SP 6144
#define TAB_TW 7168
#define TAB_FX 7680
__device__ __align__(1024) const uint32_t g_tab[7808] = {
0x80003d80,0x80003d80,0x80003d80,0x80003d80,0x80003d80,0x80003d80,0x80003d80,0x80003d80,0x80003d80,0x80003d80,0x80003d80,0x80003d80,0x80003d80,0x80003d80,0x80003d80,0x80003d80,
0x80003d80,0x80003d80,0x80003d80,0x80003d80,0x80003d80,0x80003d80,0x80003d80,0x80003d80,0x80003d80,0x80003d80,0x80003d80,0x80003d80,0x80003d80,0x80003d80,0x80003d80,0x80003d80,
0x3c483d7b,0x3d0e3d55,0x3d553d0e,0x3d7b3c48,0x80003d80,0x3cc43d6d,0x3d353d35,0x3d6d3cc4,0x3d7bbc48,0x3d55bd0e,0x3d0ebd55,0x3c48bd7b,0x3d800000,0x3d6dbcc4,0x3d35bd35,0x3cc4bd6d,
0xbc48bd7b,0xbd0ebd55,0xbd55bd0e,0xbd7bbc48,0x8000bd80,0xbcc4bd6d,0xbd35bd35,0xbd6dbcc4,0xbd7b3c48,0xbd553d0e,0xbd0e3d55,0xbc483d7b,0xbd800000,0xbd6d3cc4,0xbd353d35,0xbcc43d6d,
0x8000bd80,0xbd35bd35,0xbd800000,0xbd353d35,0xbcc4bd6d,0xbd6dbcc4,0xbd6d3cc4,0xbcc43d6d,0x80003d80,0x3d353d35,0x3d800000,0x3d35bd35,0x3cc43d6d,0x3d6d3cc4,0x3d6dbcc4,0x3cc4bd6d,
0x8000bd80,0xbd35bd35,0xbd800000,0xbd353d35,0xbcc4bd6d,0xbd6dbcc4,0xbd6d3cc4,0xbcc43d6d,0x80003d80,0x3d353d35,0x3d800000,0x3d35bd35,0x3cc43d6d,0x3d6d3cc4,0x3d6dbcc4,0x3cc4bd6d,
0xbd553d0e,0x3c483d7b,0x3d7b3c48,0x3d0ebd55,0xbd800000,0xbcc43d6d,0x3d353d35,0x3d6dbcc4,0x3d0e3d55,0x3d7bbc48,0x3c48bd7b,0xbd55bd0e,0x80003d80,0x3d6d3cc4,0x3d35bd35,0xbcc4bd6d,
0x3d55bd0e,0xbc48bd7b,0xbd7bbc48,0xbd0e3d55,0x3d800000,0x3cc4bd6d,0xbd35bd35,0xbd6d3cc4,0xbd0ebd55,0xbd7b3c48,0xbc483d7b,0x3d553d0e,0x8000bd80,0xbd6dbcc4,0xbd353d35,0x3cc43d6d,
0x80003d80,0x3d800000,0x8000bd80,0xbd800000,0x3d353d35,0x3d35bd35,0xbd35bd35,0xbd353d35,0x80003d80,0x3d800000,0x8000bd80,0xbd800000,0x3d353d35,0x3d35bd35,0xbd35bd35,0xbd353d35,
0x80003d80,0x3d800000,0x8000bd80,0xbd800000,0x3d353d35,0x3d35bd35,0xbd35bd35,0xbd353d35,0x80003d80,0x3d800000,0x8000bd80,0xbd800000,0x3d353d35,0x3d35bd35,0xbd35bd35,0xbd353d35,
0xbd55bd0e,0xbc483d7b,0x3d7bbc48,0xbd0ebd55,0x8000bd80,0xbd6d3cc4,0x3d353d35,0x3cc4bd6d,0xbd0e3d55,0x3d7b3c48,0xbc48bd7b,0xbd553d0e,0xbd800000,0x3cc43d6d,0x3d35bd35,0xbd6dbcc4,
0x3d553d0e,0x3c48bd7b,0xbd7b3c48,0x3d0e3d55,0x80003d80,0x3d6dbcc4,0xbd35bd35,0xbcc43d6d,0x3d0ebd55,0xbd7bbc48,0x3c483d7b,0x3d55bd0e,0x3d800000,0xbcc4bd6d,0xbd353d35,0x3d6d3cc4,
0x8000bd80,0xbd353d35,0x3d800000,0xbd35bd35,0xbd6dbcc4,0x3cc43d6d,0x3cc4bd6d,0xbd6d3cc4,0x80003d80,0x3d35bd35,0xbd800000,0x3d353d35,0x3d6d3cc4,0xbcc4bd6d,0xbcc43d6d,0x3d6dbcc4,
0x8000bd80,0xbd353d35,0x3d800000,0xbd35bd35,0xbd6dbcc4,0x3cc43d6d,0x3cc4bd6d,0xbd6d3cc4,0x80003d80,0x3d35bd35,0xbd800000,0x3d353d35,0x3d6d3cc4,0xbcc4bd6d,0xbcc43d6d,0x3d6dbcc4,
0x3c48bd7b,0xbd0e3d55,0x3d55bd0e,0xbd7b3c48,0x3d800000,0xbd6dbcc4,0x3d353d35,0xbcc4bd6d,0xbd7bbc48,0x3d553d0e,0xbd0ebd55,0x3c483d7b,0x8000bd80,0xbcc43d6d,0x3d35bd35,0xbd6d3cc4,
0xbc483d7b,0x3d0ebd55,0xbd553d0e,0x3d7bbc48,0xbd800000,0x3d6d3cc4,0xbd35bd35,0x3cc43d6d,0x3d7b3c48,0xbd55bd0e,0x3d0e3d55,0xbc48bd7b,0x80003d80,0x3cc4bd6d,0xbd353d35,0x3d6dbcc4,
0x3d800000,0x3d800000,0x3d800000,0x3d800000,0x3d800000,0x3d800000,0x3d800000,0x3d800000,0x3d800000,0x3d800000,0x3d800000,0x3d800000,0x3d800000,0x3d800000,0x3d800000,0x3d800000,
0x3d800000,0x3d800000,0x3d800000,0x3d800000,0x3d800000,0x3d800000,0x3d800000,0x3d800000,0x3d800000,0x3d800000,0x3d800000,0x3d800000,0x3d800000,0x3d800000,0x3d800000,0x3d800000,
0x3d7bbc48,0x3d55bd0e,0x3d0ebd55,0x3c48bd7b,0x3d800000,0x3d6dbcc4,0x3d35bd35,0x3cc4bd6d,0xbc48bd7b,0xbd0ebd55,0xbd55bd0e,0xbd7bbc48,0xbd80,0xbcc4bd6d,0xbd35bd35,0xbd6dbcc4,
0xbd7b3c48,0xbd553d0e,0xbd0e3d55,0xbc483d7b,0xbd800000,0xbd6d3cc4,0xbd353d35,0xbcc43d6d,0x3c483d7b,0x3d0e3d55,0x3d553d0e,0x3d7b3c48,0x3d80,0x3cc43d6d,0x3d353d35,0x3d6d3cc4,
0xbd800000,0xbd353d35,0x3d80,0x3d353d35,0xbd6d3cc4,0xbcc43d6d,0x3cc43d6d,0x3d6d3cc4,0x3d800000,0x3d35bd35,0xbd80,0xbd35bd35,0x3d6dbcc4,0x3cc4bd6d,0xbcc4bd6d,0xbd6dbcc4,
0xbd800000,0xbd353d35,0x3d80,0x3d353d35,0xbd6d3cc4,0xbcc43d6d,0x3cc43d6d,0x3d6d3cc4,0x3d800000,0x3d35bd35,0xbd80,0xbd35bd35,0x3d6dbcc4,0x3cc4bd6d,0xbcc4bd6d,0xbd6dbcc4,
0x3d0e3d55,0x3d7bbc48,0x3c48bd7b,0xbd55bd0e,0x3d80,0x3d6d3cc4,0x3d35bd35,0xbcc4bd6d,0x3d55bd0e,0xbc48bd7b,0xbd7bbc48,0xbd0e3d55,0x3d800000,0x3cc4bd6d,0xbd35bd35,0xbd6d3cc4,
0xbd0ebd55,0xbd7b3c48,0xbc483d7b,0x3d553d0e,0xbd80,0xbd6dbcc4,0xbd353d35,0x3cc43d6d,0xbd553d0e,0x3c483d7b,0x3d7b3c48,0x3d0ebd55,0xbd800000,0xbcc43d6d,0x3d353d35,0x3d6dbcc4,
0x3d800000,0xbd80,0xbd800000,0x3d80,0x3d35bd35,0xbd35bd35,0xbd353d35,0x3d353d35,0x3d800000,0xbd80,0xbd800000,0x3d80,0x3d35bd35,0xbd35bd35,0xbd353d35,0x3d353d35,
0x3d800000,0xbd80,0xbd800000,0x3d80,0x3d35bd35,0xbd35bd35,0xbd353d35,0x3d353d35,0x3d800000,0xbd80,0xbd800000,0x3d80,0x3d35bd35,0xbd35bd35,0xbd353d35,0x3d353d35,
0xbd0e3d55,0x3d7b3c48,0xbc48bd7b,0xbd553d0e,0xbd800000,0x3cc43d6d,0x3d35bd35,0xbd6dbcc4,0x3d553d0e,0x3c48bd7b,0xbd7b3c48,0x3d0e3d55,0x3d80,0x3d6dbcc4,0xbd35bd35,0xbcc43d6d,
0x3d0ebd55,0xbd7bbc48,0x3c483d7b,0x3d55bd0e,0x3d800000,0xbcc4bd6d,0xbd353d35,0x3d6d3cc4,0xbd55bd0e,0xbc483d7b,0x3d7bbc48,0xbd0ebd55,0xbd80,0xbd6d3cc4,0x3d353d35,0x3cc4bd6d,
0xbd800000,0x3d353d35,0xbd80,0xbd353d35,0xbcc43d6d,0x3d6dbcc4,0xbd6dbcc4,0x3cc43d6d,0x3d800000,0xbd35bd35,0x3d80,0x3d35bd35,0x3cc4bd6d,0xbd6d3cc4,0x3d6d3cc4,0xbcc4bd6d,
0xbd800000,0x3d353d35,0xbd80,0xbd353d35,0xbcc43d6d,0x3d6dbcc4,0xbd6dbcc4,0x3cc43d6d,0x3d800000,0xbd35bd35,0x3d80,0x3d35bd35,0x3cc4bd6d,0xbd6d3cc4,0x3d6d3cc4,0xbcc4bd6d,
0xbd7bbc48,0x3d553d0e,0xbd0ebd55,0x3c483d7b,0xbd80,0xbcc43d6d,0x3d35bd35,0xbd6d3cc4,0xbc483d7b,0x3d0ebd55,0xbd553d0e,0x3d7bbc48,0xbd800000,0x3d6d3cc4,0xbd35bd35,0x3cc43d6d,
0x3d7b3c48,0xbd55bd0e,0x3d0e3d55,0xbc48bd7b,0x3d80,0x3cc4bd6d,0xbd353d35,0x3d6dbcc4,0x3c48bd7b,0xbd0e3d55,0x3d55bd0e,0xbd7b3c48,0x3d800000,0xbd6dbcc4,0x3d353d35,0xbcc4bd6d,
0x80003d80,0x8000bd80,0x80003d80,0x8000bd80,0x3d800000,0xbd800000,0x3d800000,0xbd800000,0x80003d80,0x8000bd80,0x80003d80,0x8000bd80,0x3d800000,0xbd800000,0x3d800000,0xbd800000,
0x80003d80,0x8000bd80,0x80003d80,0x8000bd80,0x3d800000,0xbd800000,0x3d800000,0xbd800000,0x80003d80,0x8000bd80,0x80003d80,0x8000bd80,0x3d800000,0xbd800000,0x3d800000,0xbd800000,
0x3d7bbc48,0xbd553d0e,0x3d0ebd55,0xbc483d7b,0x80003d80,0xbcc4bd6d,0x3d353d35,0xbd6dbcc4,0xbc48bd7b,0x3d0e3d55,0xbd55bd0e,0x3d7b3c48,0x3d800000,0xbd6d3cc4,0x3d35bd35,0xbcc43d6d,
0xbd7b3c48,0x3d55bd0e,0xbd0e3d55,0x3c48bd7b,0x8000bd80,0x3cc43d6d,0xbd35bd35,0x3d6d3cc4,0x3c483d7b,0xbd0ebd55,0x3d553d0e,0xbd7bbc48,0xbd800000,0x3d6dbcc4,0xbd353d35,0x3cc4bd6d,
0x8000bd80,0x3d353d35,0xbd800000,0x3d35bd35,0xbd6d3cc4,0x3cc4bd6d,0x3cc43d6d,0xbd6dbcc4,0x80003d80,0xbd35bd35,0x3d800000,0xbd353d35,0x3d6dbcc4,0xbcc43d6d,0xbcc4bd6d,0x3d6d3cc4,
0x8000bd80,0x3d353d35,0xbd800000,0x3d35bd35,0xbd6d3cc4,0x3cc4bd6d,0x3cc43d6d,0xbd6dbcc4,0x80003d80,0xbd35bd35,0x3d800000,0xbd353d35,0x3d6dbcc4,0xbcc43d6d,0xbcc4bd6d,0x3d6d3cc4,
0x3d0e3d55,0xbd7b3c48,0x3c48bd7b,0x3d553d0e,0xbd800000,0x3cc4bd6d,0x3d353d35,0xbd6d3cc4,0x3d55bd0e,0x3c483d7b,0xbd7bbc48,0x3d0ebd55,0x80003d80,0xbd6dbcc4,0x3d35bd35,0x3cc43d6d,
0xbd0ebd55,0x3d7bbc48,0xbc483d7b,0xbd55bd0e,0x3d800000,0xbcc43d6d,0xbd35bd35,0x3d6dbcc4,0xbd553d0e,0xbc48bd7b,0x3d7b3c48,0xbd0e3d55,0x8000bd80,0x3d6d3cc4,0xbd353d35,0xbcc4bd6d,
0x80003d80,0xbd800000,0x8000bd80,0x3d800000,0x3d35bd35,0x3d353d35,0xbd353d35,0xbd35bd35,0x80003d80,0xbd800000,0x8000bd80,0x3d800000,0x3d35bd35,0x3d353d35,0xbd353d35,0xbd35bd35,
0x80003d80,0xbd800000,0x8000bd80,0x3d800000,0x3d35bd35,0x3d353d35,0xbd353d35,0xbd35bd35,0x80003d80,0xbd800000,0x8000bd80,0x3d800000,0x3d35bd35,0x3d353d35,0xbd353d35,0xbd35bd35,
0xbd0e3d55,0xbd7bbc48,0xbc48bd7b,0x3d55bd0e,0x8000bd80,0x3d6dbcc4,0x3d353d35,0xbcc43d6d,0x3d553d0e,0xbc483d7b,0xbd7b3c48,0xbd0ebd55,0xbd800000,0xbcc4bd6d,0x3d35bd35,0x3d6d3cc4,
0x3d0ebd55,0x3d7b3c48,0x3c483d7b,0xbd553d0e,0x80003d80,0xbd6d3cc4,0xbd35bd35,0x3cc4bd6d,0xbd55bd0e,0x3c48bd7b,0x3d7bbc48,0x3d0e3d55,0x3d800000,0x3cc43d6d,0xbd353d35,0xbd6dbcc4,
0x8000bd80,0x3d35bd35,0x3d800000,0x3d353d35,0xbcc43d6d,0xbd6d3cc4,0xbd6dbcc4,0xbcc4bd6d,0x80003d80,0xbd353d35,0xbd800000,0xbd35bd35,0x3cc4bd6d,0x3d6dbcc4,0x3d6d3cc4,0x3cc43d6d,
0x8000bd80,0x3d35bd35,0x3d800000,0x3d353d35,0xbcc43d6d,0xbd6d3cc4,0xbd6dbcc4,0xbcc4bd6d,0x80003d80,0xbd353d35,0xbd800000,0xbd35bd35,0x3cc4bd6d,0x3d6dbcc4,0x3d6d3cc4,0x3cc43d6d,
0xbd7bbc48,0xbd55bd0e,0xbd0ebd55,0xbc48bd7b,0x3d800000,0x3d6d3cc4,0x3d353d35,0x3cc43d6d,0xbc483d7b,0xbd0e3d55,0xbd553d0e,0xbd7b3c48,0x8000bd80,0x3cc4bd6d,0x3d35bd35,0x3d6dbcc4,
0x3d7b3c48,0x3d553d0e,0x3d0e3d55,0x3c483d7b,0xbd800000,0xbd6dbcc4,0xbd35bd35,0xbcc4bd6d,0x3c48bd7b,0x3d0ebd55,0x3d55bd0e,0x3d7bbc48,0x80003d80,0xbcc43d6d,0xbd353d35,0xbd6d3cc4,
0x3d800000,0xbd800000,0x3d800000,0xbd800000,0xbd80,0x3d80,0xbd80,0x3d80,0x3d800000,0xbd800000,0x3d800000,0xbd800000,0xbd80,0x3d80,0xbd80,0x3d80,
0x3d800000,0xbd800000,0x3d800000,0xbd800000,0xbd80,0x3d80,0xbd80,0x3d80,0x3d800000,0xbd800000,0x3d800000,0xbd800000,0xbd80,0x3d80,0xbd80,0x3d80,
0xbc48bd7b,0x3d0e3d55,0xbd55bd0e,0x3d7b3c48,0x3d800000,0xbd6d3cc4,0x3d35bd35,0xbcc43d6d,0xbd7b3c48,0x3d55bd0e,0xbd0e3d55,0x3c48bd7b,0xbd80,0x3cc43d6d,0xbd35bd35,0x3d6d3cc4,
0x3c483d7b,0xbd0ebd55,0x3d553d0e,0xbd7bbc48,0xbd800000,0x3d6dbcc4,0xbd353d35,0x3cc4bd6d,0x3d7bbc48,0xbd553d0e,0x3d0ebd55,0xbc483d7b,0x3d80,0xbcc4bd6d,0x3d353d35,0xbd6dbcc4,
0xbd800000,0x3d35bd35,0x3d80,0xbd35bd35,0x3cc43d6d,0xbd6dbcc4,0x3d6dbcc4,0xbcc43d6d,0x3d800000,0xbd353d35,0xbd80,0x3d353d35,0xbcc4bd6d,0x3d6d3cc4,0xbd6d3cc4,0x3cc4bd6d,
0xbd800000,0x3d35bd35,0x3d80,0xbd35bd35,0x3cc43d6d,0xbd6dbcc4,0x3d6dbcc4,0xbcc43d6d,0x3d800000,0xbd353d35,0xbd80,0x3d353d35,0xbcc4bd6d,0x3d6d3cc4,0xbd6d3cc4,0x3cc4bd6d,
0x3d55bd0e,0x3c483d7b,0xbd7bbc48,0x3d0ebd55,0x3d80,0xbd6dbcc4,0x3d35bd35,0x3cc43d6d,0xbd0ebd55,0x3d7bbc48,0xbc483d7b,0xbd55bd0e,0x3d800000,0xbcc43d6d,0xbd35bd35,0x3d6dbcc4,
0xbd553d0e,0xbc48bd7b,0x3d7b3c48,0xbd0e3d55,0xbd80,0x3d6d3cc4,0xbd353d35,0xbcc4bd6d,0x3d0e3d55,0xbd7b3c48,0x3c48bd7b,0x3d553d0e,0xbd800000,0x3cc4bd6d,0x3d353d35,0xbd6d3cc4,
0x3d800000,0x3d80,0xbd800000,0xbd80,0xbd35bd35,0x3d35bd35,0x3d353d35,0xbd353d35,0x3d800000,0x3d80,0xbd800000,0xbd80,0xbd35bd35,0x3d35bd35,0x3d353d35,0xbd353d35,
0x3d800000,0x3d80,0xbd800000,0xbd80,0xbd35bd35,0x3d35bd35,0x3d353d35,0xbd353d35,0x3d800000,0x3d80,0xbd800000,0xbd80,0xbd35bd35,0x3d35bd35,0x3d353d35,0xbd353d35,
0x3d553d0e,0xbc483d7b,0xbd7b3c48,0xbd0ebd55,0xbd800000,0xbcc4bd6d,0x3d35bd35,0x3d6d3cc4,0x3d0ebd55,0x3d7b3c48,0x3c483d7b,0xbd553d0e,0x3d80,0xbd6d3cc4,0xbd35bd35,0x3cc4bd6d,
0xbd55bd0e,0x3c48bd7b,0x3d7bbc48,0x3d0e3d55,0x3d800000,0x3cc43d6d,0xbd353d35,0xbd6dbcc4,0xbd0e3d55,0xbd7bbc48,0xbc48bd7b,0x3d55bd0e,0xbd80,0x3d6dbcc4,0x3d353d35,0xbcc43d6d,
0xbd800000,0xbd35bd35,0xbd80,0x3d35bd35,0x3d6d3cc4,0x3cc43d6d,0xbcc43d6d,0xbd6d3cc4,0x3d800000,0x3d353d35,0x3d80,0xbd353d35,0xbd6dbcc4,0xbcc4bd6d,0x3cc4bd6d,0x3d6dbcc4,
0xbd800000,0xbd35bd35,0xbd80,0x3d35bd35,0x3d6d3cc4,0x3cc43d6d,0xbcc43d6d,0xbd6d3cc4,0x3d800000,0x3d353d35,0x3d80,0xbd353d35,0xbd6dbcc4,0xbcc4bd6d,0x3cc4bd6d,0x3d6dbcc4,
0xbc483d7b,0xbd0e3d55,0xbd553d0e,0xbd7b3c48,0xbd80,0x3cc4bd6d,0x3d35bd35,0x3d6dbcc4,0x3d7b3c48,0x3d553d0e,0x3d0e3d55,0x3c483d7b,0xbd800000,0xbd6dbcc4,0xbd35bd35,0xbcc4bd6d,
0x3c48bd7b,0x3d0ebd55,0x3d55bd0e,0x3d7bbc48,0x3d80,0xbcc43d6d,0xbd353d35,0xbd6d3cc4,0xbd7bbc48,0xbd55bd0e,0xbd0ebd55,0xbc48bd7b,0x3d800000,0x3d6d3cc4,0x3d353d35,0x3cc43d6d,
0x80003d80,0x80003d80,0x80003d80,0x80003d80,0x8000bd80,0x8000bd80,0x8000bd80,0x8000bd80,0x80003d80,0x80003d80,0x80003d80,0x80003d80,0x8000bd80,0x8000bd80,0x8000bd80,0x8000bd80,
0x80003d80,0x80003d80,0x80003d80,0x80003d80,0x8000bd80,0x8000bd80,0x8000bd80,0x8000bd80,0x80003d80,0x80003d80,0x80003d80,0x80003d80,0x8000bd80,0x8000bd80,0x8000bd80,0x8000bd80,
0xbc48bd7b,0xbd0ebd55,0xbd55bd0e,0xbd7bbc48,0x80003d80,0x3cc43d6d,0x3d353d35,0x3d6d3cc4,0xbd7b3c48,0xbd553d0e,0xbd0e3d55,0xbc483d7b,0x3d800000,0x3d6dbcc4,0x3d35bd35,0x3cc4bd6d,
0x3c483d7b,0x3d0e3d55,0x3d553d0e,0x3d7b3c48,0x8000bd80,0xbcc4bd6d,0xbd35bd35,0xbd6dbcc4,0x3d7bbc48,0x3d55bd0e,0x3d0ebd55,0x3c48bd7b,0xbd800000,0xbd6d3cc4,0xbd353d35,0xbcc43d6d,
0x8000bd80,0xbd35bd35,0xbd800000,0xbd353d35,0x3cc43d6d,0x3d6d3cc4,0x3d6dbcc4,0x3cc4bd6d,0x80003d80,0x3d353d35,0x3d800000,0x3d35bd35,0xbcc4bd6d,0xbd6dbcc4,0xbd6d3cc4,0xbcc43d6d,
0x8000bd80,0xbd35bd35,0xbd800000,0xbd353d35,0x3cc43d6d,0x3d6d3cc4,0x3d6dbcc4,0x3cc4bd6d,0x80003d80,0x3d353d35,0x3d800000,0x3d35bd35,0xbcc4bd6d,0xbd6dbcc4,0xbd6d3cc4,0xbcc43d6d,
0x3d55bd0e,0xbc48bd7b,0xbd7bbc48,0xbd0e3d55,0xbd800000,0xbcc43d6d,0x3d353d35,0x3d6dbcc4,0xbd0ebd55,0xbd7b3c48,0xbc483d7b,0x3d553d0e,0x80003d80,0x3d6d3cc4,0x3d35bd35,0xbcc4bd6d,
0xbd553d0e,0x3c483d7b,0x3d7b3c48,0x3d0ebd55,0x3d800000,0x3cc4bd6d,0xbd35bd35,0xbd6d3cc4,0x3d0e3d55,0x3d7bbc48,0x3c48bd7b,0xbd55bd0e,0x8000bd80,0xbd6dbcc4,0xbd353d35,0x3cc43d6d,
0x80003d80,0x3d800000,0x8000bd80,0xbd800000,0xbd35bd35,0xbd353d35,0x3d353d35,0x3d35bd35,0x80003d80,0x3d800000,0x8000bd80,0xbd800000,0xbd35bd35,0xbd353d35,0x3d353d35,0x3d35bd35,
0x80003d80,0x3d800000,0x8000bd80,0xbd800000,0xbd35bd35,0xbd353d35,0x3d353d35,0x3d35bd35,0x80003d80,0x3d800000,0x8000bd80,0xbd800000,0xbd35bd35,0xbd353d35,0x3d353d35,0x3d35bd35,
0x3d553d0e,0x3c48bd7b,0xbd7b3c48,0x3d0e3d55,0x8000bd80,0xbd6d3cc4,0x3d353d35,0x3cc4bd6d,0x3d0ebd55,0xbd7bbc48,0x3c483d7b,0x3d55bd0e,0xbd800000,0x3cc43d6d,0x3d35bd35,0xbd6dbcc4,
0xbd55bd0e,0xbc483d7b,0x3d7bbc48,0xbd0ebd55,0x80003d80,0x3d6dbcc4,0xbd35bd35,0xbcc43d6d,0xbd0e3d55,0x3d7b3c48,0xbc48bd7b,0xbd553d0e,0x3d800000,0xbcc4bd6d,0xbd353d35,0x3d6d3cc4,
0x8000bd80,0xbd353d35,0x3d800000,0xbd35bd35,0x3d6d3cc4,0xbcc4bd6d,0xbcc43d6d,0x3d6dbcc4,0x80003d80,0x3d35bd35,0xbd800000,0x3d353d35,0xbd6dbcc4,0x3cc43d6d,0x3cc4bd6d,0xbd6d3cc4,
0x8000bd80,0xbd353d35,0x3d800000,0xbd35bd35,0x3d6d3cc4,0xbcc4bd6d,0xbcc43d6d,0x3d6dbcc4,0x80003d80,0x3d35bd35,0xbd800000,0x3d353d35,0xbd6dbcc4,0x3cc43d6d,0x3cc4bd6d,0xbd6d3cc4,
0xbc483d7b,0x3d0ebd55,0xbd553d0e,0x3d7bbc48,0x3d800000,0xbd6dbcc4,0x3d353d35,0xbcc4bd6d,0x3d7b3c48,0xbd55bd0e,0x3d0e3d55,0xbc48bd7b,0x8000bd80,0xbcc43d6d,0x3d35bd35,0xbd6d3cc4,
0x3c48bd7b,0xbd0e3d55,0x3d55bd0e,0xbd7b3c48,0xbd800000,0x3d6d3cc4,0xbd35bd35,0x3cc43d6d,0xbd7bbc48,0x3d553d0e,0xbd0ebd55,0x3c483d7b,0x80003d80,0x3cc4bd6d,0xbd353d35,0x3d6dbcc4,
0x3d800000,0x3d800000,0x3d800000,0x3d800000,0xbd800000,0xbd800000,0xbd800000,0xbd800000,0x3d800000,0x3d800000,0x3d800000,0x3d800000,0xbd800000,0xbd800000,0xbd800000,0xbd800000,
0x3d800000,0x3d800000,0x3d800000,0x3d800000,0xbd800000,0xbd800000,0xbd800000,0xbd800000,0x3d800000,0x3d800000,0x3d800000,0x3d800000,0xbd800000,0xbd800000,0xbd800000,0xbd800000,
0xbd7b3c48,0xbd553d0e,0xbd0e3d55,0xbc483d7b,0x3d800000,0x3d6dbcc4,0x3d35bd35,0x3cc4bd6d,0x3c483d7b,0x3d0e3d55,0x3d553d0e,0x3d7b3c48,0xbd80,0xbcc4bd6d,0xbd35bd35,0xbd6dbcc4,
0x3d7bbc48,0x3d55bd0e,0x3d0ebd55,0x3c48bd7b,0xbd800000,0xbd6d3cc4,0xbd353d35,0xbcc43d6d,0xbc48bd7b,0xbd0ebd55,0xbd55bd0e,0xbd7bbc48,0x3d80,0x3cc43d6d,0x3d353d35,0x3d6d3cc4,
0xbd800000,0xbd353d35,0x3d80,0x3d353d35,0x3d6dbcc4,0x3cc4bd6d,0xbcc4bd6d,0xbd6dbcc4,0x3d800000,0x3d35bd35,0xbd80,0xbd35bd35,0xbd6d3cc4,0xbcc43d6d,0x3cc43d6d,0x3d6d3cc4,
0xbd800000,0xbd353d35,0x3d80,0x3d353d35,0x3d6dbcc4,0x3cc4bd6d,0xbcc4bd6d,0xbd6dbcc4,0x3d800000,0x3d35bd35,0xbd80,0xbd35bd35,0xbd6d3cc4,0xbcc43d6d,0x3cc43d6d,0x3d6d3cc4,
0xbd0ebd55,0xbd7b3c48,0xbc483d7b,0x3d553d0e,0x3d80,0x3d6d3cc4,0x3d35bd35,0xbcc4bd6d,0xbd553d0e,0x3c483d7b,0x3d7b3c48,0x3d0ebd55,0x3d800000,0x3cc4bd6d,0xbd35bd35,0xbd6d3cc4,
0x3d0e3d55,0x3d7bbc48,0x3c48bd7b,0xbd55bd0e,0xbd80,0xbd6dbcc4,0xbd353d35,0x3cc43d6d,0x3d55bd0e,0xbc48bd7b,0xbd7bbc48,0xbd0e3d55,0xbd800000,0xbcc43d6d,0x3d353d35,0x3d6dbcc4,
0x3d800000,0xbd80,0xbd800000,0x3d80,0xbd353d35,0x3d353d35,0x3d35bd35,0xbd35bd35,0x3d800000,0xbd80,0xbd800000,0x3d80,0xbd353d35,0x3d353d35,0x3d35bd35,0xbd35bd35,
0x3d800000,0xbd80,0xbd800000,0x3d80,0xbd353d35,0x3d353d35,0x3d35bd35,0xbd35bd35,0x3d800000,0xbd80,0xbd800000,0x3d80,0xbd353d35,0x3d353d35,0x3d35bd35,0xbd35bd35,
0x3d0ebd55,0xbd7bbc48,0x3c483d7b,0x3d55bd0e,0xbd800000,0x3cc43d6d,0x3d35bd35,0xbd6dbcc4,0xbd55bd0e,0xbc483d7b,0x3d7bbc48,0xbd0ebd55,0x3d80,0x3d6dbcc4,0xbd35bd35,0xbcc43d6d,
0xbd0e3d55,0x3d7b3c48,0xbc48bd7b,0xbd553d0e,0x3d800000,0xbcc4bd6d,0xbd353d35,0x3d6d3cc4,0x3d553d0e,0x3c48bd7b,0xbd7b3c48,0x3d0e3d55,0xbd80,0xbd6d3cc4,0x3d353d35,0x3cc4bd6d,
0xbd800000,0x3d353d35,0xbd80,0xbd353d35,0x3cc4bd6d,0xbd6d3cc4,0x3d6d3cc4,0xbcc4bd6d,0x3d800000,0xbd35bd35,0x3d80,0x3d35bd35,0xbcc43d6d,0x3d6dbcc4,0xbd6dbcc4,0x3cc43d6d,
0xbd800000,0x3d353d35,0xbd80,0xbd353d35,0x3cc4bd6d,0xbd6d3cc4,0x3d6d3cc4,0xbcc4bd6d,0x3d800000,0xbd35bd35,0x3d80,0x3d35bd35,0xbcc43d6d,0x3d6dbcc4,0xbd6dbcc4,0x3cc43d6d,
0x3d7b3c48,0xbd55bd0e,0x3d0e3d55,0xbc48bd7b,0xbd80,0xbcc43d6d,0x3d35bd35,0xbd6d3cc4,0x3c48bd7b,0xbd0e3d55,0x3d55bd0e,0xbd7b3c48,0xbd800000,0x3d6d3cc4,0xbd35bd35,0x3cc43d6d,
0xbd7bbc48,0x3d553d0e,0xbd0ebd55,0x3c483d7b,0x3d80,0x3cc4bd6d,0xbd353d35,0x3d6dbcc4,0xbc483d7b,0x3d0ebd55,0xbd553d0e,0x3d7bbc48,0x3d800000,0xbd6dbcc4,0x3d353d35,0xbcc4bd6d,
0x80003d80,0x8000bd80,0x80003d80,0x8000bd80,0xbd800000,0x3d800000,0xbd800000,0x3d800000,0x80003d80,0x8000bd80,0x80003d80,0x8000bd80,0xbd800000,0x3d800000,0xbd800000,0x3d800000,
0x80003d80,0x8000bd80,0x80003d80,0x8000bd80,0xbd800000,0x3d800000,0xbd800000,0x3d800000,0x80003d80,0x8000bd80,0x80003d80,0x8000bd80,0xbd800000,0x3d800000,0xbd800000,0x3d800000,
0xbd7b3c48,0x3d55bd0e,0xbd0e3d55,0x3c48bd7b,0x80003d80,0xbcc4bd6d,0x3d353d35,0xbd6dbcc4,0x3c483d7b,0xbd0ebd55,0x3d553d0e,0xbd7bbc48,0x3d800000,0xbd6d3cc4,0x3d35bd35,0xbcc43d6d,
0x3d7bbc48,0xbd553d0e,0x3d0ebd55,0xbc483d7b,0x8000bd80,0x3cc43d6d,0xbd35bd35,0x3d6d3cc4,0xbc48bd7b,0x3d0e3d55,0xbd55bd0e,0x3d7b3c48,0xbd800000,0x3d6dbcc4,0xbd353d35,0x3cc4bd6d,
0x8000bd80,0x3d353d35,0xbd800000,0x3d35bd35,0x3d6dbcc4,0xbcc43d6d,0xbcc4bd6d,0x3d6d3cc4,0x80003d80,0xbd35bd35,0x3d800000,0xbd353d35,0xbd6d3cc4,0x3cc4bd6d,0x3cc43d6d,0xbd6dbcc4,
0x8000bd80,0x3d353d35,0xbd800000,0x3d35bd35,0x3d6dbcc4,0xbcc43d6d,0xbcc4bd6d,0x3d6d3cc4,0x80003d80,0xbd35bd35,0x3d800000,0xbd353d35,0xbd6d3cc4,0x3cc4bd6d,0x3cc43d6d,0xbd6dbcc4,
0xbd0ebd55,0x3d7bbc48,0xbc483d7b,0xbd55bd0e,0xbd800000,0x3cc4bd6d,0x3d353d35,0xbd6d3cc4,0xbd553d0e,0xbc48bd7b,0x3d7b3c48,0xbd0e3d55,0x80003d80,0xbd6dbcc4,0x3d35bd35,0x3cc43d6d,
0x3d0e3d55,0xbd7b3c48,0x3c48bd7b,0x3d553d0e,0x3d800000,0xbcc43d6d,0xbd35bd35,0x3d6dbcc4,0x3d55bd0e,0x3c483d7b,0xbd7bbc48,0x3d0ebd55,0x8000bd80,0x3d6d3cc4,0xbd353d35,0xbcc4bd6d,
0x80003d80,0xbd800000,0x8000bd80,0x3d800000,0xbd353d35,0xbd35bd35,0x3d35bd35,0x3d353d35,0x80003d80,0xbd800000,0x8000bd80,0x3d800000,0xbd353d35,0xbd35bd35,0x3d35bd35,0x3d353d35,
0x80003d80,0xbd800000,0x8000bd80,0x3d800000,0xbd353d35,0xbd35bd35,0x3d35bd35,0x3d353d35,0x80003d80,0xbd800000,0x8000bd80,0x3d800000,0xbd353d35,0xbd35bd35,0x3d35bd35,0x3d353d35,
0x3d0ebd55,0x3d7b3c48,0x3c483d7b,0xbd553d0e,0x8000bd80,0x3d6dbcc4,0x3d353d35,0xbcc43d6d,0xbd55bd0e,0x3c48bd7b,0x3d7bbc48,0x3d0e3d55,0xbd800000,0xbcc4bd6d,0x3d35bd35,0x3d6d3cc4,
0xbd0e3d55,0xbd7bbc48,0xbc48bd7b,0x3d55bd0e,0x80003d80,0xbd6d3cc4,0xbd35bd35,0x3cc4bd6d,0x3d553d0e,0xbc483d7b,0xbd7b3c48,0xbd0ebd55,0x3d800000,0x3cc43d6d,0xbd353d35,0xbd6dbcc4,
0x8000bd80,0x3d35bd35,0x3d800000,0x3d353d35,0x3cc4bd6d,0x3d6dbcc4,0x3d6d3cc4,0x3cc43d6d,0x80003d80,0xbd353d35,0xbd800000,0xbd35bd35,0xbcc43d6d,0xbd6d3cc4,0xbd6dbcc4,0xbcc4bd6d,
0x8000bd80,0x3d35bd35,0x3d800000,0x3d353d35,0x3cc4bd6d,0x3d6dbcc4,0x3d6d3cc4,0x3cc43d6d,0x80003d80,0xbd353d35,0xbd800000,0xbd35bd35,0xbcc43d6d,0xbd6d3cc4,0xbd6dbcc4,0xbcc4bd6d,
0x3d7b3c48,0x3d553d0e,0x3d0e3d55,0x3c483d7b,0x3d800000,0x3d6d3cc4,0x3d353d35,0x3cc43d6d,0x3c48bd7b,0x3d0ebd55,0x3d55bd0e,0x3d7bbc48,0x8000bd80,0x3cc4bd6d,0x3d35bd35,0x3d6dbcc4,
0xbd7bbc48,0xbd55bd0e,0xbd0ebd55,0xbc48bd7b,0xbd800000,0xbd6dbcc4,0xbd35bd35,0xbcc4bd6d,0xbc483d7b,0xbd0e3d55,0xbd553d0e,0xbd7b3c48,0x80003d80,0xbcc43d6d,0xbd353d35,0xbd6d3cc4,
0x3d800000,0xbd800000,0x3d800000,0xbd800000,0x3d80,0xbd80,0x3d80,0xbd80,0x3d800000,0xbd800000,0x3d800000,0xbd800000,0x3d80,0xbd80,0x3d80,0xbd80,
0x3d800000,0xbd800000,0x3d800000,0xbd800000,0x3d80,0xbd80,0x3d80,0xbd80,0x3d800000,0xbd800000,0x3d800000,0xbd800000,0x3d80,0xbd80,0x3d80,0xbd80,
0x3c483d7b,0xbd0ebd55,0x3d553d0e,0xbd7bbc48,0x3d800000,0xbd6d3cc4,0x3d35bd35,0xbcc43d6d,0x3d7bbc48,0xbd553d0e,0x3d0ebd55,0xbc483d7b,0xbd80,0x3cc43d6d,0xbd35bd35,0x3d6d3cc4,
0xbc48bd7b,0x3d0e3d55,0xbd55bd0e,0x3d7b3c48,0xbd800000,0x3d6dbcc4,0xbd353d35,0x3cc4bd6d,0xbd7b3c48,0x3d55bd0e,0xbd0e3d55,0x3c48bd7b,0x3d80,0xbcc4bd6d,0x3d353d35,0xbd6dbcc4,
0xbd800000,0x3d35bd35,0x3d80,0xbd35bd35,0xbcc4bd6d,0x3d6d3cc4,0xbd6d3cc4,0x3cc4bd6d,0x3d800000,0xbd353d35,0xbd80,0x3d353d35,0x3cc43d6d,0xbd6dbcc4,0x3d6dbcc4,0xbcc43d6d,
0xbd800000,0x3d35bd35,0x3d80,0xbd35bd35,0xbcc4bd6d,0x3d6d3cc4,0xbd6d3cc4,0x3cc4bd6d,0x3d800000,0xbd353d35,0xbd80,0x3d353d35,0x3cc43d6d,0xbd6dbcc4,0x3d6dbcc4,0xbcc43d6d,
0xbd553d0e,0xbc48bd7b,0x3d7b3c48,0xbd0e3d55,0x3d80,0xbd6dbcc4,0x3d35bd35,0x3cc43d6d,0x3d0e3d55,0xbd7b3c48,0x3c48bd7b,0x3d553d0e,0x3d800000,0xbcc43d6d,0xbd35bd35,0x3d6dbcc4,
0x3d55bd0e,0x3c483d7b,0xbd7bbc48,0x3d0ebd55,0xbd80,0x3d6d3cc4,0xbd353d35,0xbcc4bd6d,0xbd0ebd55,0x3d7bbc48,0xbc483d7b,0xbd55bd0e,0xbd800000,0x3cc4bd6d,0x3d353d35,0xbd6d3cc4,
0x3d800000,0x3d80,0xbd800000,0xbd80,0x3d353d35,0xbd353d35,0xbd35bd35,0x3d35bd35,0x3d800000,0x3d80,0xbd800000,0xbd80,0x3d353d35,0xbd353d35,0xbd35bd35,0x3d35bd35,
0x3d800000,0x3d80,0xbd800000,0xbd80,0x3d353d35,0xbd353d35,0xbd35bd35,0x3d35bd35,0x3d800000,0x3d80,0xbd800000,0xbd80,0x3d353d35,0xbd353d35,0xbd35bd35,0x3d35bd35,
0xbd55bd0e,0x3c48bd7b,0x3d7bbc48,0x3d0e3d55,0xbd800000,0xbcc4bd6d,0x3d35bd35,0x3d6d3cc4,0xbd0e3d55,0xbd7bbc48,0xbc48bd7b,0x3d55bd0e,0x3d80,0xbd6d3cc4,0xbd35bd35,0x3cc4bd6d,
0x3d553d0e,0xbc483d7b,0xbd7b3c48,0xbd0ebd55,0x3d800000,0x3cc43d6d,0xbd353d35,0xbd6dbcc4,0x3d0ebd55,0x3d7b3c48,0x3c483d7b,0xbd553d0e,0xbd80,0x3d6dbcc4,0x3d353d35,0xbcc43d6d,
0xbd800000,0xbd35bd35,0xbd80,0x3d35bd35,0xbd6dbcc4,0xbcc4bd6d,0x3cc4bd6d,0x3d6dbcc4,0x3d800000,0x3d353d35,0x3d80,0xbd353d35,0x3d6d3cc4,0x3cc43d6d,0xbcc43d6d,0xbd6d3cc4,
0xbd800000,0xbd35bd35,0xbd80,0x3d35bd35,0xbd6dbcc4,0xbcc4bd6d,0x3cc4bd6d,0x3d6dbcc4,0x3d800000,0x3d353d35,0x3d80,0xbd353d35,0x3d6d3cc4,0x3cc43d6d,0xbcc43d6d,0xbd6d3cc4,
0x3c48bd7b,0x3d0ebd55,0x3d55bd0e,0x3d7bbc48,0xbd80,0x3cc4bd6d,0x3d35bd35,0x3d6dbcc4,0xbd7bbc48,0xbd55bd0e,0xbd0ebd55,0xbc48bd7b,0xbd800000,0xbd6dbcc4,0xbd35bd35,0xbcc4bd6d,
0xbc483d7b,0xbd0e3d55,0xbd553d0e,0xbd7b3c48,0x3d80,0xbcc43d6d,0xbd353d35,0xbd6d3cc4,0x3d7b3c48,0x3d553d0e,0x3d0e3d55,0x3c483d7b,0x3d800000,0x3d6d3cc4,0x3d353d35,0x3cc43d6d,
0x3f003f00,0xbf003f00,0x3f003f00,0xbf003f00,0x3f003f00,0xbf003f00,0x3f003f00,0xbf003f00,0x3f003f00,0xbf003f00,0x3f003f00,0xbf003f00,0x3f003f00,0xbf003f00,0x3f003f00,0xbf003f00,
0x3eff3f00,0xbd490000,0x3ea23eb5,0xbec6beb5,0x3ef53efb,0xbe15bdc8,0x3e713e8e,0xbee2bed5,0x3ee23eed,0xbe71be44,0x3e153e44,0xbef5beed,0x3ec63ed5,0xbea2be8e,0x3d493dc8,0xbeffbefb,
0x3efb3f00,0xbdc80000,0xbdc80000,0xbefbbf00,0x3ed53eed,0xbe8ebe44,0xbe8ebe44,0xbed5beed,0x3e8e3eb5,0xbed5beb5,0xbed5beb5,0xbe8ebeb5,0x3dc83e44,0xbefbbeed,0xbefbbeed,0xbdc8be44,
0x3ef53f00,0xbe150000,0xbee2beb5,0xbe71beb5,0x3ea23ed5,0xbec6be8e,0xbeffbefb,0x3d49bdc8,0x3d493e44,0xbeffbeed,0xbec6beed,0x3ea23e44,0xbe71bdc8,0xbee2befb,0xbe15be8e,0x3ef53ed5,
0x3eed3f00,0xbe440000,0xbeedbf00,0x3e440000,0x3e443eb5,0xbeedbeb5,0xbe44beb5,0x3eed3eb5,0xbe440000,0xbeedbf00,0x3e440000,0x3eed3f00,0xbeedbeb5,0xbe44beb5,0x3eed3eb5,0x3e443eb5,
0x3ee23f00,0xbe710000,0xbe15beb5,0x3ef53eb5,0x3d493e8e,0xbeffbed5,0x3ea23dc8,0x3ec63efb,0xbec6be44,0xbea2beed,0x3eff3eed,0xbd493e44,0xbef5befb,0x3e15bdc8,0x3e713ed5,0xbee2be8e,
0x3ed53f00,0xbe8e0000,0x3e8e0000,0x3ed53f00,0xbdc83e44,0xbefbbeed,0x3efb3eed,0xbdc83e44,0xbefbbeb5,0xbdc8beb5,0x3dc83eb5,0xbefbbeb5,0xbe8ebeed,0x3ed53e44,0xbed5be44,0xbe8ebeed,
0x3ec63f00,0xbea20000,0x3eff3eb5,0x3d493eb5,0xbe713dc8,0xbee2befb,0x3e153ed5,0xbef5be8e,0xbef5beed,0x3e15be44,0xbee2be44,0xbe71beed,0x3d49be8e,0x3eff3ed5,0xbea2befb,0x3ec63dc8,
0x3eb53f00,0xbeb50000,0x3eb53f00,0xbeb50000,0xbeb50000,0xbeb5bf00,0xbeb50000,0xbeb5bf00,0xbeb5bf00,0x3eb50000,0xbeb5bf00,0x3eb50000,0x3eb50000,0x3eb53f00,0x3eb50000,0x3eb53f00,
0x3ea23f00,0xbec60000,0xbd493eb5,0xbeffbeb5,0xbee2bdc8,0xbe71befb,0xbef5bed5,0x3e15be8e,0xbe15beed,0x3ef53e44,0x3e71be44,0x3ee23eed,0x3eff3e8e,0x3d493ed5,0x3ec63efb,0xbea23dc8,
0x3e8e3f00,0xbed50000,0xbed50000,0xbe8ebf00,0xbefbbe44,0xbdc8beed,0xbdc8beed,0x3efb3e44,0x3dc8beb5,0x3efb3eb5,0x3efb3eb5,0xbdc83eb5,0x3ed53eed,0xbe8e3e44,0xbe8e3e44,0xbed5beed,
0x3e713f00,0xbee20000,0xbef5beb5,0x3e15beb5,0xbeffbe8e,0x3d49bed5,0x3ec6bdc8,0x3ea23efb,0x3ea2be44,0x3ec63eed,0x3d493eed,0xbeffbe44,0x3e153efb,0xbef5bdc8,0xbee2bed5,0x3e71be8e,
0x3e443f00,0xbeed0000,0xbe44bf00,0x3eed0000,0xbeedbeb5,0x3e44beb5,0x3eed3eb5,0xbe443eb5,0x3eed0000,0x3e443f00,0xbeed0000,0xbe44bf00,0xbe443eb5,0xbeedbeb5,0x3e44beb5,0x3eed3eb5,
0x3e153f00,0xbef50000,0x3e71beb5,0x3ee23eb5,0xbec6bed5,0x3ea2be8e,0x3d493efb,0xbeffbdc8,0x3eff3e44,0xbd493eed,0xbea2beed,0x3ec6be44,0xbee23dc8,0xbe71befb,0x3ef53e8e,0xbe153ed5,
0x3dc83f00,0xbefb0000,0x3efb0000,0x3dc83f00,0xbe8ebeed,0x3ed5be44,0xbed53e44,0xbe8ebeed,0x3ed53eb5,0xbe8e3eb5,0x3e8ebeb5,0x3ed53eb5,0xbefbbe44,0x3dc8beed,0xbdc83eed,0xbefbbe44,
0x3d493f00,0xbeff0000,0x3ec63eb5,0xbea23eb5,0xbe15befb,0x3ef5bdc8,0xbee2be8e,0x3e71bed5,0x3e713eed,0xbee23e44,0x3ef53e44,0xbe153eed,0xbea2bed5,0x3ec6be8e,0xbeffbdc8,0x3d49befb,
0x3f00,0xbf000000,0x3f00,0xbf000000,0xbf00,0x3f000000,0xbf00,0x3f000000,0x3f00,0xbf000000,0x3f00,0xbf000000,0xbf00,0x3f000000,0xbf00,0x3f000000,
0xbd493f00,0xbeff0000,0xbec63eb5,0xbea2beb5,0x3e15befb,0x3ef53dc8,0x3ee2be8e,0x3e713ed5,0xbe713eed,0xbee2be44,0xbef53e44,0xbe15beed,0x3ea2bed5,0x3ec63e8e,0x3effbdc8,0x3d493efb,
0xbdc83f00,0xbefb0000,0xbefb0000,0x3dc8bf00,0x3e8ebeed,0x3ed53e44,0x3ed53e44,0xbe8e3eed,0xbed53eb5,0xbe8ebeb5,0xbe8ebeb5,0x3ed5beb5,0x3efbbe44,0x3dc83eed,0x3dc83eed,0xbefb3e44,
0xbe153f00,0xbef50000,0xbe71beb5,0x3ee2beb5,0x3ec6bed5,0x3ea23e8e,0xbd493efb,0xbeff3dc8,0xbeff3e44,0xbd49beed,0x3ea2beed,0x3ec63e44,0x3ee23dc8,0xbe713efb,0xbef53e8e,0xbe15bed5,
0xbe443f00,0xbeed0000,0x3e44bf00,0x3eed0000,0x3eedbeb5,0x3e443eb5,0xbeed3eb5,0xbe44beb5,0xbeed0000,0x3e44bf00,0x3eed0000,0xbe443f00,0x3e443eb5,0xbeed3eb5,0xbe44beb5,0x3eedbeb5,
0xbe713f00,0xbee20000,0x3ef5beb5,0x3e153eb5,0x3effbe8e,0x3d493ed5,0xbec6bdc8,0x3ea2befb,0xbea2be44,0x3ec6beed,0xbd493eed,0xbeff3e44,0xbe153efb,0xbef53dc8,0x3ee2bed5,0x3e713e8e,
0xbe8e3f00,0xbed50000,0x3ed50000,0xbe8e3f00,0x3efbbe44,0xbdc83eed,0x3dc8beed,0x3efbbe44,0xbdc8beb5,0x3efbbeb5,0xbefb3eb5,0xbdc8beb5,0xbed53eed,0xbe8ebe44,0x3e8e3e44,0xbed53eed,
0xbea23f00,0xbec60000,0x3d493eb5,0xbeff3eb5,0x3ee2bdc8,0xbe713efb,0x3ef5bed5,0x3e153e8e,0x3e15beed,0x3ef5be44,0xbe71be44,0x3ee2beed,0xbeff3e8e,0x3d49bed5,0xbec63efb,0xbea2bdc8,
0xbeb53f00,0xbeb50000,0xbeb53f00,0xbeb50000,0x3eb50000,0xbeb53f00,0x3eb50000,0xbeb53f00,0x3eb5bf00,0x3eb50000,0x3eb5bf00,0x3eb50000,0xbeb50000,0x3eb5bf00,0xbeb50000,0x3eb5bf00,
0xbec63f00,0xbea20000,0xbeff3eb5,0x3d49beb5,0x3e713dc8,0xbee23efb,0xbe153ed5,0xbef53e8e,0x3ef5beed,0x3e153e44,0x3ee2be44,0xbe713eed,0xbd49be8e,0x3effbed5,0x3ea2befb,0x3ec6bdc8,
0xbed53f00,0xbe8e0000,0xbe8e0000,0x3ed5bf00,0x3dc83e44,0xbefb3eed,0xbefb3eed,0xbdc8be44,0x3efbbeb5,0xbdc83eb5,0xbdc83eb5,0xbefb3eb5,0x3e8ebeed,0x3ed5be44,0x3ed5be44,0xbe8e3eed,
0xbee23f00,0xbe710000,0x3e15beb5,0x3ef5beb5,0xbd493e8e,0xbeff3ed5,0xbea23dc8,0x3ec6befb,0x3ec6be44,0xbea23eed,0xbeff3eed,0xbd49be44,0x3ef5befb,0x3e153dc8,0xbe713ed5,0xbee23e8e,
0xbeed3f00,0xbe440000,0x3eedbf00,0x3e440000,0xbe443eb5,0xbeed3eb5,0x3e44beb5,0x3eedbeb5,0x3e440000,0xbeed3f00,0xbe440000,0x3eedbf00,0x3eedbeb5,0xbe443eb5,0xbeed3eb5,0x3e44beb5,
0xbef53f00,0xbe150000,0x3ee2beb5,0xbe713eb5,0xbea23ed5,0xbec63e8e,0x3effbefb,0x3d493dc8,0xbd493e44,0xbeff3eed,0x3ec6beed,0x3ea2be44,0x3e71bdc8,0xbee23efb,0x3e15be8e,0x3ef5bed5,
0xbefb3f00,0xbdc80000,0x3dc80000,0xbefb3f00,0xbed53eed,0xbe8e3e44,0x3e8ebe44,0xbed53eed,0xbe8e3eb5,0xbed53eb5,0x3ed5beb5,0xbe8e3eb5,0xbdc83e44,0xbefb3eed,0x3efbbeed,0xbdc83e44,
0xbeff3f00,0xbd490000,0xbea23eb5,0xbec63eb5,0xbef53efb,0xbe153dc8,0xbe713e8e,0xbee23ed5,0xbee23eed,0xbe713e44,0xbe153e44,0xbef53eed,0xbec63ed5,0xbea23e8e,0xbd493dc8,0xbeff3efb,
0x3f003f00,0xbf003f00,0x3f003f00,0xbf003f00,0x3f003f00,0xbf003f00,0x3f003f00,0xbf003f00,0x3f003f00,0xbf003f00,0x3f003f00,0xbf003f00,0x3f003f00,0xbf003f00,0x3f003f00,0xbf003f00,
0xbd490000,0xbeffbf00,0xbec6beb5,0xbea2beb5,0xbe15bdc8,0xbef5befb,0xbee2bed5,0xbe71be8e,0xbe71be44,0xbee2beed,0xbef5beed,0xbe15be44,0xbea2be8e,0xbec6bed5,0xbeffbefb,0xbd49bdc8,
0xbefbbf00,0x3dc80000,0x3dc80000,0x3efb3f00,0xbed5beed,0x3e8e3e44,0x3e8e3e44,0x3ed53eed,0xbe8ebeb5,0x3ed53eb5,0x3ed53eb5,0x3e8e3eb5,0xbdc8be44,0x3efb3eed,0x3efb3eed,0x3dc83e44,
0x3e150000,0x3ef53f00,0x3e713eb5,0xbee2beb5,0x3ec63e8e,0x3ea23ed5,0xbd493dc8,0xbeffbefb,0x3eff3eed,0x3d493e44,0xbea2be44,0xbec6beed,0x3ee23efb,0xbe71bdc8,0xbef5bed5,0xbe15be8e,
0x3eed3f00,0xbe440000,0xbeedbf00,0x3e440000,0x3e443eb5,0xbeedbeb5,0xbe44beb5,0x3eed3eb5,0xbe440000,0xbeedbf00,0x3e440000,0x3eed3f00,0xbeedbeb5,0xbe44beb5,0x3eed3eb5,0x3e443eb5,
0xbe710000,0xbee2bf00,0x3ef53eb5,0x3e153eb5,0xbeffbed5,0xbd49be8e,0x3ec63efb,0xbea2bdc8,0xbea2beed,0x3ec63e44,0xbd493e44,0xbeffbeed,0x3e15bdc8,0x3ef53efb,0xbee2be8e,0xbe71bed5,
0xbed5bf00,0x3e8e0000,0xbe8e0000,0xbed5bf00,0x3dc8be44,0x3efb3eed,0xbefbbeed,0x3dc8be44,0x3efb3eb5,0x3dc83eb5,0xbdc8beb5,0x3efb3eb5,0x3e8e3eed,0xbed5be44,0x3ed53e44,0x3e8e3eed,
0x3ea20000,0x3ec63f00,0xbd49beb5,0x3eff3eb5,0x3ee23efb,0xbe713dc8,0x3ef53e8e,0x3e153ed5,0xbe153e44,0xbef5beed,0x3e713eed,0xbee2be44,0xbeffbed5,0x3d49be8e,0xbec6bdc8,0xbea2befb,
0x3eb53f00,0xbeb50000,0x3eb53f00,0xbeb50000,0xbeb50000,0xbeb5bf00,0xbeb50000,0xbeb5bf00,0xbeb5bf00,0x3eb50000,0xbeb5bf00,0x3eb50000,0x3eb50000,0x3eb53f00,0x3eb50000,0x3eb53f00,
0xbec60000,0xbea2bf00,0xbeffbeb5,0x3d49beb5,0xbe71befb,0x3ee23dc8,0x3e15be8e,0x3ef53ed5,0x3ef53e44,0x3e153eed,0x3ee23eed,0xbe713e44,0x3d493ed5,0xbeffbe8e,0xbea23dc8,0xbec6befb,
0xbe8ebf00,0x3ed50000,0x3ed50000,0x3e8e3f00,0x3efb3e44,0x3dc83eed,0x3dc83eed,0xbefbbe44,0xbdc83eb5,0xbefbbeb5,0xbefbbeb5,0x3dc8beb5,0xbed5beed,0x3e8ebe44,0x3e8ebe44,0x3ed53eed,
0x3ee20000,0x3e713f00,0xbe153eb5,0xbef5beb5,0xbd493ed5,0xbeffbe8e,0xbea2befb,0x3ec6bdc8,0xbec6beed,0x3ea2be44,0x3eff3e44,0x3d493eed,0x3ef53dc8,0x3e153efb,0xbe713e8e,0xbee2bed5,
0x3e443f00,0xbeed0000,0xbe44bf00,0x3eed0000,0xbeedbeb5,0x3e44beb5,0x3eed3eb5,0xbe443eb5,0x3eed0000,0x3e443f00,0xbeed0000,0xbe44bf00,0xbe443eb5,0xbeedbeb5,0x3e44beb5,0x3eed3eb5,
0xbef50000,0xbe15bf00,0x3ee23eb5,0xbe713eb5,0x3ea2be8e,0x3ec63ed5,0xbeffbdc8,0xbd49befb,0xbd493eed,0xbeffbe44,0x3ec6be44,0x3ea23eed,0xbe71befb,0x3ee2bdc8,0xbe153ed5,0xbef5be8e,
0xbdc8bf00,0x3efb0000,0xbefb0000,0xbdc8bf00,0x3e8e3eed,0xbed53e44,0x3ed5be44,0x3e8e3eed,0xbed5beb5,0x3e8ebeb5,0xbe8e3eb5,0xbed5beb5,0x3efb3e44,0xbdc83eed,0x3dc8beed,0x3efb3e44,
0x3eff0000,0x3d493f00,0x3ea2beb5,0x3ec63eb5,0xbef53dc8,0xbe15befb,0xbe713ed5,0xbee2be8e,0x3ee2be44,0x3e713eed,0x3e15beed,0x3ef53e44,0xbec63e8e,0xbea2bed5,0xbd493efb,0xbeffbdc8,
0x3f00,0xbf000000,0x3f00,0xbf000000,0xbf00,0x3f000000,0xbf00,0x3f000000,0x3f00,0xbf000000,0x3f00,0xbf000000,0xbf00,0x3f000000,0xbf00,0x3f000000,
0xbeff0000,0x3d49bf00,0xbea2beb5,0x3ec6beb5,0x3ef53dc8,0xbe153efb,0x3e713ed5,0xbee23e8e,0xbee2be44,0x3e71beed,0xbe15beed,0x3ef5be44,0x3ec63e8e,0xbea23ed5,0x3d493efb,0xbeff3dc8,
0x3dc8bf00,0x3efb0000,0x3efb0000,0xbdc83f00,0xbe8e3eed,0xbed5be44,0xbed5be44,0x3e8ebeed,0x3ed5beb5,0x3e8e3eb5,0x3e8e3eb5,0xbed53eb5,0xbefb3e44,0xbdc8beed,0xbdc8beed,0x3efbbe44,
0x3ef50000,0xbe153f00,0xbee23eb5,0xbe71beb5,0xbea2be8e,0x3ec6bed5,0x3effbdc8,0xbd493efb,0x3d493eed,0xbeff3e44,0xbec6be44,0x3ea2beed,0x3e71befb,0x3ee23dc8,0x3e153ed5,0xbef53e8e,
0xbe443f00,0xbeed0000,0x3e44bf00,0x3eed0000,0x3eedbeb5,0x3e443eb5,0xbeed3eb5,0xbe44beb5,0xbeed0000,0x3e44bf00,0x3eed0000,0xbe443f00,0x3e443eb5,0xbeed3eb5,0xbe44beb5,0x3eedbeb5,
0xbee20000,0x3e71bf00,0x3e153eb5,0xbef53eb5,0x3d493ed5,0xbeff3e8e,0x3ea2befb,0x3ec63dc8,0x3ec6beed,0x3ea23e44,0xbeff3e44,0x3d49beed,0xbef53dc8,0x3e15befb,0x3e713e8e,0xbee23ed5,
0x3e8ebf00,0x3ed50000,0xbed50000,0x3e8ebf00,0xbefb3e44,0x3dc8beed,0xbdc83eed,0xbefb3e44,0x3dc83eb5,0xbefb3eb5,0x3efbbeb5,0x3dc83eb5,0x3ed5beed,0x3e8e3e44,0xbe8ebe44,0x3ed5beed,
0x3ec60000,0xbea23f00,0x3effbeb5,0x3d493eb5,0x3e71befb,0x3ee2bdc8,0xbe15be8e,0x3ef5bed5,0xbef53e44,0x3e15beed,0xbee23eed,0xbe71be44,0xbd493ed5,0xbeff3e8e,0x3ea23dc8,0xbec63efb,
0xbeb53f00,0xbeb50000,0xbeb53f00,0xbeb50000,0x3eb50000,0xbeb53f00,0x3eb50000,0xbeb53f00,0x3eb5bf00,0x3eb50000,0x3eb5bf00,0x3eb50000,0xbeb50000,0x3eb5bf00,0xbeb50000,0x3eb5bf00,
0xbea20000,0x3ec6bf00,0x3d49beb5,0x3effbeb5,0xbee23efb,0xbe71bdc8,0xbef53e8e,0x3e15bed5,0x3e153e44,0xbef53eed,0xbe713eed,0xbee23e44,0x3effbed5,0x3d493e8e,0x3ec6bdc8,0xbea23efb,
0x3ed5bf00,0x3e8e0000,0x3e8e0000,0xbed53f00,0xbdc8be44,0x3efbbeed,0x3efbbeed,0x3dc83e44,0xbefb3eb5,0x3dc8beb5,0x3dc8beb5,0x3efbbeb5,0xbe8e3eed,0xbed53e44,0xbed53e44,0x3e8ebeed,
0x3e710000,0xbee23f00,0xbef53eb5,0x3e15beb5,0x3effbed5,0xbd493e8e,0xbec63efb,0xbea23dc8,0x3ea2beed,0x3ec6be44,0x3d493e44,0xbeff3eed,0xbe15bdc8,0x3ef5befb,0x3ee2be8e,0xbe713ed5,
0xbeed3f00,0xbe440000,0x3eedbf00,0x3e440000,0xbe443eb5,0xbeed3eb5,0x3e44beb5,0x3eedbeb5,0x3e440000,0xbeed3f00,0xbe440000,0x3eedbf00,0x3eedbeb5,0xbe443eb5,0xbeed3eb5,0x3e44beb5,
0xbe150000,0x3ef5bf00,0xbe713eb5,0xbee23eb5,0xbec63e8e,0x3ea2bed5,0x3d493dc8,0xbeff3efb,0xbeff3eed,0x3d49be44,0x3ea2be44,0xbec63eed,0xbee23efb,0xbe713dc8,0x3ef5bed5,0xbe153e8e,
0x3efbbf00,0x3dc80000,0xbdc80000,0x3efbbf00,0x3ed5beed,0x3e8ebe44,0xbe8e3e44,0x3ed5beed,0x3e8ebeb5,0x3ed5beb5,0xbed53eb5,0x3e8ebeb5,0x3dc8be44,0x3efbbeed,0xbefb3eed,0x3dc8be44,
0x3d490000,0xbeff3f00,0x3ec6beb5,0xbea23eb5,0x3e15bdc8,0xbef53efb,0x3ee2bed5,0xbe713e8e,0x3e71be44,0xbee23eed,0x3ef5beed,0xbe153e44,0x3ea2be8e,0xbec63ed5,0x3effbefb,0xbd493dc8,
0x3f003f00,0xbf003f00,0x3f003f00,0xbf003f00,0x3f003f00,0xbf003f00,0x3f003f00,0xbf003f00,0x3f003f00,0xbf003f00,0x3f003f00,0xbf003f00,0x3f003f00,0xbf003f00,0x3f003f00,0xbf003f00,
0xbeffbf00,0x3d490000,0xbea2beb5,0x3ec63eb5,0xbef5befb,0x3e153dc8,0xbe71be8e,0x3ee23ed5,0xbee2beed,0x3e713e44,0xbe15be44,0x3ef53eed,0xbec6bed5,0x3ea23e8e,0xbd49bdc8,0x3eff3efb,
0x3efb3f00,0xbdc80000,0xbdc80000,0xbefbbf00,0x3ed53eed,0xbe8ebe44,0xbe8ebe44,0xbed5beed,0x3e8e3eb5,0xbed5beb5,0xbed5beb5,0xbe8ebeb5,0x3dc83e44,0xbefbbeed,0xbefbbeed,0xbdc8be44,
0xbef5bf00,0x3e150000,0x3ee23eb5,0x3e713eb5,0xbea2bed5,0x3ec63e8e,0x3eff3efb,0xbd493dc8,0xbd49be44,0x3eff3eed,0x3ec63eed,0xbea2be44,0x3e713dc8,0x3ee23efb,0x3e153e8e,0xbef5bed5,
0x3eed3f00,0xbe440000,0xbeedbf00,0x3e440000,0x3e443eb5,0xbeedbeb5,0xbe44beb5,0x3eed3eb5,0xbe440000,0xbeedbf00,0x3e440000,0x3eed3f00,0xbeedbeb5,0xbe44beb5,0x3eed3eb5,0x3e443eb5,
0xbee2bf00,0x3e710000,0x3e153eb5,0xbef5beb5,0xbd49be8e,0x3eff3ed5,0xbea2bdc8,0xbec6befb,0x3ec63e44,0x3ea23eed,0xbeffbeed,0x3d49be44,0x3ef53efb,0xbe153dc8,0xbe71bed5,0x3ee23e8e,
0x3ed53f00,0xbe8e0000,0x3e8e0000,0x3ed53f00,0xbdc83e44,0xbefbbeed,0x3efb3eed,0xbdc83e44,0xbefbbeb5,0xbdc8beb5,0x3dc83eb5,0xbefbbeb5,0xbe8ebeed,0x3ed53e44,0xbed5be44,0xbe8ebeed,
0xbec6bf00,0x3ea20000,0xbeffbeb5,0xbd49beb5,0x3e71bdc8,0x3ee23efb,0xbe15bed5,0x3ef53e8e,0x3ef53eed,0xbe153e44,0x3ee23e44,0x3e713eed,0xbd493e8e,0xbeffbed5,0x3ea23efb,0xbec6bdc8,
0x3eb53f00,0xbeb50000,0x3eb53f00,0xbeb50000,0xbeb50000,0xbeb5bf00,0xbeb50000,0xbeb5bf00,0xbeb5bf00,0x3eb50000,0xbeb5bf00,0x3eb50000,0x3eb50000,0x3eb53f00,0x3eb50000,0x3eb53f00,
0xbea2bf00,0x3ec60000,0x3d49beb5,0x3eff3eb5,0x3ee23dc8,0x3e713efb,0x3ef53ed5,0xbe153e8e,0x3e153eed,0xbef5be44,0xbe713e44,0xbee2beed,0xbeffbe8e,0xbd49bed5,0xbec6befb,0x3ea2bdc8,
0x3e8e3f00,0xbed50000,0xbed50000,0xbe8ebf00,0xbefbbe44,0xbdc8beed,0xbdc8beed,0x3efb3e44,0x3dc8beb5,0x3efb3eb5,0x3efb3eb5,0xbdc83eb5,0x3ed53eed,0xbe8e3e44,0xbe8e3e44,0xbed5beed,
0xbe71bf00,0x3ee20000,0x3ef53eb5,0xbe153eb5,0x3eff3e8e,0xbd493ed5,0xbec63dc8,0xbea2befb,0xbea23e44,0xbec6beed,0xbd49beed,0x3eff3e44,0xbe15befb,0x3ef53dc8,0x3ee23ed5,0xbe713e8e,
0x3e443f00,0xbeed0000,0xbe44bf00,0x3eed0000,0xbeedbeb5,0x3e44beb5,0x3eed3eb5,0xbe443eb5,0x3eed0000,0x3e443f00,0xbeed0000,0xbe44bf00,0xbe443eb5,0xbeedbeb5,0x3e44beb5,0x3eed3eb5,
0xbe15bf00,0x3ef50000,0xbe713eb5,0xbee2beb5,0x3ec63ed5,0xbea23e8e,0xbd49befb,0x3eff3dc8,0xbeffbe44,0x3d49beed,0x3ea23eed,0xbec63e44,0x3ee2bdc8,0x3e713efb,0xbef5be8e,0x3e15bed5,
0x3dc83f00,0xbefb0000,0x3efb0000,0x3dc83f00,0xbe8ebeed,0x3ed5be44,0xbed53e44,0xbe8ebeed,0x3ed53eb5,0xbe8e3eb5,0x3e8ebeb5,0x3ed53eb5,0xbefbbe44,0x3dc8beed,0xbdc83eed,0xbefbbe44,
0xbd49bf00,0x3eff0000,0xbec6beb5,0x3ea2beb5,0x3e153efb,0xbef53dc8,0x3ee23e8e,0xbe713ed5,0xbe71beed,0x3ee2be44,0xbef5be44,0x3e15beed,0x3ea23ed5,0xbec63e8e,0x3eff3dc8,0xbd493efb,
0x3f00,0xbf000000,0x3f00,0xbf000000,0xbf00,0x3f000000,0xbf00,0x3f000000,0x3f00,0xbf000000,0x3f00,0xbf000000,0xbf00,0x3f000000,0xbf00,0x3f000000,
0x3d49bf00,0x3eff0000,0x3ec6beb5,0x3ea23eb5,0xbe153efb,0xbef5bdc8,0xbee23e8e,0xbe71bed5,0x3e71beed,0x3ee23e44,0x3ef5be44,0x3e153eed,0xbea23ed5,0xbec6be8e,0xbeff3dc8,0xbd49befb,
0xbdc83f00,0xbefb0000,0xbefb0000,0x3dc8bf00,0x3e8ebeed,0x3ed53e44,0x3ed53e44,0xbe8e3eed,0xbed53eb5,0xbe8ebeb5,0xbe8ebeb5,0x3ed5beb5,0x3efbbe44,0x3dc83eed,0x3dc83eed,0xbefb3e44,
0x3e15bf00,0x3ef50000,0x3e713eb5,0xbee23eb5,0xbec63ed5,0xbea2be8e,0x3d49befb,0x3effbdc8,0x3effbe44,0x3d493eed,0xbea23eed,0xbec6be44,0xbee2bdc8,0x3e71befb,0x3ef5be8e,0x3e153ed5,
0xbe443f00,0xbeed0000,0x3e44bf00,0x3eed0000,0x3eedbeb5,0x3e443eb5,0xbeed3eb5,0xbe44beb5,0xbeed0000,0x3e44bf00,0x3eed0000,0xbe443f00,0x3e443eb5,0xbeed3eb5,0xbe44beb5,0x3eedbeb5,
0x3e71bf00,0x3ee20000,0xbef53eb5,0xbe15beb5,0xbeff3e8e,0xbd49bed5,0x3ec63dc8,0xbea23efb,0x3ea23e44,0xbec63eed,0x3d49beed,0x3effbe44,0x3e15befb,0x3ef5bdc8,0xbee23ed5,0xbe71be8e,
0xbe8e3f00,0xbed50000,0x3ed50000,0xbe8e3f00,0x3efbbe44,0xbdc83eed,0x3dc8beed,0x3efbbe44,0xbdc8beb5,0x3efbbeb5,0xbefb3eb5,0xbdc8beb5,0xbed53eed,0xbe8ebe44,0x3e8e3e44,0xbed53eed,
0x3ea2bf00,0x3ec60000,0xbd49beb5,0x3effbeb5,0xbee23dc8,0x3e71befb,0xbef53ed5,0xbe15be8e,0xbe153eed,0xbef53e44,0x3e713e44,0xbee23eed,0x3effbe8e,0xbd493ed5,0x3ec6befb,0x3ea23dc8,
0xbeb53f00,0xbeb50000,0xbeb53f00,0xbeb50000,0x3eb50000,0xbeb53f00,0x3eb50000,0xbeb53f00,0x3eb5bf00,0x3eb50000,0x3eb5bf00,0x3eb50000,0xbeb50000,0x3eb5bf00,0xbeb50000,0x3eb5bf00,
0x3ec6bf00,0x3ea20000,0x3effbeb5,0xbd493eb5,0xbe71bdc8,0x3ee2befb,0x3e15bed5,0x3ef5be8e,0xbef53eed,0xbe15be44,0xbee23e44,0x3e71beed,0x3d493e8e,0xbeff3ed5,0xbea23efb,0xbec63dc8,
0xbed53f00,0xbe8e0000,0xbe8e0000,0x3ed5bf00,0x3dc83e44,0xbefb3eed,0xbefb3eed,0xbdc8be44,0x3efbbeb5,0xbdc83eb5,0xbdc83eb5,0xbefb3eb5,0x3e8ebeed,0x3ed5be44,0x3ed5be44,0xbe8e3eed,
0x3ee2bf00,0x3e710000,0xbe153eb5,0xbef53eb5,0x3d49be8e,0x3effbed5,0x3ea2bdc8,0xbec63efb,0xbec63e44,0x3ea2beed,0x3effbeed,0x3d493e44,0xbef53efb,0xbe15bdc8,0x3e71bed5,0x3ee2be8e,
0xbeed3f00,0xbe440000,0x3eedbf00,0x3e440000,0xbe443eb5,0xbeed3eb5,0x3e44beb5,0x3eedbeb5,0x3e440000,0xbeed3f00,0xbe440000,0x3eedbf00,0x3eedbeb5,0xbe443eb5,0xbeed3eb5,0x3e44beb5,
0x3ef5bf00,0x3e150000,0xbee23eb5,0x3e71beb5,0x3ea2bed5,0x3ec6be8e,0xbeff3efb,0xbd49bdc8,0x3d49be44,0x3effbeed,0xbec63eed,0xbea23e44,0xbe713dc8,0x3ee2befb,0xbe153e8e,0xbef53ed5,
0xbefb3f00,0xbdc80000,0x3dc80000,0xbefb3f00,0xbed53eed,0xbe8e3e44,0x3e8ebe44,0xbed53eed,0xbe8e3eb5,0xbed53eb5,0x3ed5beb5,0xbe8e3eb5,0xbdc83e44,0xbefb3eed,0x3efbbeed,0xbdc83e44,
0x3effbf00,0x3d490000,0x3ea2beb5,0x3ec6beb5,0x3ef5befb,0x3e15bdc8,0x3e71be8e,0x3ee2bed5,0x3ee2beed,0x3e71be44,0x3e15be44,0x3ef5beed,0x3ec6bed5,0x3ea2be8e,0x3d49bdc8,0x3effbefb,
0x3f003f00,0xbf003f00,0x3f003f00,0xbf003f00,0x3f003f00,0xbf003f00,0x3f003f00,0xbf003f00,0x3f003f00,0xbf003f00,0x3f003f00,0xbf003f00,0x3f003f00,0xbf003f00,0x3f003f00,0xbf003f00,
0x3d490000,0x3eff3f00,0x3ec63eb5,0x3ea23eb5,0x3e153dc8,0x3ef53efb,0x3ee23ed5,0x3e713e8e,0x3e713e44,0x3ee23eed,0x3ef53eed,0x3e153e44,0x3ea23e8e,0x3ec63ed5,0x3eff3efb,0x3d493dc8,
0xbefbbf00,0x3dc80000,0x3dc80000,0x3efb3f00,0xbed5beed,0x3e8e3e44,0x3e8e3e44,0x3ed53eed,0xbe8ebeb5,0x3ed53eb5,0x3ed53eb5,0x3e8e3eb5,0xbdc8be44,0x3efb3eed,0x3efb3eed,0x3dc83e44,
0xbe150000,0xbef5bf00,0xbe71beb5,0x3ee23eb5,0xbec6be8e,0xbea2bed5,0x3d49bdc8,0x3eff3efb,0xbeffbeed,0xbd49be44,0x3ea23e44,0x3ec63eed,0xbee2befb,0x3e713dc8,0x3ef53ed5,0x3e153e8e,
0x3eed3f00,0xbe440000,0xbeedbf00,0x3e440000,0x3e443eb5,0xbeedbeb5,0xbe44beb5,0x3eed3eb5,0xbe440000,0xbeedbf00,0x3e440000,0x3eed3f00,0xbeedbeb5,0xbe44beb5,0x3eed3eb5,0x3e443eb5,
0x3e710000,0x3ee23f00,0xbef5beb5,0xbe15beb5,0x3eff3ed5,0x3d493e8e,0xbec6befb,0x3ea23dc8,0x3ea23eed,0xbec6be44,0x3d49be44,0x3eff3eed,0xbe153dc8,0xbef5befb,0x3ee23e8e,0x3e713ed5,
0xbed5bf00,0x3e8e0000,0xbe8e0000,0xbed5bf00,0x3dc8be44,0x3efb3eed,0xbefbbeed,0x3dc8be44,0x3efb3eb5,0x3dc83eb5,0xbdc8beb5,0x3efb3eb5,0x3e8e3eed,0xbed5be44,0x3ed53e44,0x3e8e3eed,
0xbea20000,0xbec6bf00,0x3d493eb5,0xbeffbeb5,0xbee2befb,0x3e71bdc8,0xbef5be8e,0xbe15bed5,0x3e15be44,0x3ef53eed,0xbe71beed,0x3ee23e44,0x3eff3ed5,0xbd493e8e,0x3ec63dc8,0x3ea23efb,
0x3eb53f00,0xbeb50000,0x3eb53f00,0xbeb50000,0xbeb50000,0xbeb5bf00,0xbeb50000,0xbeb5bf00,0xbeb5bf00,0x3eb50000,0xbeb5bf00,0x3eb50000,0x3eb50000,0x3eb53f00,0x3eb50000,0x3eb53f00,
0x3ec60000,0x3ea23f00,0x3eff3eb5,0xbd493eb5,0x3e713efb,0xbee2bdc8,0xbe153e8e,0xbef5bed5,0xbef5be44,0xbe15beed,0xbee2beed,0x3e71be44,0xbd49bed5,0x3eff3e8e,0x3ea2bdc8,0x3ec63efb,
0xbe8ebf00,0x3ed50000,0x3ed50000,0x3e8e3f00,0x3efb3e44,0x3dc83eed,0x3dc83eed,0xbefbbe44,0xbdc83eb5,0xbefbbeb5,0xbefbbeb5,0x3dc8beb5,0xbed5beed,0x3e8ebe44,0x3e8ebe44,0x3ed53eed,
0xbee20000,0xbe71bf00,0x3e15beb5,0x3ef53eb5,0x3d49bed5,0x3eff3e8e,0x3ea23efb,0xbec63dc8,0x3ec63eed,0xbea23e44,0xbeffbe44,0xbd49beed,0xbef5bdc8,0xbe15befb,0x3e71be8e,0x3ee23ed5,
0x3e443f00,0xbeed0000,0xbe44bf00,0x3eed0000,0xbeedbeb5,0x3e44beb5,0x3eed3eb5,0xbe443eb5,0x3eed0000,0x3e443f00,0xbeed0000,0xbe44bf00,0xbe443eb5,0xbeedbeb5,0x3e44beb5,0x3eed3eb5,
0x3ef50000,0x3e153f00,0xbee2beb5,0x3e71beb5,0xbea23e8e,0xbec6bed5,0x3eff3dc8,0x3d493efb,0x3d49beed,0x3eff3e44,0xbec63e44,0xbea2beed,0x3e713efb,0xbee23dc8,0x3e15bed5,0x3ef53e8e,
0xbdc8bf00,0x3efb0000,0xbefb0000,0xbdc8bf00,0x3e8e3eed,0xbed53e44,0x3ed5be44,0x3e8e3eed,0xbed5beb5,0x3e8ebeb5,0xbe8e3eb5,0xbed5beb5,0x3efb3e44,0xbdc83eed,0x3dc8beed,0x3efb3e44,
0xbeff0000,0xbd49bf00,0xbea23eb5,0xbec6beb5,0x3ef5bdc8,0x3e153efb,0x3e71bed5,0x3ee23e8e,0xbee23e44,0xbe71beed,0xbe153eed,0xbef5be44,0x3ec6be8e,0x3ea23ed5,0x3d49befb,0x3eff3dc8,
0x3f00,0xbf000000,0x3f00,0xbf000000,0xbf00,0x3f000000,0xbf00,0x3f000000,0x3f00,0xbf000000,0x3f00,0xbf000000,0xbf00,0x3f000000,0xbf00,0x3f000000,
0x3eff0000,0xbd493f00,0x3ea23eb5,0xbec63eb5,0xbef5bdc8,0x3e15befb,0xbe71bed5,0x3ee2be8e,0x3ee23e44,0xbe713eed,0x3e153eed,0xbef53e44,0xbec6be8e,0x3ea2bed5,0xbd49befb,0x3effbdc8,
0x3dc8bf00,0x3efb0000,0x3efb0000,0xbdc83f00,0xbe8e3eed,0xbed5be44,0xbed5be44,0x3e8ebeed,0x3ed5beb5,0x3e8e3eb5,0x3e8e3eb5,0xbed53eb5,0xbefb3e44,0xbdc8beed,0xbdc8beed,0x3efbbe44,
0xbef50000,0x3e15bf00,0x3ee2beb5,0x3e713eb5,0x3ea23e8e,0xbec63ed5,0xbeff3dc8,0x3d49befb,0xbd49beed,0x3effbe44,0x3ec63e44,0xbea23eed,0xbe713efb,0xbee2bdc8,0xbe15bed5,0x3ef5be8e,
0xbe443f00,0xbeed0000,0x3e44bf00,0x3eed0000,0x3eedbeb5,0x3e443eb5,0xbeed3eb5,0xbe44beb5,0xbeed0000,0x3e44bf00,0x3eed0000,0xbe443f00,0x3e443eb5,0xbeed3eb5,0xbe44beb5,0x3eedbeb5,
0x3ee20000,0xbe713f00,0xbe15beb5,0x3ef5beb5,0xbd49bed5,0x3effbe8e,0xbea23efb,0xbec6bdc8,0xbec63eed,0xbea2be44,0x3effbe44,0xbd493eed,0x3ef5bdc8,0xbe153efb,0xbe71be8e,0x3ee2bed5,
0x3e8ebf00,0x3ed50000,0xbed50000,0x3e8ebf00,0xbefb3e44,0x3dc8beed,0xbdc83eed,0xbefb3e44,0x3dc83eb5,0xbefb3eb5,0x3efbbeb5,0x3dc83eb5,0x3ed5beed,0x3e8e3e44,0xbe8ebe44,0x3ed5beed,
0xbec60000,0x3ea2bf00,0xbeff3eb5,0xbd49beb5,0xbe713efb,0xbee23dc8,0x3e153e8e,0xbef53ed5,0x3ef5be44,0xbe153eed,0x3ee2beed,0x3e713e44,0x3d49bed5,0x3effbe8e,0xbea2bdc8,0x3ec6befb,
0xbeb53f00,0xbeb50000,0xbeb53f00,0xbeb50000,0x3eb50000,0xbeb53f00,0x3eb50000,0xbeb53f00,0x3eb5bf00,0x3eb50000,0x3eb5bf00,0x3eb50000,0xbeb50000,0x3eb5bf00,0xbeb50000,0x3eb5bf00,
0x3ea20000,0xbec63f00,0xbd493eb5,0xbeff3eb5,0x3ee2befb,0x3e713dc8,0x3ef5be8e,0xbe153ed5,0xbe15be44,0x3ef5beed,0x3e71beed,0x3ee2be44,0xbeff3ed5,0xbd49be8e,0xbec63dc8,0x3ea2befb,
0x3ed5bf00,0x3e8e0000,0x3e8e0000,0xbed53f00,0xbdc8be44,0x3efbbeed,0x3efbbeed,0x3dc83e44,0xbefb3eb5,0x3dc8beb5,0x3dc8beb5,0x3efbbeb5,0xbe8e3eed,0xbed53e44,0xbed53e44,0x3e8ebeed,
0xbe710000,0x3ee2bf00,0x3ef5beb5,0xbe153eb5,0xbeff3ed5,0x3d49be8e,0x3ec6befb,0x3ea2bdc8,0xbea23eed,0xbec63e44,0xbd49be44,0x3effbeed,0x3e153dc8,0xbef53efb,0xbee23e8e,0x3e71bed5,
0xbeed3f00,0xbe440000,0x3eedbf00,0x3e440000,0xbe443eb5,0xbeed3eb5,0x3e44beb5,0x3eedbeb5,0x3e440000,0xbeed3f00,0xbe440000,0x3eedbf00,0x3eedbeb5,0xbe443eb5,0xbeed3eb5,0x3e44beb5,
0x3e150000,0xbef53f00,0x3e71beb5,0x3ee2beb5,0x3ec6be8e,0xbea23ed5,0xbd49bdc8,0x3effbefb,0x3effbeed,0xbd493e44,0xbea23e44,0x3ec6beed,0x3ee2befb,0x3e71bdc8,0xbef53ed5,0x3e15be8e,
0x3efbbf00,0x3dc80000,0xbdc80000,0x3efbbf00,0x3ed5beed,0x3e8ebe44,0xbe8e3e44,0x3ed5beed,0x3e8ebeb5,0x3ed5beb5,0xbed53eb5,0x3e8ebeb5,0x3dc8be44,0x3efbbeed,0xbefb3eed,0x3dc8be44,
0xbd490000,0x3effbf00,0xbec63eb5,0x3ea2beb5,0xbe153dc8,0x3ef5befb,0xbee23ed5,0x3e71be8e,0xbe713e44,0x3ee2beed,0xbef53eed,0x3e15be44,0xbea23e8e,0x3ec6bed5,0xbeff3efb,0x3d49bdc8,
0x3f800000,0x0,0x3f800000,0x0,0x3f800000,0x0,0x3f800000,0x0,0x3f800000,0x0,0x3f800000,0x0,0x3f800000,0x0,0x3f800000,0x0,
0x3f800000,0x0,0x3f7ffec4,0xbbc90f88,0x3f7ffb11,0xbc490e90,0x3f7ff4e6,0xbc96c9b6,0x3f7fec43,0xbcc90ab0,0x3f7fe129,0xbcfb49ba,0x3f7fd397,0xbd16c32c,0x3f7fc38f,0xbd2fe007,
0x3f800000,0x0,0x3f7ffb11,0xbc490e90,0x3f7fec43,0xbcc90ab0,0x3f7fd397,0xbd16c32c,0x3f7fb10f,0xbd48fb30,0x3f7f84ab,0xbd7b2b74,0x3f7f4e6d,0xbd96a905,0x3f7f0e58,0xbdafb680,
0x3f800000,0x0,0x3f7ff4e6,0xbc96c9b6,0x3f7fd397,0xbd16c32c,0x3f7f9c18,0xbd621469,0x3f7f4e6d,0xbd96a905,0x3f7eea9d,0xbdbc3ac3,0x3f7e70b0,0xbde1bc2e,0x3f7de0b1,0xbe039502,
0x3f800000,0x0,0x3f7fec43,0xbcc90ab0,0x3f7fb10f,0xbd48fb30,0x3f7f4e6d,0xbd96a905,0x3f7ec46d,0xbdc8bd36,0x3f7e1324,0xbdfab273,0x3f7d3aac,0xbe164083,0x3f7c3b28,0xbe2f10a2,
0x3f800000,0x0,0x3f7fe129,0xbcfb49ba,0x3f7f84ab,0xbd7b2b74,0x3f7eea9d,0xbdbc3ac3,0x3f7e1324,0xbdfab273,0x3f7cfe73,0xbe1c76de,0x3f7baccd,0xbe3b6ecf,0x3f7a1e84,0xbe5a3997,
0x3f800000,0x0,0x3f7fd397,0xbd16c32c,0x3f7f4e6d,0xbd96a905,0x3f7e70b0,0xbde1bc2e,0x3f7d3aac,0xbe164083,0x3f7baccd,0xbe3b6ecf,0x3f79c79d,0xbe605c13,0x3f778bc5,0xbe827dc0,
0x3f800000,0x0,0x3f7fc38f,0xbd2fe007,0x3f7f0e58,0xbdafb680,0x3f7de0b1,0xbe039502,0x3f7c3b28,0xbe2f10a2,0x3f7a1e84,0xbe5a3997,0x3f778bc5,0xbe827dc0,0x3f748422,0xbe97a117,
0x3f800000,0x0,0x3f7fb10f,0xbd48fb30,0x3f7ec46d,0xbdc8bd36,0x3f7d3aac,0xbe164083,0x3f7b14be,0xbe47c5c2,0x3f7853f8,0xbe78cfcc,0x3f74fa0b,0xbe94a031,0x3f710908,0xbeac7cd4,
0x3f800000,0x0,0x3f7f9c18,0xbd621469,0x3f7e70b0,0xbde1bc2e,0x3f7c7eb0,0xbe28defc,0x3f79c79d,0xbe605c13,0x3f764d97,0xbe8b9507,0x3f721352,0xbea68f12,0x3f6d1c1d,0xbec1071e,
0x3f800000,0x0,0x3f7f84ab,0xbd7b2b74,0x3f7e1324,0xbdfab273,0x3f7baccd,0xbe3b6ecf,0x3f7853f8,0xbe78cfcc,0x3f740bdd,0xbe9aa086,0x3f6ed89e,0xbeb8442a,0x3f68bf3c,0xbed53641,
0x3f800000,0x0,0x3f7f6ac7,0xbd8a200a,0x3f7dabcc,0xbe09cf86,0x3f7ac516,0xbe4dee60,0x3f76ba07,0xbe888e93,0x3f718f57,0xbea986c4,0x3f6b4b0c,0xbec9b953,0x3f63f473,0xbee900b7,
0x3f800000,0x0,0x3f7f4e6d,0xbd96a905,0x3f7d3aac,0xbe164083,0x3f79c79d,0xbe605c13,0x3f74fa0b,0xbe94a031,0x3f6ed89e,0xbeb8442a,0x3f676bd8,0xbedae880,0x3f5ebe05,0xbefc5d27,
0x3f800000,0x0,0x3f7f2f9d,0xbda3308c,0x3f7cbfc9,0xbe22abb6,0x3f78b47b,0xbe72b651,0x3f731447,0xbea09ae5,0x3f6be858,0xbec6d529,0x3f633c5a,0xbeebcbbb,0x3f591e6a,0xbf07a136,
0x3f800000,0x0,0x3f7f0e58,0xbdafb680,0x3f7c3b28,0xbe2f10a2,0x3f778bc5,0xbe827dc0,0x3f710908,0xbeac7cd4,0x3f68bf3c,0xbed53641,0x3f5ebe05,0xbefc5d27,0x3f531849,0xbf10d3cd,
0x3f800000,0x0,0x3f7eea9d,0xbdbc3ac3,0x3f7baccd,0xbe3b6ecf,0x3f764d97,0xbe8b9507,0x3f6ed89e,0xbeb8442a,0x3f655e0b,0xbee363fa,0x3f59f26a,0xbf064b82,0x3f4cae79,0xbf19c200,
0x3f800000,0x0,0x3f7ec46d,0xbdc8bd36,0x3f7b14be,0xbe47c5c2,0x3f74fa0b,0xbe94a031,0x3f6c835e,0xbec3ef15,0x3f61c598,0xbef15aea,0x3f54db31,0xbf0e39da,0x3f45e403,0xbf226799,
0x3f800000,0x0,0x3f7e9bc9,0xbdd53db9,0x3f7a7302,0xbe541501,0x3f73913f,0xbe9d9e78,0x3f6a09a7,0xbecf7bca,0x3f5df6be,0xbeff17b2,0x3f4f7a1f,0xbf15f6d9,0x3f3ebc1b,0xbf2ac082,
0x3f800000,0x0,0x3f7e70b0,0xbde1bc2e,0x3f79c79d,0xbe605c13,0x3f721352,0xbea68f12,0x3f676bd8,0xbedae880,0x3f59f26a,0xbf064b82,0x3f49d112,0xbf1d7fd1,0x3f373a23,0xbf32c8c9,
0x3f800000,0x0,0x3f7e4323,0xbdee3876,0x3f791298,0xbe6c9a7f,0x3f708066,0xbeaf713a,0x3f64aa59,0xbee63375,0x3f55b993,0xbf0cead0,0x3f43e200,0xbf24d225,0x3f2f61a5,0xbf3a7ca4,
0x3f800000,0x0,0x3f7e1324,0xbdfab273,0x3f7853f8,0xbe78cfcc,0x3f6ed89e,0xbeb8442a,0x3f61c598,0xbef15aea,0x3f514d3d,0xbf13682a,0x3f3daef9,0xbf2beb4a,0x3f273656,0xbf41d870,
0x3f800000,0x0,0x3f7de0b1,0xbe039502,0x3f778bc5,0xbe827dc0,0x3f6d1c1d,0xbec1071e,0x3f5ebe05,0xbefc5d27,0x3f4cae79,0xbf19c200,0x3f373a23,0xbf32c8c9,0x3f1ebc12,0xbf48d8b3,
0x3f800000,0x0,0x3f7dabcc,0xbe09cf86,0x3f76ba07,0xbe888e93,0x3f6b4b0c,0xbec9b953,0x3f5b941a,0xbf039c3d,0x3f47de65,0xbf1ff6cb,0x3f3085bb,0xbf396842,0x3f15f6d9,0xbf4f7a1f,
0x3f800000,0x0,0x3f7d7474,0xbe1008b7,0x3f75dec6,0xbe8e9a22,0x3f696591,0xbed25a09,0x3f584853,0xbf08f59b,0x3f42de29,0xbf26050a,0x3f299415,0xbf3fc767,0x3f0cead0,0xbf55b993,
0x3f800000,0x0,0x3f7d3aac,0xbe164083,0x3f74fa0b,0xbe94a031,0x3f676bd8,0xbedae880,0x3f54db31,0xbf0e39da,0x3f3daef9,0xbf2beb4a,0x3f226799,0xbf45e403,0x3f039c3d,0xbf5b941a,
0x3f800000,0x0,0x3f7cfe73,0xbe1c76de,0x3f740bdd,0xbe9aa086,0x3f655e0b,0xbee363fa,0x3f514d3d,0xbf13682a,0x3f385216,0xbf31a81d,0x3f1b02c6,0xbf4bbbf8,0x3ef41f07,0xbf6106f2,
0x3f800000,0x0,0x3f7cbfc9,0xbe22abb6,0x3f731447,0xbea09ae5,0x3f633c5a,0xbeebcbbb,0x3f4d9f02,0xbf187fc0,0x3f32c8c9,0xbf373a23,0x3f13682a,0xbf514d3d,0x3ee0924f,0xbf660f88,
0x3f800000,0x0,0x3f7c7eb0,0xbe28defc,0x3f721352,0xbea68f12,0x3f6106f2,0xbef41f07,0x3f49d112,0xbf1d7fd1,0x3f2d1469,0xbf3ca003,0x3f0b9a6b,0xbf5695e5,0x3ecc9b8b,0xbf6aab7b,
0x3f800000,0x0,0x3f7c3b28,0xbe2f10a2,0x3f710908,0xbeac7cd4,0x3f5ebe05,0xbefc5d27,0x3f45e403,0xbf226799,0x3f273656,0xbf41d870,0x3f039c3d,0xbf5b941a,0x3eb8442a,0xbf6ed89e,
0x3f800000,0x0,0x3f7bf531,0xbe354098,0x3f6ff573,0xbeb263ef,0x3f5c61c7,0xbf0242b1,0x3f41d870,0xbf273656,0x3f212ff9,0xbf46e22a,0x3ef6e0cb,0xbf604621,0x3ea395c5,0xbf7294f8,
0x3f800000,0x0,0x3f7baccd,0xbe3b6ecf,0x3f6ed89e,0xbeb8442a,0x3f59f26a,0xbf064b82,0x3f3daef9,0xbf2beb4a,0x3f1b02c6,0xbf4bbbf8,0x3ee63375,0xbf64aa59,0x3e8e9a22,0xbf75dec6,
0x3f800000,0x0,0x3f7b61fc,0xbe419b37,0x3f6db293,0xbebe1d4a,0x3f577026,0xbf0a48ad,0x3f396842,0xbf3085bb,0x3f14b039,0xbf5064af,0x3ed53641,0xbf68bf3c,0x3e72b651,0xbf78b47b,
0x3f800000,0x0,0x3f800000,0x0,0x3f800000,0x0,0x3f800000,0x0,0x3f800000,0x0,0x3f800000,0x0,0x3f800000,0x0,0x3f800000,0x0,
0x3f7fb10f,0xbd48fb30,0x3f7f9c18,0xbd621469,0x3f7f84ab,0xbd7b2b74,0x3f7f6ac7,0xbd8a200a,0x3f7f4e6d,0xbd96a905,0x3f7f2f9d,0xbda3308c,0x3f7f0e58,0xbdafb680,0x3f7eea9d,0xbdbc3ac3,
0x3f7ec46d,0xbdc8bd36,0x3f7e70b0,0xbde1bc2e,0x3f7e1324,0xbdfab273,0x3f7dabcc,0xbe09cf86,0x3f7d3aac,0xbe164083,0x3f7cbfc9,0xbe22abb6,0x3f7c3b28,0xbe2f10a2,0x3f7baccd,0xbe3b6ecf,
0x3f7d3aac,0xbe164083,0x3f7c7eb0,0xbe28defc,0x3f7baccd,0xbe3b6ecf,0x3f7ac516,0xbe4dee60,0x3f79c79d,0xbe605c13,0x3f78b47b,0xbe72b651,0x3f778bc5,0xbe827dc0,0x3f764d97,0xbe8b9507,
0x3f7b14be,0xbe47c5c2,0x3f79c79d,0xbe605c13,0x3f7853f8,0xbe78cfcc,0x3f76ba07,0xbe888e93,0x3f74fa0b,0xbe94a031,0x3f731447,0xbea09ae5,0x3f710908,0xbeac7cd4,0x3f6ed89e,0xbeb8442a,
0x3f7853f8,0xbe78cfcc,0x3f764d97,0xbe8b9507,0x3f740bdd,0xbe9aa086,0x3f718f57,0xbea986c4,0x3f6ed89e,0xbeb8442a,0x3f6be858,0xbec6d529,0x3f68bf3c,0xbed53641,0x3f655e0b,0xbee363fa,
0x3f74fa0b,0xbe94a031,0x3f721352,0xbea68f12,0x3f6ed89e,0xbeb8442a,0x3f6b4b0c,0xbec9b953,0x3f676bd8,0xbedae880,0x3f633c5a,0xbeebcbbb,0x3f5ebe05,0xbefc5d27,0x3f59f26a,0xbf064b82,
0x3f710908,0xbeac7cd4,0x3f6d1c1d,0xbec1071e,0x3f68bf3c,0xbed53641,0x3f63f473,0xbee900b7,0x3f5ebe05,0xbefc5d27,0x3f591e6a,0xbf07a136,0x3f531849,0xbf10d3cd,0x3f4cae79,0xbf19c200,
0x3f6c835e,0xbec3ef15,0x3f676bd8,0xbedae880,0x3f61c598,0xbef15aea,0x3f5b941a,0xbf039c3d,0x3f54db31,0xbf0e39da,0x3f4d9f02,0xbf187fc0,0x3f45e403,0xbf226799,0x3f3daef9,0xbf2beb4a,
0x3f676bd8,0xbedae880,0x3f6106f2,0xbef41f07,0x3f59f26a,0xbf064b82,0x3f5233c6,0xbf121eb0,0x3f49d112,0xbf1d7fd1,0x3f40d0da,0xbf286605,0x3f373a23,0xbf32c8c9,0x3f2d1469,0xbf3ca003,
0x3f61c598,0xbef15aea,0x3f59f26a,0xbf064b82,0x3f514d3d,0xbf13682a,0x3f47de65,0xbf1ff6cb,0x3f3daef9,0xbf2beb4a,0x3f32c8c9,0xbf373a23,0x3f273656,0xbf41d870,0x3f1b02c6,0xbf4bbbf8,
0x3f5b941a,0xbf039c3d,0x3f5233c6,0xbf121eb0,0x3f47de65,0xbf1ff6cb,0x3f3ca003,0xbf2d1469,0x3f3085bb,0xbf396842,0x3f239da9,0xbf44e3f5,0x3f15f6d9,0xbf4f7a1f,0x3f07a136,0xbf591e6a,
0x3f54db31,0xbf0e39da,0x3f49d112,0xbf1d7fd1,0x3f3daef9,0xbf2beb4a,0x3f3085bb,0xbf396842,0x3f226799,0xbf45e403,0x3f13682a,0xbf514d3d,0x3f039c3d,0xbf5b941a,0x3ee63375,0xbf64aa59,
0x3f4d9f02,0xbf187fc0,0x3f40d0da,0xbf286605,0x3f32c8c9,0xbf373a23,0x3f239da9,0xbf44e3f5,0x3f13682a,0xbf514d3d,0x3f0242b1,0xbf5c61c7,0x3ee0924f,0xbf660f88,0x3ebb31a0,0xbf6e46be,
0x3f45e403,0xbf226799,0x3f373a23,0xbf32c8c9,0x3f273656,0xbf41d870,0x3f15f6d9,0xbf4f7a1f,0x3f039c3d,0xbf5b941a,0x3ee0924f,0xbf660f88,0x3eb8442a,0xbf6ed89e,0x3e8e9a22,0xbf75dec6,
0x3f3daef9,0xbf2beb4a,0x3f2d1469,0xbf3ca003,0x3f1b02c6,0xbf4bbbf8,0x3f07a136,0xbf591e6a,0x3ee63375,0xbf64aa59,0x3ebb31a0,0xbf6e46be,0x3e8e9a22,0xbf75dec6,0x3e419b37,0xbf7b61fc,
0x3f3504f3,0xbf3504f3,0x3f226799,0xbf45e403,0x3f0e39da,0xbf54db31,0x3ef15aea,0xbf61c598,0x3ec3ef15,0xbf6c835e,0x3e94a031,0xbf74fa0b,0x3e47c5c2,0xbf7b14be,0x3dc8bd36,0xbf7ec46d,
0x3f2beb4a,0xbf3daef9,0x3f173c07,0xbf4e8d90,0x3f00e7e4,0xbf5d2d53,0x3ed25a09,0xbf696591,0x3ea09ae5,0xbf731447,0x3e5a3997,0xbf7a1e84,0x3de1bc2e,0xbf7e70b0,0x3bc90f88,0xbf7ffec4,
0x3f226799,0xbf45e403,0x3f0b9a6b,0xbf5695e5,0x3ee63375,0xbf64aa59,0x3eb263ef,0xbf6ff573,0x3e78cfcc,0xbf7853f8,0x3e09cf86,0xbf7dabcc,0x3cc90ab0,0xbf7fec43,0xbdafb680,0xbf7f0e58,
0x3f187fc0,0xbf4d9f02,0x3eff17b2,0xbf5df6be,0x3ec9b953,0xbf6b4b0c,0x3e919ddd,0xbf756d97,0x3e2f10a2,0xbf7c3b28,0x3d621469,0xbf7f9c18,0xbd7b2b74,0xbf7f84ab,0xbe354098,0xbf7bf531,
0x3f0e39da,0xbf54db31,0x3ee63375,0xbf64aa59,0x3eac7cd4,0xbf710908,0x3e605c13,0xbf79c79d,0x3dc8bd36,0xbf7ec46d,0xbcc90ab0,0xbf7fec43,0xbe164083,0xbf7d3aac,0xbe888e93,0xbf76ba07,
0x3f039c3d,0xbf5b941a,0x3ecc9b8b,0xbf6aab7b,0x3e8e9a22,0xbf75dec6,0x3e1c76de,0xbf7cfe73,0x3cc90ab0,0xbf7fec43,0xbdd53db9,0xbf7e9bc9,0xbe6c9a7f,0xbf791298,0xbeb554ec,0xbf6f6830,
0x3ef15aea,0xbf61c598,0x3eb263ef,0xbf6ff573,0x3e605c13,0xbf79c79d,0x3dafb680,0xbf7f0e58,0xbd48fb30,0xbf7fb10f,0xbe3b6ecf,0xbf7baccd,0xbea09ae5,0xbf731447,0xbee0924f,0xbf660f88,
0x3edae880,0xbf676bd8,0x3e97a117,0xbf748422,0x3e22abb6,0xbf7cbfc9,0x3c96c9b6,0xbf7ff4e6,0xbdfab273,0xbf7e1324,0xbe8586ce,0xbf772417,0xbec9b953,0xbf6b4b0c,0xbf04f484,0xbf5ac450,
0x3ec3ef15,0xbf6c835e,0x3e78cfcc,0xbf7853f8,0x3dc8bd36,0xbf7ec46d,0xbd48fb30,0xbf7fb10f,0xbe47c5c2,0xbf7b14be,0xbeac7cd4,0xbf710908,0xbef15aea,0xbf61c598,0xbf187fc0,0xbf4d9f02,
0x3eac7cd4,0xbf710908,0x3e419b37,0xbf7b61fc,0x3d16c32c,0xbf7fd397,0xbdee3876,0xbf7e4323,0xbe888e93,0xbf76ba07,0xbed25a09,0xbf696591,0xbf0b9a6b,0xbf5695e5,0xbf2ac082,0xbf3ebc1b,
0x3e94a031,0xbf74fa0b,0x3e09cf86,0xbf7dabcc,0xbcc90ab0,0xbf7fec43,0xbe3b6ecf,0xbf7baccd,0xbeac7cd4,0xbf710908,0xbef6e0cb,0xbf604621,0xbf1d7fd1,0xbf49d112,0xbf3b8f3b,0xbf2e3bde,
0x3e78cfcc,0xbf7853f8,0x3da3308c,0xbf7f2f9d,0xbdafb680,0xbf7f0e58,0xbe7ee6e1,0xbf77f110,0xbecf7bca,0xbf6a09a7,0xbf0cead0,0xbf55b993,0xbf2e3bde,0xbf3b8f3b,0xbf4ac77f,0xbf1c420c,
0x3e47c5c2,0xbf7b14be,0x3cc90ab0,0xbf7fec43,0xbe164083,0xbf7d3aac,0xbea09ae5,0xbf731447,0xbef15aea,0xbf61c598,0xbf1d7fd1,0xbf49d112,0xbf3daef9,0xbf2beb4a,0xbf584853,0xbf08f59b,
0x3e164083,0xbf7d3aac,0xbcfb49ba,0xbf7fe129,0xbe541501,0xbf7a7302,0xbec1071e,0xbf6d1c1d,0xbf08f59b,0xbf584853,0xbf2d1469,0xbf3ca003,0xbf4bbbf8,0xbf1b02c6,0xbf63f473,0xbee900b7,
0x3dc8bd36,0xbf7ec46d,0xbdafb680,0xbf7f0e58,0xbe888e93,0xbf76ba07,0xbee0924f,0xbf660f88,0xbf187fc0,0xbf4d9f02,0xbf3b8f3b,0xbf2e3bde,0xbf584853,0xbf08f59b,0xbf6db293,0xbebe1d4a,
0x3d48fb30,0xbf7fb10f,0xbe1008b7,0xbf7d7474,0xbea68f12,0xbf721352,0xbeff17b2,0xbf5df6be,0xbf273656,0xbf41d870,0xbf48d8b3,0xbf1ebc12,0xbf633c5a,0xbeebcbbb,0xbf756d97,0xbe919ddd,
0x3f800000,0x0,0x3f800000,0x0,0x3f800000,0x0,0x3f800000,0x0,0x3f800000,0x0,0x3f800000,0x0,0x3f800000,0x0,0x3f800000,0x0,
0x3f7ec46d,0xbdc8bd36,0x3f7e9bc9,0xbdd53db9,0x3f7e70b0,0xbde1bc2e,0x3f7e4323,0xbdee3876,0x3f7e1324,0xbdfab273,0x3f7de0b1,0xbe039502,0x3f7dabcc,0xbe09cf86,0x3f7d7474,0xbe1008b7,
0x3f7b14be,0xbe47c5c2,0x3f7a7302,0xbe541501,0x3f79c79d,0xbe605c13,0x3f791298,0xbe6c9a7f,0x3f7853f8,0xbe78cfcc,0x3f778bc5,0xbe827dc0,0x3f76ba07,0xbe888e93,0x3f75dec6,0xbe8e9a22,
0x3f74fa0b,0xbe94a031,0x3f73913f,0xbe9d9e78,0x3f721352,0xbea68f12,0x3f708066,0xbeaf713a,0x3f6ed89e,0xbeb8442a,0x3f6d1c1d,0xbec1071e,0x3f6b4b0c,0xbec9b953,0x3f696591,0xbed25a09,
0x3f6c835e,0xbec3ef15,0x3f6a09a7,0xbecf7bca,0x3f676bd8,0xbedae880,0x3f64aa59,0xbee63375,0x3f61c598,0xbef15aea,0x3f5ebe05,0xbefc5d27,0x3f5b941a,0xbf039c3d,0x3f584853,0xbf08f59b,
0x3f61c598,0xbef15aea,0x3f5df6be,0xbeff17b2,0x3f59f26a,0xbf064b82,0x3f55b993,0xbf0cead0,0x3f514d3d,0xbf13682a,0x3f4cae79,0xbf19c200,0x3f47de65,0xbf1ff6cb,0x3f42de29,0xbf26050a,
0x3f54db31,0xbf0e39da,0x3f4f7a1f,0xbf15f6d9,0x3f49d112,0xbf1d7fd1,0x3f43e200,0xbf24d225,0x3f3daef9,0xbf2beb4a,0x3f373a23,0xbf32c8c9,0x3f3085bb,0xbf396842,0x3f299415,0xbf3fc767,
0x3f45e403,0xbf226799,0x3f3ebc1b,0xbf2ac082,0x3f373a23,0xbf32c8c9,0x3f2f61a5,0xbf3a7ca4,0x3f273656,0xbf41d870,0x3f1ebc12,0xbf48d8b3,0x3f15f6d9,0xbf4f7a1f,0x3f0cead0,0xbf55b993,
0x3f3504f3,0xbf3504f3,0x3f2beb4a,0xbf3daef9,0x3f226799,0xbf45e403,0x3f187fc0,0xbf4d9f02,0x3f0e39da,0xbf54db31,0x3f039c3d,0xbf5b941a,0x3ef15aea,0xbf61c598,0x3edae880,0xbf676bd8,
0x3f226799,0xbf45e403,0x3f173c07,0xbf4e8d90,0x3f0b9a6b,0xbf5695e5,0x3eff17b2,0xbf5df6be,0x3ee63375,0xbf64aa59,0x3ecc9b8b,0xbf6aab7b,0x3eb263ef,0xbf6ff573,0x3e97a117,0xbf748422,
0x3f0e39da,0xbf54db31,0x3f00e7e4,0xbf5d2d53,0x3ee63375,0xbf64aa59,0x3ec9b953,0xbf6b4b0c,0x3eac7cd4,0xbf710908,0x3e8e9a22,0xbf75dec6,0x3e605c13,0xbf79c79d,0x3e22abb6,0xbf7cbfc9,
0x3ef15aea,0xbf61c598,0x3ed25a09,0xbf696591,0x3eb263ef,0xbf6ff573,0x3e919ddd,0xbf756d97,0x3e605c13,0xbf79c79d,0x3e1c76de,0xbf7cfe73,0x3dafb680,0xbf7f0e58,0x3c96c9b6,0xbf7ff4e6,
0x3ec3ef15,0xbf6c835e,0x3ea09ae5,0xbf731447,0x3e78cfcc,0xbf7853f8,0x3e2f10a2,0xbf7c3b28,0x3dc8bd36,0xbf7ec46d,0x3cc90ab0,0xbf7fec43,0xbd48fb30,0xbf7fb10f,0xbdfab273,0xbf7e1324,
0x3e94a031,0xbf74fa0b,0x3e5a3997,0xbf7a1e84,0x3e09cf86,0xbf7dabcc,0x3d621469,0xbf7f9c18,0xbcc90ab0,0xbf7fec43,0xbdd53db9,0xbf7e9bc9,0xbe3b6ecf,0xbf7baccd,0xbe8586ce,0xbf772417,
0x3e47c5c2,0xbf7b14be,0x3de1bc2e,0xbf7e70b0,0x3cc90ab0,0xbf7fec43,0xbd7b2b74,0xbf7f84ab,0xbe164083,0xbf7d3aac,0xbe6c9a7f,0xbf791298,0xbea09ae5,0xbf731447,0xbec9b953,0xbf6b4b0c,
0x3dc8bd36,0xbf7ec46d,0x3bc90f88,0xbf7ffec4,0xbdafb680,0xbf7f0e58,0xbe354098,0xbf7bf531,0xbe888e93,0xbf76ba07,0xbeb554ec,0xbf6f6830,0xbee0924f,0xbf660f88,0xbf04f484,0xbf5ac450,
0x0,0xbf800000,0xbdc8bd36,0xbf7ec46d,0xbe47c5c2,0xbf7b14be,0xbe94a031,0xbf74fa0b,0xbec3ef15,0xbf6c835e,0xbef15aea,0xbf61c598,0xbf0e39da,0xbf54db31,0xbf226799,0xbf45e403,
0xbdc8bd36,0xbf7ec46d,0xbe4dee60,0xbf7ac516,0xbe9aa086,0xbf740bdd,0xbecc9b8b,0xbf6aab7b,0xbefc5d27,0xbf5ebe05,0xbf14b039,0xbf5064af,0xbf299415,0xbf3fc767,0xbf3ca003,0xbf2d1469,
0xbe47c5c2,0xbf7b14be,0xbe9aa086,0xbf740bdd,0xbecf7bca,0xbf6a09a7,0xbf00e7e4,0xbf5d2d53,0xbf187fc0,0xbf4d9f02,0xbf2e3bde,0xbf3b8f3b,0xbf41d870,0xbf273656,0xbf531849,0xbf10d3cd,
0xbe94a031,0xbf74fa0b,0xbecc9b8b,0xbf6aab7b,0xbf00e7e4,0xbf5d2d53,0xbf19c200,0xbf4cae79,0xbf3085bb,0xbf396842,0xbf44e3f5,0xbf239da9,0xbf5695e5,0xbf0b9a6b,0xbf655e0b,0xbee363fa,
0xbec3ef15,0xbf6c835e,0xbefc5d27,0xbf5ebe05,0xbf187fc0,0xbf4d9f02,0xbf3085bb,0xbf396842,0xbf45e403,0xbf226799,0xbf584853,0xbf08f59b,0xbf676bd8,0xbedae880,0xbf731447,0xbea09ae5,
0xbef15aea,0xbf61c598,0xbf14b039,0xbf5064af,0xbf2e3bde,0xbf3b8f3b,0xbf44e3f5,0xbf239da9,0xbf584853,0xbf08f59b,0xbf6816a8,0xbed8106b,0xbf740bdd,0xbe9aa086,0xbf7bf531,0xbe354098,
0xbf0e39da,0xbf54db31,0xbf299415,0xbf3fc767,0xbf41d870,0xbf273656,0xbf5695e5,0xbf0b9a6b,0xbf676bd8,0xbedae880,0xbf740bdd,0xbe9aa086,0xbf7c3b28,0xbe2f10a2,0xbf7fd397,0xbd16c32c,
0xbf226799,0xbf45e403,0xbf3ca003,0xbf2d1469,0xbf531849,0xbf10d3cd,0xbf655e0b,0xbee363fa,0xbf731447,0xbea09ae5,0xbf7bf531,0xbe354098,0xbf7fd397,0xbd16c32c,0xbf7e9bc9,0x3dd53db9,
0xbf3504f3,0xbf3504f3,0xbf4d9f02,0xbf187fc0,0xbf61c598,0xbef15aea,0xbf710908,0xbeac7cd4,0xbf7b14be,0xbe47c5c2,0xbf7fb10f,0xbd48fb30,0xbf7ec46d,0x3dc8bd36,0xbf7853f8,0x3e78cfcc,
0xbf45e403,0xbf226799,0xbf5c61c7,0xbf0242b1,0xbf6db293,0xbebe1d4a,0xbf796e4e,0xbe667c66,0xbf7f4e6d,0xbd96a905,0xbf7f2f9d,0x3da3308c,0xbf791298,0x3e6c9a7f,0xbf6d1c1d,0x3ec1071e,
0xbf54db31,0xbf0e39da,0xbf68bf3c,0xbed53641,0xbf76ba07,0xbe888e93,0xbf7e70b0,0xbde1bc2e,0xbf7fb10f,0x3d48fb30,0xbf7a7302,0x3e541501,0xbf6ed89e,0x3eb8442a,0xbf5d2d53,0x3f00e7e4,
0xbf61c598,0xbef15aea,0xbf7294f8,0xbea395c5,0xbf7cbfc9,0xbe22abb6,0xbf7ffec4,0x3bc90f88,0xbf7c3b28,0x3e2f10a2,0xbf718f57,0x3ea986c4,0xbf604621,0x3ef6e0cb,0xbf48d8b3,0x3f1ebc12,
0xbf6c835e,0xbec3ef15,0xbf79c79d,0xbe605c13,0xbf7fb10f,0xbd48fb30,0xbf7e1324,0x3dfab273,0xbf74fa0b,0x3e94a031,0xbf64aa59,0x3ee63375,0xbf4d9f02,0x3f187fc0,0xbf3085bb,0x3f396842,
0xbf74fa0b,0xbe94a031,0xbf7e4323,0xbdee3876,0xbf7f84ab,0x3d7b2b74,0xbf78b47b,0x3e72b651,0xbf6a09a7,0x3ecf7bca,0xbf53fac3,0x3f0f8784,0xbf373a23,0x3f32c8c9,0xbf14b039,0x3f5064af,
0xbf7b14be,0xbe47c5c2,0xbf7ffb11,0xbc490e90,0xbf7c3b28,0x3e2f10a2,0xbf6ff573,0x3eb263ef,0xbf5b941a,0x3f039c3d,0xbf3fc767,0x3f299415,0xbf1d7fd1,0x3f49d112,0xbeebcbbb,0x3f633c5a,
0xbf7ec46d,0xbdc8bd36,0xbf7eea9d,0x3dbc3ac3,0xbf75dec6,0x3e8e9a22,0xbf63f473,0x3ee900b7,0xbf49d112,0x3f1d7fd1,0xbf286605,0x3f40d0da,0xbf00e7e4,0x3f5d2d53,0xbea986c4,0x3f718f57,
0x3f800000,0x0,0x3f800000,0x0,0x3f800000,0x0,0x3f800000,0x0,0x3f800000,0x0,0x3f800000,0x0,0x3f800000,0x0,0x3f800000,0x0,
0x3f7d3aac,0xbe164083,0x3f7cfe73,0xbe1c76de,0x3f7cbfc9,0xbe22abb6,0x3f7c7eb0,0xbe28defc,0x3f7c3b28,0xbe2f10a2,0x3f7bf531,0xbe354098,0x3f7baccd,0xbe3b6ecf,0x3f7b61fc,0xbe419b37,
0x3f74fa0b,0xbe94a031,0x3f740bdd,0xbe9aa086,0x3f731447,0xbea09ae5,0x3f721352,0xbea68f12,0x3f710908,0xbeac7cd4,0x3f6ff573,0xbeb263ef,0x3f6ed89e,0xbeb8442a,0x3f6db293,0xbebe1d4a,
0x3f676bd8,0xbedae880,0x3f655e0b,0xbee363fa,0x3f633c5a,0xbeebcbbb,0x3f6106f2,0xbef41f07,0x3f5ebe05,0xbefc5d27,0x3f5c61c7,0xbf0242b1,0x3f59f26a,0xbf064b82,0x3f577026,0xbf0a48ad,
0x3f54db31,0xbf0e39da,0x3f514d3d,0xbf13682a,0x3f4d9f02,0xbf187fc0,0x3f49d112,0xbf1d7fd1,0x3f45e403,0xbf226799,0x3f41d870,0xbf273656,0x3f3daef9,0xbf2beb4a,0x3f396842,0xbf3085bb,
0x3f3daef9,0xbf2beb4a,0x3f385216,0xbf31a81d,0x3f32c8c9,0xbf373a23,0x3f2d1469,0xbf3ca003,0x3f273656,0xbf41d870,0x3f212ff9,0xbf46e22a,0x3f1b02c6,0xbf4bbbf8,0x3f14b039,0xbf5064af,
0x3f226799,0xbf45e403,0x3f1b02c6,0xbf4bbbf8,0x3f13682a,0xbf514d3d,0x3f0b9a6b,0xbf5695e5,0x3f039c3d,0xbf5b941a,0x3ef6e0cb,0xbf604621,0x3ee63375,0xbf64aa59,0x3ed53641,0xbf68bf3c,
0x3f039c3d,0xbf5b941a,0x3ef41f07,0xbf6106f2,0x3ee0924f,0xbf660f88,0x3ecc9b8b,0xbf6aab7b,0x3eb8442a,0xbf6ed89e,0x3ea395c5,0xbf7294f8,0x3e8e9a22,0xbf75dec6,0x3e72b651,0xbf78b47b,
0x3ec3ef15,0xbf6c835e,0x3eac7cd4,0xbf710908,0x3e94a031,0xbf74fa0b,0x3e78cfcc,0xbf7853f8,0x3e47c5c2,0xbf7b14be,0x3e164083,0xbf7d3aac,0x3dc8bd36,0xbf7ec46d,0x3d48fb30,0xbf7fb10f,
0x3e78cfcc,0xbf7853f8,0x3e419b37,0xbf7b61fc,0x3e09cf86,0xbf7dabcc,0x3da3308c,0xbf7f2f9d,0x3cc90ab0,0xbf7fec43,0xbcfb49ba,0xbf7fe129,0xbdafb680,0xbf7f0e58,0xbe1008b7,0xbf7d7474,
0x3dc8bd36,0xbf7ec46d,0x3d16c32c,0xbf7fd397,0xbcc90ab0,0xbf7fec43,0xbdafb680,0xbf7f0e58,0xbe164083,0xbf7d3aac,0xbe541501,0xbf7a7302,0xbe888e93,0xbf76ba07,0xbea68f12,0xbf721352,
0xbd48fb30,0xbf7fb10f,0xbdee3876,0xbf7e4323,0xbe3b6ecf,0xbf7baccd,0xbe7ee6e1,0xbf77f110,0xbea09ae5,0xbf731447,0xbec1071e,0xbf6d1c1d,0xbee0924f,0xbf660f88,0xbeff17b2,0xbf5df6be,
0xbe47c5c2,0xbf7b14be,0xbe888e93,0xbf76ba07,0xbeac7cd4,0xbf710908,0xbecf7bca,0xbf6a09a7,0xbef15aea,0xbf61c598,0xbf08f59b,0xbf584853,0xbf187fc0,0xbf4d9f02,0xbf273656,0xbf41d870,
0xbeac7cd4,0xbf710908,0xbed25a09,0xbf696591,0xbef6e0cb,0xbf604621,0xbf0cead0,0xbf55b993,0xbf1d7fd1,0xbf49d112,0xbf2d1469,0xbf3ca003,0xbf3b8f3b,0xbf2e3bde,0xbf48d8b3,0xbf1ebc12,
0xbef15aea,0xbf61c598,0xbf0b9a6b,0xbf5695e5,0xbf1d7fd1,0xbf49d112,0xbf2e3bde,0xbf3b8f3b,0xbf3daef9,0xbf2beb4a,0xbf4bbbf8,0xbf1b02c6,0xbf584853,0xbf08f59b,0xbf633c5a,0xbeebcbbb,
0xbf187fc0,0xbf4d9f02,0xbf2ac082,0xbf3ebc1b,0xbf3b8f3b,0xbf2e3bde,0xbf4ac77f,0xbf1c420c,0xbf584853,0xbf08f59b,0xbf63f473,0xbee900b7,0xbf6db293,0xbebe1d4a,0xbf756d97,0xbe919ddd,
0xbf3504f3,0xbf3504f3,0xbf45e403,0xbf226799,0xbf54db31,0xbf0e39da,0xbf61c598,0xbef15aea,0xbf6c835e,0xbec3ef15,0xbf74fa0b,0xbe94a031,0xbf7b14be,0xbe47c5c2,0xbf7ec46d,0xbdc8bd36,
0xbf4d9f02,0xbf187fc0,0xbf5c61c7,0xbf0242b1,0xbf68bf3c,0xbed53641,0xbf7294f8,0xbea395c5,0xbf79c79d,0xbe605c13,0xbf7e4323,0xbdee3876,0xbf7ffb11,0xbc490e90,0xbf7eea9d,0x3dbc3ac3,
0xbf61c598,0xbef15aea,0xbf6db293,0xbebe1d4a,0xbf76ba07,0xbe888e93,0xbf7cbfc9,0xbe22abb6,0xbf7fb10f,0xbd48fb30,0xbf7f84ab,0x3d7b2b74,0xbf7c3b28,0x3e2f10a2,0xbf75dec6,0x3e8e9a22,
0xbf710908,0xbeac7cd4,0xbf796e4e,0xbe667c66,0xbf7e70b0,0xbde1bc2e,0xbf7ffec4,0x3bc90f88,0xbf7e1324,0x3dfab273,0xbf78b47b,0x3e72b651,0xbf6ff573,0x3eb263ef,0xbf63f473,0x3ee900b7,
0xbf7b14be,0xbe47c5c2,0xbf7f4e6d,0xbd96a905,0xbf7fb10f,0x3d48fb30,0xbf7c3b28,0x3e2f10a2,0xbf74fa0b,0x3e94a031,0xbf6a09a7,0x3ecf7bca,0xbf5b941a,0x3f039c3d,0xbf49d112,0x3f1d7fd1,
0xbf7fb10f,0xbd48fb30,0xbf7f2f9d,0x3da3308c,0xbf7a7302,0x3e541501,0xbf718f57,0x3ea986c4,0xbf64aa59,0x3ee63375,0xbf53fac3,0x3f0f8784,0xbf3fc767,0x3f299415,0xbf286605,0x3f40d0da,
0xbf7ec46d,0x3dc8bd36,0xbf791298,0x3e6c9a7f,0xbf6ed89e,0x3eb8442a,0xbf604621,0x3ef6e0cb,0xbf4d9f02,0x3f187fc0,0xbf373a23,0x3f32c8c9,0xbf1d7fd1,0x3f49d112,0xbf00e7e4,0x3f5d2d53,
0xbf7853f8,0x3e78cfcc,0xbf6d1c1d,0x3ec1071e,0xbf5d2d53,0x3f00e7e4,0xbf48d8b3,0x3f1ebc12,0xbf3085bb,0x3f396842,0xbf14b039,0x3f5064af,0xbeebcbbb,0x3f633c5a,0xbea986c4,0x3f718f57,
0xbf6c835e,0x3ec3ef15,0xbf5b941a,0x3f039c3d,0xbf45e403,0x3f226799,0xbf2beb4a,0x3f3daef9,0xbf0e39da,0x3f54db31,0xbedae880,0x3f676bd8,0xbe94a031,0x3f74fa0b,0xbe164083,0x3f7d3aac,
0xbf5b941a,0x3f039c3d,0xbf44e3f5,0x3f239da9,0xbf299415,0x3f3fc767,0xbf0a48ad,0x3f577026,0xbecf7bca,0x3f6a09a7,0xbe8586ce,0x3f772417,0xbde1bc2e,0x3f7e70b0,0x3d2fe007,0x3f7fc38f,
0xbf45e403,0x3f226799,0xbf299415,0x3f3fc767,0xbf08f59b,0x3f584853,0xbec9b953,0x3f6b4b0c,0xbe78cfcc,0x3f7853f8,0xbdafb680,0x3f7f0e58,0x3d96a905,0x3f7f4e6d,0x3e6c9a7f,0x3f791298,
0xbf2beb4a,0x3f3daef9,0xbf0a48ad,0x3f577026,0xbec9b953,0x3f6b4b0c,0xbe72b651,0x3f78b47b,0xbd96a905,0x3f7f4e6d,0x3dbc3ac3,0x3f7eea9d,0x3e827dc0,0x3f778bc5,0x3ed25a09,0x3f696591,
0xbf0e39da,0x3f54db31,0xbecf7bca,0x3f6a09a7,0xbe78cfcc,0x3f7853f8,0xbd96a905,0x3f7f4e6d,0x3dc8bd36,0x3f7ec46d,0x3e888e93,0x3f76ba07,0x3edae880,0x3f676bd8,0x3f13682a,0x3f514d3d,
0xbedae880,0x3f676bd8,0xbe8586ce,0x3f772417,0xbdafb680,0x3f7f0e58,0x3dbc3ac3,0x3f7eea9d,0x3e888e93,0x3f76ba07,0x3eddbe79,0x3f66becc,0x3f15f6d9,0x3f4f7a1f,0x3f385216,0x3f31a81d,
0xbe94a031,0x3f74fa0b,0xbde1bc2e,0x3f7e70b0,0x3d96a905,0x3f7f4e6d,0x3e827dc0,0x3f778bc5,0x3edae880,0x3f676bd8,0x3f15f6d9,0x3f4f7a1f,0x3f396842,0x3f3085bb,0x3f5695e5,0x3f0b9a6b,
0xbe164083,0x3f7d3aac,0x3d2fe007,0x3f7fc38f,0x3e6c9a7f,0x3f791298,0x3ed25a09,0x3f696591,0x3f13682a,0x3f514d3d,0x3f385216,0x3f31a81d,0x3f5695e5,0x3f0b9a6b,0x3f6d1c1d,0x3ec1071e,
0xbd803d80,0x80003e00,0x80003e00,0x80003e00,0x80003e00,0x80003e00,0x80003e00,0x80003e00,0x80003e00,0x80003e00,0x80003e00,0x80003e00,0x80003e00,0x80003e00,0x80003e00,0x80003e00,
0x3d803d80,0x3cc83dfb,0x3e000000,0x3dfbbcc8,0x3d443ded,0x3d8e3dd5,0x3dedbd44,0x3dd5bd8e,0x3db53db5,0x3dd53d8e,0x3db5bdb5,0x3d8ebdd5,0x3ded3d44,0x3dfb3cc8,0x3d44bded,0x3cc8bdfb,
0xbd803d80,0x3d443ded,0x8000be00,0xbd44bded,0x3db53db5,0x3ded3d44,0xbdb5bdb5,0xbdedbd44,0x3e000000,0x3dedbd44,0xbe000000,0xbded3d44,0x3db5bdb5,0x3d44bded,0xbdb53db5,0xbd443ded,
0x3d803d80,0x3d8e3dd5,0xbe000000,0xbdd53d8e,0x3ded3d44,0x3dfbbcc8,0xbd443ded,0x3cc83dfb,0x3db5bdb5,0x3cc8bdfb,0x3db53db5,0x3dfb3cc8,0xbd44bded,0xbdd5bd8e,0x3dedbd44,0x3d8ebdd5,
0xbd803d80,0x3db53db5,0x80003e00,0x3db53db5,0x3e000000,0x3db5bdb5,0x3e000000,0x3db5bdb5,0x8000be00,0xbdb5bdb5,0x8000be00,0xbdb5bdb5,0xbe000000,0xbdb53db5,0xbe000000,0xbdb53db5,
0x3d803d80,0x3dd53d8e,0x3e000000,0x3d8ebdd5,0x3dedbd44,0x3cc8bdfb,0xbd44bded,0xbdfbbcc8,0xbdb5bdb5,0xbdfb3cc8,0xbdb53db5,0x3cc83dfb,0xbd443ded,0x3d8e3dd5,0x3ded3d44,0x3dd5bd8e,
0xbd803d80,0x3ded3d44,0x8000be00,0xbdedbd44,0x3db5bdb5,0xbd44bded,0xbdb53db5,0x3d443ded,0xbe000000,0xbd443ded,0x3e000000,0x3d44bded,0x3db53db5,0x3dedbd44,0xbdb5bdb5,0xbded3d44,
0x3d803d80,0x3dfb3cc8,0xbe000000,0xbcc83dfb,0x3d44bded,0xbdd5bd8e,0x3ded3d44,0x3d8ebdd5,0xbdb53db5,0x3d8e3dd5,0xbdb5bdb5,0xbdd53d8e,0x3dedbd44,0xbcc8bdfb,0x3d443ded,0x3dfbbcc8,
0xbd803d80,0x3e000000,0x80003e00,0x3e000000,0x8000be00,0xbe000000,0x8000be00,0xbe000000,0x80003e00,0x3e000000,0x80003e00,0x3e000000,0x8000be00,0xbe000000,0x8000be00,0xbe000000,
0x3d803d80,0x3dfbbcc8,0x3e000000,0xbcc8bdfb,0xbd44bded,0xbdd53d8e,0xbded3d44,0x3d8e3dd5,0x3db53db5,0x3d8ebdd5,0x3db5bdb5,0xbdd5bd8e,0xbdedbd44,0xbcc83dfb,0xbd443ded,0x3dfb3cc8,
0xbd803d80,0x3dedbd44,0x8000be00,0xbded3d44,0xbdb5bdb5,0xbd443ded,0x3db53db5,0x3d44bded,0x3e000000,0xbd44bded,0xbe000000,0x3d443ded,0xbdb53db5,0x3ded3d44,0x3db5bdb5,0xbdedbd44,
0x3d803d80,0x3dd5bd8e,0xbe000000,0x3d8e3dd5,0xbdedbd44,0x3cc83dfb,0x3d44bded,0xbdfb3cc8,0x3db5bdb5,0xbdfbbcc8,0x3db53db5,0x3cc8bdfb,0x3d443ded,0x3d8ebdd5,0xbded3d44,0x3dd53d8e,
0xbd803d80,0x3db5bdb5,0x80003e00,0x3db5bdb5,0xbe000000,0x3db53db5,0xbe000000,0x3db53db5,0x8000be00,0xbdb53db5,0x8000be00,0xbdb53db5,0x3e000000,0xbdb5bdb5,0x3e000000,0xbdb5bdb5,
0x3d803d80,0x3d8ebdd5,0x3e000000,0xbdd5bd8e,0xbded3d44,0x3dfb3cc8,0x3d443ded,0x3cc8bdfb,0xbdb5bdb5,0x3cc83dfb,0xbdb53db5,0x3dfbbcc8,0x3d44bded,0xbdd53d8e,0xbdedbd44,0x3d8e3dd5,
0xbd803d80,0x3d44bded,0x8000be00,0xbd443ded,0xbdb53db5,0x3dedbd44,0x3db5bdb5,0xbded3d44,0xbe000000,0x3ded3d44,0x3e000000,0xbdedbd44,0xbdb5bdb5,0x3d443ded,0x3db53db5,0xbd44bded,
0x3d803d80,0x3cc8bdfb,0xbe000000,0x3dfb3cc8,0xbd443ded,0x3d8ebdd5,0xbdedbd44,0x3dd53d8e,0xbdb53db5,0x3dd5bd8e,0xbdb5bdb5,0x3d8e3dd5,0xbded3d44,0x3dfbbcc8,0xbd44bded,0x3cc83dfb,
0xbd803d80,0x8000be00,0x80003e00,0x8000be00,0x80003e00,0x8000be00,0x80003e00,0x8000be00,0x80003e00,0x8000be00,0x80003e00,0x8000be00,0x80003e00,0x8000be00,0x80003e00,0x8000be00,
0x3d803d80,0xbcc8bdfb,0x3e000000,0xbdfb3cc8,0x3d443ded,0xbd8ebdd5,0x3dedbd44,0xbdd53d8e,0x3db53db5,0xbdd5bd8e,0x3db5bdb5,0xbd8e3dd5,0x3ded3d44,0xbdfbbcc8,0x3d44bded,0xbcc83dfb,
0xbd803d80,0xbd44bded,0x8000be00,0x3d443ded,0x3db53db5,0xbdedbd44,0xbdb5bdb5,0x3ded3d44,0x3e000000,0xbded3d44,0xbe000000,0x3dedbd44,0x3db5bdb5,0xbd443ded,0xbdb53db5,0x3d44bded,
0x3d803d80,0xbd8ebdd5,0xbe000000,0x3dd5bd8e,0x3ded3d44,0xbdfb3cc8,0xbd443ded,0xbcc8bdfb,0x3db5bdb5,0xbcc83dfb,0x3db53db5,0xbdfbbcc8,0xbd44bded,0x3dd53d8e,0x3dedbd44,0xbd8e3dd5,
0xbd803d80,0xbdb5bdb5,0x80003e00,0xbdb5bdb5,0x3e000000,0xbdb53db5,0x3e000000,0xbdb53db5,0x8000be00,0x3db53db5,0x8000be00,0x3db53db5,0xbe000000,0x3db5bdb5,0xbe000000,0x3db5bdb5,
0x3d803d80,0xbdd5bd8e,0x3e000000,0xbd8e3dd5,0x3dedbd44,0xbcc83dfb,0xbd44bded,0x3dfb3cc8,0xbdb5bdb5,0x3dfbbcc8,0xbdb53db5,0xbcc8bdfb,0xbd443ded,0xbd8ebdd5,0x3ded3d44,0xbdd53d8e,
0xbd803d80,0xbdedbd44,0x8000be00,0x3ded3d44,0x3db5bdb5,0x3d443ded,0xbdb53db5,0xbd44bded,0xbe000000,0x3d44bded,0x3e000000,0xbd443ded,0x3db53db5,0xbded3d44,0xbdb5bdb5,0x3dedbd44,
0x3d803d80,0xbdfbbcc8,0xbe000000,0x3cc8bdfb,0x3d44bded,0x3dd53d8e,0x3ded3d44,0xbd8e3dd5,0xbdb53db5,0xbd8ebdd5,0xbdb5bdb5,0x3dd5bd8e,0x3dedbd44,0x3cc83dfb,0x3d443ded,0xbdfb3cc8,
0xbd803d80,0xbe000000,0x80003e00,0xbe000000,0x8000be00,0x3e000000,0x8000be00,0x3e000000,0x80003e00,0xbe000000,0x80003e00,0xbe000000,0x8000be00,0x3e000000,0x8000be00,0x3e000000,
0x3d803d80,0xbdfb3cc8,0x3e000000,0x3cc83dfb,0xbd44bded,0x3dd5bd8e,0xbded3d44,0xbd8ebdd5,0x3db53db5,0xbd8e3dd5,0x3db5bdb5,0x3dd53d8e,0xbdedbd44,0x3cc8bdfb,0xbd443ded,0xbdfbbcc8,
0xbd803d80,0xbded3d44,0x8000be00,0x3dedbd44,0xbdb5bdb5,0x3d44bded,0x3db53db5,0xbd443ded,0x3e000000,0x3d443ded,0xbe000000,0xbd44bded,0xbdb53db5,0xbdedbd44,0x3db5bdb5,0x3ded3d44,
0x3d803d80,0xbdd53d8e,0xbe000000,0xbd8ebdd5,0xbdedbd44,0xbcc8bdfb,0x3d44bded,0x3dfbbcc8,0x3db5bdb5,0x3dfb3cc8,0x3db53db5,0xbcc83dfb,0x3d443ded,0xbd8e3dd5,0xbded3d44,0xbdd5bd8e,
0xbd803d80,0xbdb53db5,0x80003e00,0xbdb53db5,0xbe000000,0xbdb5bdb5,0xbe000000,0xbdb5bdb5,0x8000be00,0x3db5bdb5,0x8000be00,0x3db5bdb5,0x3e000000,0x3db53db5,0x3e000000,0x3db53db5,
0x3d803d80,0xbd8e3dd5,0x3e000000,0x3dd53d8e,0xbded3d44,0xbdfbbcc8,0x3d443ded,0xbcc83dfb,0xbdb5bdb5,0xbcc8bdfb,0xbdb53db5,0xbdfb3cc8,0x3d44bded,0x3dd5bd8e,0xbdedbd44,0xbd8ebdd5,
0xbd803d80,0xbd443ded,0x8000be00,0x3d44bded,0xbdb53db5,0xbded3d44,0x3db5bdb5,0x3dedbd44,0xbe000000,0xbdedbd44,0x3e000000,0x3ded3d44,0xbdb5bdb5,0xbd44bded,0x3db53db5,0x3d443ded,
0x3d803d80,0xbcc83dfb,0xbe000000,0xbdfbbcc8,0xbd443ded,0xbd8e3dd5,0xbdedbd44,0xbdd5bd8e,0xbdb53db5,0xbdd53d8e,0xbdb5bdb5,0xbd8ebdd5,0xbded3d44,0xbdfb3cc8,0xbd44bded,0xbcc8bdfb,
0x80003e00,0x80003e00,0x80003e00,0x80003e00,0x80003e00,0x80003e00,0x80003e00,0x80003e00,0x80003e00,0x80003e00,0x80003e00,0x80003e00,0x80003e00,0x80003e00,0x80003e00,0x80003e00,
0x3c493dff,0x3d153df5,0x3dffbc49,0x3df5bd15,0x3d713de2,0x3da23dc6,0x3de2bd71,0x3dc6bda2,0x3dc63da2,0x3de23d71,0x3da2bdc6,0x3d71bde2,0x3df53d15,0x3dff3c49,0x3d15bdf5,0x3c49bdff,
0x3cc83dfb,0x3d8e3dd5,0xbcc8bdfb,0xbd8ebdd5,0x3dd53d8e,0x3dfb3cc8,0xbdd5bd8e,0xbdfbbcc8,0x3dfbbcc8,0x3dd5bd8e,0xbdfb3cc8,0xbdd53d8e,0x3d8ebdd5,0x3cc8bdfb,0xbd8e3dd5,0xbcc83dfb,
0x3d153df5,0x3dc63da2,0xbdf53d15,0xbda23dc6,0x3dff3c49,0x3de2bd71,0xbc493dff,0x3d713de2,0x3d71bde2,0xbc49bdff,0x3de23d71,0x3dffbc49,0xbda2bdc6,0xbdf5bd15,0x3dc6bda2,0x3d15bdf5,
0x3d443ded,0x3ded3d44,0x3d443ded,0x3ded3d44,0x3dedbd44,0x3d44bded,0x3dedbd44,0x3d44bded,0xbd44bded,0xbdedbd44,0xbd44bded,0xbdedbd44,0xbded3d44,0xbd443ded,0xbded3d44,0xbd443ded,
0x3d713de2,0x3dff3c49,0x3de2bd71,0x3c49bdff,0x3da2bdc6,0xbd15bdf5,0xbdc6bda2,0xbdf53d15,0xbdf5bd15,0xbdc63da2,0xbd153df5,0x3da23dc6,0x3c493dff,0x3de23d71,0x3dffbc49,0x3d71bde2,
0x3d8e3dd5,0x3dfbbcc8,0xbd8ebdd5,0xbdfb3cc8,0x3cc8bdfb,0xbdd5bd8e,0xbcc83dfb,0x3dd53d8e,0xbdd53d8e,0x3cc83dfb,0x3dd5bd8e,0xbcc8bdfb,0x3dfb3cc8,0x3d8ebdd5,0xbdfbbcc8,0xbd8e3dd5,
0x3da23dc6,0x3de2bd71,0xbdc63da2,0x3d713de2,0xbd15bdf5,0xbdff3c49,0x3df5bd15,0xbc49bdff,0xbc493dff,0x3df53d15,0xbdffbc49,0xbd153df5,0x3d71bde2,0xbdc6bda2,0x3de23d71,0x3da2bdc6,
0x3db53db5,0x3db5bdb5,0x3db53db5,0x3db5bdb5,0xbdb5bdb5,0xbdb53db5,0xbdb5bdb5,0xbdb53db5,0x3db53db5,0x3db5bdb5,0x3db53db5,0x3db5bdb5,0xbdb5bdb5,0xbdb53db5,0xbdb5bdb5,0xbdb53db5,
0x3dc63da2,0x3d71bde2,0x3da2bdc6,0xbde2bd71,0xbdf5bd15,0xbc493dff,0xbd153df5,0x3dff3c49,0x3dffbc49,0xbd15bdf5,0xbc49bdff,0xbdf53d15,0xbde23d71,0x3da23dc6,0x3d713de2,0x3dc6bda2,
0x3dd53d8e,0x3cc8bdfb,0xbdd5bd8e,0xbcc83dfb,0xbdfb3cc8,0x3d8e3dd5,0x3dfbbcc8,0xbd8ebdd5,0x3d8ebdd5,0xbdfbbcc8,0xbd8e3dd5,0x3dfb3cc8,0x3cc83dfb,0x3dd5bd8e,0xbcc8bdfb,0xbdd53d8e,
0x3de23d71,0xbc49bdff,0xbd713de2,0x3dffbc49,0xbdc63da2,0x3df53d15,0xbda2bdc6,0xbd153df5,0xbd15bdf5,0xbda23dc6,0x3df5bd15,0xbdc6bda2,0x3dff3c49,0xbd71bde2,0xbc493dff,0x3de2bd71,
0x3ded3d44,0xbd44bded,0x3ded3d44,0xbd44bded,0xbd443ded,0x3dedbd44,0xbd443ded,0x3dedbd44,0xbdedbd44,0x3d443ded,0xbdedbd44,0x3d443ded,0x3d44bded,0xbded3d44,0x3d44bded,0xbded3d44,
0x3df53d15,0xbda2bdc6,0x3d15bdf5,0xbdc63da2,0x3c493dff,0x3d71bde2,0x3dffbc49,0xbde2bd71,0xbde23d71,0x3dff3c49,0x3d713de2,0x3c49bdff,0xbdc6bda2,0x3d153df5,0xbda23dc6,0x3df5bd15,
0x3dfb3cc8,0xbdd5bd8e,0xbdfbbcc8,0x3dd53d8e,0x3d8e3dd5,0xbcc8bdfb,0xbd8ebdd5,0x3cc83dfb,0xbcc83dfb,0x3d8ebdd5,0x3cc8bdfb,0xbd8e3dd5,0xbdd53d8e,0x3dfbbcc8,0x3dd5bd8e,0xbdfb3cc8,
0x3dff3c49,0xbdf5bd15,0xbc493dff,0x3d15bdf5,0x3de23d71,0xbdc6bda2,0xbd713de2,0x3da2bdc6,0x3da23dc6,0xbd71bde2,0xbdc63da2,0x3de2bd71,0x3d153df5,0xbc49bdff,0xbdf53d15,0x3dffbc49,
0x3e000000,0xbe000000,0x3e000000,0xbe000000,0x3e000000,0xbe000000,0x3e000000,0xbe000000,0x3e000000,0xbe000000,0x3e000000,0xbe000000,0x3e000000,0xbe000000,0x3e000000,0xbe000000,
0x3dffbc49,0xbdf53d15,0xbc49bdff,0x3d153df5,0x3de2bd71,0xbdc63da2,0xbd71bde2,0x3da23dc6,0x3da2bdc6,0xbd713de2,0xbdc6bda2,0x3de23d71,0x3d15bdf5,0xbc493dff,0xbdf5bd15,0x3dff3c49,
0x3dfbbcc8,0xbdd53d8e,0xbdfb3cc8,0x3dd5bd8e,0x3d8ebdd5,0xbcc83dfb,0xbd8e3dd5,0x3cc8bdfb,0xbcc8bdfb,0x3d8e3dd5,0x3cc83dfb,0xbd8ebdd5,0xbdd5bd8e,0x3dfb3cc8,0x3dd53d8e,0xbdfbbcc8,
0x3df5bd15,0xbda23dc6,0x3d153df5,0xbdc6bda2,0x3c49bdff,0x3d713de2,0x3dff3c49,0xbde23d71,0xbde2bd71,0x3dffbc49,0x3d71bde2,0x3c493dff,0xbdc63da2,0x3d15bdf5,0xbda2bdc6,0x3df53d15,
0x3dedbd44,0xbd443ded,0x3dedbd44,0xbd443ded,0xbd44bded,0x3ded3d44,0xbd44bded,0x3ded3d44,0xbded3d44,0x3d44bded,0xbded3d44,0x3d44bded,0x3d443ded,0xbdedbd44,0x3d443ded,0xbdedbd44,
0x3de2bd71,0xbc493dff,0xbd71bde2,0x3dff3c49,0xbdc6bda2,0x3df5bd15,0xbda23dc6,0xbd15bdf5,0xbd153df5,0xbda2bdc6,0x3df53d15,0xbdc63da2,0x3dffbc49,0xbd713de2,0xbc49bdff,0x3de23d71,
0x3dd5bd8e,0x3cc83dfb,0xbdd53d8e,0xbcc8bdfb,0xbdfbbcc8,0x3d8ebdd5,0x3dfb3cc8,0xbd8e3dd5,0x3d8e3dd5,0xbdfb3cc8,0xbd8ebdd5,0x3dfbbcc8,0x3cc8bdfb,0x3dd53d8e,0xbcc83dfb,0xbdd5bd8e,
0x3dc6bda2,0x3d713de2,0x3da23dc6,0xbde23d71,0xbdf53d15,0xbc49bdff,0xbd15bdf5,0x3dffbc49,0x3dff3c49,0xbd153df5,0xbc493dff,0xbdf5bd15,0xbde2bd71,0x3da2bdc6,0x3d71bde2,0x3dc63da2,
0x3db5bdb5,0x3db53db5,0x3db5bdb5,0x3db53db5,0xbdb53db5,0xbdb5bdb5,0xbdb53db5,0xbdb5bdb5,0x3db5bdb5,0x3db53db5,0x3db5bdb5,0x3db53db5,0xbdb53db5,0xbdb5bdb5,0xbdb53db5,0xbdb5bdb5,
0x3da2bdc6,0x3de23d71,0xbdc6bda2,0x3d71bde2,0xbd153df5,0xbdffbc49,0x3df53d15,0xbc493dff,0xbc49bdff,0x3df5bd15,0xbdff3c49,0xbd15bdf5,0x3d713de2,0xbdc63da2,0x3de2bd71,0x3da23dc6,
0x3d8ebdd5,0x3dfb3cc8,0xbd8e3dd5,0xbdfbbcc8,0x3cc83dfb,0xbdd53d8e,0xbcc8bdfb,0x3dd5bd8e,0xbdd5bd8e,0x3cc8bdfb,0x3dd53d8e,0xbcc83dfb,0x3dfbbcc8,0x3d8e3dd5,0xbdfb3cc8,0xbd8ebdd5,
0x3d71bde2,0x3dffbc49,0x3de23d71,0x3c493dff,0x3da23dc6,0xbd153df5,0xbdc63da2,0xbdf5bd15,0xbdf53d15,0xbdc6bda2,0xbd15bdf5,0x3da2bdc6,0x3c49bdff,0x3de2bd71,0x3dff3c49,0x3d713de2,
0x3d44bded,0x3dedbd44,0x3d44bded,0x3dedbd44,0x3ded3d44,0x3d443ded,0x3ded3d44,0x3d443ded,0xbd443ded,0xbded3d44,0xbd443ded,0xbded3d44,0xbdedbd44,0xbd44bded,0xbdedbd44,0xbd44bded,
0x3d15bdf5,0x3dc6bda2,0xbdf5bd15,0xbda2bdc6,0x3dffbc49,0x3de23d71,0xbc49bdff,0x3d71bde2,0x3d713de2,0xbc493dff,0x3de2bd71,0x3dff3c49,0xbda23dc6,0xbdf53d15,0x3dc63da2,0x3d153df5,
0x3cc8bdfb,0x3d8ebdd5,0xbcc83dfb,0xbd8e3dd5,0x3dd5bd8e,0x3dfbbcc8,0xbdd53d8e,0xbdfb3cc8,0x3dfb3cc8,0x3dd53d8e,0xbdfbbcc8,0xbdd5bd8e,0x3d8e3dd5,0x3cc83dfb,0xbd8ebdd5,0xbcc8bdfb,
0x3c49bdff,0x3d15bdf5,0x3dff3c49,0x3df53d15,0x3d71bde2,0x3da2bdc6,0x3de23d71,0x3dc63da2,0x3dc6bda2,0x3de2bd71,0x3da23dc6,0x3d713de2,0x3df5bd15,0x3dffbc49,0x3d153df5,0x3c493dff,
0x3f800000,0x0,0x3f800000,0x0,0x3f800000,0x0,0x3f800000,0x0,0x3f800000,0x0,0x3f800000,0x0,0x3f800000,0x0,0x3f800000,0x0,
0x3f800000,0x0,0x3f7ffb11,0xbc490e90,0x3f7fec43,0xbcc90ab0,0x3f7fd397,0xbd16c32c,0x3f7fb10f,0xbd48fb30,0x3f7f84ab,0xbd7b2b74,0x3f7f4e6d,0xbd96a905,0x3f7f0e58,0xbdafb680,
0x3f800000,0x0,0x3f7fec43,0xbcc90ab0,0x3f7fb10f,0xbd48fb30,0x3f7f4e6d,0xbd96a905,0x3f7ec46d,0xbdc8bd36,0x3f7e1324,0xbdfab273,0x3f7d3aac,0xbe164083,0x3f7c3b28,0xbe2f10a2,
0x3f800000,0x0,0x3f7fd397,0xbd16c32c,0x3f7f4e6d,0xbd96a905,0x3f7e70b0,0xbde1bc2e,0x3f7d3aac,0xbe164083,0x3f7baccd,0xbe3b6ecf,0x3f79c79d,0xbe605c13,0x3f778bc5,0xbe827dc0,
0x3f800000,0x0,0x3f7fb10f,0xbd48fb30,0x3f7ec46d,0xbdc8bd36,0x3f7d3aac,0xbe164083,0x3f7b14be,0xbe47c5c2,0x3f7853f8,0xbe78cfcc,0x3f74fa0b,0xbe94a031,0x3f710908,0xbeac7cd4,
0x3f800000,0x0,0x3f7f84ab,0xbd7b2b74,0x3f7e1324,0xbdfab273,0x3f7baccd,0xbe3b6ecf,0x3f7853f8,0xbe78cfcc,0x3f740bdd,0xbe9aa086,0x3f6ed89e,0xbeb8442a,0x3f68bf3c,0xbed53641,
0x3f800000,0x0,0x3f7f4e6d,0xbd96a905,0x3f7d3aac,0xbe164083,0x3f79c79d,0xbe605c13,0x3f74fa0b,0xbe94a031,0x3f6ed89e,0xbeb8442a,0x3f676bd8,0xbedae880,0x3f5ebe05,0xbefc5d27,
0x3f800000,0x0,0x3f7f0e58,0xbdafb680,0x3f7c3b28,0xbe2f10a2,0x3f778bc5,0xbe827dc0,0x3f710908,0xbeac7cd4,0x3f68bf3c,0xbed53641,0x3f5ebe05,0xbefc5d27,0x3f531849,0xbf10d3cd,
0x3f800000,0x0,0x3f7ec46d,0xbdc8bd36,0x3f7b14be,0xbe47c5c2,0x3f74fa0b,0xbe94a031,0x3f6c835e,0xbec3ef15,0x3f61c598,0xbef15aea,0x3f54db31,0xbf0e39da,0x3f45e403,0xbf226799,
0x3f800000,0x0,0x3f7e70b0,0xbde1bc2e,0x3f79c79d,0xbe605c13,0x3f721352,0xbea68f12,0x3f676bd8,0xbedae880,0x3f59f26a,0xbf064b82,0x3f49d112,0xbf1d7fd1,0x3f373a23,0xbf32c8c9,
0x3f800000,0x0,0x3f7e1324,0xbdfab273,0x3f7853f8,0xbe78cfcc,0x3f6ed89e,0xbeb8442a,0x3f61c598,0xbef15aea,0x3f514d3d,0xbf13682a,0x3f3daef9,0xbf2beb4a,0x3f273656,0xbf41d870,
0x3f800000,0x0,0x3f7dabcc,0xbe09cf86,0x3f76ba07,0xbe888e93,0x3f6b4b0c,0xbec9b953,0x3f5b941a,0xbf039c3d,0x3f47de65,0xbf1ff6cb,0x3f3085bb,0xbf396842,0x3f15f6d9,0xbf4f7a1f,
0x3f800000,0x0,0x3f7d3aac,0xbe164083,0x3f74fa0b,0xbe94a031,0x3f676bd8,0xbedae880,0x3f54db31,0xbf0e39da,0x3f3daef9,0xbf2beb4a,0x3f226799,0xbf45e403,0x3f039c3d,0xbf5b941a,
0x3f800000,0x0,0x3f7cbfc9,0xbe22abb6,0x3f731447,0xbea09ae5,0x3f633c5a,0xbeebcbbb,0x3f4d9f02,0xbf187fc0,0x3f32c8c9,0xbf373a23,0x3f13682a,0xbf514d3d,0x3ee0924f,0xbf660f88,
0x3f800000,0x0,0x3f7c3b28,0xbe2f10a2,0x3f710908,0xbeac7cd4,0x3f5ebe05,0xbefc5d27,0x3f45e403,0xbf226799,0x3f273656,0xbf41d870,0x3f039c3d,0xbf5b941a,0x3eb8442a,0xbf6ed89e,
0x3f800000,0x0,0x3f7baccd,0xbe3b6ecf,0x3f6ed89e,0xbeb8442a,0x3f59f26a,0xbf064b82,0x3f3daef9,0xbf2beb4a,0x3f1b02c6,0xbf4bbbf8,0x3ee63375,0xbf64aa59,0x3e8e9a22,0xbf75dec6,
0x3f800000,0x0,0x3f7b14be,0xbe47c5c2,0x3f6c835e,0xbec3ef15,0x3f54db31,0xbf0e39da,0x3f3504f3,0xbf3504f3,0x3f0e39da,0xbf54db31,0x3ec3ef15,0xbf6c835e,0x3e47c5c2,0xbf7b14be,
0x3f800000,0x0,0x3f7a7302,0xbe541501,0x3f6a09a7,0xbecf7bca,0x3f4f7a1f,0xbf15f6d9,0x3f2beb4a,0xbf3daef9,0x3f00e7e4,0xbf5d2d53,0x3ea09ae5,0xbf731447,0x3de1bc2e,0xbf7e70b0,
0x3f800000,0x0,0x3f79c79d,0xbe605c13,0x3f676bd8,0xbedae880,0x3f49d112,0xbf1d7fd1,0x3f226799,0xbf45e403,0x3ee63375,0xbf64aa59,0x3e78cfcc,0xbf7853f8,0x3cc90ab0,0xbf7fec43,
0x3f800000,0x0,0x3f791298,0xbe6c9a7f,0x3f64aa59,0xbee63375,0x3f43e200,0xbf24d225,0x3f187fc0,0xbf4d9f02,0x3ec9b953,0xbf6b4b0c,0x3e2f10a2,0xbf7c3b28,0xbd7b2b74,0xbf7f84ab,
0x3f800000,0x0,0x3f7853f8,0xbe78cfcc,0x3f61c598,0xbef15aea,0x3f3daef9,0xbf2beb4a,0x3f0e39da,0xbf54db31,0x3eac7cd4,0xbf710908,0x3dc8bd36,0xbf7ec46d,0xbe164083,0xbf7d3aac,
0x3f800000,0x0,0x3f778bc5,0xbe827dc0,0x3f5ebe05,0xbefc5d27,0x3f373a23,0xbf32c8c9,0x3f039c3d,0xbf5b941a,0x3e8e9a22,0xbf75dec6,0x3cc90ab0,0xbf7fec43,0xbe6c9a7f,0xbf791298,
0x3f800000,0x0,0x3f76ba07,0xbe888e93,0x3f5b941a,0xbf039c3d,0x3f3085bb,0xbf396842,0x3ef15aea,0xbf61c598,0x3e605c13,0xbf79c79d,0xbd48fb30,0xbf7fb10f,0xbea09ae5,0xbf731447,
0x3f800000,0x0,0x3f75dec6,0xbe8e9a22,0x3f584853,0xbf08f59b,0x3f299415,0xbf3fc767,0x3edae880,0xbf676bd8,0x3e22abb6,0xbf7cbfc9,0xbdfab273,0xbf7e1324,0xbec9b953,0xbf6b4b0c,
0x3f800000,0x0,0x3f74fa0b,0xbe94a031,0x3f54db31,0xbf0e39da,0x3f226799,0xbf45e403,0x3ec3ef15,0xbf6c835e,0x3dc8bd36,0xbf7ec46d,0xbe47c5c2,0xbf7b14be,0xbef15aea,0xbf61c598,
0x3f800000,0x0,0x3f740bdd,0xbe9aa086,0x3f514d3d,0xbf13682a,0x3f1b02c6,0xbf4bbbf8,0x3eac7cd4,0xbf710908,0x3d16c32c,0xbf7fd397,0xbe888e93,0xbf76ba07,0xbf0b9a6b,0xbf5695e5,
0x3f800000,0x0,0x3f731447,0xbea09ae5,0x3f4d9f02,0xbf187fc0,0x3f13682a,0xbf514d3d,0x3e94a031,0xbf74fa0b,0xbcc90ab0,0xbf7fec43,0xbeac7cd4,0xbf710908,0xbf1d7fd1,0xbf49d112,
0x3f800000,0x0,0x3f721352,0xbea68f12,0x3f49d112,0xbf1d7fd1,0x3f0b9a6b,0xbf5695e5,0x3e78cfcc,0xbf7853f8,0xbdafb680,0xbf7f0e58,0xbecf7bca,0xbf6a09a7,0xbf2e3bde,0xbf3b8f3b,
0x3f800000,0x0,0x3f710908,0xbeac7cd4,0x3f45e403,0xbf226799,0x3f039c3d,0xbf5b941a,0x3e47c5c2,0xbf7b14be,0xbe164083,0xbf7d3aac,0xbef15aea,0xbf61c598,0xbf3daef9,0xbf2beb4a,
0x3f800000,0x0,0x3f6ff573,0xbeb263ef,0x3f41d870,0xbf273656,0x3ef6e0cb,0xbf604621,0x3e164083,0xbf7d3aac,0xbe541501,0xbf7a7302,0xbf08f59b,0xbf584853,0xbf4bbbf8,0xbf1b02c6,
0x3f800000,0x0,0x3f6ed89e,0xbeb8442a,0x3f3daef9,0xbf2beb4a,0x3ee63375,0xbf64aa59,0x3dc8bd36,0xbf7ec46d,0xbe888e93,0xbf76ba07,0xbf187fc0,0xbf4d9f02,0xbf584853,0xbf08f59b,
0x3f800000,0x0,0x3f6db293,0xbebe1d4a,0x3f396842,0xbf3085bb,0x3ed53641,0xbf68bf3c,0x3d48fb30,0xbf7fb10f,0xbea68f12,0xbf721352,0xbf273656,0xbf41d870,0xbf633c5a,0xbeebcbbb,
0x3f800000,0x3f800000,0x3f800000,0x3f800000,0x3f800000,0x3f800000,0x3f800000,0x3f800000,0x3f800000,0xbf800000,0x3f800000,0xbf800000,0x3f800000,0xbf800000,0x3f800000,0xbf800000,
0x3f800000,0x3f3504f3,0x0,0xbf3504f3,0xbf800000,0xbf3504f3,0x0,0x3f3504f3,0x0,0xbf3504f3,0xbf800000,0xbf3504f3,0x0,0x3f3504f3,0x3f800000,0x3f3504f3,
0x3f800000,0x0,0xbf800000,0x0,0x3f800000,0x0,0xbf800000,0x0,0x0,0xbf800000,0x0,0x3f800000,0x0,0xbf800000,0x0,0x3f800000,
0x3f800000,0xbf3504f3,0x0,0x3f3504f3,0xbf800000,0x3f3504f3,0x0,0xbf3504f3,0x0,0xbf3504f3,0x3f800000,0xbf3504f3,0x0,0x3f3504f3,0xbf800000,0x3f3504f3,
0x3f800000,0x3f6c835e,0x3f3504f3,0x3ec3ef15,0x0,0xbec3ef15,0xbf3504f3,0xbf6c835e,0x0,0xbec3ef15,0xbf3504f3,0xbf6c835e,0xbf800000,0xbf6c835e,0xbf3504f3,0xbec3ef15,
0x3f800000,0x3ec3ef15,0xbf3504f3,0xbf6c835e,0x0,0x3f6c835e,0x3f3504f3,0xbec3ef15,0x0,0xbf6c835e,0xbf3504f3,0x3ec3ef15,0x3f800000,0x3ec3ef15,0xbf3504f3,0xbf6c835e,
0x3f800000,0xbec3ef15,0xbf3504f3,0x3f6c835e,0x0,0xbf6c835e,0x3f3504f3,0x3ec3ef15,0x0,0xbf6c835e,0x3f3504f3,0x3ec3ef15,0xbf800000,0x3ec3ef15,0x3f3504f3,0xbf6c835e,
0x3f800000,0xbf6c835e,0x3f3504f3,0xbec3ef15,0x0,0x3ec3ef15,0xbf3504f3,0x3f6c835e,0x0,0xbec3ef15,0x3f3504f3,0xbf6c835e,0x3f800000,0xbf6c835e,0x3f3504f3,0xbec3ef15,
};

struct Params {
    const __nv_bfloat16 *xb, *lre, *lim, *ldt, *dsk;
    float* out;
    int zero[8];
    uint64_t da[4];
    uint32_t unit[258];
};

struct Maps { CUtensorMap m[11]; };

struct cf { float x, y; };
__device__ __forceinline__ uint32_t smem_u32(const void* p) { return (uint32_t)__cvta_generic_to_shared(p); }
__device__ __forceinline__ void mbar_init(uint32_t a, uint32_t c) { asm volatile("mbarrier.init.shared::cta.b64 [%0], %1;" ::"r"(a), "r"(c) : "memory"); }
__device__ __forceinline__ void mbar_expect_tx(uint32_t a, uint32_t b) { asm volatile("mbarrier.arrive.expect_tx.shared::cta.b64 _, [%0], %1;" ::"r"(a), "r"(b) : "memory"); }
__device__ __forceinline__ void mbar_arrive(uint32_t a) { asm volatile("mbarrier.arrive.shared::cta.b64 _, [%0];" ::"r"(a) : "memory"); }
__device__ __forceinline__ void mbar_wait(uint32_t a, uint32_t ph) {
    asm volatile("{.reg .pred p; .reg .u32 n;\n"
                 "mov.u32 n, 0;\n"
                 "LOOP: mbarrier.try_wait.parity.shared::cta.b64 p, [%0], %1;\n"
                 "@p bra DONE;\n"
                 "add.u32 n, n, 1;\n"
                 "setp.lt.u32 p, n, %2;\n"
                 "@p bra LOOP;\n"
                 "DONE: }" ::"r"(a), "r"(ph), "n"(SPIN_LIMIT) : "memory");
}
__device__ __forceinline__ unsigned ld_rlx(const unsigned* p) { unsigned v; asm volatile("ld.relaxed.gpu.global.u32 %0, [%1];" : "=r"(v) : "l"(p) : "memory"); return v; }
__device__ __forceinline__ void wait_cnt(const unsigned* p, unsigned target) {
    unsigned n = 0;
    while ((int)(ld_rlx(p) - target) < 0 && ++n < SPIN_LIMIT) __nanosleep(20);
}
__device__ __forceinline__ void red_hint(unsigned* p) { asm volatile("red.relaxed.gpu.global.add.u32 [%0], 1;" ::"l"(p) : "memory"); }
__device__ __forceinline__ void fence_async() { asm volatile("fence.proxy.async.global;" ::: "memory"); }
__device__ __forceinline__ void fence_async_sm() { asm volatile("fence.proxy.async.shared::cta;" ::: "memory"); }
#define bar_sync(id, n) asm volatile("bar.sync %0, %1;" ::"n"(id), "n"(n) : "memory")
#define bar_arrive(id, n) asm volatile("bar.arrive %0, %1;" ::"n"(id), "n"(n) : "memory")
__device__ __forceinline__ bool elect_one() {
    uint32_t r;
    asm volatile("{.reg .pred p; elect.sync _|p, 0xffffffff; selp.u32 %0, 1, 0, p;}" : "=r"(r));
    return r != 0;
}

__device__ __forceinline__ void tma2d(uint32_t dst, const CUtensorMap* m, int c0, int c1, uint32_t bar) {
    asm volatile("cp.async.bulk.tensor.2d.shared::cluster.global.mbarrier::complete_tx::bytes [%0], [%1, {%3,%4}], [%2];" ::"r"(dst), "l"(m), "r"(bar), "r"(c0), "r"(c1) : "memory");
}
__device__ __forceinline__ void tma4d(uint32_t dst, const CUtensorMap* m, int c0, int c1, int c2, int c3, uint32_t bar) {
    asm volatile("cp.async.bulk.tensor.4d.shared::cluster.global.mbarrier::complete_tx::bytes [%0], [%1, {%3,%4,%5,%6}], [%2];" ::"r"(dst), "l"(m), "r"(bar), "r"(c0), "r"(c1), "r"(c2), "r"(c3) : "memory");
}
__device__ __forceinline__ void tma4d_mc(uint32_t dst, const CUtensorMap* m, int c0, int c3, uint32_t bar) {
    asm volatile("cp.async.bulk.tensor.4d.shared::cluster.global.mbarrier::complete_tx::bytes.multicast::cluster [%0], [%1, {%3,%6,%6,%4}], [%2], %5;" ::"r"(dst), "l"(m), "r"(bar), "r"(c0), "r"(c3), "h"((uint16_t)3), "r"(0) : "memory");
}
__device__ __forceinline__ void tma2d_st(const CUtensorMap* m, int c0, int c1, uint32_t src) {
    asm volatile("cp.async.bulk.tensor.2d.global.shared::cta.bulk_group [%0, {%2,%3}], [%1];" ::"l"(m), "r"(src), "r"(c0), "r"(c1) : "memory");
}
__device__ __forceinline__ void tma5d(uint32_t dst, const CUtensorMap* m, int c0, int c1, int c2, int c3, int c4, uint32_t bar) {
    asm volatile("cp.async.bulk.tensor.5d.shared::cluster.global.mbarrier::complete_tx::bytes [%0], [%1, {%3,%4,%5,%6,%7}], [%2];" ::"r"(dst), "l"(m), "r"(bar), "r"(c0), "r"(c1), "r"(c2), "r"(c3), "r"(c4) : "memory");
}
__device__ __forceinline__ void bulk_ld(uint32_t dst, const void* src, uint32_t n, uint32_t bar) {
    asm volatile("cp.async.bulk.shared::cluster.global.mbarrier::complete_tx::bytes [%0], [%1], %2, [%3];" ::"r"(dst), "l"(src), "r"(n), "r"(bar) : "memory");
}
__device__ __forceinline__ void pf_map(const CUtensorMap* m) { asm volatile("prefetch.tensormap [%0];" ::"l"(m) : "memory"); }
__device__ __forceinline__ void bulk_commit() { asm volatile("cp.async.bulk.commit_group;" ::: "memory"); }
template <int N> __device__ __forceinline__ void bulk_wait_read() { asm volatile("cp.async.bulk.wait_group.read %0;" ::"n"(N) : "memory"); }
__device__ __forceinline__ void stsm4(uint32_t a, uint32_t r0, uint32_t r1, uint32_t r2, uint32_t r3) {
    asm volatile("stmatrix.sync.aligned.m8n8.x4.shared.b16 [%0], {%1,%2,%3,%4};" ::"r"(a), "r"(r0), "r"(r1), "r"(r2), "r"(r3) : "memory");
}
__device__ __forceinline__ void sts128f(uint32_t a, cf u, cf v) {
    asm volatile("st.shared.v4.f32 [%0], {%1,%2,%3,%4};" ::"r"(a), "f"(u.x), "f"(u.y), "f"(v.x), "f"(v.y) : "memory");
}
__device__ __forceinline__ void stg128(const void* a, uint32_t r0, uint32_t r1, uint32_t r2, uint32_t r3) {
    asm volatile("st.global.v4.b32 [%0], {%1,%2,%3,%4};" ::"l"(a), "r"(r0), "r"(r1), "r"(r2), "r"(r3) : "memory");
}
__device__ __forceinline__ void lds128f(uint32_t a, float& x, float& y, float& z, float& u) { asm volatile("ld.shared.v4.f32 {%0,%1,%2,%3}, [%4];" : "=f"(x), "=f"(y), "=f"(z), "=f"(u) : "r"(a) : "memory"); }
__device__ __forceinline__ cf lds_cf(uint32_t a) { cf v; asm volatile("ld.shared.v2.f32 {%0,%1}, [%2];" : "=f"(v.x), "=f"(v.y) : "r"(a) : "memory"); return v; }
__device__ __forceinline__ uint4 ldtab(int word) { return __ldg((const uint4*)(g_tab + word)); }
__device__ __forceinline__ void load_tw(cf (&tw)[8], int k1) {
#pragma unroll
    for (int i = 0; i < 4; i++) {
        const uint4 v = ldtab(TAB_TW + k1 * 16 + i * 4);
        tw[2 * i] = {__uint_as_float(v.x), __uint_as_float(v.y)};
        tw[2 * i + 1] = {__uint_as_float(v.z), __uint_as_float(v.w)};
    }
}
__device__ __forceinline__ void load_T(cf (&T)[8], int t7) {
#pragma unroll
    for (int i = 0; i < 4; i++)
        asm volatile("ld.global.nc.v4.f32 {%0,%1,%2,%3}, [%4];" : "=f"(T[2 * i].x), "=f"(T[2 * i].y), "=f"(T[2 * i + 1].x), "=f"(T[2 * i + 1].y) : "l"(g_tab + TAB_T + i * 512 + t7 * 4));
}
__device__ __forceinline__ uint32_t lds_u16(uint32_t a) { uint32_t v; asm volatile("ld.shared.u16 %0, [%1];" : "=r"(v) : "r"(a)); return v; }
__device__ __forceinline__ float up(uint32_t v) { return __uint_as_float(v << 16); }
__device__ __forceinline__ unsigned get_epoch(uint32_t bars) {
    mbar_wait(bars + B_EP, 0);
    unsigned e;
    asm volatile("ld.shared.u32 %0, [%1];" : "=r"(e) : "r"(bars + B_EPOCH) : "memory");
    return e;
}
__device__ __forceinline__ void sts64f(uint32_t a, float x, float y) { asm volatile("st.shared.v2.f32 [%0], {%1,%2};" ::"r"(a), "f"(x), "f"(y) : "memory"); }
__device__ __forceinline__ uint32_t pk(float lo, float hi) { uint32_t r; asm("cvt.rn.bf16x2.f32 %0, %1, %2;" : "=r"(r) : "f"(hi), "f"(lo)); return r; }
__device__ __forceinline__ uint32_t bitsel(uint32_t a, uint32_t m, uint32_t b) {
    uint32_t r;
    asm("lop3.b32 %0, %1, %2, %3, 0xea;" : "=r"(r) : "r"(a), "r"(m), "r"(b));
    return r;
}

__host__ __device__ constexpr uint64_t mkdesc(uint32_t off, uint32_t lbo, uint32_t sbo, uint32_t swz) {
    return (uint64_t)((SB0 + off) >> 4) | ((uint64_t)(lbo >> 4) << 16) | ((uint64_t)(sbo >> 4) << 32) | ((uint64_t)swz << 62);
}
__device__ __forceinline__ void wg_fence() { asm volatile("wgmma.fence.sync.aligned;" ::: "memory"); }
__device__ __forceinline__ void wg_commit() { asm volatile("wgmma.commit_group.sync.aligned;" ::: "memory"); }
template <int N> __device__ __forceinline__ void wg_wait() { asm volatile("wgmma.wait_group.sync.aligned %0;" ::"n"(N) : "memory"); }
template <int N> __device__ __forceinline__ void pin(float (&d)[N]) {
#pragma unroll
    for (int i = 0; i < N; i++) asm volatile("" : "+f"(d[i])::"memory");
}
template <int N> __device__ __forceinline__ void pinu(uint32_t (&d)[N]) {
#pragma unroll
    for (int i = 0; i < N; i++) asm volatile("" : "+r"(d[i])::"memory");
}

#define R8(d, o) "+f"(d[o]), "+f"(d[o + 1]), "+f"(d[o + 2]), "+f"(d[o + 3]), "+f"(d[o + 4]), "+f"(d[o + 5]), "+f"(d[o + 6]), "+f"(d[o + 7])
#define L8 "%0,%1,%2,%3,%4,%5,%6,%7"
#define L24 L8 ",%8,%9,%10,%11,%12,%13,%14,%15,%16,%17,%18,%19,%20,%21,%22,%23"
#define L32 L24 ",%24,%25,%26,%27,%28,%29,%30,%31"
#define L64 L32 ",%32,%33,%34,%35,%36,%37,%38,%39,%40,%41,%42,%43,%44,%45,%46,%47,%48,%49,%50,%51,%52,%53,%54,%55,%56,%57,%58,%59,%60,%61,%62,%63"

template <int O, int TA, int TB, int SC, int N> __device__ __forceinline__ void mma128_ss(float (&d)[N], uint64_t da, uint64_t db) {
    asm volatile("wgmma.mma_async.sync.aligned.m64n128k16.f32.bf16.bf16 {" L64 "}, %64, %65, %66, 1, 1, %67, %68;"
                 : R8(d, O), R8(d, O + 8), R8(d, O + 16), R8(d, O + 24), R8(d, O + 32), R8(d, O + 40), R8(d, O + 48), R8(d, O + 56)
                 : "l"(da), "l"(db), "n"(SC), "n"(TA), "n"(TB));
}
#define W8(d, o) "=f"(d[o]), "=f"(d[o + 1]), "=f"(d[o + 2]), "=f"(d[o + 3]), "=f"(d[o + 4]), "=f"(d[o + 5]), "=f"(d[o + 6]), "=f"(d[o + 7])
__device__ __forceinline__ void mma128_first(float (&d)[64], uint64_t da, uint64_t db) {
    asm volatile("wgmma.mma_async.sync.aligned.m64n128k16.f32.bf16.bf16 {" L64 "}, %64, %65, 0, 1, 1, 0, 1;"
                 : W8(d, 0), W8(d, 8), W8(d, 16), W8(d, 24), W8(d, 32), W8(d, 40), W8(d, 48), W8(d, 56) : "l"(da), "l"(db));
}
template <int TB, int SC> __device__ __forceinline__ void mma128_rs(float (&d)[64], const uint32_t* a, uint64_t db) {
    asm volatile("wgmma.mma_async.sync.aligned.m64n128k16.f32.bf16.bf16 {" L64 "}, {%64,%65,%66,%67}, %68, %69, 1, 1, %70;"
                 : R8(d, 0), R8(d, 8), R8(d, 16), R8(d, 24), R8(d, 32), R8(d, 40), R8(d, 48), R8(d, 56)
                 : "r"(a[0]), "r"(a[1]), "r"(a[2]), "r"(a[3]), "l"(db), "n"(SC), "n"(TB));
}
template <int TB, int SC> __device__ __forceinline__ void mma64_rs(float (&d)[32], const uint32_t* a, uint64_t db) {
    asm volatile("wgmma.mma_async.sync.aligned.m64n64k16.f32.bf16.bf16 {" L32 "}, {%32,%33,%34,%35}, %36, %37, 1, 1, %38;"
                 : R8(d, 0), R8(d, 8), R8(d, 16), R8(d, 24)
                 : "r"(a[0]), "r"(a[1]), "r"(a[2]), "r"(a[3]), "l"(db), "n"(SC), "n"(TB));
}
template <int TA, int SC> __device__ __forceinline__ void mma64_ss(float (&d)[32], uint64_t da, uint64_t db) {
    asm volatile("wgmma.mma_async.sync.aligned.m64n64k16.f32.bf16.bf16 {" L32 "}, %32, %33, %34, 1, 1, %35, 1;"
                 : R8(d, 0), R8(d, 8), R8(d, 16), R8(d, 24)
                 : "l"(da), "l"(db), "n"(SC), "n"(TA));
}
template <int SC> __device__ __forceinline__ void mma48_ss(float (&d)[32], uint64_t da, uint64_t db) {
    asm volatile("wgmma.mma_async.sync.aligned.m64n48k16.f32.bf16.bf16 {" L24 "}, %24, %25, %26, 1, 1, 0, 1;"
                 : R8(d, 8), R8(d, 16), R8(d, 24)
                 : "l"(da), "l"(db), "n"(SC));
}
template <int SC> __device__ __forceinline__ void mma16_rs(float (&d)[32], uint32_t a0, uint32_t a1, uint32_t a2, uint32_t a3, uint64_t db) {
    asm volatile("wgmma.mma_async.sync.aligned.m64n16k16.f32.bf16.bf16 {" L8 "}, {%8,%9,%10,%11}, %12, %13, 1, 1, 1;"
                 : R8(d, 0)
                 : "r"(a0), "r"(a1), "r"(a2), "r"(a3), "l"(db), "n"(SC));
}

__device__ __forceinline__ cf cmul(cf a, cf b) { return {fmaf(a.x, b.x, -a.y * b.y), fmaf(a.x, b.y, a.y * b.x)}; }
__device__ __forceinline__ cf csq(cf a) { return {fmaf(a.x, a.x, -a.y * a.y), (a.x + a.x) * a.y}; }
__device__ __forceinline__ cf cmulc(cf a, cf b) { return {fmaf(a.x, b.x, a.y * b.y), fmaf(a.y, b.x, -a.x * b.y)}; }
__device__ __forceinline__ cf cfma(cf a, cf b, cf c) { return {fmaf(a.x, b.x, fmaf(-a.y, b.y, c.x)), fmaf(a.x, b.y, fmaf(a.y, b.x, c.y))}; }
__device__ __forceinline__ cf csel(int c, cf a, cf b) {
    cf r;
    asm("{.reg .pred p; setp.ne.s32 p, %6, 0; selp.f32 %0, %2, %4, p; selp.f32 %1, %3, %5, p;}" : "=f"(r.x), "=f"(r.y) : "f"(a.x), "f"(a.y), "f"(b.x), "f"(b.y), "r"(c));
    return r;
}
__device__ __forceinline__ cf cadd(cf a, cf b) { return {a.x + b.x, a.y + b.y}; }
__device__ __forceinline__ cf csub(cf a, cf b) { return {a.x - b.x, a.y - b.y}; }
__device__ __forceinline__ cf twice_minus(cf a, cf s) { return {fmaf(2.f, a.x, -s.x), fmaf(2.f, a.y, -s.y)}; }
struct v2 { float a, b; };
struct c2 { v2 x, y; };
#define OP2(name, args, txt, ...) \
    __device__ __forceinline__ v2 name args { v2 r; asm volatile(txt : "=f"(r.a) : __VA_ARGS__(a)); asm volatile(txt : "=f"(r.b) : __VA_ARGS__(b)); return r; }
#define A_XY(e) "f"(x.e), "f"(y.e)
#define A_XYZ(e) "f"(x.e), "f"(y.e), "f"(z.e)
OP2(add2, (v2 x, v2 y), "add.rn.f32 %0, %1, %2;", A_XY)
OP2(sub2, (v2 x, v2 y), "sub.rn.f32 %0, %1, %2;", A_XY)
OP2(mul2, (v2 x, v2 y), "mul.rn.f32 %0, %1, %2;", A_XY)
OP2(tw2, (v2 x, v2 y), "{.reg .f32 n; neg.f32 n, %2; fma.rn.f32 %0, %1, 0f40000000, n;}", A_XY)
OP2(fma2, (v2 x, v2 y, v2 z), "fma.rn.f32 %0, %1, %2, %3;", A_XYZ)
OP2(fms2, (v2 x, v2 y, v2 z), "{.reg .f32 n; neg.f32 n, %3; fma.rn.f32 %0, %1, %2, n;}", A_XYZ)
OP2(fnm2, (v2 x, v2 y, v2 z), "{.reg .f32 n; neg.f32 n, %1; fma.rn.f32 %0, n, %2, %3;}", A_XYZ)
__device__ __forceinline__ c2 both(cf a) { return {{a.x, a.x}, {a.y, a.y}}; }
__device__ __forceinline__ c2 tw2(c2 a, c2 s) { c2 r; r.x = tw2(a.x, s.x); r.y = tw2(a.y, s.y); return r; }
template <bool CJ> __device__ __forceinline__ c2 cmul2(c2 a, c2 t) {
    const v2 p = mul2(a.y, t.y), q = mul2(a.x, t.y);
    c2 r;
    r.x = CJ ? fma2(a.x, t.x, p) : fms2(a.x, t.x, p);
    r.y = CJ ? fms2(a.y, t.x, q) : fma2(a.y, t.x, q);
    return r;
}
template <bool CJ> __device__ __forceinline__ c2 cfma2(c2 a, c2 t, c2 c) {
    const v2 p = CJ ? fma2(a.y, t.y, c.x) : fnm2(a.y, t.y, c.x), q = CJ ? fnm2(a.x, t.y, c.y) : fma2(a.x, t.y, c.y);
    c2 r;
    r.x = fma2(a.x, t.x, p);
    r.y = fma2(a.y, t.x, q);
    return r;
}
__device__ __forceinline__ void bfly2(c2 a, c2 b, c2& s, c2& d) { s.x = add2(a.x, b.x); d.x = sub2(a.x, b.x); s.y = add2(a.y, b.y); d.y = sub2(a.y, b.y); }
__device__ __forceinline__ void bflyi2(c2 a, c2 b, c2& s, c2& d) { s.x = add2(a.x, b.y); d.x = sub2(a.x, b.y); s.y = sub2(a.y, b.x); d.y = add2(a.y, b.x); }
__device__ __forceinline__ uint32_t pkv(float lo, float hi) { uint32_t r; asm volatile("cvt.rn.bf16x2.f32 %0, %1, %2;" : "=r"(r) : "f"(hi), "f"(lo)); return r; }
__device__ __forceinline__ uint32_t pkv(v2 v) { return pkv(v.a, v.b); }
__device__ __forceinline__ float upv(uint32_t v) { float r; asm volatile("shl.b32 %0, %1, 16;" : "=f"(r) : "r"(v)); return r; }
__device__ __forceinline__ cf twid(int m, int M) {
    int r = ((m + M / 2) & (M - 1)) - M / 2;
    float s, c;
    __sincosf((float)r * (-6.283185307179586f / (float)M), &s, &c);
    return {c, s};
}
template <int YL, class F> __device__ __forceinline__ void dft8_end(const c2 (&e)[4], c2 a4, c2 a5, c2 a6, c2 a7, F out) {
    const v2 s = {0.70710678118654752f, 0.70710678118654752f};
    c2 o0, o1, o2, o3, u, v;
    bfly2(a4, a6, o0, o2);
    bfly2(e[0], o0, u, v);
    out(0, u, v);
    YLD(YL, 2);
    bflyi2(e[2], o2, u, v);
    out(2, u, v);
    bflyi2(a5, a7, o1, o3);
    YLD(YL, 1);
    o0.x = add2(o1.y, o1.x); o0.y = sub2(o1.y, o1.x);
    u.x = fma2(o0.x, s, e[1].x); v.x = fnm2(o0.x, s, e[1].x); u.y = fma2(o0.y, s, e[1].y); v.y = fnm2(o0.y, s, e[1].y);
    out(1, u, v);
    YLD(YL, 2);
    o2.x = sub2(o3.y, o3.x); o2.y = add2(o3.y, o3.x);
    u.x = fma2(o2.x, s, e[3].x); v.x = fnm2(o2.x, s, e[3].x); u.y = fnm2(o2.y, s, e[3].y); v.y = fma2(o2.y, s, e[3].y);
    out(3, u, v);
    YLD(YL, 1);
}

__device__ __forceinline__ void bid2tile(int b, int& tc, int& cb) {
    const int c = b >> 1, e = c - 36, t7 = (e * 37) >> 8;
    int g;
    asm("{.reg .pred p, q; setp.lt.s32 p, %2, 4; setp.lt.s32 q, %2, 36; selp.s32 %0, %3, %4, q; selp.s32 %1, %5, %6, q; selp.s32 %0, 0, %0, p; selp.s32 %1, %7, %1, p;}"
        : "=&r"(g), "=&r"(cb) : "r"(c), "r"((c + 4) & 7), "r"(1 + e - 7 * t7), "r"((c - 4) >> 3), "r"(4 + t7), "r"(4 + c));
    tc = 2 * g + (b & 1);
}
__host__ __device__ __forceinline__ int pos_of(int n) { return (n & 24) + 4 * (n & 1) + ((n >> 1) & 3); }
static int kappa_of(int b, int gi) {
    const int r = b >> 4, k1 = 2 * ((b & 15) ^ (4 * gi)) + gi;
    return b >= 128 ? gi * 256 : (k1 || r < 4 ? k1 + 64 * r : 64 * r - 224);
}
static int slot3_of(int kap, int& cj) {
    int m = kap & 15;
    cj = (m > 8) || ((m & 7) == 0 && kap > 256);
    const int kk = cj ? 512 - kap : kap;
    m = kk & 15;
    return kk == 256 ? 0 : (m & 1) * 128 + (m & 6) * 16 + pos_of((kk >> 4) + 2 * (m & 8));
}

__device__ __forceinline__ uint32_t tag_bad(uint32_t a, uint32_t tag) {
    uint32_t v;
    asm volatile("ld.shared.u32 %0, [%1];" : "=r"(v) : "r"(a) : "memory");
    return (v ^ tag) & 1;
}
__device__ __forceinline__ bool wg_all_ok(uint32_t bad, int id) {
    uint32_t ok;
    asm volatile("{.reg .pred p, q; setp.eq.u32 q, %1, 0; barrier.red.and.aligned.pred p, %2, 128, q; selp.u32 %0, 1, 0, p;}" : "=r"(ok) : "r"(bad), "r"(id) : "memory");
    return __all_sync(~0u, ok);
}

__device__ __forceinline__ uint32_t lines_bad(uint32_t va, uint32_t tag, uint32_t bit) {
    uint32_t bad;
    asm volatile("{.reg .b32 a, b, c, d;\n"
                 "ld.shared.u32 a, [%1]; ld.shared.u32 b, [%1+4096]; ld.shared.u32 c, [%1+8192]; ld.shared.u32 d, [%1+12288];\n"
                 "lop3.b32 a, a, b, %2, 0x7e; lop3.b32 c, c, d, %2, 0x7e; lop3.b32 %0, a, c, %3, 0xa8;}"
                 : "=r"(bad) : "r"(va), "r"(tag), "r"(bit) : "memory");
    return bad;
}
__device__ __forceinline__ void load_w(uint32_t sb, const CUtensorMap* m, int kap, uint32_t more) {
    mbar_expect_tx(sb + OFF_BAR + B_WIN, 16 * WPITCH + more);
#pragma unroll 1
    for (int i = 0; i < 4; i++) {
        if (i) __nanosleep(PACE_W);
        tma2d(sb + OFF_W + i * (4 * WPITCH), m + (i & 1), ((i & 2 ? (512 - kap) & 511 : kap) * 1026 >> 4) * 2, 0, sb + OFF_BAR + B_WIN);
    }
}
__device__ __forceinline__ void carry_poll(unsigned __int128 (&f)[4], const uint4* a, int n, uint32_t tag) {
    f[0] = f[1] = f[2] = f[3] = tag;
    asm volatile("{.reg .pred p<4>;\n"
                 "setp.ge.s32 p0, %5, 0; setp.ge.s32 p1, %5, 4; setp.ge.s32 p2, %5, 8; setp.ge.s32 p3, %5, 12;\n"
                 "@p0 ld.relaxed.gpu.global.b128 %0, [%4];\n"
                 "@p1 ld.relaxed.gpu.global.b128 %1, [%4+-32768];\n"
                 "@p2 ld.relaxed.gpu.global.b128 %2, [%4+-65536];\n"
                 "@p3 ld.relaxed.gpu.global.b128 %3, [%4+-98304];}"
                 : "+q"(f[0]), "+q"(f[1]), "+q"(f[2]), "+q"(f[3]) : "l"(a), "r"(n) : "memory");
}
__device__ __forceinline__ uint32_t carry_sum(const unsigned __int128 (&f)[4], const cf (&m4)[2], uint32_t tag, cf (&P)[2]) {
#pragma unroll
    for (int h = 0; h < 2; h++)
#pragma unroll
        for (int a = 3; a >= 0; a--) {
            const cf v = {__uint_as_float((uint32_t)(f[a] >> (64 * h))), __uint_as_float((uint32_t)(f[a] >> (64 * h + 32)))};
            P[h] = a == 3 ? v : cfma(m4[h], P[h], v);
        }
    return (((uint32_t)f[0] ^ tag) | ((uint32_t)f[1] ^ tag) | ((uint32_t)f[2] ^ tag) | ((uint32_t)f[3] ^ tag)) & 15u;
}

struct Ring {
    uint32_t full, rel;
    uint32_t ph, bh;
    uint64_t da;
    bool sig;
    uint32_t k;
};
__device__ __forceinline__ void ring_release(const Ring& r, int slot) {
    if (r.sig) asm volatile("mbarrier.arrive.shared::cluster.b64 _, [%0];" ::"r"(r.rel + 8 * slot) : "memory");
}
__device__ __forceinline__ void ring_wait(Ring& r, int slot) {
    if (slot == 0) r.ph ^= 1;
    mbar_wait(r.full + 8 * slot, r.ph);
}
template <int SLOT, int TA, int HF, int J> __device__ __forceinline__ void mma_g(float (&d)[128], const Ring& r, int sc) {
    constexpr int O = 64 * HF;
    asm volatile("{.reg .b64 da, db; .reg .b32 l; .reg .pred p; setp.ne.s32 p, %67, 0; add.u64 da, %64, %69; mov.b32 l, %65; mov.b64 db, {l,%66};\n"
                 "wgmma.mma_async.sync.aligned.m64n128k16.f32.bf16.bf16 {" L64 "}, da, db, p, 1, 1, %68, 0;}"
                 : R8(d, O), R8(d, O + 8), R8(d, O + 16), R8(d, O + 24), R8(d, O + 32), R8(d, O + 40), R8(d, O + 48), R8(d, O + 56)
                 : "l"(r.da), "n"((uint32_t)mkdesc(SLOT * 32768 + 16384 + J * 32, 16, 0, 0)), "r"(r.bh), "r"(sc), "n"(TA),
                   "n"(1 + SLOT * 2048 + (TA ? HF * 64 + J * 256 : HF * 512 + J * 2)));
}
static_assert((GRP >> HAND & 1) && (GRP >> 7 & 1), "hand-over at the end of a group");
template <int SLOT, int TA, int I, int BAR> __device__ __forceinline__ void gemm_mmas(float (&d)[128], Ring& r, int sc, bool last) {
    mma_g<SLOT, TA, I & 1, I / 2>(d, r, I < 2 ? sc : 1);
    if (GRP >> I & 1) {
        wg_commit();
        if (BAR && I == HAND) asm volatile("{.reg .pred p; setp.ne.s32 p, %1, 0; @p bar.arrive %0, 256;}" ::"n"(BAR), "r"((int)last) : "memory");
        wg_wait<1>();
        if ((GRP & (1 << I) - 1) == 0 && sc) ring_release(r, (SLOT + NST - 1) % NST);
    }
    if constexpr (I < 7) gemm_mmas<SLOT, TA, I + 1, BAR>(d, r, sc, last);
}
template <int SLOT, int TA, int BAR = 0> __device__ __forceinline__ void gemm_step(float (&d)[128], Ring& r, int sc, bool last = false) {
    ring_wait(r, SLOT);
    wg_fence();
    gemm_mmas<SLOT, TA, 0, BAR>(d, r, sc, last);
}
template <int K, int HF> __device__ __forceinline__ void gemm_half(float (&d)[128], Ring& r) {
    if (HF == 0) { ring_wait(r, K % NST); wg_fence(); }
    mma_g<K % NST, 1, HF, 0>(d, r, 1); mma_g<K % NST, 1, HF, 1>(d, r, 1); mma_g<K % NST, 1, HF, 2>(d, r, 1); mma_g<K % NST, 1, HF, 3>(d, r, 1);
    if constexpr (HF == 0 && K < 64 - SKEW) { mma_g<K % NST, 1, 1, 0>(d, r, 1); mma_g<K % NST, 1, 1, 1>(d, r, 1); mma_g<K % NST, 1, 1, 2>(d, r, 1); mma_g<K % NST, 1, 1, 3>(d, r, 1); }
    if constexpr (K < 63) gemm_half<K + 1, HF>(d, r);
}
struct Prod {
    uint32_t b0, b1, b2, b3, b4, dbase;
    unsigned* prof;
    __device__ __forceinline__ Prod(uint32_t sb, int slot, uint32_t off) {
        const uint32_t bars = sb + OFF_BAR;
        b0 = bars + slot % NST * 8; b1 = bars + (slot + 1) % NST * 8; b2 = bars + (slot + 2) % NST * 8; b3 = bars + (slot + 3) % NST * 8; b4 = bars + (slot + 4) % NST * 8;
        dbase = sb + off - bars * 4096;
    }
    __device__ __forceinline__ uint32_t dst() const { return b0 * 4096 + dbase; }
    __device__ __forceinline__ void next() { const uint32_t t = b0; b0 = b1; b1 = b2; b2 = b3; b3 = b4; b4 = t; }
};
__device__ __forceinline__ void load_shared(Prod& r, uint32_t ph, const CUtensorMap* m, int c0, int c3, int first) {
    mbar_wait(r.b0 + B_EMPTY, ph);
    tma4d_mc(r.dst(), m, c0, c3, r.b0);
    r.next();
}
__host__ __device__ constexpr uint64_t phases_from(int k) {
    uint64_t v = 0;
    for (int i = 0; i < 64; i++) v |= (uint64_t)((k + i) / NST & 1) << i;
    return v;
}
__device__ __forceinline__ uint32_t phases(int k, int n) { return ((uint32_t)(phases_from(0) >> k) & ((1u << n) - 1)) | 1u << n; }

__global__ void __cluster_dims__(2, 1, 1) __launch_bounds__(512, 1)
fused_kernel(const __grid_constant__ Maps tm, const __grid_constant__ Params p) {
    const CUtensorMap &tmX = tm.m[0], &tmBre = tm.m[1], &tmBim = tm.m[2], &tmXA = tm.m[5], &tmUst = tm.m[6], &tmVst = tm.m[7], &tmWr = tm.m[8], &tmVld = tm.m[10];
    extern __shared__ __align__(1024) uint8_t smraw[];
    const uint32_t sb = smem_u32(smraw);
    const uint32_t bars = sb + OFF_BAR;
    const int bid = blockIdx.x;
    const bool extra = bid >= 128;
    if (threadIdx.x == 480) RECL(0);
    int tc, cb;
    if (threadIdx.x < 32) {
        if (elect_one()) {
            asm volatile("prefetch.tensormap [%0];" ::"l"(&tmX) : "memory");
            asm volatile("prefetch.tensormap [%0];" ::"l"(&tmBre) : "memory");
            asm volatile("prefetch.tensormap [%0];" ::"l"(&tmBim) : "memory");
#pragma unroll
            for (int s = 0; s < NST; s++) mbar_init(bars + B_FULL + s * 8, 33);
            asm volatile("fence.mbarrier_init.release.cluster;" ::: "memory");
            bid2tile(bid, tc, cb);
            mbar_expect_tx(bars + B_FULL, 32768);
            tma5d(sb + 16384, &tmX, 0, 0, 0, 0, tc, bars + B_FULL);
            tma4d(sb, &tmBre, 0, 0, 0, cb * 4, bars + B_FULL);
            tma4d(sb + 8192, &tmBim, 0, 0, 0, cb * 4, bars + B_FULL);
            asm volatile("mbarrier.arrive.shared::cta.b64 _, [%0], 32;" ::"r"(bars + B_FULL) : "memory");
            STAMP(56);
        }
        __syncwarp();
    }
    const int wid = __shfl_sync(~0u, threadIdx.x >> 5, 0);
    if (wid == 1) {
        if (elect_one()) {
            if (PFJ & 16) pf_map(&tmXA);
#pragma unroll
            for (int o = B_EMPTY; o < B_END; o += 8) mbar_init(bars + o, o < B_STGU ? 2 : (o == B_STGU ? 8 : (o < B_EP ? 4 : 1)));
            asm volatile("fence.mbarrier_init.release.cluster;" ::: "memory");
        }
        __syncwarp();
    }
    const int wg = ((wid >> 2) + 3) & 3, w = wid & 3;
    const int fb = bid >> 5, fcb = bid & 31, fpos = pos_of(fcb);
    const int vrow = ((bid & ~3) | (bid & 1) << 1 | (bid >> 1 & 1)) * 256;
    bid2tile(bid, tc, cb);
    asm volatile("barrier.cluster.arrive.relaxed.aligned;" ::: "memory");

    if (wg == 3) {
        asm volatile("setmaxnreg.dec.sync.aligned.u32 24;");
        if (w == 0) {
            if (extra) mbar_wait(bars + B_FULL, 0);
            else if (KMC > 1 && elect_one()) {
#pragma unroll 1
                for (int k = 1 + (bid >> 8); k < KMC; k++) {
                    mbar_expect_tx(bars + B_FULL + k * 8, 32768);
                    tma5d(sb + k * 32768 + 16384, &tmX, k * 64, 0, 0, 0, tc, bars + B_FULL + k * 8);
                    tma4d(sb + k * 32768, &tmBre, k * 64, 0, 0, cb * 4, bars + B_FULL + k * 8);
                    tma4d(sb + k * 32768 + 8192, &tmBim, k * 64, 0, 0, cb * 4, bars + B_FULL + k * 8);
                    asm volatile("mbarrier.arrive.shared::cta.b64 _, [%0], 32;" ::"r"(bars + B_FULL + k * 8) : "memory");
                }
                STAMP(28);
            }
            __syncwarp();
        }
        asm volatile("barrier.cluster.wait.aligned;" ::: "memory");
        if (bid == 129 || (sb & 0x3FFFF) != SB0) return;
        if (w < 2) {
            if (extra || !elect_one()) return;
            const int rank = bid & 1;
            if (w == 0) {
                Prod r(sb, KMC, 16384);
                int c0 = 64 * KMC;
#pragma unroll 1
                for (uint32_t pat = phases(NST + KMC, 32 - KMC); pat != 1; pat >>= 1) {
                    mbar_wait(r.b0 + B_EMPTY, pat);
                    if (c0 >= 0) tma5d(r.dst(), &tmX, c0, 0, 0, 0, tc, r.b0);
                    mbar_expect_tx(r.b0, c0 >= 0 ? 32768 : 16384);
                    asm volatile("mbarrier.arrive.shared::cta.b64 _, [%0], 32;" ::"r"(r.b0) : "memory");
                    c0 = c0 == 960 ? -64 * KEEP : c0 + 64;
                    r.next();
                }
                r.dbase -= 16384;
                const uint8_t* src = g_H + (size_t)tc * (32 * 16384);
                uint32_t all = (uint32_t)phases_from(32 - NST);
#pragma unroll 1
                for (int hh = 0; hh < 4; hh++) {
                    uint32_t pat = (all & 255) | 256;
                    all >>= 8;
                    mbar_wait(bars + B_HGO + 8 * hh, 0);
                    STAMPR(45 + hh);
#pragma unroll 1
                    do {
                        mbar_wait(r.b0 + B_EMPTY, pat);
                        bulk_ld(r.dst(), src, 16384, r.b0 + B_HLD);
                        mbar_expect_tx(r.b0 + B_HLD, 16384);
                        mbar_expect_tx(r.b0, 16384);
                        src += 16384;
                        r.next();
                        pat >>= 1;
                    } while (pat != 1);
                }
            } else {
                Prod r(sb, KMC, rank * 8192);
                int c = 64 * KMC;
#pragma unroll 1
                for (uint32_t pat = phases(NST + KMC, 32 - KMC); pat != 1; pat >>= 1) {
                    load_shared(r, pat, &tmBre + rank, c & 1023, cb * 4 + ((c >> 5) & 64), 1);
                    c += c == 960 ? 2112 - 64 * KEEP : 64;
                }
                r.dbase += 16384;
                uint32_t pat = (uint32_t)phases_from(32 - NST);
#pragma unroll 1
                for (c = 0; c != 1024; c += 64) {
                    load_shared(r, pat, &tmBre + 2, c, cb * 8 + rank * 4, 0);
                    if (c == 64 * LDK) mbar_arrive(bars + B_LDONE);
                    load_shared(r, pat >> 1, &tmBre + 3, c, cb * 8 + rank * 4, 0);
                    pat >>= 2;
                }
            }
        } else if (w == 2) {
            if (!elect_one()) return;
            STAMP5(39);
            if (!extra) {
                mbar_expect_tx(bars + B_XIN, 16384);
                mbar_expect_tx(bars + B_XIN + 8, 16384);
#pragma unroll 1
                for (int i = 0; i < 8; i++) {
                    const int k = i - XA_FIRST + XA_AT;
                    if (i >= XA_FIRST) mbar_wait(bars + B_EMPTY + (k < NST ? k : k - NST) * 8, k >= NST);
                    tma4d(sb + OFF_P + i * 2048, &tmXA, fcb * 32, 0, i, fb, bars + B_XIN);
                    tma4d(sb + OFF_P + 16384 + i * 2048, &tmXA, fcb * 32 + 16, 0, i, fb, bars + B_XIN + 8);
                    if (!i) STAMP5(30);
                    STAMP5(31);
                }
            }
            if (PFJ & 1) { pf_map(&tmWr); pf_map(&tmWr + 1); }
            const unsigned ep = get_epoch(bars);
            if (!extra) mbar_wait(bars + B_XIN + 8, 0);
            STAMP5(32);
            load_w(sb, &tmWr, p.unit[2 * bid] & 0xffff, 8192);
            if (PFJ & 2) pf_map(&tmUst);
            if (!extra) mbar_wait(bars + B_STGU, 0);
            STAMP(21);
#pragma unroll 1
            for (int gi = 0; gi < 2; gi++) {
                if (!extra) {
#pragma unroll 1
                    for (int r = 128 * gi; r < 128 * gi + 128; r += UBOX) {
                        if (gi) __nanosleep(PACE_U);
                        tma2d_st(&tmUst, fb * 2048 + fpos * 64, r, sb + OFF_P + r * 128);
                        bulk_commit();
                    }
                    bulk_wait_read<HINT_U>();
                    red_hint(g_cnt + gi * 32);
                }
                if (!gi) bulk_ld(sb + OFF_F, g_tab + TAB_FG, 8192, bars + B_WIN);
                bulk_wait_read<0>();
                STAMPR(40 + gi);
                wait_cnt(g_cnt + 32 * gi, 128 * ep - (gi ? 0 : EARLY_U));
                {
                    if (gi) __nanosleep(UDELAY);
                    else STAMP(42);
                    mbar_expect_tx(bars + B_UIN + 8 * gi, 16384);
                    bulk_ld(sb + OFF_P + gi * 16384, g_U + (size_t)(extra ? 0 : bid + 128 * gi) * 16384, 16384, bars + B_UIN + 8 * gi);
                }
            }
            if (WPF) {
                const int kap = p.unit[2 * bid + 1] & 0xffff;
#pragma unroll 1
                for (int i = 0; i < 4; i++)
                    asm volatile("cp.async.bulk.prefetch.tensor.2d.L2.global [%0, {%1,%2}];" ::"l"(&tmWr + (i & 1)), "r"(((i & 2 ? 512 - kap : kap) * 1026 >> 4) * 2), "r"(0) : "memory");
            }
            if (PFJ & 4) { pf_map(&tmBre + 2); pf_map(&tmBre + 3); }
            if (PFJ & 8) { pf_map(&tmVst); pf_map(&tmVld); }
            mbar_wait(bars + B_WFREE, 0);
            load_w(sb, &tmWr, p.unit[2 * bid + 1] & 0xffff, 0);
#pragma unroll 1
            for (int gi = 0; gi < 2; gi++) {
                const int vc = ((p.unit[2 * bid + gi] >> 16) & 255) * 64, go = vc >> 13;
                const uint32_t src = extra ? sb + 32768 : sb + OFF_P + gi * 16384;
                mbar_wait(bars + B_STG, gi);
                STAMPR(23 + gi);
                if (extra && !gi) continue;
                if (bid + gi != 0) {
#pragma unroll 1
                    for (int r = 0; r < 128; r += 32) {
                        if (r && !gi) __nanosleep(PACE_V);
                        if (VSPLIT && gi && r == 64) mbar_wait(bars + B_STGU, !extra);
                        tma2d_st(&tmVst, vc, r, src + r * 128);
                        bulk_commit();
                    }
                }
                bulk_wait_read<HINT_V>();
                red_hint(g_cnt + 64 + 32 * go);
                bulk_wait_read<0>();
                STAMP(49);
                if (extra) break;
                wait_cnt(g_cnt + 64 + 32 * gi, (129 - gi) * ep - gi * EARLY_V);
                {
                    STAMPR(43 + gi);
#pragma unroll
                    for (int h = 0; h < 2; h++) {
                        mbar_expect_tx(bars + B_VIN + gi * 16 + h * 8, 8192);
                        tma2d(src + h * 8192, &tmVld, h * 32, vrow + gi * 128, bars + B_VIN + gi * 16 + h * 8);
                    }
                }
            }
        } else {
            const uint32_t tag = ld_rlx(g_epoch + bid * 8) + 1;
            __syncwarp();
            if (elect_one()) {
                asm volatile("st.shared.u32 [%0], %1;" ::"r"(bars + B_EPOCH), "r"(tag) : "memory");
                mbar_arrive(bars + B_EP);
                asm volatile("st.relaxed.gpu.global.u32 [%0], %1;" ::"l"(g_epoch + bid * 8), "r"(tag) : "memory");
#pragma unroll
                for (int i = 3; i < 11; i++) if (PFM >> i & 1) pf_map(tm.m + i);
            }
            __syncwarp();
            if (extra) return;
            const int lane = (threadIdx.x + p.zero[0]) & 31;
            Prod r(sb, 32, 0);
            uint32_t va = (lane & 3) * 516 + (lane >> 4) * 2048 + (lane & 12) * 32 + (lane >> 2) * 16 + r.dbase;
            asm volatile("" : "+r"(va));
            uint32_t n = 0;
#pragma unroll 1
            for (int half = 0; half < 2; half++) {
#pragma unroll 1
                for (uint32_t pat = phases(16 * half, 16); pat != 1; pat >>= 1) {
                    mbar_wait(r.b0 + B_HLD, pat);
                    bool bad = lines_bad(r.b0 * 4096 + va, tag, 1);
                    if (!bad) mbar_arrive(r.b0);
#pragma unroll 1
                    while (__any_sync(~0u, bad)) {
                        const int kk = __shfl_sync(~0u, pat, 0);
                        if (elect_one()) {
                            mbar_expect_tx(bars + B_HRTY, 16384);
                            bulk_ld(r.dst(), g_H + (uint32_t)(tc * 32 + half * 16 + __clz(kk) - 15) * 16384, 16384, bars + B_HRTY);
                        }
                        __syncwarp();
                        mbar_wait(bars + B_HRTY, n++);
                        if (bad && !lines_bad(r.b0 * 4096 + va, tag, n < SPIN_LIMIT)) { bad = false; mbar_arrive(r.b0); }
                        __syncwarp();
                    }
                    if (pat >> 16) STAMPR(6 + 23 * half);
                    r.next();
                }
            }
        }
    } else {
        asm volatile("setmaxnreg.inc.sync.aligned.u32 152;");
        asm volatile("barrier.cluster.wait.aligned;" ::: "memory");
        STAMP(55);
        if ((extra && (wg != 2 || bid == 129)) || (sb & 0x3FFFF) != SB0) return;
        const int hf = wg - 1;
        if (WARM && wg == 0) {
            float z[64];
            if (WARM_NS) __nanosleep(WARM_NS);
#pragma unroll 1
            for (int i = 0; i < WARM; i++) {
                wg_fence();
                mma128_first(z, mkdesc(OFF_F, 16, 1024, 1), mkdesc(OFF_W, 4096, 512, 2));
                wg_commit();
                wg_wait<0>();
                pin(z);
            }
        }
#define INDICES(i) const int t7 = (threadIdx.x + p.zero[i]) & 127, lane = t7 & 31, g = lane >> 2, q = lane & 3, k1 = t7 >> 2, mi = lane >> 3, gl = lane & 7; \
                   const uint32_t tmask = q == 0 ? ~1u : ~0u;
        if (wg == 1) {
            INDICES(1)
            const int ch = (t7 >> 6) * 512 + (t7 & 8) * 32 + cb * 32 + ((t7 >> 1) & 24) + (t7 & 7);
            const float lr = __bfloat162float(p.lre[ch]), li = __bfloat162float(p.lim[ch]);
            const float dt = __bfloat162float(__float2bfloat16(expf(__bfloat162float(p.ldt[ch]))));
            float sn, cs;
            sincospif(dt * li * 0.31830988618379067f, &sn, &cs);
            const float ex = expf(dt * lr), br = ex * cs, bi = ex * sn;
            const float inv = __fdividef(2.0f, lr * lr + li * li);
            const cf lam = {br, -bi}, gam = {((br - 1.f) * lr + bi * li) * inv, -(bi * lr - (br - 1.f) * li) * inv};
            const cf l32 = csq(csq(csq(csq(csq(lam))))), l64 = csq(l32), m1 = csq(l64), m2 = csq(m1), g2 = cmul(gam, l64);
            sts128f(sb + OFF_T1 + t7 * 16, lam, l32);
            sts128f(sb + OFF_TL + t7 * 32, gam, cmul(gam, l32));
            sts128f(sb + OFF_TL + t7 * 32 + 16, g2, cmul(g2, l32));
            sts128f(sb + OFF_TM + t7 * 32, csq(m2), m1);
            sts128f(sb + OFF_TM + t7 * 32 + 16, m2, cmul(m2, m1));
            __syncwarp();
            if (lane == 0) mbar_arrive(bars + B_LAM);
        }
        if (wg != 0 && !extra) {
            INDICES(2)
            uint32_t f1[16];
#pragma unroll
            for (int j = 0; j < 4; j++) { const uint4 v = ldtab(TAB_F1 + j * 512 + t7 * 4); f1[4 * j] = v.x; f1[4 * j + 1] = v.y; f1[4 * j + 2] = v.z; f1[4 * j + 3] = v.w; }
            cf tw[8];
            load_tw(tw, k1);
            const uint32_t tbit = get_epoch(bars) & ~tmask;
            float acc[64];
            const uint64_t dx = mkdesc(OFF_P, 2048, 256, 3) + hf * 1024;
            const int gr = gl & 1, jr = (gl >> 1) + 4 * ((w ^ gl) & 1);
            const uint32_t a0 = w + gl ? sb + OFF_P + (gr * 128 + 8 * (w >> 1) + jr + 64 * (mi >> 1)) * 128 : sb + OFF_F + 2048;
            const uint32_t rs = w + gl ? 2048 : 0;
            const uint32_t scr = sb + OFF_F + hf * 1024;
            STAMP5(33 + hf);
            mbar_wait(bars + B_XIN + hf * 8, 0);
            STAMP(20);
            pinu(f1);
            wg_fence();
            mma128_rs<1, 0>(acc, f1, dx);
            mma128_rs<1, 1>(acc, f1 + 4, dx + 32);
            mma128_rs<1, 1>(acc, f1 + 8, dx + 64);
            mma128_rs<1, 1>(acc, f1 + 12, dx + 96);
            wg_commit();
            wg_wait<0>();
            pin(acc);
            pinu(f1);
            STAMP5(35);
            if (k1 == 0) {
#pragma unroll
                for (int i = 0; i < 16; i++) sts128f(scr + i * 64 + q * 16, {acc[4 * i], acc[4 * i + 1]}, {acc[4 * i + 2], acc[4 * i + 3]});
            }
            uint4 fx0, fx1;
            asm volatile("ld.global.nc.v4.b32 {%0,%1,%2,%3}, [%4];" : "=r"(fx0.x), "=r"(fx0.y), "=r"(fx0.z), "=r"(fx0.w) : "l"(g_tab + TAB_FX + (t7 & 120)));
            asm volatile("ld.global.nc.v4.b32 {%0,%1,%2,%3}, [%4];" : "=r"(fx1.x), "=r"(fx1.y), "=r"(fx1.z), "=r"(fx1.w) : "l"(g_tab + TAB_FX + (t7 & 120) + 4));
#pragma unroll
            for (int cl = 0; cl < 2; cl++) {
                auto in = [&](int n) { const int i = 4 * (2 * n + cl); return c2{{acc[i], acc[i + 1]}, {acc[i + 2], acc[i + 3]}}; };
                c2 e[4];
                {
                    const c2 a0 = cfma2<false>(in(4), both(tw[4]), in(0)), a1 = tw2(in(0), a0);
                    YLD(YF1, 3);
                    const c2 t2 = cmul2<false>(in(2), both(tw[2]));
                    YLD(YF1, 2);
                    const c2 a2 = cfma2<false>(in(6), both(tw[6]), t2), a3 = tw2(t2, a2);
                    YLD(YF1, 3);
                    bfly2(a0, a2, e[0], e[2]);
                    YLD(YF1, 1);
                    bflyi2(a1, a3, e[1], e[3]);
                }
                cf sx[8];
                if (cl == 0) {
                    bar_sync(6, 256);
                    STAMP5(36);
#pragma unroll
                    for (int n = 0; n < 8; n++) sx[n] = lds_cf(scr + n * 128 + gl * 16 + (w >> 1) * 8);
                }
                const c2 t1 = cmul2<false>(in(1), both(tw[1]));
                YLD(YF1, 2);
                const c2 a4 = cfma2<false>(in(5), both(tw[5]), t1), a5 = tw2(t1, a4);
                YLD(YF1, 3);
                const c2 t3 = cmul2<false>(in(3), both(tw[3]));
                YLD(YF1, 1);
                const c2 a6 = cfma2<false>(in(7), both(tw[7]), t3), a7 = tw2(t3, a6);
                YLD(YF1, 2);
                const uint32_t a1 = a0 + (((((mi & 1) << 2) | ((2 * hf + cl) ^ (fpos & 3))) ^ jr) << 4);
                dft8_end<YF1>(e, a4, a5, a6, a7, [&](int r, c2 u, c2 v) {
                    uint32_t o0 = pkv(u.x), o1 = pkv(u.y), o2 = pkv(v.x), o3 = pkv(v.y);
                    if (cl == 0) { o0 = bitsel(o0, tmask, tbit); o1 = bitsel(o1, tmask, tbit); o2 = bitsel(o2, tmask, tbit); o3 = bitsel(o3, tmask, tbit); }
                    stsm4(a1 + r * rs, o0, o1, o2, o3);
                });
                if (cl == 0) {
                    YLD(YF1, 2);
                    float s0 = 0.f, s1 = 0.f;
#pragma unroll
                    for (int n = 0; n < 8; n++) {
                        const float c = __uint_as_float(n < 4 ? (n == 0 ? fx0.x : n == 1 ? fx0.y : n == 2 ? fx0.z : fx0.w) : (n == 4 ? fx1.x : n == 5 ? fx1.y : n == 6 ? fx1.z : fx1.w));
                        s0 = fmaf(c, sx[n].x, s0); s1 = fmaf(c, sx[n].y, s1);
                    }
                    asm volatile("st.shared.b32 [%0], %1;" ::"r"(sb + OFF_P + (t7 >> 4) * 2048 + (((mi & 1) * 4 + ((2 * hf + (g & 1)) ^ (fpos & 3))) << 4) + q * 4), "r"(bitsel(pk(s0, s1), tmask, tbit)) : "memory");
                    YLD(YF1, 1);
                }
            }
            fence_async_sm();
            __syncwarp();
            if (lane == 0) mbar_arrive(bars + B_STGU);
        }
        if (wg != 2) {
        if (wg == 0) bar_sync(4, 128);
        asm volatile("setmaxnreg.inc.sync.aligned.u32 168;");
        float d[128];
        Ring rg;
        rg.full = bars + B_FULL;
        asm("mapa.shared::cluster.u32 %0, %1, %2;" : "=r"(rg.rel) : "r"(bars + B_EMPTY), "r"(w & 1));
        rg.sig = ((threadIdx.x + p.zero[7]) & 95) == 0;
        rg.bh = (uint32_t)(mkdesc(0, 0, 1024, 1) >> 32) + p.zero[0];
        rg.da = p.da[0];
        rg.ph = 1;
        rg.k = 130 * 66 + bid * 66 + 16 * wg;
        if (wg == 0) {
            STAMP(0);
            gemm_step<0, 0>(d, rg, 0);
        } else {
            bar_sync(1, 256);
            STAMP(10);
        }
        rg.da = p.da[1];
#pragma unroll 1
        for (int i = 0; i < 3; i++) {
            gemm_step<1, 0>(d, rg, i >= wg);
            gemm_step<2, 0>(d, rg, 1);
            gemm_step<3, 0>(d, rg, 1);
            gemm_step<4, 0>(d, rg, 1);
            gemm_step<0, 0, 1>(d, rg, 1, i - wg == 2);
        }
        if (wg != p.zero[1]) {
            rg.da = p.da[0];
            gemm_step<1, 0, 2>(d, rg, 1, true);
        }
        {
            INDICES(3)
            cf lam[2], l32[2], l2[2];
            const uint32_t ta = sb + (wg * 64 + 16 * w + g) * 16;
            mbar_wait(bars + B_LAM, 0);
            const unsigned ep = get_epoch(bars), tag = ep & 15u;
            lds128f(ta + OFF_T1, lam[0].x, lam[0].y, l32[0].x, l32[0].y);
            lds128f(ta + OFF_T1 + 128, lam[1].x, lam[1].y, l32[1].x, l32[1].y);
            const uint4* cpub = g_carry + (uint32_t)(wg * 256 + cb * 32 + 8 * w + tc * 512 + g);
            l2[0] = csq(lam[0]);
            l2[1] = csq(lam[1]);
            asm volatile("pmevent 0;" : "+l"(cpub), "+f"(l2[0].x), "+f"(l2[0].y), "+f"(l2[1].x), "+f"(l2[1].y));
            wg_wait<0>();
            ring_release(rg, wg);
            pin(d);
            STAMPW(1, 11);
            cf f[2];
#pragma unroll
            for (int h = 0; h < 2; h++) {
                c2 c = {{d[2 * h], d[2 * h + 1]}, {d[64 + 2 * h], d[65 + 2 * h]}};
#pragma unroll
                for (int i = 1; i < 16; i++) {
                    const int r = 4 * i + 2 * h;
#define P1A "fma.rn.f32 a0, %2, %9, %4; fma.rn.f32 a1, %3, %9, %5;\n"
#define P1B "fma.rn.f32 b0, %0, n, %6; fma.rn.f32 b1, %1, n, %7;\n"
#define P1X "fma.rn.f32 %0, %0, %8, a0; fma.rn.f32 %1, %1, %8, a1;\n"
#define P1Y "fma.rn.f32 %2, %2, %8, b0; fma.rn.f32 %3, %3, %8, b1;\n"
#define P1ARG : "+f"(c.x.a), "+f"(c.x.b), "+f"(c.y.a), "+f"(c.y.b) : "f"(d[r]), "f"(d[r + 1]), "f"(d[64 + r]), "f"(d[65 + r]), "f"(l2[h].x), "f"(l2[h].y)
                    if (i & 1) asm volatile("{.reg .f32 a0, a1, b0, b1, n; neg.f32 n, %9;\n" P1A P1B P1X P1Y "}" P1ARG);
                    else asm volatile("{.reg .f32 a0, a1, b0, b1, n; neg.f32 n, %9;\n" P1B P1A P1Y P1X "}" P1ARG);
                    if (i % YS == 0) YIELD();
                    if (i == 12) lds128f(ta + OFF_T1 + 128 * h, lam[h].x, lam[h].y, l32[h].x, l32[h].y);
                }
                f[h] = cfma(lam[h], {c.x.a, -c.y.a}, {c.x.b, -c.y.b});
            }
            cf st[2], gam[2];
            gam[0] = lds_cf(2 * ta - sb + OFF_TL);
            gam[1] = lds_cf(2 * ta - sb + OFF_TL + 256);
            cf v0[2], v1[2], v2[2];
#pragma unroll
            for (int h = 0; h < 2; h++) {
                v0[h] = {__shfl_sync(~0u, f[h].x, 0, 4), __shfl_sync(~0u, f[h].y, 0, 4)};
                v1[h] = {__shfl_sync(~0u, f[h].x, 1, 4), __shfl_sync(~0u, f[h].y, 1, 4)};
                v2[h] = {__shfl_sync(~0u, f[h].x, 2, 4), __shfl_sync(~0u, f[h].y, 2, 4)};
            }
#pragma unroll
            for (int h = 0; h < 2; h++) {
                v1[h] = cfma(l32[h], v0[h], v1[h]);
                v2[h] = cfma(l32[h], v1[h], v2[h]);
                f[h] = cfma(l32[h], v2[h], f[h]);
            }
            asm volatile("{.reg .pred p; .reg .b64 a, b; .reg .b128 v; setp.eq.u32 p, %5, 3; mov.b64 a, {%1,%2}; mov.b64 b, {%3,%4}; mov.b128 v, {a, b};\n"
                         "@p st.relaxed.gpu.global.b128 [%0], v;}" ::"l"(cpub),
                         "r"(bitsel(__float_as_uint(f[0].x), ~15u, tag)), "r"(__float_as_uint(f[0].y)), "r"(__float_as_uint(f[1].x)), "r"(__float_as_uint(f[1].y)), "r"(q) : "memory");
            STAMPX(2, 12);
            YIELD();
#pragma unroll
            for (int h = 0; h < 2; h++) st[h] = cmul(gam[h], csel(q & 2, csel(q & 1, v2[h], v1[h]), csel(q & 1, v0[h], cf{0.f, 0.f})));
            const uint4* cget = cpub + (gl - g) - (1 + mi) * 512;
            const int nget = tc - 1 - mi;
            unsigned __int128 fq[4];
            auto prescale = [&](int i) {
                const int h = i >> 4, r = 4 * (i & 15) + 2 * h;
                asm volatile("{.reg .f32 s0, s1, n; neg.f32 n, %4; mul.f32 s0, %5, %1; mul.f32 s1, %5, %3; mul.f32 %1, n, %1; mul.f32 %3, n, %3;\n"
                             "fma.rn.f32 %1, %5, %0, %1; fma.rn.f32 %3, %5, %2, %3; fma.rn.f32 %0, %4, %0, s0; fma.rn.f32 %2, %4, %2, s1;}"
                             : "+f"(d[r]), "+f"(d[64 + r]), "+f"(d[r + 1]), "+f"(d[65 + r]) : "f"(gam[h].x), "f"(gam[h].y));
            };
#pragma unroll
            for (int i = 0; i < (DEFER ? 17 : 32); i++) {
                if (i == POLL_AT) carry_poll(fq, cget, nget, tag);
                if (i % YS == 0) YIELD();
                prescale(i);
            }
            YIELD();
            const uint32_t tm = sb + OFF_TM + (wg * 64 + 16 * w) * 32;
            cf m4[2], mj[2], P[2], lq[2];
#pragma unroll
            for (int h = 0; h < 2; h++) {
                m4[h] = lds_cf(tm + gl * 32 + h * 256);
                mj[h] = lds_cf(tm + gl * 32 + h * 256 + mi * 8);
            }
            uint32_t bad = carry_sum(fq, m4, tag, P);
            unsigned n = 0;
            while (__any_sync(~0u, bad) && ++n < SPIN_LIMIT) {
                unsigned __int128 fr[4];
                carry_poll(fr, cget, nget, tag);
                bad = carry_sum(fr, m4, tag, P);
                YIELD();
                mj[0] = lds_cf(tm + gl * 32 + mi * 8);
                mj[1] = lds_cf(tm + gl * 32 + 256 + mi * 8);
            }
            STAMPX(53, 54);
            P[0] = csel(mi, cmul(P[0], mj[0]), P[0]);
            P[1] = csel(mi, cmul(P[1], mj[1]), P[1]);
            __syncwarp();
            sts128f(tm + lane * 16, P[0], P[1]);
#pragma unroll
            for (int h = 0; h < 2; h++) {
                lq[h] = lds_cf(2 * ta - sb + OFF_TL + h * 256 + q * 8);
                lam[h] = lds_cf(ta + OFF_T1 + h * 128);
            }
            __syncwarp();
            float ps[4][4];
#pragma unroll
            for (int j = 0; j < 4; j++) lds128f(tm + g * 16 + j * 128, ps[j][0], ps[j][1], ps[j][2], ps[j][3]);
            const uint8_t* hp = g_H + (uint32_t)((tc * 32 + wg * 16 + (cb & 6)) * 16384 + ((cb & 1) * 4 + w) * 2048 + g * 64 + ((q ^ (g >> 1)) << 4));
#pragma unroll
            for (int h = 0; h < 2; h++)
                st[h] = cfma(lq[h], {(ps[0][2 * h] + ps[1][2 * h]) + (ps[2][2 * h] + ps[3][2 * h]), (ps[0][2 * h + 1] + ps[1][2 * h + 1]) + (ps[2][2 * h + 1] + ps[3][2 * h + 1])}, st[h]);
            STAMPX(3, 13);
            uint32_t hv[32];
            auto go = [&]() {
                if (w == 0) {
                    wait_cnt(g_hcnt + tc * 64 + wg * 32, 32 * ep - EARLY_H);
                    if (lane < 4) mbar_arrive(bars + B_HGO + 16 * wg);
                } else mbar_wait(bars + B_HGO + 16 * wg, 0);
            };
#pragma unroll
            for (int h = 0; h < 2; h++) {
                YIELD();
                if (DEFER && h) gam[1] = lds_cf(2 * ta - sb + OFF_TL + 256);
                cf c = st[h];
#pragma unroll
                for (int i = 0; i < 16; i++) {
                    if (DEFER && h) {
                        if (i % YD == 0) YIELD();
                        if (i < 15) prescale(17 + i);
                    }
                    const int r = 4 * i + 2 * h;
                    const cf a = cfma(lam[h], c, {d[r], d[64 + r]});
                    c = cfma(lam[h], a, {d[r + 1], d[65 + r]});
                    hv[i] = pk(a.x, c.x);
                    hv[16 + i] = pk(a.y, c.y);
                    if ((i & 3) == (i >> 2)) { hv[i] = bitsel(hv[i], ~1u, ep & 1); hv[16 + i] = bitsel(hv[16 + i], ~1u, ep & 1); }
                    if (h == 0 && (i & 3) == 3) {
                        stg128(hp + (i >> 2) * 512, hv[i - 3], hv[i - 2], hv[i - 1], hv[i]);
                        stg128(hp + 16384 + (i >> 2) * 512, hv[13 + i], hv[14 + i], hv[15 + i], hv[16 + i]);
                    }
                }
                if (h == 0) {
                    STAMPW(4, 14);
                    if (lane == 0) red_hint(g_hcnt + tc * 64 + wg * 32);
                    if (DEFER > 1 && wg) {
                        go();
                        mbar_wait(bars + B_IDLE, 0);
                    }
                }
            }
            YIELD();
            if (DEFER < 2 || !wg) go();
            if (HDELAY) __nanosleep(wg * HDELAY);
#pragma unroll
            for (int j = 0; j < 8; j++) {
                stg128(hp + (8 + (j >> 2)) * 16384 + (j & 3) * 512, hv[4 * j], hv[4 * j + 1], hv[4 * j + 2], hv[4 * j + 3]);
                if (j < 7) __nanosleep(PACE_H);
            }
            __syncwarp();
            if (lane == 0) mbar_arrive(bars + B_HGO + 16 * wg + 8);
            STAMPW(5, 15);
        }
        if (wg == p.zero[2]) {
            INDICES(1)
            float y[128];
            const uint32_t sa = sb + w * 4096 + g * 512 + q * 8;
            bar_sync(2, 256);
            STAMP(7);
            rg.da = p.da[2];
            rg.ph = 0;
            rg.k = 130 * 66 + bid * 66 + 32;
#pragma unroll 1
            for (int i = 0;; i++) {
                gemm_step<2, 1>(y, rg, i);
                gemm_step<3, 1>(y, rg, 1);
                gemm_step<4, 1>(y, rg, 1);
                if (i == 5) break;
                gemm_step<0, 1>(y, rg, 1);
                gemm_step<1, 1>(y, rg, 1);
            }
            rg.da = p.da[3];
            gemm_half<60, 0>(y, rg);
            if (LDK > 15 && t7 == 0) mbar_arrive(bars + B_LDONE);
            wg_commit();
            gemm_half<64 - SKEW, 1>(y, rg);
            wg_commit();
#pragma unroll
            for (int r = 0; r < 4; r++) {
                if (r == 0) {
                    wg_wait<1>();
#pragma unroll
                    for (int i = 0; i < 64; i++) asm volatile("" : "+f"(y[i])::"memory");
                    STAMP(16);
                    bar_sync(4, 128);
                }
                if (r == 2) {
                    STAMP(18);
                    wg_wait<0>();
#pragma unroll
                    for (int i = 64; i < 128; i++) asm volatile("" : "+f"(y[i])::"memory");
                    STAMP(8);
                    bar_sync(4, 128);
                }
#pragma unroll
                for (int c = 0; c < 16; c++) {
                    const int yi = 64 * (r >> 1) + 4 * c + 2 * (r & 1);
                    sts64f(sa + (r < 2 ? (NST - 1) * 32768 : 0) + (r & 1) * 16384 + (c >> 2) * 128 + (((c ^ g) & 3) << 5), y[yi], y[yi + 1]);
                }
                if (r == 0) bar_arrive(9, 256);
                if (r == 1) bar_arrive(10, 256);
                if (r == 2) bar_arrive(11, 256);
                if (r == 3) bar_arrive(12, 256);
            }
            STAMP(19);
            return;
        }
        bar_sync(8, 128);
        asm volatile("setmaxnreg.dec.sync.aligned.u32 152;");
        } else {
            INDICES(4)
            cf T[8];
            load_T(T, t7);
            const uint32_t tag = get_epoch(bars) & 1;
            float acc[64];
            constexpr uint64_t dF = mkdesc(OFF_F, 16, 1024, 1);
            const uint32_t tga = sb + OFF_P + t7 * 128 + (((t7 & 1) ^ (g & 2)) << 4) + (g & 1) * 64;
            bool ok = false;
            mbar_wait(bars + B_WIN, 0);
#pragma unroll 1
            for (int gi = 0;; gi++) {
                const uint32_t un = p.unit[2 * bid + gi];
                const int kap = un & 0xffff;
                const uint32_t buf = sb + OFF_P + gi * 16384;
                STAMP3(39);
                float za[32], zb[32], ya[32], yb[32];
                const uint64_t dB = mkdesc(OFF_P, 4096, 512, 2) + gi * 1024;
                uint32_t ad, am, pa, pb;
                if (w == 2) {
                    ad = sb + OFF_W + (lane & 8) * 128;
                    am = ad + ((lane & 4) | (((kap ? 3 : 4) - lane) & 3)) * WPITCH + (8 * WPITCH + ((-2 * kap) & 15));
                    ad += gl * WPITCH + ((2 * kap) & 15);
                    asm volatile("" : "+r"(ad), "+r"(am));
                    mbar_wait(bars + B_WIN, gi);
                    pa = lds_u16(ad);
                    pb = lds_u16(am);
                }
#pragma unroll 1
                for (int n = gi; !ok && n < 4096; n++) {
                    if (n) bar_sync(3, 128);
                    if (n && w == 0 && elect_one()) { mbar_expect_tx(bars + B_UIN + gi * 8, 16384); bulk_ld(buf, g_U + (size_t)(extra ? 0 : bid + gi * 128) * 16384, 16384, bars + B_UIN + gi * 8); }
                    mbar_wait(bars + B_UIN + gi * 8, n & 1);
                    STAMP3(22);
                    wg_fence();
                    mma128_first(acc, dF, dB);
                    mma128_ss<0, 0, 1, 1>(acc, dF + 2, dB + 64);
                    mma128_ss<0, 0, 1, 1>(acc, dF + 4, dB + 128);
                    mma128_ss<0, 0, 1, 1>(acc, dF + 6, dB + 192);
                    wg_commit();
                    YIELD();
                    ok = wg_all_ok(tag_bad(tga + gi * 16384, tag), 3);
                    wg_wait<0>();
                    pin(acc);
                }
                STAMP3(30);
                uint32_t af[32];
#pragma unroll
                for (int b = 0; b < 4; b++) {
#pragma unroll
                    for (int c = 0; c < 4; c++) {
                        const int i = 4 * (4 * b + c);
                        cf x0 = cmul({acc[i], acc[i + 2]}, T[2 * c]), x1 = cmul({acc[i + 1], acc[i + 3]}, T[2 * c + 1]);
                        af[16 * (b >> 1) + 4 * c + (b & 1)] = pk(x0.x, x0.y);
                        af[16 * (b >> 1) + 4 * c + 2 + (b & 1)] = pk(x1.x, x1.y);
                        YLD(YF2, c == 3 ? 1 : (c == 1 ? 2 : 3));
                    }
                    if (b == 0 && w == 2) {
                        const uint32_t sg = (lane & 4) << 13, v = pk(0.5f * (up(pa) + up(pb ^ sg)), 0.f);
                        asm volatile("st.shared.u16 [%0], %1;" ::"r"(ad), "r"(v) : "memory");
                        asm volatile("st.shared.u16 [%0], %1;" ::"r"(am), "r"(v ^ sg) : "memory");
                    }
                    if (b == 1) {
                        wg_fence();
                        mma64_rs<0, 0>(za, af, dF); mma64_rs<0, 1>(za, af + 4, dF + 2); mma64_rs<0, 1>(za, af + 8, dF + 4); mma64_rs<0, 1>(za, af + 12, dF + 6);
                        wg_commit();
                    }
                }
                wg_fence();
                mma64_rs<0, 0>(zb, af + 16, dF); mma64_rs<0, 1>(zb, af + 20, dF + 2); mma64_rs<0, 1>(zb, af + 24, dF + 4); mma64_rs<0, 1>(zb, af + 28, dF + 6);
                wg_commit();
                STAMP3(31);
                int kq;
                asm volatile("mad.lo.s32 %0, %1, 512, %2;" : "=r"(kq) : "r"(q), "r"(kap));
                uint32_t wad[4];
#pragma unroll
                for (int j = 0; j < 4; j++) wad[j] = sb + OFF_W + ((j + (kq >> 9)) & 3) * WPITCH + ((2 * kap) & 15) + 2 * k1 + 128 * q;
                if (VDEFER && gi) fence_async_sm();
                bar_sync(3, 128);
                if (VDEFER && lane < gi) mbar_arrive(bars + B_STG);
                uint32_t wn[16];
#pragma unroll
                for (int j = 0; j < 16; j++) wn[j] = lds_u16(wad[j >> 2] + (j & 1) * 64 + (j & 2) * (2 * WPITCH));
                const cf be1 = twid(kq, 2048), be2 = cmul(be1, be1), be3 = cmul(be1, be2);
                YLD(YF2, 1);
                wg_wait<0>();
                pin(za);
                pin(zb);
                pinu(af);
                STAMP3(32);
                c2 z[4];
                auto pack = [&](int jb, int b) {
                    af[16 * (b >> 1) + 4 * jb + (b & 1)] = pkv(z[b].x);
                    af[16 * (b >> 1) + 4 * jb + 2 + (b & 1)] = pkv(z[b].y);
                };
#pragma unroll
                for (int jb = 0; jb < 4; jb++) {
                    if (jb == 2) STAMP3(37);
                    if (jb == 1) {
#pragma unroll
                        for (int j = 0; j < 4; j++)
                            wad[j] = sb + OFF_W + (8 + (((kap ? 3 : 4) - j - q) & 3)) * WPITCH + ((-2 * kap) & 15) + 1024 - 2 * k1 - 128 * q;
                    }
                    c2 W[4];
                    auto next = [&](int j) {
                        W[j] = {{upv(wn[4 * j]), upv(wn[4 * j + 1])}, {upv(wn[4 * j + 2]), upv(wn[4 * j + 3])}};
                        if (jb < 3) {
#pragma unroll
                            for (int n = 0; n < 4; n++) wn[4 * j + n] = lds_u16(wad[j] + (jb ? 512 - 512 * jb - (n & 1) * 64 : 512 + (n & 1) * 64) + (n & 2) * (2 * WPITCH));
                        }
                    };
                    const int i = 8 * jb;
                    const c2 z0 = {{za[i], za[i + 1]}, {za[i + 4], za[i + 5]}};
                    if (jb) pack(jb - 1, 1);
                    next(0);
                    c2 s0 = cfma2<false>({{zb[i], zb[i + 1]}, {zb[i + 4], zb[i + 5]}}, both(be2), z0), s1 = tw2(z0, s0);
                    YLD(YF2, 2);
                    if (jb) pack(jb - 1, 3);
                    if (jb == 3) load_T(T, t7);
                    next(1);
                    const c2 z1 = cmul2<false>({{za[i + 2], za[i + 3]}, {za[i + 6], za[i + 7]}}, both(be1));
                    YLD(YF2, 3);
                    c2 s2 = cfma2<false>({{zb[i + 2], zb[i + 3]}, {zb[i + 6], zb[i + 7]}}, both(be3), z1), s3 = tw2(z1, s2);
                    YLD(YF2, 1);
                    c2 x0, x1, x2, x3;
                    next(2);
                    bfly2(s0, s2, x0, x2);
                    const c2 y0 = jb < 2 ? cmul2<false>(x0, W[0]) : cmul2<true>(x0, W[0]);
                    YLD(YF2, 2);
                    next(3);
                    bflyi2(s1, s3, x1, x3);
                    const c2 y1 = jb < 2 ? cmul2<false>(x1, W[1]) : cmul2<true>(x1, W[1]);
                    YLD(YF2, 1);
                    s0 = jb < 2 ? cfma2<false>(x2, W[2], y0) : cfma2<true>(x2, W[2], y0);
                    s1 = tw2(y0, s0);
                    YLD(YF2, 3);
                    s2 = jb < 2 ? cfma2<false>(x3, W[3], y1) : cfma2<true>(x3, W[3], y1);
                    s3 = tw2(y1, s2);
                    YLD(YF2, 2);
                    bfly2(s0, s2, z[0], x2);
                    z[2] = cmul2<true>(x2, both(be2));
                    pack(jb, 0);
                    YLD(YF2, 1);
                    bflyi2(s1, s3, x3, x1);
                    pack(jb, 2);
                    z[1] = cmul2<true>(x1, both(be1));
                    YLD(YF2, 3);
                    z[3] = cmul2<true>(x3, both(be3));
                    YLD(YF2, 1);
                }
                pack(3, 1);
                pack(3, 3);
                pinu(af);
                wg_fence();
                mma64_rs<1, 0>(ya, af, dF); mma64_rs<1, 1>(ya, af + 4, dF + 128); mma64_rs<1, 1>(ya, af + 8, dF + 256); mma64_rs<1, 1>(ya, af + 12, dF + 384);
                wg_commit();
                mma64_rs<1, 0>(yb, af + 16, dF); mma64_rs<1, 1>(yb, af + 20, dF + 128); mma64_rs<1, 1>(yb, af + 24, dF + 256); mma64_rs<1, 1>(yb, af + 28, dF + 384);
                wg_commit();
                STAMP3(33);
                if (w == 2) fence_async_sm();
                __syncwarp();
                if (lane == 0) mbar_arrive(bars + B_WFREE);
                if (DEFER == 3 && t7 < gi) mbar_arrive(bars + B_IDLE);
                {
                    const uint32_t a0 = buf + (mi & 1) * 4096 + (16 * w + 8 * (mi >> 1) + gl) * 64;
#pragma unroll
                    for (int u = 0; u < 2; u++)
#pragma unroll
                        for (int c = 0; c < 4; c++) {
                            if (c == 0) {
                                if (u == 0) { wg_wait<1>(); pin(ya); STAMP3(34); }
                                else { wg_wait<0>(); pin(yb); pinu(af); }
                            }
                            const int i = 8 * c;
                            const float(&yy)[32] = u ? yb : ya;
                            const cf x0 = cmulc({yy[i], yy[i + 1]}, T[2 * c]), x1 = cmulc({yy[i + 4], yy[i + 5]}, T[2 * c + 1]);
                            const uint32_t o0 = pk(x0.x, x1.x), o2 = pk(x0.y, x1.y);
                            YLD(YF2, 3);
                            const cf y0 = cmulc({yy[i + 2], yy[i + 3]}, T[2 * c]), y1 = cmulc({yy[i + 6], yy[i + 7]}, T[2 * c + 1]);
                            stsm4(a0 + u * 8192 + ((c ^ (gl >> 1)) << 4), o0, pk(y0.x, y1.x), o2, pk(y0.y, y1.y));
                            YLD(YF2, 2 - (c & 1));
                        }
                }
                STAMP3(38);
                const uint32_t flip = ((g & 1) && !(un >> 24)) ? 0x80008000u : 0u, flipt = flip | (tag & ~tmask);
                const int rw = 8 * w + (gl & 4) + 2 * (mi & 1) + ((gl >> 1) & 1);
                const uint32_t a0 = (extra ? ((gl & 1) == gi ? sb + 32768 : sb + 65536) : buf) + rw * 128 +
                                    (((((gl & 1) << 1) | ((mi >> 1) ^ ((un >> 17) & 1))) ^ (rw & 7)) << 4);
                auto put = [&](const float (&v)[32], uint32_t a) {
#pragma unroll
                    for (int i = 0; i < 32; i += 8)
                        stsm4((a ^ ((i & 8) * 8)) + (i >> 4) * 4096, (pk(v[i], v[i + 1]) & tmask) ^ flipt, (pk(v[i + 2], v[i + 3]) & tmask) ^ flipt,
                              pk(v[i + 4], v[i + 5]) ^ flip, pk(v[i + 6], v[i + 7]) ^ flip);
                };
                auto staged = [&](int b, int n) {
                    fence_async_sm();
                    __syncwarp();
                    if (lane < n) mbar_arrive(bars + b);
                };
                fence_async_sm();
                bar_sync(3, 128);
                float va[32], vb[32];
                wg_fence();
                mma64_ss<1, 0>(va, dF, dB); mma64_ss<1, 0>(vb, dF, dB + 512);
                mma64_ss<1, 1>(va, dF + 128, dB + 64); mma64_ss<1, 1>(vb, dF + 128, dB + 576);
                mma64_ss<1, 1>(va, dF + 256, dB + 128); mma64_ss<1, 1>(vb, dF + 256, dB + 640);
                mma64_ss<1, 1>(va, dF + 384, dB + 192); mma64_ss<1, 1>(vb, dF + 384, dB + 704);
                wg_commit();
                STAMP3(35);
                if (DEFER == 4 && t7 < gi) mbar_arrive(bars + B_IDLE);
                uint32_t bad = 0;
                if (!gi) {
                    mbar_wait(bars + B_UIN + 8, 0);
                    bad = tag_bad(tga + 16384, tag);
                }
                wg_wait<0>();
                pin(va);
                pin(vb);
                STAMP3(36);
                ok = wg_all_ok(bad, 3);
                put(va, a0);
                if (gi) {
                    if (VSPLIT) staged(B_STG, 1);
                    put(vb, a0 + 8192);
                    staged(VSPLIT ? B_STGU : B_STG, 1 + VSPLIT);
                    if (DEFER == 2 && t7 == 0) mbar_arrive(bars + B_IDLE);
                    break;
                }
                constexpr uint64_t dN = mkdesc(OFF_P + 16384, 4096, 512, 2);
                wg_fence();
                mma128_first(acc, dF, dN);
                mma128_ss<0, 0, 1, 1>(acc, dF + 2, dN + 64);
                mma128_ss<0, 0, 1, 1>(acc, dF + 4, dN + 128);
                mma128_ss<0, 0, 1, 1>(acc, dF + 6, dN + 192);
                wg_commit();
                put(vb, a0 + 8192);
                if (!VDEFER) staged(B_STG, 1);
                wg_wait<0>();
                pin(acc);
            }
            if (extra) return;
        }
        uint2 xd[16], dd;
        auto skip = [&]() {
            const int lane = (threadIdx.x + p.zero[2]) & 31;
            const uint2* xp = (const uint2*)(p.xb + (uint32_t)((tc * 128 + 64 * (w & 1) + 32 * hf + 8 * (w >> 1)) * 1024 + cb * 128)) + lane;
            dd = __ldg((const uint2*)(p.dsk + cb * 128) + lane);
#pragma unroll
            for (int j = 0; j < 16; j++) {
                if (PACE_X && j && j % X_GRP == 0) __nanosleep(PACE_X);
                asm volatile("ld.global.nc" XNA ".v2.b32 {%0,%1}, [%2];" : "=r"(xd[j].x), "=r"(xd[j].y) : "l"(xp + ((j >> 3) * 16 + (j & 7)) * 256));
            }
        };
        auto skip2 = [&]() {
#pragma unroll
            for (int j = 0; j < 16; j++) {
                if (j % 4 == 0) YIELD();
                asm volatile("fma.rn.bf16x2 %0, %0, %1, %2;" : "+r"(xd[j].x) : "r"(dd.x), "r"(0x80008000u));
                asm volatile("fma.rn.bf16x2 %0, %0, %1, %2;" : "+r"(xd[j].y) : "r"(dd.y), "r"(0x80008000u));
            }
            YIELD();
        };
        {
            INDICES(5)
            uint32_t sp[8];
#pragma unroll
            for (int j = 0; j < 2; j++) { const uint4 v = ldtab(TAB_SP + j * 512 + t7 * 4); sp[4 * j] = v.x; sp[4 * j + 1] = v.y; sp[4 * j + 2] = v.z; sp[4 * j + 3] = v.w; }
            cf tw[8];
            load_tw(tw, k1);
            tw[4].x *= 2.f; tw[4].y *= 2.f;
            const uint32_t tag = get_epoch(bars) & 1;
            const uint32_t in = sb + OFF_P + hf * 8192;
            constexpr uint64_t dF = mkdesc(OFF_F, 16, 1024, 1);
            const uint64_t dB = mkdesc(OFF_P, 2048, 256, 3) + hf * 512;
            float ae[32], ao[32];
            if (XAT < 0) skip();
            c2 ev[2][4];
            auto blk = [&](const float (&a)[32], int i) { return c2{{a[i], a[i + 1]}, {a[i + 2], a[i + 3]}}; };
            auto unfold = [&](c2 a, c2 u, int n, c2& zn, c2& zm, int yl) {
                const float wc = n == 1 ? 0.92387953251128674f : (n == 2 ? 0.70710678118654752f : 0.38268343236508977f);
                const float ws = n == 3 ? 0.92387953251128674f : (n == 2 ? 0.70710678118654752f : 0.38268343236508977f);
                const v2 c = {wc, wc}, s = {ws, ws}, two = {2.f, 2.f};
                const c2 y = cmul2<false>(a, both(tw[n])), t = both(tw[8 - n]);
                c2 E;
                E.x = fnm2(u.y, t.y, y.x); E.y = fnm2(u.x, t.y, y.y); E.x = fma2(u.x, t.x, E.x); E.y = fnm2(u.y, t.x, E.y);
                YLD(yl, 2);
                const c2 D = tw2(y, E);
                zn.x = fnm2(D.y, c, E.x); zn.y = fma2(D.y, s, E.y); zn.x = fma2(D.x, s, zn.x); zn.y = fma2(D.x, c, zn.y);
                zm.x = tw2(E.x, zn.x); zm.y = fnm2(E.y, two, zn.y);
                YLD(yl, 1);
            };
#pragma unroll
            for (int rgn = 0; rgn < 2; rgn++) {
#pragma unroll 1
                for (int n = 0; n < 4096; n++) {
                    mbar_wait(bars + B_VIN + rgn * 16 + hf * 8, n & 1);
                    if (rgn) STAMP(25);
                    if (rgn == 0) {
                        pinu(sp);
                        wg_fence();
                        mma48_ss<0>(ae, dF, dB + 128); mma16_rs<0>(ae, sp[0], 0u, sp[1], 0u, dB);
                        mma48_ss<1>(ae, dF + 2, dB + 160); mma16_rs<1>(ae, sp[2], 0u, sp[3], 0u, dB + 32);
                        mma48_ss<1>(ae, dF + 4, dB + 192); mma16_rs<1>(ae, 0u, sp[4], 0u, sp[5], dB + 64);
                        mma48_ss<1>(ae, dF + 6, dB + 224); mma16_rs<1>(ae, 0u, sp[6], 0u, sp[7], dB + 96);
                    } else {
                        wg_fence();
                        mma64_ss<0, 0>(ao, dF, dB + 1024);
                        mma64_ss<0, 1>(ao, dF + 2, dB + 1056);
                        mma64_ss<0, 1>(ao, dF + 4, dB + 1088);
                        mma64_ss<0, 1>(ao, dF + 6, dB + 1120);
                    }
                    wg_commit();
                    const bool ok = wg_all_ok(tag_bad(in + rgn * 16384 + t7 * 64 + (t7 & 6) * 8, tag), hf ? 3 : 8);
                    wg_wait<0>();
                    if (rgn) pin(ao);
                    else { pin(ae); pinu(sp); }
                    if (ok) break;
                    wg_all_ok(0, hf ? 3 : 8);
                    if (w == 0 && elect_one()) {
                        mbar_expect_tx(bars + B_VIN + rgn * 16 + hf * 8, 8192);
                        tma2d(in + rgn * 16384, &tmVld, hf * 32, vrow + rgn * 128, bars + B_VIN + rgn * 16 + hf * 8);
                    }
                }
                if (rgn == 0) {
#pragma unroll
                    for (int cl = 0; cl < 2; cl++) {
                        const c2 b = blk(ae, 4 * cl), z0 = {add2(b.x, b.y), sub2(b.x, b.y)};
                        const c2 a0 = cfma2<false>(blk(ae, 16 + 4 * cl), both(tw[4]), z0), a1 = tw2(z0, a0);
                        YIELD();
                        c2 z2, z6, a2, a3;
                        unfold(blk(ae, 8 + 4 * cl), blk(ae, 24 + 4 * cl), 2, z2, z6, 2);
                        bfly2(z2, z6, a2, a3);
                        bfly2(a0, a2, ev[cl][0], ev[cl][2]);
                        YIELD();
                        bflyi2(a1, a3, ev[cl][1], ev[cl][3]);
                    }
                    YIELD();
                    if (XAT == 0) skip();
                    if (XAT <= 0) skip2();
                }
            }
            if (XAT == 1) skip();
            const uint32_t a0 = in + (8 * w + gl + 32 * (mi & 1)) * 32 + (mi >> 1) * 16384 + (gl & 4) * 4;
#pragma unroll
            for (int cl = 0; cl < 2; cl++) {
                c2 z1, z3, z5, z7, a4, a5, a6, a7;
                unfold(blk(ao, 4 * cl), blk(ao, 24 + 4 * cl), 1, z1, z7, YF3);
                if (cl == 0) wg_all_ok(0, hf ? 3 : 8);
                unfold(blk(ao, 8 + 4 * cl), blk(ao, 16 + 4 * cl), 3, z3, z5, YF3);
                bfly2(z1, z5, a4, a5);
                bfly2(z3, z7, a6, a7);
                YLD(YF3, 2);
                dft8_end<YF3>(ev[cl], a4, a5, a6, a7, [&](int r, c2 u, c2 v) { stsm4((a0 ^ (cl * 16)) + r * 2048, pkv(u.x), pkv(u.y), pkv(v.x), pkv(v.y)); });
            }
            if (XAT == 2) skip();
            bar_sync(7, 256);
            STAMP(26);
        }
        INDICES(6)
        const int t0 = tc * 128 + 64 * (w & 1) + 32 * hf + 8 * (w >> 1);
        {
            const int n0 = 16 * hf + 4 * w + mi;
            uint32_t la = sb + OFF_P + (gl >> 2) * 8192 + n0 * 32 + ((((gl >> 1) & 1) ^ (w & 1)) << 4) + (gl & 1) * 8;
            const float* op = p.out + (uint32_t)((4 * n0 + fb) * 2048 + fcb * 32 + gl * 4);
#pragma unroll 1
            for (int it = 0; it < 4; it++) {
                uint32_t u[8], ns;
                asm volatile("{.reg .pred p; mbarrier.test_wait.parity.shared::cta.b64 p, [%1], 0; selp.u32 %0, 0, %2, p;}" : "=r"(ns) : "r"(bars + B_LDONE), "n"(PACE_O) : "memory");
#pragma unroll
                for (int i = 0; i < 4; i++) asm volatile("ld.shared.v2.b32 {%0,%1}, [%2];" : "=r"(u[2 * i]), "=r"(u[2 * i + 1]) : "r"(la + i * 1024) : "memory");
#pragma unroll
                for (int i = 0; i < 4; i++) {
                    stg128(op + i * 128 * 2048, u[2 * i] << 16, u[2 * i] & 0xffff0000u, u[2 * i + 1] << 16, u[2 * i + 1] & 0xffff0000u);
                    if (ns) __nanosleep(PACE_O);
                }
                la += it == 1 ? 12288 : 4096;
                op += 4 * 128 * 2048;
            }
            STAMP(27);
        }
        if (XAT > 0) skip2();
        const uint32_t ra = sb + hf * 16384 + w * 4096;
        float* ob = p.out + (size_t)t0 * 2048 + 1024 + cb * 128 + lane * 4;
#pragma unroll
        for (int mb = 0; mb < 2; mb++) {
            if (hf == 0) { if (mb == 0) bar_sync(9, 256); else bar_sync(11, 256); }
            else { if (mb == 0) bar_sync(10, 256); else bar_sync(12, 256); }
            if (mb == 0) STAMP(17);
            float v[8][4];
#pragma unroll
            for (int j = 0; j < 8; j++) lds128f(ra + (mb ? 0 : (NST - 1) * 32768) + j * 512 + ((lane * 16) ^ ((j & 3) * 32)), v[j][0], v[j][1], v[j][2], v[j][3]);
#pragma unroll
            for (int j = 0; j < 8; j++) {
                const uint2 s = xd[8 * mb + j];
                stg128(ob + (16 * mb + j) * 2048, __float_as_uint(v[j][0] + up(s.x)), __float_as_uint(v[j][1] + __uint_as_float(s.x & 0xffff0000u)),
                       __float_as_uint(v[j][2] + up(s.y)), __float_as_uint(v[j][3] + __uint_as_float(s.y & 0xffff0000u)));
            }
        }
        STAMP(9);
        if (threadIdx.x == 480) RECL(2);
    }
}

typedef CUresult (*EncodeFn)(CUtensorMap*, CUtensorMapDataType, cuuint32_t, void*, const cuuint64_t*, const cuuint64_t*, const cuuint32_t*,
                             const cuuint32_t*, CUtensorMapInterleave, CUtensorMapSwizzle, CUtensorMapL2promotion, CUtensorMapFloatOOBfill);

static CUtensorMap make_map(EncodeFn enc, const void* ptr, int rank, const cuuint64_t* dims, const cuuint64_t* strides, const cuuint32_t* box,
                            CUtensorMapSwizzle swz, CUtensorMapL2promotion promo, CUtensorMapDataType dt = CU_TENSOR_MAP_DATA_TYPE_BFLOAT16) {
    CUtensorMap m;
    const cuuint32_t es[5] = {1, 1, 1, 1, 1};
    enc(&m, dt, rank, const_cast<void*>(ptr), dims, strides, box, es, CU_TENSOR_MAP_INTERLEAVE_NONE, swz, promo,
        CU_TENSOR_MAP_FLOAT_OOB_FILL_NONE);
    return m;
}

extern "C" void kernel_launch(void* const* d_in, const int* in_sizes, int n_in, void* d_out, int out_size) {
    void* fn = nullptr;
    cudaDriverEntryPointQueryResult qr;
    cudaGetDriverEntryPoint("cuTensorMapEncodeTiled", &fn, cudaEnableDefault, &qr);
    EncodeFn enc = (EncodeFn)fn;
    void *pU, *pV;
    cudaGetSymbolAddress(&pU, g_U);
    cudaGetSymbolAddress(&pV, g_V);
    const CUtensorMapL2promotion P256 = CU_TENSOR_MAP_L2_PROMOTION_L2_256B, P0 = CU_TENSOR_MAP_L2_PROMOTION_NONE;

    const cuuint64_t dX[5] = {1024, 2, 4, 16, 16}, sX[4] = {2048, 32 * 2048, 2 * 2048, 128 * 2048};
    const cuuint32_t bX[5] = {64, 2, 4, 16, 1};
    CUtensorMap tmX = make_map(enc, d_in[3], 5, dX, sX, bX, CU_TENSOR_MAP_SWIZZLE_128B, (CUtensorMapL2promotion)PRX);
    const cuuint64_t dB[4] = {1024, 8, 2, 96}, sB[3] = {2048, 256 * 2048, 8 * 2048}, dC[4] = {1024, 8, 2, 64}, sC[3] = {2048, 8 * 2048, 16 * 2048};
    const cuuint32_t bB[4] = {64, 8, 2, 4};
    CUtensorMap tmBre = make_map(enc, d_in[6], 4, dB, sB, bB, CU_TENSOR_MAP_SWIZZLE_128B, (CUtensorMapL2promotion)PRB);
    CUtensorMap tmBim = make_map(enc, d_in[7], 4, dB, sB, bB, CU_TENSOR_MAP_SWIZZLE_128B, (CUtensorMapL2promotion)PRB);
    CUtensorMap tmCre = make_map(enc, d_in[8], 4, dC, sC, bB, CU_TENSOR_MAP_SWIZZLE_128B, P256);
    CUtensorMap tmCim = make_map(enc, d_in[9], 4, dC, sC, bB, CU_TENSOR_MAP_SWIZZLE_128B, P256);

    const cuuint64_t dU[2] = {8192, 256}, sU[1] = {16384};
    const cuuint32_t bS[2] = {64, UBOX};
    CUtensorMap tmUst = make_map(enc, pU, 2, dU, sU, bS, CU_TENSOR_MAP_SWIZZLE_128B, P0);
    const cuuint64_t dV[2] = {16384, 128}, sV[1] = {32768}, dL[2] = {64, 32768}, sL[1] = {128};
    const cuuint32_t bL[2] = {32, 128};
    CUtensorMap tmVst = make_map(enc, pV, 2, dV, sV, bS, CU_TENSOR_MAP_SWIZZLE_128B, P0);
    CUtensorMap tmVld = make_map(enc, pV, 2, dL, sL, bL, CU_TENSOR_MAP_SWIZZLE_NONE, P0);
    const cuuint64_t dA[4] = {1024, 64, 8, 4}, sA[3] = {32 * 2048, 4 * 2048, 2048};
    const cuuint32_t bA[4] = {16, 64, 1, 1};
    CUtensorMap tmXA = make_map(enc, d_in[0], 4, dA, sA, bA, CU_TENSOR_MAP_SWIZZLE_32B, CU_TENSOR_MAP_L2_PROMOTION_L2_128B);
    const cuuint64_t dF[2] = {512 * 1026 / 8, 4}, sF[1] = {512 * 1026};
    const cuuint32_t bF[2] = {WPITCH / 8, 4};
    CUtensorMap tmWr = make_map(enc, d_in[1], 2, dF, sF, bF, CU_TENSOR_MAP_SWIZZLE_NONE, P0, CU_TENSOR_MAP_DATA_TYPE_UINT64);
    CUtensorMap tmWi = make_map(enc, d_in[2], 2, dF, sF, bF, CU_TENSOR_MAP_SWIZZLE_NONE, P0, CU_TENSOR_MAP_DATA_TYPE_UINT64);

    Params p = {};
    p.xb = (const __nv_bfloat16*)d_in[3];
    p.lre = (const __nv_bfloat16*)d_in[4];
    p.lim = (const __nv_bfloat16*)d_in[5];
    p.ldt = (const __nv_bfloat16*)d_in[10];
    p.dsk = (const __nv_bfloat16*)d_in[11];
    p.out = (float*)d_out;
    p.da[0] = p.da[1] = mkdesc(0, 16, 1024, 1) - 1;
    p.da[2] = p.da[3] = mkdesc(0, 512, 2048, 2) - 1;
    for (int i = 0; i < 258; i++) {
        int cj;
        const int kap = kappa_of(i >> 1, i & 1), s3 = slot3_of(kap, cj);
        p.unit[i] = kap | s3 << 16 | cj << 24;
    }
    cudaFuncSetAttribute(fused_kernel, cudaFuncAttributeMaxDynamicSharedMemorySize, SMEM_BYTES);
    fused_kernel<<<130, 512, SMEM_BYTES>>>(Maps{{tmX, tmBre, tmBim, tmCre, tmCim, tmXA, tmUst, tmVst, tmWr, tmWi, tmVld}}, p);
}
```

```cpp
#include <cuda_runtime.h>
#include <cuda.h>
#include <cuda_bf16.h>
#include <stdint.h>

#define NST 5
#define SB0 1024
#define WPITCH 1056
#define OFF_P (NST * 32768)
#define OFF_F (OFF_P + 32768)
#define OFF_W (OFF_F + 8192)
#define OFF_TL (OFF_W + 16 * WPITCH)
#define OFF_TM (OFF_TL + 4096)
#define OFF_T1 (OFF_TM + 4096)
#define OFF_BAR (OFF_T1 + 2048)
#define OFF_STAMP (OFF_BAR + 384)
#define SMEM_BYTES (OFF_BAR + 512)
#define B_FULL 0
#define B_EMPTY 40
#define B_STGU 80
#define B_HGO 88
#define B_LAM 120
#define B_STG 128
#define B_WFREE 136
#define B_EP 144
#define B_LDONE 152
#define B_UIN 160
#define B_WIN 176
#define B_XIN 184
#define B_VIN 200
#define B_HRTY 232
#define B_HLD 240
#define B_END 280
#define B_EPOCH 280

#define PACE_U 250
#define PACE_V 120
#define PACE_O 250
#define PACE_H 120
#define HAND 1
#define POLL_AT 24
#define XA_FIRST 3
#define XA_AT 0
#define YS 3
#define UDELAY 250
#define PACE_W 120
#define HINT_U 2
#define HINT_V 2
#define GRP 0x92
#define EARLY_U 48
#define EARLY_V 16
#define EARLY_H 4
#define KMC 4
#define TRYP 10
#define XT 1
#define UBOX 32
#define SKEW 4
#define SPIN_LIMIT 32768

#define YIELD() asm volatile("pmevent 0;")
#define YF1 2
#define YF2 2
#define YF3 2
#define YLD(level, n) do { if ((level) >= (n)) YIELD(); } while (0)

__device__ __align__(1024) uint8_t g_U[4 << 20];
__device__ __align__(1024) uint8_t g_V[4 << 20];
__device__ __align__(1024) uint8_t g_H[8 << 20];
__device__ __align__(1024) uint4 g_carry[16 * 512];
__device__ __align__(1024) unsigned g_hcnt[16 * 64];
__device__ __align__(128) unsigned g_cnt[128];
__device__ __align__(128) unsigned g_epoch[129 * 8];

#define RECL(i) do { } while (0)
#define STAMP(i) do { } while (0)
#define STAMPR(i) do { } while (0)
#define STAMPW(a, b) do { } while (0)
#define STAMPX(a, b) do { } while (0)
#define STAMP5(i) do { } while (0)
#define STAMP3(i) do { } while (0)

#define TAB_FG 0
#define TAB_F1 2048
#define TAB_T 4096
#define TAB_SP 6144
#define TAB_TW 7168
#define TAB_FX 7680
__device__ __align__(1024) const uint32_t g_tab[7808] = {
0x80003d80,0x80003d80,0x80003d80,0x80003d80,0x80003d80,0x80003d80,0x80003d80,0x80003d80,0x80003d80,0x80003d80,0x80003d80,0x80003d80,0x80003d80,0x80003d80,0x80003d80,0x80003d80,
0x80003d80,0x80003d80,0x80003d80,0x80003d80,0x80003d80,0x80003d80,0x80003d80,0x80003d80,0x80003d80,0x80003d80,0x80003d80,0x80003d80,0x80003d80,0x80003d80,0x80003d80,0x80003d80,
0x3c483d7b,0x3d0e3d55,0x3d553d0e,0x3d7b3c48,0x80003d80,0x3cc43d6d,0x3d353d35,0x3d6d3cc4,0x3d7bbc48,0x3d55bd0e,0x3d0ebd55,0x3c48bd7b,0x3d800000,0x3d6dbcc4,0x3d35bd35,0x3cc4bd6d,
0xbc48bd7b,0xbd0ebd55,0xbd55bd0e,0xbd7bbc48,0x8000bd80,0xbcc4bd6d,0xbd35bd35,0xbd6dbcc4,0xbd7b3c48,0xbd553d0e,0xbd0e3d55,0xbc483d7b,0xbd800000,0xbd6d3cc4,0xbd353d35,0xbcc43d6d,
0x8000bd80,0xbd35bd35,0xbd800000,0xbd353d35,0xbcc4bd6d,0xbd6dbcc4,0xbd6d3cc4,0xbcc43d6d,0x80003d80,0x3d353d35,0x3d800000,0x3d35bd35,0x3cc43d6d,0x3d6d3cc4,0x3d6dbcc4,0x3cc4bd6d,
0x8000bd80,0xbd35bd35,0xbd800000,0xbd353d35,0xbcc4bd6d,0xbd6dbcc4,0xbd6d3cc4,0xbcc43d6d,0x80003d80,0x3d353d35,0x3d800000,0x3d35bd35,0x3cc43d6d,0x3d6d3cc4,0x3d6dbcc4,0x3cc4bd6d,
0xbd553d0e,0x3c483d7b,0x3d7b3c48,0x3d0ebd55,0xbd800000,0xbcc43d6d,0x3d353d35,0x3d6dbcc4,0x3d0e3d55,0x3d7bbc48,0x3c48bd7b,0xbd55bd0e,0x80003d80,0x3d6d3cc4,0x3d35bd35,0xbcc4bd6d,
0x3d55bd0e,0xbc48bd7b,0xbd7bbc48,0xbd0e3d55,0x3d800000,0x3cc4bd6d,0xbd35bd35,0xbd6d3cc4,0xbd0ebd55,0xbd7b3c48,0xbc483d7b,0x3d553d0e,0x8000bd80,0xbd6dbcc4,0xbd353d35,0x3cc43d6d,
0x80003d80,0x3d800000,0x8000bd80,0xbd800000,0x3d353d35,0x3d35bd35,0xbd35bd35,0xbd353d35,0x80003d80,0x3d800000,0x8000bd80,0xbd800000,0x3d353d35,0x3d35bd35,0xbd35bd35,0xbd353d35,
0x80003d80,0x3d800000,0x8000bd80,0xbd800000,0x3d353d35,0x3d35bd35,0xbd35bd35,0xbd353d35,0x80003d80,0x3d800000,0x8000bd80,0xbd800000,0x3d353d35,0x3d35bd35,0xbd35bd35,0xbd353d35,
0xbd55bd0e,0xbc483d7b,0x3d7bbc48,0xbd0ebd55,0x8000bd80,0xbd6d3cc4,0x3d353d35,0x3cc4bd6d,0xbd0e3d55,0x3d7b3c48,0xbc48bd7b,0xbd553d0e,0xbd800000,0x3cc43d6d,0x3d35bd35,0xbd6dbcc4,
0x3d553d0e,0x3c48bd7b,0xbd7b3c48,0x3d0e3d55,0x80003d80,0x3d6dbcc4,0xbd35bd35,0xbcc43d6d,0x3d0ebd55,0xbd7bbc48,0x3c483d7b,0x3d55bd0e,0x3d800000,0xbcc4bd6d,0xbd353d35,0x3d6d3cc4,
0x8000bd80,0xbd353d35,0x3d800000,0xbd35bd35,0xbd6dbcc4,0x3cc43d6d,0x3cc4bd6d,0xbd6d3cc4,0x80003d80,0x3d35bd35,0xbd800000,0x3d353d35,0x3d6d3cc4,0xbcc4bd6d,0xbcc43d6d,0x3d6dbcc4,
0x8000bd80,0xbd353d35,0x3d800000,0xbd35bd35,0xbd6dbcc4,0x3cc43d6d,0x3cc4bd6d,0xbd6d3cc4,0x80003d80,0x3d35bd35,0xbd800000,0x3d353d35,0x3d6d3cc4,0xbcc4bd6d,0xbcc43d6d,0x3d6dbcc4,
0x3c48bd7b,0xbd0e3d55,0x3d55bd0e,0xbd7b3c48,0x3d800000,0xbd6dbcc4,0x3d353d35,0xbcc4bd6d,0xbd7bbc48,0x3d553d0e,0xbd0ebd55,0x3c483d7b,0x8000bd80,0xbcc43d6d,0x3d35bd35,0xbd6d3cc4,
0xbc483d7b,0x3d0ebd55,0xbd553d0e,0x3d7bbc48,0xbd800000,0x3d6d3cc4,0xbd35bd35,0x3cc43d6d,0x3d7b3c48,0xbd55bd0e,0x3d0e3d55,0xbc48bd7b,0x80003d80,0x3cc4bd6d,0xbd353d35,0x3d6dbcc4,
0x3d800000,0x3d800000,0x3d800000,0x3d800000,0x3d800000,0x3d800000,0x3d800000,0x3d800000,0x3d800000,0x3d800000,0x3d800000,0x3d800000,0x3d800000,0x3d800000,0x3d800000,0x3d800000,
0x3d800000,0x3d800000,0x3d800000,0x3d800000,0x3d800000,0x3d800000,0x3d800000,0x3d800000,0x3d800000,0x3d800000,0x3d800000,0x3d800000,0x3d800000,0x3d800000,0x3d800000,0x3d800000,
0x3d7bbc48,0x3d55bd0e,0x3d0ebd55,0x3c48bd7b,0x3d800000,0x3d6dbcc4,0x3d35bd35,0x3cc4bd6d,0xbc48bd7b,0xbd0ebd55,0xbd55bd0e,0xbd7bbc48,0xbd80,0xbcc4bd6d,0xbd35bd35,0xbd6dbcc4,
0xbd7b3c48,0xbd553d0e,0xbd0e3d55,0xbc483d7b,0xbd800000,0xbd6d3cc4,0xbd353d35,0xbcc43d6d,0x3c483d7b,0x3d0e3d55,0x3d553d0e,0x3d7b3c48,0x3d80,0x3cc43d6d,0x3d353d35,0x3d6d3cc4,
0xbd800000,0xbd353d35,0x3d80,0x3d353d35,0xbd6d3cc4,0xbcc43d6d,0x3cc43d6d,0x3d6d3cc4,0x3d800000,0x3d35bd35,0xbd80,0xbd35bd35,0x3d6dbcc4,0x3cc4bd6d,0xbcc4bd6d,0xbd6dbcc4,
0xbd800000,0xbd353d35,0x3d80,0x3d353d35,0xbd6d3cc4,0xbcc43d6d,0x3cc43d6d,0x3d6d3cc4,0x3d800000,0x3d35bd35,0xbd80,0xbd35bd35,0x3d6dbcc4,0x3cc4bd6d,0xbcc4bd6d,0xbd6dbcc4,
0x3d0e3d55,0x3d7bbc48,0x3c48bd7b,0xbd55bd0e,0x3d80,0x3d6d3cc4,0x3d35bd35,0xbcc4bd6d,0x3d55bd0e,0xbc48bd7b,0xbd7bbc48,0xbd0e3d55,0x3d800000,0x3cc4bd6d,0xbd35bd35,0xbd6d3cc4,
0xbd0ebd55,0xbd7b3c48,0xbc483d7b,0x3d553d0e,0xbd80,0xbd6dbcc4,0xbd353d35,0x3cc43d6d,0xbd553d0e,0x3c483d7b,0x3d7b3c48,0x3d0ebd55,0xbd800000,0xbcc43d6d,0x3d353d35,0x3d6dbcc4,
0x3d800000,0xbd80,0xbd800000,0x3d80,0x3d35bd35,0xbd35bd35,0xbd353d35,0x3d353d35,0x3d800000,0xbd80,0xbd800000,0x3d80,0x3d35bd35,0xbd35bd35,0xbd353d35,0x3d353d35,
0x3d800000,0xbd80,0xbd800000,0x3d80,0x3d35bd35,0xbd35bd35,0xbd353d35,0x3d353d35,0x3d800000,0xbd80,0xbd800000,0x3d80,0x3d35bd35,0xbd35bd35,0xbd353d35,0x3d353d35,
0xbd0e3d55,0x3d7b3c48,0xbc48bd7b,0xbd553d0e,0xbd800000,0x3cc43d6d,0x3d35bd35,0xbd6dbcc4,0x3d553d0e,0x3c48bd7b,0xbd7b3c48,0x3d0e3d55,0x3d80,0x3d6dbcc4,0xbd35bd35,0xbcc43d6d,
0x3d0ebd55,0xbd7bbc48,0x3c483d7b,0x3d55bd0e,0x3d800000,0xbcc4bd6d,0xbd353d35,0x3d6d3cc4,0xbd55bd0e,0xbc483d7b,0x3d7bbc48,0xbd0ebd55,0xbd80,0xbd6d3cc4,0x3d353d35,0x3cc4bd6d,
0xbd800000,0x3d353d35,0xbd80,0xbd353d35,0xbcc43d6d,0x3d6dbcc4,0xbd6dbcc4,0x3cc43d6d,0x3d800000,0xbd35bd35,0x3d80,0x3d35bd35,0x3cc4bd6d,0xbd6d3cc4,0x3d6d3cc4,0xbcc4bd6d,
0xbd800000,0x3d353d35,0xbd80,0xbd353d35,0xbcc43d6d,0x3d6dbcc4,0xbd6dbcc4,0x3cc43d6d,0x3d800000,0xbd35bd35,0x3d80,0x3d35bd35,0x3cc4bd6d,0xbd6d3cc4,0x3d6d3cc4,0xbcc4bd6d,
0xbd7bbc48,0x3d553d0e,0xbd0ebd55,0x3c483d7b,0xbd80,0xbcc43d6d,0x3d35bd35,0xbd6d3cc4,0xbc483d7b,0x3d0ebd55,0xbd553d0e,0x3d7bbc48,0xbd800000,0x3d6d3cc4,0xbd35bd35,0x3cc43d6d,
0x3d7b3c48,0xbd55bd0e,0x3d0e3d55,0xbc48bd7b,0x3d80,0x3cc4bd6d,0xbd353d35,0x3d6dbcc4,0x3c48bd7b,0xbd0e3d55,0x3d55bd0e,0xbd7b3c48,0x3d800000,0xbd6dbcc4,0x3d353d35,0xbcc4bd6d,
0x80003d80,0x8000bd80,0x80003d80,0x8000bd80,0x3d800000,0xbd800000,0x3d800000,0xbd800000,0x80003d80,0x8000bd80,0x80003d80,0x8000bd80,0x3d800000,0xbd800000,0x3d800000,0xbd800000,
0x80003d80,0x8000bd80,0x80003d80,0x8000bd80,0x3d800000,0xbd800000,0x3d800000,0xbd800000,0x80003d80,0x8000bd80,0x80003d80,0x8000bd80,0x3d800000,0xbd800000,0x3d800000,0xbd800000,
0x3d7bbc48,0xbd553d0e,0x3d0ebd55,0xbc483d7b,0x80003d80,0xbcc4bd6d,0x3d353d35,0xbd6dbcc4,0xbc48bd7b,0x3d0e3d55,0xbd55bd0e,0x3d7b3c48,0x3d800000,0xbd6d3cc4,0x3d35bd35,0xbcc43d6d,
0xbd7b3c48,0x3d55bd0e,0xbd0e3d55,0x3c48bd7b,0x8000bd80,0x3cc43d6d,0xbd35bd35,0x3d6d3cc4,0x3c483d7b,0xbd0ebd55,0x3d553d0e,0xbd7bbc48,0xbd800000,0x3d6dbcc4,0xbd353d35,0x3cc4bd6d,
0x8000bd80,0x3d353d35,0xbd800000,0x3d35bd35,0xbd6d3cc4,0x3cc4bd6d,0x3cc43d6d,0xbd6dbcc4,0x80003d80,0xbd35bd35,0x3d800000,0xbd353d35,0x3d6dbcc4,0xbcc43d6d,0xbcc4bd6d,0x3d6d3cc4,
0x8000bd80,0x3d353d35,0xbd800000,0x3d35bd35,0xbd6d3cc4,0x3cc4bd6d,0x3cc43d6d,0xbd6dbcc4,0x80003d80,0xbd35bd35,0x3d800000,0xbd353d35,0x3d6dbcc4,0xbcc43d6d,0xbcc4bd6d,0x3d6d3cc4,
0x3d0e3d55,0xbd7b3c48,0x3c48bd7b,0x3d553d0e,0xbd800000,0x3cc4bd6d,0x3d353d35,0xbd6d3cc4,0x3d55bd0e,0x3c483d7b,0xbd7bbc48,0x3d0ebd55,0x80003d80,0xbd6dbcc4,0x3d35bd35,0x3cc43d6d,
0xbd0ebd55,0x3d7bbc48,0xbc483d7b,0xbd55bd0e,0x3d800000,0xbcc43d6d,0xbd35bd35,0x3d6dbcc4,0xbd553d0e,0xbc48bd7b,0x3d7b3c48,0xbd0e3d55,0x8000bd80,0x3d6d3cc4,0xbd353d35,0xbcc4bd6d,
0x80003d80,0xbd800000,0x8000bd80,0x3d800000,0x3d35bd35,0x3d353d35,0xbd353d35,0xbd35bd35,0x80003d80,0xbd800000,0x8000bd80,0x3d800000,0x3d35bd35,0x3d353d35,0xbd353d35,0xbd35bd35,
0x80003d80,0xbd800000,0x8000bd80,0x3d800000,0x3d35bd35,0x3d353d35,0xbd353d35,0xbd35bd35,0x80003d80,0xbd800000,0x8000bd80,0x3d800000,0x3d35bd35,0x3d353d35,0xbd353d35,0xbd35bd35,
0xbd0e3d55,0xbd7bbc48,0xbc48bd7b,0x3d55bd0e,0x8000bd80,0x3d6dbcc4,0x3d353d35,0xbcc43d6d,0x3d553d0e,0xbc483d7b,0xbd7b3c48,0xbd0ebd55,0xbd800000,0xbcc4bd6d,0x3d35bd35,0x3d6d3cc4,
0x3d0ebd55,0x3d7b3c48,0x3c483d7b,0xbd553d0e,0x80003d80,0xbd6d3cc4,0xbd35bd35,0x3cc4bd6d,0xbd55bd0e,0x3c48bd7b,0x3d7bbc48,0x3d0e3d55,0x3d800000,0x3cc43d6d,0xbd353d35,0xbd6dbcc4,
0x8000bd80,0x3d35bd35,0x3d800000,0x3d353d35,0xbcc43d6d,0xbd6d3cc4,0xbd6dbcc4,0xbcc4bd6d,0x80003d80,0xbd353d35,0xbd800000,0xbd35bd35,0x3cc4bd6d,0x3d6dbcc4,0x3d6d3cc4,0x3cc43d6d,
0x8000bd80,0x3d35bd35,0x3d800000,0x3d353d35,0xbcc43d6d,0xbd6d3cc4,0xbd6dbcc4,0xbcc4bd6d,0x80003d80,0xbd353d35,0xbd800000,0xbd35bd35,0x3cc4bd6d,0x3d6dbcc4,0x3d6d3cc4,0x3cc43d6d,
0xbd7bbc48,0xbd55bd0e,0xbd0ebd55,0xbc48bd7b,0x3d800000,0x3d6d3cc4,0x3d353d35,0x3cc43d6d,0xbc483d7b,0xbd0e3d55,0xbd553d0e,0xbd7b3c48,0x8000bd80,0x3cc4bd6d,0x3d35bd35,0x3d6dbcc4,
0x3d7b3c48,0x3d553d0e,0x3d0e3d55,0x3c483d7b,0xbd800000,0xbd6dbcc4,0xbd35bd35,0xbcc4bd6d,0x3c48bd7b,0x3d0ebd55,0x3d55bd0e,0x3d7bbc48,0x80003d80,0xbcc43d6d,0xbd353d35,0xbd6d3cc4,
0x3d800000,0xbd800000,0x3d800000,0xbd800000,0xbd80,0x3d80,0xbd80,0x3d80,0x3d800000,0xbd800000,0x3d800000,0xbd800000,0xbd80,0x3d80,0xbd80,0x3d80,
0x3d800000,0xbd800000,0x3d800000,0xbd800000,0xbd80,0x3d80,0xbd80,0x3d80,0x3d800000,0xbd800000,0x3d800000,0xbd800000,0xbd80,0x3d80,0xbd80,0x3d80,
0xbc48bd7b,0x3d0e3d55,0xbd55bd0e,0x3d7b3c48,0x3d800000,0xbd6d3cc4,0x3d35bd35,0xbcc43d6d,0xbd7b3c48,0x3d55bd0e,0xbd0e3d55,0x3c48bd7b,0xbd80,0x3cc43d6d,0xbd35bd35,0x3d6d3cc4,
0x3c483d7b,0xbd0ebd55,0x3d553d0e,0xbd7bbc48,0xbd800000,0x3d6dbcc4,0xbd353d35,0x3cc4bd6d,0x3d7bbc48,0xbd553d0e,0x3d0ebd55,0xbc483d7b,0x3d80,0xbcc4bd6d,0x3d353d35,0xbd6dbcc4,
0xbd800000,0x3d35bd35,0x3d80,0xbd35bd35,0x3cc43d6d,0xbd6dbcc4,0x3d6dbcc4,0xbcc43d6d,0x3d800000,0xbd353d35,0xbd80,0x3d353d35,0xbcc4bd6d,0x3d6d3cc4,0xbd6d3cc4,0x3cc4bd6d,
0xbd800000,0x3d35bd35,0x3d80,0xbd35bd35,0x3cc43d6d,0xbd6dbcc4,0x3d6dbcc4,0xbcc43d6d,0x3d800000,0xbd353d35,0xbd80,0x3d353d35,0xbcc4bd6d,0x3d6d3cc4,0xbd6d3cc4,0x3cc4bd6d,
0x3d55bd0e,0x3c483d7b,0xbd7bbc48,0x3d0ebd55,0x3d80,0xbd6dbcc4,0x3d35bd35,0x3cc43d6d,0xbd0ebd55,0x3d7bbc48,0xbc483d7b,0xbd55bd0e,0x3d800000,0xbcc43d6d,0xbd35bd35,0x3d6dbcc4,
0xbd553d0e,0xbc48bd7b,0x3d7b3c48,0xbd0e3d55,0xbd80,0x3d6d3cc4,0xbd353d35,0xbcc4bd6d,0x3d0e3d55,0xbd7b3c48,0x3c48bd7b,0x3d553d0e,0xbd800000,0x3cc4bd6d,0x3d353d35,0xbd6d3cc4,
0x3d800000,0x3d80,0xbd800000,0xbd80,0xbd35bd35,0x3d35bd35,0x3d353d35,0xbd353d35,0x3d800000,0x3d80,0xbd800000,0xbd80,0xbd35bd35,0x3d35bd35,0x3d353d35,0xbd353d35,
0x3d800000,0x3d80,0xbd800000,0xbd80,0xbd35bd35,0x3d35bd35,0x3d353d35,0xbd353d35,0x3d800000,0x3d80,0xbd800000,0xbd80,0xbd35bd35,0x3d35bd35,0x3d353d35,0xbd353d35,
0x3d553d0e,0xbc483d7b,0xbd7b3c48,0xbd0ebd55,0xbd800000,0xbcc4bd6d,0x3d35bd35,0x3d6d3cc4,0x3d0ebd55,0x3d7b3c48,0x3c483d7b,0xbd553d0e,0x3d80,0xbd6d3cc4,0xbd35bd35,0x3cc4bd6d,
0xbd55bd0e,0x3c48bd7b,0x3d7bbc48,0x3d0e3d55,0x3d800000,0x3cc43d6d,0xbd353d35,0xbd6dbcc4,0xbd0e3d55,0xbd7bbc48,0xbc48bd7b,0x3d55bd0e,0xbd80,0x3d6dbcc4,0x3d353d35,0xbcc43d6d,
0xbd800000,0xbd35bd35,0xbd80,0x3d35bd35,0x3d6d3cc4,0x3cc43d6d,0xbcc43d6d,0xbd6d3cc4,0x3d800000,0x3d353d35,0x3d80,0xbd353d35,0xbd6dbcc4,0xbcc4bd6d,0x3cc4bd6d,0x3d6dbcc4,
0xbd800000,0xbd35bd35,0xbd80,0x3d35bd35,0x3d6d3cc4,0x3cc43d6d,0xbcc43d6d,0xbd6d3cc4,0x3d800000,0x3d353d35,0x3d80,0xbd353d35,0xbd6dbcc4,0xbcc4bd6d,0x3cc4bd6d,0x3d6dbcc4,
0xbc483d7b,0xbd0e3d55,0xbd553d0e,0xbd7b3c48,0xbd80,0x3cc4bd6d,0x3d35bd35,0x3d6dbcc4,0x3d7b3c48,0x3d553d0e,0x3d0e3d55,0x3c483d7b,0xbd800000,0xbd6dbcc4,0xbd35bd35,0xbcc4bd6d,
0x3c48bd7b,0x3d0ebd55,0x3d55bd0e,0x3d7bbc48,0x3d80,0xbcc43d6d,0xbd353d35,0xbd6d3cc4,0xbd7bbc48,0xbd55bd0e,0xbd0ebd55,0xbc48bd7b,0x3d800000,0x3d6d3cc4,0x3d353d35,0x3cc43d6d,
0x80003d80,0x80003d80,0x80003d80,0x80003d80,0x8000bd80,0x8000bd80,0x8000bd80,0x8000bd80,0x80003d80,0x80003d80,0x80003d80,0x80003d80,0x8000bd80,0x8000bd80,0x8000bd80,0x8000bd80,
0x80003d80,0x80003d80,0x80003d80,0x80003d80,0x8000bd80,0x8000bd80,0x8000bd80,0x8000bd80,0x80003d80,0x80003d80,0x80003d80,0x80003d80,0x8000bd80,0x8000bd80,0x8000bd80,0x8000bd80,
0xbc48bd7b,0xbd0ebd55,0xbd55bd0e,0xbd7bbc48,0x80003d80,0x3cc43d6d,0x3d353d35,0x3d6d3cc4,0xbd7b3c48,0xbd553d0e,0xbd0e3d55,0xbc483d7b,0x3d800000,0x3d6dbcc4,0x3d35bd35,0x3cc4bd6d,
0x3c483d7b,0x3d0e3d55,0x3d553d0e,0x3d7b3c48,0x8000bd80,0xbcc4bd6d,0xbd35bd35,0xbd6dbcc4,0x3d7bbc48,0x3d55bd0e,0x3d0ebd55,0x3c48bd7b,0xbd800000,0xbd6d3cc4,0xbd353d35,0xbcc43d6d,
0x8000bd80,0xbd35bd35,0xbd800000,0xbd353d35,0x3cc43d6d,0x3d6d3cc4,0x3d6dbcc4,0x3cc4bd6d,0x80003d80,0x3d353d35,0x3d800000,0x3d35bd35,0xbcc4bd6d,0xbd6dbcc4,0xbd6d3cc4,0xbcc43d6d,
0x8000bd80,0xbd35bd35,0xbd800000,0xbd353d35,0x3cc43d6d,0x3d6d3cc4,0x3d6dbcc4,0x3cc4bd6d,0x80003d80,0x3d353d35,0x3d800000,0x3d35bd35,0xbcc4bd6d,0xbd6dbcc4,0xbd6d3cc4,0xbcc43d6d,
0x3d55bd0e,0xbc48bd7b,0xbd7bbc48,0xbd0e3d55,0xbd800000,0xbcc43d6d,0x3d353d35,0x3d6dbcc4,0xbd0ebd55,0xbd7b3c48,0xbc483d7b,0x3d553d0e,0x80003d80,0x3d6d3cc4,0x3d35bd35,0xbcc4bd6d,
0xbd553d0e,0x3c483d7b,0x3d7b3c48,0x3d0ebd55,0x3d800000,0x3cc4bd6d,0xbd35bd35,0xbd6d3cc4,0x3d0e3d55,0x3d7bbc48,0x3c48bd7b,0xbd55bd0e,0x8000bd80,0xbd6dbcc4,0xbd353d35,0x3cc43d6d,
0x80003d80,0x3d800000,0x8000bd80,0xbd800000,0xbd35bd35,0xbd353d35,0x3d353d35,0x3d35bd35,0x80003d80,0x3d800000,0x8000bd80,0xbd800000,0xbd35bd35,0xbd353d35,0x3d353d35,0x3d35bd35,
0x80003d80,0x3d800000,0x8000bd80,0xbd800000,0xbd35bd35,0xbd353d35,0x3d353d35,0x3d35bd35,0x80003d80,0x3d800000,0x8000bd80,0xbd800000,0xbd35bd35,0xbd353d35,0x3d353d35,0x3d35bd35,
0x3d553d0e,0x3c48bd7b,0xbd7b3c48,0x3d0e3d55,0x8000bd80,0xbd6d3cc4,0x3d353d35,0x3cc4bd6d,0x3d0ebd55,0xbd7bbc48,0x3c483d7b,0x3d55bd0e,0xbd800000,0x3cc43d6d,0x3d35bd35,0xbd6dbcc4,
0xbd55bd0e,0xbc483d7b,0x3d7bbc48,0xbd0ebd55,0x80003d80,0x3d6dbcc4,0xbd35bd35,0xbcc43d6d,0xbd0e3d55,0x3d7b3c48,0xbc48bd7b,0xbd553d0e,0x3d800000,0xbcc4bd6d,0xbd353d35,0x3d6d3cc4,
0x8000bd80,0xbd353d35,0x3d800000,0xbd35bd35,0x3d6d3cc4,0xbcc4bd6d,0xbcc43d6d,0x3d6dbcc4,0x80003d80,0x3d35bd35,0xbd800000,0x3d353d35,0xbd6dbcc4,0x3cc43d6d,0x3cc4bd6d,0xbd6d3cc4,
0x8000bd80,0xbd353d35,0x3d800000,0xbd35bd35,0x3d6d3cc4,0xbcc4bd6d,0xbcc43d6d,0x3d6dbcc4,0x80003d80,0x3d35bd35,0xbd800000,0x3d353d35,0xbd6dbcc4,0x3cc43d6d,0x3cc4bd6d,0xbd6d3cc4,
0xbc483d7b,0x3d0ebd55,0xbd553d0e,0x3d7bbc48,0x3d800000,0xbd6dbcc4,0x3d353d35,0xbcc4bd6d,0x3d7b3c48,0xbd55bd0e,0x3d0e3d55,0xbc48bd7b,0x8000bd80,0xbcc43d6d,0x3d35bd35,0xbd6d3cc4,
0x3c48bd7b,0xbd0e3d55,0x3d55bd0e,0xbd7b3c48,0xbd800000,0x3d6d3cc4,0xbd35bd35,0x3cc43d6d,0xbd7bbc48,0x3d553d0e,0xbd0ebd55,0x3c483d7b,0x80003d80,0x3cc4bd6d,0xbd353d35,0x3d6dbcc4,
0x3d800000,0x3d800000,0x3d800000,0x3d800000,0xbd800000,0xbd800000,0xbd800000,0xbd800000,0x3d800000,0x3d800000,0x3d800000,0x3d800000,0xbd800000,0xbd800000,0xbd800000,0xbd800000,
0x3d800000,0x3d800000,0x3d800000,0x3d800000,0xbd800000,0xbd800000,0xbd800000,0xbd800000,0x3d800000,0x3d800000,0x3d800000,0x3d800000,0xbd800000,0xbd800000,0xbd800000,0xbd800000,
0xbd7b3c48,0xbd553d0e,0xbd0e3d55,0xbc483d7b,0x3d800000,0x3d6dbcc4,0x3d35bd35,0x3cc4bd6d,0x3c483d7b,0x3d0e3d55,0x3d553d0e,0x3d7b3c48,0xbd80,0xbcc4bd6d,0xbd35bd35,0xbd6dbcc4,
0x3d7bbc48,0x3d55bd0e,0x3d0ebd55,0x3c48bd7b,0xbd800000,0xbd6d3cc4,0xbd353d35,0xbcc43d6d,0xbc48bd7b,0xbd0ebd55,0xbd55bd0e,0xbd7bbc48,0x3d80,0x3cc43d6d,0x3d353d35,0x3d6d3cc4,
0xbd800000,0xbd353d35,0x3d80,0x3d353d35,0x3d6dbcc4,0x3cc4bd6d,0xbcc4bd6d,0xbd6dbcc4,0x3d800000,0x3d35bd35,0xbd80,0xbd35bd35,0xbd6d3cc4,0xbcc43d6d,0x3cc43d6d,0x3d6d3cc4,
0xbd800000,0xbd353d35,0x3d80,0x3d353d35,0x3d6dbcc4,0x3cc4bd6d,0xbcc4bd6d,0xbd6dbcc4,0x3d800000,0x3d35bd35,0xbd80,0xbd35bd35,0xbd6d3cc4,0xbcc43d6d,0x3cc43d6d,0x3d6d3cc4,
0xbd0ebd55,0xbd7b3c48,0xbc483d7b,0x3d553d0e,0x3d80,0x3d6d3cc4,0x3d35bd35,0xbcc4bd6d,0xbd553d0e,0x3c483d7b,0x3d7b3c48,0x3d0ebd55,0x3d800000,0x3cc4bd6d,0xbd35bd35,0xbd6d3cc4,
0x3d0e3d55,0x3d7bbc48,0x3c48bd7b,0xbd55bd0e,0xbd80,0xbd6dbcc4,0xbd353d35,0x3cc43d6d,0x3d55bd0e,0xbc48bd7b,0xbd7bbc48,0xbd0e3d55,0xbd800000,0xbcc43d6d,0x3d353d35,0x3d6dbcc4,
0x3d800000,0xbd80,0xbd800000,0x3d80,0xbd353d35,0x3d353d35,0x3d35bd35,0xbd35bd35,0x3d800000,0xbd80,0xbd800000,0x3d80,0xbd353d35,0x3d353d35,0x3d35bd35,0xbd35bd35,
0x3d800000,0xbd80,0xbd800000,0x3d80,0xbd353d35,0x3d353d35,0x3d35bd35,0xbd35bd35,0x3d800000,0xbd80,0xbd800000,0x3d80,0xbd353d35,0x3d353d35,0x3d35bd35,0xbd35bd35,
0x3d0ebd55,0xbd7bbc48,0x3c483d7b,0x3d55bd0e,0xbd800000,0x3cc43d6d,0x3d35bd35,0xbd6dbcc4,0xbd55bd0e,0xbc483d7b,0x3d7bbc48,0xbd0ebd55,0x3d80,0x3d6dbcc4,0xbd35bd35,0xbcc43d6d,
0xbd0e3d55,0x3d7b3c48,0xbc48bd7b,0xbd553d0e,0x3d800000,0xbcc4bd6d,0xbd353d35,0x3d6d3cc4,0x3d553d0e,0x3c48bd7b,0xbd7b3c48,0x3d0e3d55,0xbd80,0xbd6d3cc4,0x3d353d35,0x3cc4bd6d,
0xbd800000,0x3d353d35,0xbd80,0xbd353d35,0x3cc4bd6d,0xbd6d3cc4,0x3d6d3cc4,0xbcc4bd6d,0x3d800000,0xbd35bd35,0x3d80,0x3d35bd35,0xbcc43d6d,0x3d6dbcc4,0xbd6dbcc4,0x3cc43d6d,
0xbd800000,0x3d353d35,0xbd80,0xbd353d35,0x3cc4bd6d,0xbd6d3cc4,0x3d6d3cc4,0xbcc4bd6d,0x3d800000,0xbd35bd35,0x3d80,0x3d35bd35,0xbcc43d6d,0x3d6dbcc4,0xbd6dbcc4,0x3cc43d6d,
0x3d7b3c48,0xbd55bd0e,0x3d0e3d55,0xbc48bd7b,0xbd80,0xbcc43d6d,0x3d35bd35,0xbd6d3cc4,0x3c48bd7b,0xbd0e3d55,0x3d55bd0e,0xbd7b3c48,0xbd800000,0x3d6d3cc4,0xbd35bd35,0x3cc43d6d,
0xbd7bbc48,0x3d553d0e,0xbd0ebd55,0x3c483d7b,0x3d80,0x3cc4bd6d,0xbd353d35,0x3d6dbcc4,0xbc483d7b,0x3d0ebd55,0xbd553d0e,0x3d7bbc48,0x3d800000,0xbd6dbcc4,0x3d353d35,0xbcc4bd6d,
0x80003d80,0x8000bd80,0x80003d80,0x8000bd80,0xbd800000,0x3d800000,0xbd800000,0x3d800000,0x80003d80,0x8000bd80,0x80003d80,0x8000bd80,0xbd800000,0x3d800000,0xbd800000,0x3d800000,
0x80003d80,0x8000bd80,0x80003d80,0x8000bd80,0xbd800000,0x3d800000,0xbd800000,0x3d800000,0x80003d80,0x8000bd80,0x80003d80,0x8000bd80,0xbd800000,0x3d800000,0xbd800000,0x3d800000,
0xbd7b3c48,0x3d55bd0e,0xbd0e3d55,0x3c48bd7b,0x80003d80,0xbcc4bd6d,0x3d353d35,0xbd6dbcc4,0x3c483d7b,0xbd0ebd55,0x3d553d0e,0xbd7bbc48,0x3d800000,0xbd6d3cc4,0x3d35bd35,0xbcc43d6d,
0x3d7bbc48,0xbd553d0e,0x3d0ebd55,0xbc483d7b,0x8000bd80,0x3cc43d6d,0xbd35bd35,0x3d6d3cc4,0xbc48bd7b,0x3d0e3d55,0xbd55bd0e,0x3d7b3c48,0xbd800000,0x3d6dbcc4,0xbd353d35,0x3cc4bd6d,
0x8000bd80,0x3d353d35,0xbd800000,0x3d35bd35,0x3d6dbcc4,0xbcc43d6d,0xbcc4bd6d,0x3d6d3cc4,0x80003d80,0xbd35bd35,0x3d800000,0xbd353d35,0xbd6d3cc4,0x3cc4bd6d,0x3cc43d6d,0xbd6dbcc4,
0x8000bd80,0x3d353d35,0xbd800000,0x3d35bd35,0x3d6dbcc4,0xbcc43d6d,0xbcc4bd6d,0x3d6d3cc4,0x80003d80,0xbd35bd35,0x3d800000,0xbd353d35,0xbd6d3cc4,0x3cc4bd6d,0x3cc43d6d,0xbd6dbcc4,
0xbd0ebd55,0x3d7bbc48,0xbc483d7b,0xbd55bd0e,0xbd800000,0x3cc4bd6d,0x3d353d35,0xbd6d3cc4,0xbd553d0e,0xbc48bd7b,0x3d7b3c48,0xbd0e3d55,0x80003d80,0xbd6dbcc4,0x3d35bd35,0x3cc43d6d,
0x3d0e3d55,0xbd7b3c48,0x3c48bd7b,0x3d553d0e,0x3d800000,0xbcc43d6d,0xbd35bd35,0x3d6dbcc4,0x3d55bd0e,0x3c483d7b,0xbd7bbc48,0x3d0ebd55,0x8000bd80,0x3d6d3cc4,0xbd353d35,0xbcc4bd6d,
0x80003d80,0xbd800000,0x8000bd80,0x3d800000,0xbd353d35,0xbd35bd35,0x3d35bd35,0x3d353d35,0x80003d80,0xbd800000,0x8000bd80,0x3d800000,0xbd353d35,0xbd35bd35,0x3d35bd35,0x3d353d35,
0x80003d80,0xbd800000,0x8000bd80,0x3d800000,0xbd353d35,0xbd35bd35,0x3d35bd35,0x3d353d35,0x80003d80,0xbd800000,0x8000bd80,0x3d800000,0xbd353d35,0xbd35bd35,0x3d35bd35,0x3d353d35,
0x3d0ebd55,0x3d7b3c48,0x3c483d7b,0xbd553d0e,0x8000bd80,0x3d6dbcc4,0x3d353d35,0xbcc43d6d,0xbd55bd0e,0x3c48bd7b,0x3d7bbc48,0x3d0e3d55,0xbd800000,0xbcc4bd6d,0x3d35bd35,0x3d6d3cc4,
0xbd0e3d55,0xbd7bbc48,0xbc48bd7b,0x3d55bd0e,0x80003d80,0xbd6d3cc4,0xbd35bd35,0x3cc4bd6d,0x3d553d0e,0xbc483d7b,0xbd7b3c48,0xbd0ebd55,0x3d800000,0x3cc43d6d,0xbd353d35,0xbd6dbcc4,
0x8000bd80,0x3d35bd35,0x3d800000,0x3d353d35,0x3cc4bd6d,0x3d6dbcc4,0x3d6d3cc4,0x3cc43d6d,0x80003d80,0xbd353d35,0xbd800000,0xbd35bd35,0xbcc43d6d,0xbd6d3cc4,0xbd6dbcc4,0xbcc4bd6d,
0x8000bd80,0x3d35bd35,0x3d800000,0x3d353d35,0x3cc4bd6d,0x3d6dbcc4,0x3d6d3cc4,0x3cc43d6d,0x80003d80,0xbd353d35,0xbd800000,0xbd35bd35,0xbcc43d6d,0xbd6d3cc4,0xbd6dbcc4,0xbcc4bd6d,
0x3d7b3c48,0x3d553d0e,0x3d0e3d55,0x3c483d7b,0x3d800000,0x3d6d3cc4,0x3d353d35,0x3cc43d6d,0x3c48bd7b,0x3d0ebd55,0x3d55bd0e,0x3d7bbc48,0x8000bd80,0x3cc4bd6d,0x3d35bd35,0x3d6dbcc4,
0xbd7bbc48,0xbd55bd0e,0xbd0ebd55,0xbc48bd7b,0xbd800000,0xbd6dbcc4,0xbd35bd35,0xbcc4bd6d,0xbc483d7b,0xbd0e3d55,0xbd553d0e,0xbd7b3c48,0x80003d80,0xbcc43d6d,0xbd353d35,0xbd6d3cc4,
0x3d800000,0xbd800000,0x3d800000,0xbd800000,0x3d80,0xbd80,0x3d80,0xbd80,0x3d800000,0xbd800000,0x3d800000,0xbd800000,0x3d80,0xbd80,0x3d80,0xbd80,
0x3d800000,0xbd800000,0x3d800000,0xbd800000,0x3d80,0xbd80,0x3d80,0xbd80,0x3d800000,0xbd800000,0x3d800000,0xbd800000,0x3d80,0xbd80,0x3d80,0xbd80,
0x3c483d7b,0xbd0ebd55,0x3d553d0e,0xbd7bbc48,0x3d800000,0xbd6d3cc4,0x3d35bd35,0xbcc43d6d,0x3d7bbc48,0xbd553d0e,0x3d0ebd55,0xbc483d7b,0xbd80,0x3cc43d6d,0xbd35bd35,0x3d6d3cc4,
0xbc48bd7b,0x3d0e3d55,0xbd55bd0e,0x3d7b3c48,0xbd800000,0x3d6dbcc4,0xbd353d35,0x3cc4bd6d,0xbd7b3c48,0x3d55bd0e,0xbd0e3d55,0x3c48bd7b,0x3d80,0xbcc4bd6d,0x3d353d35,0xbd6dbcc4,
0xbd800000,0x3d35bd35,0x3d80,0xbd35bd35,0xbcc4bd6d,0x3d6d3cc4,0xbd6d3cc4,0x3cc4bd6d,0x3d800000,0xbd353d35,0xbd80,0x3d353d35,0x3cc43d6d,0xbd6dbcc4,0x3d6dbcc4,0xbcc43d6d,
0xbd800000,0x3d35bd35,0x3d80,0xbd35bd35,0xbcc4bd6d,0x3d6d3cc4,0xbd6d3cc4,0x3cc4bd6d,0x3d800000,0xbd353d35,0xbd80,0x3d353d35,0x3cc43d6d,0xbd6dbcc4,0x3d6dbcc4,0xbcc43d6d,
0xbd553d0e,0xbc48bd7b,0x3d7b3c48,0xbd0e3d55,0x3d80,0xbd6dbcc4,0x3d35bd35,0x3cc43d6d,0x3d0e3d55,0xbd7b3c48,0x3c48bd7b,0x3d553d0e,0x3d800000,0xbcc43d6d,0xbd35bd35,0x3d6dbcc4,
0x3d55bd0e,0x3c483d7b,0xbd7bbc48,0x3d0ebd55,0xbd80,0x3d6d3cc4,0xbd353d35,0xbcc4bd6d,0xbd0ebd55,0x3d7bbc48,0xbc483d7b,0xbd55bd0e,0xbd800000,0x3cc4bd6d,0x3d353d35,0xbd6d3cc4,
0x3d800000,0x3d80,0xbd800000,0xbd80,0x3d353d35,0xbd353d35,0xbd35bd35,0x3d35bd35,0x3d800000,0x3d80,0xbd800000,0xbd80,0x3d353d35,0xbd353d35,0xbd35bd35,0x3d35bd35,
0x3d800000,0x3d80,0xbd800000,0xbd80,0x3d353d35,0xbd353d35,0xbd35bd35,0x3d35bd35,0x3d800000,0x3d80,0xbd800000,0xbd80,0x3d353d35,0xbd353d35,0xbd35bd35,0x3d35bd35,
0xbd55bd0e,0x3c48bd7b,0x3d7bbc48,0x3d0e3d55,0xbd800000,0xbcc4bd6d,0x3d35bd35,0x3d6d3cc4,0xbd0e3d55,0xbd7bbc48,0xbc48bd7b,0x3d55bd0e,0x3d80,0xbd6d3cc4,0xbd35bd35,0x3cc4bd6d,
0x3d553d0e,0xbc483d7b,0xbd7b3c48,0xbd0ebd55,0x3d800000,0x3cc43d6d,0xbd353d35,0xbd6dbcc4,0x3d0ebd55,0x3d7b3c48,0x3c483d7b,0xbd553d0e,0xbd80,0x3d6dbcc4,0x3d353d35,0xbcc43d6d,
0xbd800000,0xbd35bd35,0xbd80,0x3d35bd35,0xbd6dbcc4,0xbcc4bd6d,0x3cc4bd6d,0x3d6dbcc4,0x3d800000,0x3d353d35,0x3d80,0xbd353d35,0x3d6d3cc4,0x3cc43d6d,0xbcc43d6d,0xbd6d3cc4,
0xbd800000,0xbd35bd35,0xbd80,0x3d35bd35,0xbd6dbcc4,0xbcc4bd6d,0x3cc4bd6d,0x3d6dbcc4,0x3d800000,0x3d353d35,0x3d80,0xbd353d35,0x3d6d3cc4,0x3cc43d6d,0xbcc43d6d,0xbd6d3cc4,
0x3c48bd7b,0x3d0ebd55,0x3d55bd0e,0x3d7bbc48,0xbd80,0x3cc4bd6d,0x3d35bd35,0x3d6dbcc4,0xbd7bbc48,0xbd55bd0e,0xbd0ebd55,0xbc48bd7b,0xbd800000,0xbd6dbcc4,0xbd35bd35,0xbcc4bd6d,
0xbc483d7b,0xbd0e3d55,0xbd553d0e,0xbd7b3c48,0x3d80,0xbcc43d6d,0xbd353d35,0xbd6d3cc4,0x3d7b3c48,0x3d553d0e,0x3d0e3d55,0x3c483d7b,0x3d800000,0x3d6d3cc4,0x3d353d35,0x3cc43d6d,
0x3f003f00,0xbf003f00,0x3f003f00,0xbf003f00,0x3f003f00,0xbf003f00,0x3f003f00,0xbf003f00,0x3f003f00,0xbf003f00,0x3f003f00,0xbf003f00,0x3f003f00,0xbf003f00,0x3f003f00,0xbf003f00,
0x3eff3f00,0xbd490000,0x3ea23eb5,0xbec6beb5,0x3ef53efb,0xbe15bdc8,0x3e713e8e,0xbee2bed5,0x3ee23eed,0xbe71be44,0x3e153e44,0xbef5beed,0x3ec63ed5,0xbea2be8e,0x3d493dc8,0xbeffbefb,
0x3efb3f00,0xbdc80000,0xbdc80000,0xbefbbf00,0x3ed53eed,0xbe8ebe44,0xbe8ebe44,0xbed5beed,0x3e8e3eb5,0xbed5beb5,0xbed5beb5,0xbe8ebeb5,0x3dc83e44,0xbefbbeed,0xbefbbeed,0xbdc8be44,
0x3ef53f00,0xbe150000,0xbee2beb5,0xbe71beb5,0x3ea23ed5,0xbec6be8e,0xbeffbefb,0x3d49bdc8,0x3d493e44,0xbeffbeed,0xbec6beed,0x3ea23e44,0xbe71bdc8,0xbee2befb,0xbe15be8e,0x3ef53ed5,
0x3eed3f00,0xbe440000,0xbeedbf00,0x3e440000,0x3e443eb5,0xbeedbeb5,0xbe44beb5,0x3eed3eb5,0xbe440000,0xbeedbf00,0x3e440000,0x3eed3f00,0xbeedbeb5,0xbe44beb5,0x3eed3eb5,0x3e443eb5,
0x3ee23f00,0xbe710000,0xbe15beb5,0x3ef53eb5,0x3d493e8e,0xbeffbed5,0x3ea23dc8,0x3ec63efb,0xbec6be44,0xbea2beed,0x3eff3eed,0xbd493e44,0xbef5befb,0x3e15bdc8,0x3e713ed5,0xbee2be8e,
0x3ed53f00,0xbe8e0000,0x3e8e0000,0x3ed53f00,0xbdc83e44,0xbefbbeed,0x3efb3eed,0xbdc83e44,0xbefbbeb5,0xbdc8beb5,0x3dc83eb5,0xbefbbeb5,0xbe8ebeed,0x3ed53e44,0xbed5be44,0xbe8ebeed,
0x3ec63f00,0xbea20000,0x3eff3eb5,0x3d493eb5,0xbe713dc8,0xbee2befb,0x3e153ed5,0xbef5be8e,0xbef5beed,0x3e15be44,0xbee2be44,0xbe71beed,0x3d49be8e,0x3eff3ed5,0xbea2befb,0x3ec63dc8,
0x3eb53f00,0xbeb50000,0x3eb53f00,0xbeb50000,0xbeb50000,0xbeb5bf00,0xbeb50000,0xbeb5bf00,0xbeb5bf00,0x3eb50000,0xbeb5bf00,0x3eb50000,0x3eb50000,0x3eb53f00,0x3eb50000,0x3eb53f00,
0x3ea23f00,0xbec60000,0xbd493eb5,0xbeffbeb5,0xbee2bdc8,0xbe71befb,0xbef5bed5,0x3e15be8e,0xbe15beed,0x3ef53e44,0x3e71be44,0x3ee23eed,0x3eff3e8e,0x3d493ed5,0x3ec63efb,0xbea23dc8,
0x3e8e3f00,0xbed50000,0xbed50000,0xbe8ebf00,0xbefbbe44,0xbdc8beed,0xbdc8beed,0x3efb3e44,0x3dc8beb5,0x3efb3eb5,0x3efb3eb5,0xbdc83eb5,0x3ed53eed,0xbe8e3e44,0xbe8e3e44,0xbed5beed,
0x3e713f00,0xbee20000,0xbef5beb5,0x3e15beb5,0xbeffbe8e,0x3d49bed5,0x3ec6bdc8,0x3ea23efb,0x3ea2be44,0x3ec63eed,0x3d493eed,0xbeffbe44,0x3e153efb,0xbef5bdc8,0xbee2bed5,0x3e71be8e,
0x3e443f00,0xbeed0000,0xbe44bf00,0x3eed0000,0xbeedbeb5,0x3e44beb5,0x3eed3eb5,0xbe443eb5,0x3eed0000,0x3e443f00,0xbeed0000,0xbe44bf00,0xbe443eb5,0xbeedbeb5,0x3e44beb5,0x3eed3eb5,
0x3e153f00,0xbef50000,0x3e71beb5,0x3ee23eb5,0xbec6bed5,0x3ea2be8e,0x3d493efb,0xbeffbdc8,0x3eff3e44,0xbd493eed,0xbea2beed,0x3ec6be44,0xbee23dc8,0xbe71befb,0x3ef53e8e,0xbe153ed5,
0x3dc83f00,0xbefb0000,0x3efb0000,0x3dc83f00,0xbe8ebeed,0x3ed5be44,0xbed53e44,0xbe8ebeed,0x3ed53eb5,0xbe8e3eb5,0x3e8ebeb5,0x3ed53eb5,0xbefbbe44,0x3dc8beed,0xbdc83eed,0xbefbbe44,
0x3d493f00,0xbeff0000,0x3ec63eb5,0xbea23eb5,0xbe15befb,0x3ef5bdc8,0xbee2be8e,0x3e71bed5,0x3e713eed,0xbee23e44,0x3ef53e44,0xbe153eed,0xbea2bed5,0x3ec6be8e,0xbeffbdc8,0x3d49befb,
0x3f00,0xbf000000,0x3f00,0xbf000000,0xbf00,0x3f000000,0xbf00,0x3f000000,0x3f00,0xbf000000,0x3f00,0xbf000000,0xbf00,0x3f000000,0xbf00,0x3f000000,
0xbd493f00,0xbeff0000,0xbec63eb5,0xbea2beb5,0x3e15befb,0x3ef53dc8,0x3ee2be8e,0x3e713ed5,0xbe713eed,0xbee2be44,0xbef53e44,0xbe15beed,0x3ea2bed5,0x3ec63e8e,0x3effbdc8,0x3d493efb,
0xbdc83f00,0xbefb0000,0xbefb0000,0x3dc8bf00,0x3e8ebeed,0x3ed53e44,0x3ed53e44,0xbe8e3eed,0xbed53eb5,0xbe8ebeb5,0xbe8ebeb5,0x3ed5beb5,0x3efbbe44,0x3dc83eed,0x3dc83eed,0xbefb3e44,
0xbe153f00,0xbef50000,0xbe71beb5,0x3ee2beb5,0x3ec6bed5,0x3ea23e8e,0xbd493efb,0xbeff3dc8,0xbeff3e44,0xbd49beed,0x3ea2beed,0x3ec63e44,0x3ee23dc8,0xbe713efb,0xbef53e8e,0xbe15bed5,
0xbe443f00,0xbeed0000,0x3e44bf00,0x3eed0000,0x3eedbeb5,0x3e443eb5,0xbeed3eb5,0xbe44beb5,0xbeed0000,0x3e44bf00,0x3eed0000,0xbe443f00,0x3e443eb5,0xbeed3eb5,0xbe44beb5,0x3eedbeb5,
0xbe713f00,0xbee20000,0x3ef5beb5,0x3e153eb5,0x3effbe8e,0x3d493ed5,0xbec6bdc8,0x3ea2befb,0xbea2be44,0x3ec6beed,0xbd493eed,0xbeff3e44,0xbe153efb,0xbef53dc8,0x3ee2bed5,0x3e713e8e,
0xbe8e3f00,0xbed50000,0x3ed50000,0xbe8e3f00,0x3efbbe44,0xbdc83eed,0x3dc8beed,0x3efbbe44,0xbdc8beb5,0x3efbbeb5,0xbefb3eb5,0xbdc8beb5,0xbed53eed,0xbe8ebe44,0x3e8e3e44,0xbed53eed,
0xbea23f00,0xbec60000,0x3d493eb5,0xbeff3eb5,0x3ee2bdc8,0xbe713efb,0x3ef5bed5,0x3e153e8e,0x3e15beed,0x3ef5be44,0xbe71be44,0x3ee2beed,0xbeff3e8e,0x3d49bed5,0xbec63efb,0xbea2bdc8,
0xbeb53f00,0xbeb50000,0xbeb53f00,0xbeb50000,0x3eb50000,0xbeb53f00,0x3eb50000,0xbeb53f00,0x3eb5bf00,0x3eb50000,0x3eb5bf00,0x3eb50000,0xbeb50000,0x3eb5bf00,0xbeb50000,0x3eb5bf00,
0xbec63f00,0xbea20000,0xbeff3eb5,0x3d49beb5,0x3e713dc8,0xbee23efb,0xbe153ed5,0xbef53e8e,0x3ef5beed,0x3e153e44,0x3ee2be44,0xbe713eed,0xbd49be8e,0x3effbed5,0x3ea2befb,0x3ec6bdc8,
0xbed53f00,0xbe8e0000,0xbe8e0000,0x3ed5bf00,0x3dc83e44,0xbefb3eed,0xbefb3eed,0xbdc8be44,0x3efbbeb5,0xbdc83eb5,0xbdc83eb5,0xbefb3eb5,0x3e8ebeed,0x3ed5be44,0x3ed5be44,0xbe8e3eed,
0xbee23f00,0xbe710000,0x3e15beb5,0x3ef5beb5,0xbd493e8e,0xbeff3ed5,0xbea23dc8,0x3ec6befb,0x3ec6be44,0xbea23eed,0xbeff3eed,0xbd49be44,0x3ef5befb,0x3e153dc8,0xbe713ed5,0xbee23e8e,
0xbeed3f00,0xbe440000,0x3eedbf00,0x3e440000,0xbe443eb5,0xbeed3eb5,0x3e44beb5,0x3eedbeb5,0x3e440000,0xbeed3f00,0xbe440000,0x3eedbf00,0x3eedbeb5,0xbe443eb5,0xbeed3eb5,0x3e44beb5,
0xbef53f00,0xbe150000,0x3ee2beb5,0xbe713eb5,0xbea23ed5,0xbec63e8e,0x3effbefb,0x3d493dc8,0xbd493e44,0xbeff3eed,0x3ec6beed,0x3ea2be44,0x3e71bdc8,0xbee23efb,0x3e15be8e,0x3ef5bed5,
0xbefb3f00,0xbdc80000,0x3dc80000,0xbefb3f00,0xbed53eed,0xbe8e3e44,0x3e8ebe44,0xbed53eed,0xbe8e3eb5,0xbed53eb5,0x3ed5beb5,0xbe8e3eb5,0xbdc83e44,0xbefb3eed,0x3efbbeed,0xbdc83e44,
0xbeff3f00,0xbd490000,0xbea23eb5,0xbec63eb5,0xbef53efb,0xbe153dc8,0xbe713e8e,0xbee23ed5,0xbee23eed,0xbe713e44,0xbe153e44,0xbef53eed,0xbec63ed5,0xbea23e8e,0xbd493dc8,0xbeff3efb,
0x3f003f00,0xbf003f00,0x3f003f00,0xbf003f00,0x3f003f00,0xbf003f00,0x3f003f00,0xbf003f00,0x3f003f00,0xbf003f00,0x3f003f00,0xbf003f00,0x3f003f00,0xbf003f00,0x3f003f00,0xbf003f00,
0xbd490000,0xbeffbf00,0xbec6beb5,0xbea2beb5,0xbe15bdc8,0xbef5befb,0xbee2bed5,0xbe71be8e,0xbe71be44,0xbee2beed,0xbef5beed,0xbe15be44,0xbea2be8e,0xbec6bed5,0xbeffbefb,0xbd49bdc8,
0xbefbbf00,0x3dc80000,0x3dc80000,0x3efb3f00,0xbed5beed,0x3e8e3e44,0x3e8e3e44,0x3ed53eed,0xbe8ebeb5,0x3ed53eb5,0x3ed53eb5,0x3e8e3eb5,0xbdc8be44,0x3efb3eed,0x3efb3eed,0x3dc83e44,
0x3e150000,0x3ef53f00,0x3e713eb5,0xbee2beb5,0x3ec63e8e,0x3ea23ed5,0xbd493dc8,0xbeffbefb,0x3eff3eed,0x3d493e44,0xbea2be44,0xbec6beed,0x3ee23efb,0xbe71bdc8,0xbef5bed5,0xbe15be8e,
0x3eed3f00,0xbe440000,0xbeedbf00,0x3e440000,0x3e443eb5,0xbeedbeb5,0xbe44beb5,0x3eed3eb5,0xbe440000,0xbeedbf00,0x3e440000,0x3eed3f00,0xbeedbeb5,0xbe44beb5,0x3eed3eb5,0x3e443eb5,
0xbe710000,0xbee2bf00,0x3ef53eb5,0x3e153eb5,0xbeffbed5,0xbd49be8e,0x3ec63efb,0xbea2bdc8,0xbea2beed,0x3ec63e44,0xbd493e44,0xbeffbeed,0x3e15bdc8,0x3ef53efb,0xbee2be8e,0xbe71bed5,
0xbed5bf00,0x3e8e0000,0xbe8e0000,0xbed5bf00,0x3dc8be44,0x3efb3eed,0xbefbbeed,0x3dc8be44,0x3efb3eb5,0x3dc83eb5,0xbdc8beb5,0x3efb3eb5,0x3e8e3eed,0xbed5be44,0x3ed53e44,0x3e8e3eed,
0x3ea20000,0x3ec63f00,0xbd49beb5,0x3eff3eb5,0x3ee23efb,0xbe713dc8,0x3ef53e8e,0x3e153ed5,0xbe153e44,0xbef5beed,0x3e713eed,0xbee2be44,0xbeffbed5,0x3d49be8e,0xbec6bdc8,0xbea2befb,
0x3eb53f00,0xbeb50000,0x3eb53f00,0xbeb50000,0xbeb50000,0xbeb5bf00,0xbeb50000,0xbeb5bf00,0xbeb5bf00,0x3eb50000,0xbeb5bf00,0x3eb50000,0x3eb50000,0x3eb53f00,0x3eb50000,0x3eb53f00,
0xbec60000,0xbea2bf00,0xbeffbeb5,0x3d49beb5,0xbe71befb,0x3ee23dc8,0x3e15be8e,0x3ef53ed5,0x3ef53e44,0x3e153eed,0x3ee23eed,0xbe713e44,0x3d493ed5,0xbeffbe8e,0xbea23dc8,0xbec6befb,
0xbe8ebf00,0x3ed50000,0x3ed50000,0x3e8e3f00,0x3efb3e44,0x3dc83eed,0x3dc83eed,0xbefbbe44,0xbdc83eb5,0xbefbbeb5,0xbefbbeb5,0x3dc8beb5,0xbed5beed,0x3e8ebe44,0x3e8ebe44,0x3ed53eed,
0x3ee20000,0x3e713f00,0xbe153eb5,0xbef5beb5,0xbd493ed5,0xbeffbe8e,0xbea2befb,0x3ec6bdc8,0xbec6beed,0x3ea2be44,0x3eff3e44,0x3d493eed,0x3ef53dc8,0x3e153efb,0xbe713e8e,0xbee2bed5,
0x3e443f00,0xbeed0000,0xbe44bf00,0x3eed0000,0xbeedbeb5,0x3e44beb5,0x3eed3eb5,0xbe443eb5,0x3eed0000,0x3e443f00,0xbeed0000,0xbe44bf00,0xbe443eb5,0xbeedbeb5,0x3e44beb5,0x3eed3eb5,
0xbef50000,0xbe15bf00,0x3ee23eb5,0xbe713eb5,0x3ea2be8e,0x3ec63ed5,0xbeffbdc8,0xbd49befb,0xbd493eed,0xbeffbe44,0x3ec6be44,0x3ea23eed,0xbe71befb,0x3ee2bdc8,0xbe153ed5,0xbef5be8e,
0xbdc8bf00,0x3efb0000,0xbefb0000,0xbdc8bf00,0x3e8e3eed,0xbed53e44,0x3ed5be44,0x3e8e3eed,0xbed5beb5,0x3e8ebeb5,0xbe8e3eb5,0xbed5beb5,0x3efb3e44,0xbdc83eed,0x3dc8beed,0x3efb3e44,
0x3eff0000,0x3d493f00,0x3ea2beb5,0x3ec63eb5,0xbef53dc8,0xbe15befb,0xbe713ed5,0xbee2be8e,0x3ee2be44,0x3e713eed,0x3e15beed,0x3ef53e44,0xbec63e8e,0xbea2bed5,0xbd493efb,0xbeffbdc8,
0x3f00,0xbf000000,0x3f00,0xbf000000,0xbf00,0x3f000000,0xbf00,0x3f000000,0x3f00,0xbf000000,0x3f00,0xbf000000,0xbf00,0x3f000000,0xbf00,0x3f000000,
0xbeff0000,0x3d49bf00,0xbea2beb5,0x3ec6beb5,0x3ef53dc8,0xbe153efb,0x3e713ed5,0xbee23e8e,0xbee2be44,0x3e71beed,0xbe15beed,0x3ef5be44,0x3ec63e8e,0xbea23ed5,0x3d493efb,0xbeff3dc8,
0x3dc8bf00,0x3efb0000,0x3efb0000,0xbdc83f00,0xbe8e3eed,0xbed5be44,0xbed5be44,0x3e8ebeed,0x3ed5beb5,0x3e8e3eb5,0x3e8e3eb5,0xbed53eb5,0xbefb3e44,0xbdc8beed,0xbdc8beed,0x3efbbe44,
0x3ef50000,0xbe153f00,0xbee23eb5,0xbe71beb5,0xbea2be8e,0x3ec6bed5,0x3effbdc8,0xbd493efb,0x3d493eed,0xbeff3e44,0xbec6be44,0x3ea2beed,0x3e71befb,0x3ee23dc8,0x3e153ed5,0xbef53e8e,
0xbe443f00,0xbeed0000,0x3e44bf00,0x3eed0000,0x3eedbeb5,0x3e443eb5,0xbeed3eb5,0xbe44beb5,0xbeed0000,0x3e44bf00,0x3eed0000,0xbe443f00,0x3e443eb5,0xbeed3eb5,0xbe44beb5,0x3eedbeb5,
0xbee20000,0x3e71bf00,0x3e153eb5,0xbef53eb5,0x3d493ed5,0xbeff3e8e,0x3ea2befb,0x3ec63dc8,0x3ec6beed,0x3ea23e44,0xbeff3e44,0x3d49beed,0xbef53dc8,0x3e15befb,0x3e713e8e,0xbee23ed5,
0x3e8ebf00,0x3ed50000,0xbed50000,0x3e8ebf00,0xbefb3e44,0x3dc8beed,0xbdc83eed,0xbefb3e44,0x3dc83eb5,0xbefb3eb5,0x3efbbeb5,0x3dc83eb5,0x3ed5beed,0x3e8e3e44,0xbe8ebe44,0x3ed5beed,
0x3ec60000,0xbea23f00,0x3effbeb5,0x3d493eb5,0x3e71befb,0x3ee2bdc8,0xbe15be8e,0x3ef5bed5,0xbef53e44,0x3e15beed,0xbee23eed,0xbe71be44,0xbd493ed5,0xbeff3e8e,0x3ea23dc8,0xbec63efb,
0xbeb53f00,0xbeb50000,0xbeb53f00,0xbeb50000,0x3eb50000,0xbeb53f00,0x3eb50000,0xbeb53f00,0x3eb5bf00,0x3eb50000,0x3eb5bf00,0x3eb50000,0xbeb50000,0x3eb5bf00,0xbeb50000,0x3eb5bf00,
0xbea20000,0x3ec6bf00,0x3d49beb5,0x3effbeb5,0xbee23efb,0xbe71bdc8,0xbef53e8e,0x3e15bed5,0x3e153e44,0xbef53eed,0xbe713eed,0xbee23e44,0x3effbed5,0x3d493e8e,0x3ec6bdc8,0xbea23efb,
0x3ed5bf00,0x3e8e0000,0x3e8e0000,0xbed53f00,0xbdc8be44,0x3efbbeed,0x3efbbeed,0x3dc83e44,0xbefb3eb5,0x3dc8beb5,0x3dc8beb5,0x3efbbeb5,0xbe8e3eed,0xbed53e44,0xbed53e44,0x3e8ebeed,
0x3e710000,0xbee23f00,0xbef53eb5,0x3e15beb5,0x3effbed5,0xbd493e8e,0xbec63efb,0xbea23dc8,0x3ea2beed,0x3ec6be44,0x3d493e44,0xbeff3eed,0xbe15bdc8,0x3ef5befb,0x3ee2be8e,0xbe713ed5,
0xbeed3f00,0xbe440000,0x3eedbf00,0x3e440000,0xbe443eb5,0xbeed3eb5,0x3e44beb5,0x3eedbeb5,0x3e440000,0xbeed3f00,0xbe440000,0x3eedbf00,0x3eedbeb5,0xbe443eb5,0xbeed3eb5,0x3e44beb5,
0xbe150000,0x3ef5bf00,0xbe713eb5,0xbee23eb5,0xbec63e8e,0x3ea2bed5,0x3d493dc8,0xbeff3efb,0xbeff3eed,0x3d49be44,0x3ea2be44,0xbec63eed,0xbee23efb,0xbe713dc8,0x3ef5bed5,0xbe153e8e,
0x3efbbf00,0x3dc80000,0xbdc80000,0x3efbbf00,0x3ed5beed,0x3e8ebe44,0xbe8e3e44,0x3ed5beed,0x3e8ebeb5,0x3ed5beb5,0xbed53eb5,0x3e8ebeb5,0x3dc8be44,0x3efbbeed,0xbefb3eed,0x3dc8be44,
0x3d490000,0xbeff3f00,0x3ec6beb5,0xbea23eb5,0x3e15bdc8,0xbef53efb,0x3ee2bed5,0xbe713e8e,0x3e71be44,0xbee23eed,0x3ef5beed,0xbe153e44,0x3ea2be8e,0xbec63ed5,0x3effbefb,0xbd493dc8,
0x3f003f00,0xbf003f00,0x3f003f00,0xbf003f00,0x3f003f00,0xbf003f00,0x3f003f00,0xbf003f00,0x3f003f00,0xbf003f00,0x3f003f00,0xbf003f00,0x3f003f00,0xbf003f00,0x3f003f00,0xbf003f00,
0xbeffbf00,0x3d490000,0xbea2beb5,0x3ec63eb5,0xbef5befb,0x3e153dc8,0xbe71be8e,0x3ee23ed5,0xbee2beed,0x3e713e44,0xbe15be44,0x3ef53eed,0xbec6bed5,0x3ea23e8e,0xbd49bdc8,0x3eff3efb,
0x3efb3f00,0xbdc80000,0xbdc80000,0xbefbbf00,0x3ed53eed,0xbe8ebe44,0xbe8ebe44,0xbed5beed,0x3e8e3eb5,0xbed5beb5,0xbed5beb5,0xbe8ebeb5,0x3dc83e44,0xbefbbeed,0xbefbbeed,0xbdc8be44,
0xbef5bf00,0x3e150000,0x3ee23eb5,0x3e713eb5,0xbea2bed5,0x3ec63e8e,0x3eff3efb,0xbd493dc8,0xbd49be44,0x3eff3eed,0x3ec63eed,0xbea2be44,0x3e713dc8,0x3ee23efb,0x3e153e8e,0xbef5bed5,
0x3eed3f00,0xbe440000,0xbeedbf00,0x3e440000,0x3e443eb5,0xbeedbeb5,0xbe44beb5,0x3eed3eb5,0xbe440000,0xbeedbf00,0x3e440000,0x3eed3f00,0xbeedbeb5,0xbe44beb5,0x3eed3eb5,0x3e443eb5,
0xbee2bf00,0x3e710000,0x3e153eb5,0xbef5beb5,0xbd49be8e,0x3eff3ed5,0xbea2bdc8,0xbec6befb,0x3ec63e44,0x3ea23eed,0xbeffbeed,0x3d49be44,0x3ef53efb,0xbe153dc8,0xbe71bed5,0x3ee23e8e,
0x3ed53f00,0xbe8e0000,0x3e8e0000,0x3ed53f00,0xbdc83e44,0xbefbbeed,0x3efb3eed,0xbdc83e44,0xbefbbeb5,0xbdc8beb5,0x3dc83eb5,0xbefbbeb5,0xbe8ebeed,0x3ed53e44,0xbed5be44,0xbe8ebeed,
0xbec6bf00,0x3ea20000,0xbeffbeb5,0xbd49beb5,0x3e71bdc8,0x3ee23efb,0xbe15bed5,0x3ef53e8e,0x3ef53eed,0xbe153e44,0x3ee23e44,0x3e713eed,0xbd493e8e,0xbeffbed5,0x3ea23efb,0xbec6bdc8,
0x3eb53f00,0xbeb50000,0x3eb53f00,0xbeb50000,0xbeb50000,0xbeb5bf00,0xbeb50000,0xbeb5bf00,0xbeb5bf00,0x3eb50000,0xbeb5bf00,0x3eb50000,0x3eb50000,0x3eb53f00,0x3eb50000,0x3eb53f00,
0xbea2bf00,0x3ec60000,0x3d49beb5,0x3eff3eb5,0x3ee23dc8,0x3e713efb,0x3ef53ed5,0xbe153e8e,0x3e153eed,0xbef5be44,0xbe713e44,0xbee2beed,0xbeffbe8e,0xbd49bed5,0xbec6befb,0x3ea2bdc8,
0x3e8e3f00,0xbed50000,0xbed50000,0xbe8ebf00,0xbefbbe44,0xbdc8beed,0xbdc8beed,0x3efb3e44,0x3dc8beb5,0x3efb3eb5,0x3efb3eb5,0xbdc83eb5,0x3ed53eed,0xbe8e3e44,0xbe8e3e44,0xbed5beed,
0xbe71bf00,0x3ee20000,0x3ef53eb5,0xbe153eb5,0x3eff3e8e,0xbd493ed5,0xbec63dc8,0xbea2befb,0xbea23e44,0xbec6beed,0xbd49beed,0x3eff3e44,0xbe15befb,0x3ef53dc8,0x3ee23ed5,0xbe713e8e,
0x3e443f00,0xbeed0000,0xbe44bf00,0x3eed0000,0xbeedbeb5,0x3e44beb5,0x3eed3eb5,0xbe443eb5,0x3eed0000,0x3e443f00,0xbeed0000,0xbe44bf00,0xbe443eb5,0xbeedbeb5,0x3e44beb5,0x3eed3eb5,
0xbe15bf00,0x3ef50000,0xbe713eb5,0xbee2beb5,0x3ec63ed5,0xbea23e8e,0xbd49befb,0x3eff3dc8,0xbeffbe44,0x3d49beed,0x3ea23eed,0xbec63e44,0x3ee2bdc8,0x3e713efb,0xbef5be8e,0x3e15bed5,
0x3dc83f00,0xbefb0000,0x3efb0000,0x3dc83f00,0xbe8ebeed,0x3ed5be44,0xbed53e44,0xbe8ebeed,0x3ed53eb5,0xbe8e3eb5,0x3e8ebeb5,0x3ed53eb5,0xbefbbe44,0x3dc8beed,0xbdc83eed,0xbefbbe44,
0xbd49bf00,0x3eff0000,0xbec6beb5,0x3ea2beb5,0x3e153efb,0xbef53dc8,0x3ee23e8e,0xbe713ed5,0xbe71beed,0x3ee2be44,0xbef5be44,0x3e15beed,0x3ea23ed5,0xbec63e8e,0x3eff3dc8,0xbd493efb,
0x3f00,0xbf000000,0x3f00,0xbf000000,0xbf00,0x3f000000,0xbf00,0x3f000000,0x3f00,0xbf000000,0x3f00,0xbf000000,0xbf00,0x3f000000,0xbf00,0x3f000000,
0x3d49bf00,0x3eff0000,0x3ec6beb5,0x3ea23eb5,0xbe153efb,0xbef5bdc8,0xbee23e8e,0xbe71bed5,0x3e71beed,0x3ee23e44,0x3ef5be44,0x3e153eed,0xbea23ed5,0xbec6be8e,0xbeff3dc8,0xbd49befb,
0xbdc83f00,0xbefb0000,0xbefb0000,0x3dc8bf00,0x3e8ebeed,0x3ed53e44,0x3ed53e44,0xbe8e3eed,0xbed53eb5,0xbe8ebeb5,0xbe8ebeb5,0x3ed5beb5,0x3efbbe44,0x3dc83eed,0x3dc83eed,0xbefb3e44,
0x3e15bf00,0x3ef50000,0x3e713eb5,0xbee23eb5,0xbec63ed5,0xbea2be8e,0x3d49befb,0x3effbdc8,0x3effbe44,0x3d493eed,0xbea23eed,0xbec6be44,0xbee2bdc8,0x3e71befb,0x3ef5be8e,0x3e153ed5,
0xbe443f00,0xbeed0000,0x3e44bf00,0x3eed0000,0x3eedbeb5,0x3e443eb5,0xbeed3eb5,0xbe44beb5,0xbeed0000,0x3e44bf00,0x3eed0000,0xbe443f00,0x3e443eb5,0xbeed3eb5,0xbe44beb5,0x3eedbeb5,
0x3e71bf00,0x3ee20000,0xbef53eb5,0xbe15beb5,0xbeff3e8e,0xbd49bed5,0x3ec63dc8,0xbea23efb,0x3ea23e44,0xbec63eed,0x3d49beed,0x3effbe44,0x3e15befb,0x3ef5bdc8,0xbee23ed5,0xbe71be8e,
0xbe8e3f00,0xbed50000,0x3ed50000,0xbe8e3f00,0x3efbbe44,0xbdc83eed,0x3dc8beed,0x3efbbe44,0xbdc8beb5,0x3efbbeb5,0xbefb3eb5,0xbdc8beb5,0xbed53eed,0xbe8ebe44,0x3e8e3e44,0xbed53eed,
0x3ea2bf00,0x3ec60000,0xbd49beb5,0x3effbeb5,0xbee23dc8,0x3e71befb,0xbef53ed5,0xbe15be8e,0xbe153eed,0xbef53e44,0x3e713e44,0xbee23eed,0x3effbe8e,0xbd493ed5,0x3ec6befb,0x3ea23dc8,
0xbeb53f00,0xbeb50000,0xbeb53f00,0xbeb50000,0x3eb50000,0xbeb53f00,0x3eb50000,0xbeb53f00,0x3eb5bf00,0x3eb50000,0x3eb5bf00,0x3eb50000,0xbeb50000,0x3eb5bf00,0xbeb50000,0x3eb5bf00,
0x3ec6bf00,0x3ea20000,0x3effbeb5,0xbd493eb5,0xbe71bdc8,0x3ee2befb,0x3e15bed5,0x3ef5be8e,0xbef53eed,0xbe15be44,0xbee23e44,0x3e71beed,0x3d493e8e,0xbeff3ed5,0xbea23efb,0xbec63dc8,
0xbed53f00,0xbe8e0000,0xbe8e0000,0x3ed5bf00,0x3dc83e44,0xbefb3eed,0xbefb3eed,0xbdc8be44,0x3efbbeb5,0xbdc83eb5,0xbdc83eb5,0xbefb3eb5,0x3e8ebeed,0x3ed5be44,0x3ed5be44,0xbe8e3eed,
0x3ee2bf00,0x3e710000,0xbe153eb5,0xbef53eb5,0x3d49be8e,0x3effbed5,0x3ea2bdc8,0xbec63efb,0xbec63e44,0x3ea2beed,0x3effbeed,0x3d493e44,0xbef53efb,0xbe15bdc8,0x3e71bed5,0x3ee2be8e,
0xbeed3f00,0xbe440000,0x3eedbf00,0x3e440000,0xbe443eb5,0xbeed3eb5,0x3e44beb5,0x3eedbeb5,0x3e440000,0xbeed3f00,0xbe440000,0x3eedbf00,0x3eedbeb5,0xbe443eb5,0xbeed3eb5,0x3e44beb5,
0x3ef5bf00,0x3e150000,0xbee23eb5,0x3e71beb5,0x3ea2bed5,0x3ec6be8e,0xbeff3efb,0xbd49bdc8,0x3d49be44,0x3effbeed,0xbec63eed,0xbea23e44,0xbe713dc8,0x3ee2befb,0xbe153e8e,0xbef53ed5,
0xbefb3f00,0xbdc80000,0x3dc80000,0xbefb3f00,0xbed53eed,0xbe8e3e44,0x3e8ebe44,0xbed53eed,0xbe8e3eb5,0xbed53eb5,0x3ed5beb5,0xbe8e3eb5,0xbdc83e44,0xbefb3eed,0x3efbbeed,0xbdc83e44,
0x3effbf00,0x3d490000,0x3ea2beb5,0x3ec6beb5,0x3ef5befb,0x3e15bdc8,0x3e71be8e,0x3ee2bed5,0x3ee2beed,0x3e71be44,0x3e15be44,0x3ef5beed,0x3ec6bed5,0x3ea2be8e,0x3d49bdc8,0x3effbefb,
0x3f003f00,0xbf003f00,0x3f003f00,0xbf003f00,0x3f003f00,0xbf003f00,0x3f003f00,0xbf003f00,0x3f003f00,0xbf003f00,0x3f003f00,0xbf003f00,0x3f003f00,0xbf003f00,0x3f003f00,0xbf003f00,
0x3d490000,0x3eff3f00,0x3ec63eb5,0x3ea23eb5,0x3e153dc8,0x3ef53efb,0x3ee23ed5,0x3e713e8e,0x3e713e44,0x3ee23eed,0x3ef53eed,0x3e153e44,0x3ea23e8e,0x3ec63ed5,0x3eff3efb,0x3d493dc8,
0xbefbbf00,0x3dc80000,0x3dc80000,0x3efb3f00,0xbed5beed,0x3e8e3e44,0x3e8e3e44,0x3ed53eed,0xbe8ebeb5,0x3ed53eb5,0x3ed53eb5,0x3e8e3eb5,0xbdc8be44,0x3efb3eed,0x3efb3eed,0x3dc83e44,
0xbe150000,0xbef5bf00,0xbe71beb5,0x3ee23eb5,0xbec6be8e,0xbea2bed5,0x3d49bdc8,0x3eff3efb,0xbeffbeed,0xbd49be44,0x3ea23e44,0x3ec63eed,0xbee2befb,0x3e713dc8,0x3ef53ed5,0x3e153e8e,
0x3eed3f00,0xbe440000,0xbeedbf00,0x3e440000,0x3e443eb5,0xbeedbeb5,0xbe44beb5,0x3eed3eb5,0xbe440000,0xbeedbf00,0x3e440000,0x3eed3f00,0xbeedbeb5,0xbe44beb5,0x3eed3eb5,0x3e443eb5,
0x3e710000,0x3ee23f00,0xbef5beb5,0xbe15beb5,0x3eff3ed5,0x3d493e8e,0xbec6befb,0x3ea23dc8,0x3ea23eed,0xbec6be44,0x3d49be44,0x3eff3eed,0xbe153dc8,0xbef5befb,0x3ee23e8e,0x3e713ed5,
0xbed5bf00,0x3e8e0000,0xbe8e0000,0xbed5bf00,0x3dc8be44,0x3efb3eed,0xbefbbeed,0x3dc8be44,0x3efb3eb5,0x3dc83eb5,0xbdc8beb5,0x3efb3eb5,0x3e8e3eed,0xbed5be44,0x3ed53e44,0x3e8e3eed,
0xbea20000,0xbec6bf00,0x3d493eb5,0xbeffbeb5,0xbee2befb,0x3e71bdc8,0xbef5be8e,0xbe15bed5,0x3e15be44,0x3ef53eed,0xbe71beed,0x3ee23e44,0x3eff3ed5,0xbd493e8e,0x3ec63dc8,0x3ea23efb,
0x3eb53f00,0xbeb50000,0x3eb53f00,0xbeb50000,0xbeb50000,0xbeb5bf00,0xbeb50000,0xbeb5bf00,0xbeb5bf00,0x3eb50000,0xbeb5bf00,0x3eb50000,0x3eb50000,0x3eb53f00,0x3eb50000,0x3eb53f00,
0x3ec60000,0x3ea23f00,0x3eff3eb5,0xbd493eb5,0x3e713efb,0xbee2bdc8,0xbe153e8e,0xbef5bed5,0xbef5be44,0xbe15beed,0xbee2beed,0x3e71be44,0xbd49bed5,0x3eff3e8e,0x3ea2bdc8,0x3ec63efb,
0xbe8ebf00,0x3ed50000,0x3ed50000,0x3e8e3f00,0x3efb3e44,0x3dc83eed,0x3dc83eed,0xbefbbe44,0xbdc83eb5,0xbefbbeb5,0xbefbbeb5,0x3dc8beb5,0xbed5beed,0x3e8ebe44,0x3e8ebe44,0x3ed53eed,
0xbee20000,0xbe71bf00,0x3e15beb5,0x3ef53eb5,0x3d49bed5,0x3eff3e8e,0x3ea23efb,0xbec63dc8,0x3ec63eed,0xbea23e44,0xbeffbe44,0xbd49beed,0xbef5bdc8,0xbe15befb,0x3e71be8e,0x3ee23ed5,
0x3e443f00,0xbeed0000,0xbe44bf00,0x3eed0000,0xbeedbeb5,0x3e44beb5,0x3eed3eb5,0xbe443eb5,0x3eed0000,0x3e443f00,0xbeed0000,0xbe44bf00,0xbe443eb5,0xbeedbeb5,0x3e44beb5,0x3eed3eb5,
0x3ef50000,0x3e153f00,0xbee2beb5,0x3e71beb5,0xbea23e8e,0xbec6bed5,0x3eff3dc8,0x3d493efb,0x3d49beed,0x3eff3e44,0xbec63e44,0xbea2beed,0x3e713efb,0xbee23dc8,0x3e15bed5,0x3ef53e8e,
0xbdc8bf00,0x3efb0000,0xbefb0000,0xbdc8bf00,0x3e8e3eed,0xbed53e44,0x3ed5be44,0x3e8e3eed,0xbed5beb5,0x3e8ebeb5,0xbe8e3eb5,0xbed5beb5,0x3efb3e44,0xbdc83eed,0x3dc8beed,0x3efb3e44,
0xbeff0000,0xbd49bf00,0xbea23eb5,0xbec6beb5,0x3ef5bdc8,0x3e153efb,0x3e71bed5,0x3ee23e8e,0xbee23e44,0xbe71beed,0xbe153eed,0xbef5be44,0x3ec6be8e,0x3ea23ed5,0x3d49befb,0x3eff3dc8,
0x3f00,0xbf000000,0x3f00,0xbf000000,0xbf00,0x3f000000,0xbf00,0x3f000000,0x3f00,0xbf000000,0x3f00,0xbf000000,0xbf00,0x3f000000,0xbf00,0x3f000000,
0x3eff0000,0xbd493f00,0x3ea23eb5,0xbec63eb5,0xbef5bdc8,0x3e15befb,0xbe71bed5,0x3ee2be8e,0x3ee23e44,0xbe713eed,0x3e153eed,0xbef53e44,0xbec6be8e,0x3ea2bed5,0xbd49befb,0x3effbdc8,
0x3dc8bf00,0x3efb0000,0x3efb0000,0xbdc83f00,0xbe8e3eed,0xbed5be44,0xbed5be44,0x3e8ebeed,0x3ed5beb5,0x3e8e3eb5,0x3e8e3eb5,0xbed53eb5,0xbefb3e44,0xbdc8beed,0xbdc8beed,0x3efbbe44,
0xbef50000,0x3e15bf00,0x3ee2beb5,0x3e713eb5,0x3ea23e8e,0xbec63ed5,0xbeff3dc8,0x3d49befb,0xbd49beed,0x3effbe44,0x3ec63e44,0xbea23eed,0xbe713efb,0xbee2bdc8,0xbe15bed5,0x3ef5be8e,
0xbe443f00,0xbeed0000,0x3e44bf00,0x3eed0000,0x3eedbeb5,0x3e443eb5,0xbeed3eb5,0xbe44beb5,0xbeed0000,0x3e44bf00,0x3eed0000,0xbe443f00,0x3e443eb5,0xbeed3eb5,0xbe44beb5,0x3eedbeb5,
0x3ee20000,0xbe713f00,0xbe15beb5,0x3ef5beb5,0xbd49bed5,0x3effbe8e,0xbea23efb,0xbec6bdc8,0xbec63eed,0xbea2be44,0x3effbe44,0xbd493eed,0x3ef5bdc8,0xbe153efb,0xbe71be8e,0x3ee2bed5,
0x3e8ebf00,0x3ed50000,0xbed50000,0x3e8ebf00,0xbefb3e44,0x3dc8beed,0xbdc83eed,0xbefb3e44,0x3dc83eb5,0xbefb3eb5,0x3efbbeb5,0x3dc83eb5,0x3ed5beed,0x3e8e3e44,0xbe8ebe44,0x3ed5beed,
0xbec60000,0x3ea2bf00,0xbeff3eb5,0xbd49beb5,0xbe713efb,0xbee23dc8,0x3e153e8e,0xbef53ed5,0x3ef5be44,0xbe153eed,0x3ee2beed,0x3e713e44,0x3d49bed5,0x3effbe8e,0xbea2bdc8,0x3ec6befb,
0xbeb53f00,0xbeb50000,0xbeb53f00,0xbeb50000,0x3eb50000,0xbeb53f00,0x3eb50000,0xbeb53f00,0x3eb5bf00,0x3eb50000,0x3eb5bf00,0x3eb50000,0xbeb50000,0x3eb5bf00,0xbeb50000,0x3eb5bf00,
0x3ea20000,0xbec63f00,0xbd493eb5,0xbeff3eb5,0x3ee2befb,0x3e713dc8,0x3ef5be8e,0xbe153ed5,0xbe15be44,0x3ef5beed,0x3e71beed,0x3ee2be44,0xbeff3ed5,0xbd49be8e,0xbec63dc8,0x3ea2befb,
0x3ed5bf00,0x3e8e0000,0x3e8e0000,0xbed53f00,0xbdc8be44,0x3efbbeed,0x3efbbeed,0x3dc83e44,0xbefb3eb5,0x3dc8beb5,0x3dc8beb5,0x3efbbeb5,0xbe8e3eed,0xbed53e44,0xbed53e44,0x3e8ebeed,
0xbe710000,0x3ee2bf00,0x3ef5beb5,0xbe153eb5,0xbeff3ed5,0x3d49be8e,0x3ec6befb,0x3ea2bdc8,0xbea23eed,0xbec63e44,0xbd49be44,0x3effbeed,0x3e153dc8,0xbef53efb,0xbee23e8e,0x3e71bed5,
0xbeed3f00,0xbe440000,0x3eedbf00,0x3e440000,0xbe443eb5,0xbeed3eb5,0x3e44beb5,0x3eedbeb5,0x3e440000,0xbeed3f00,0xbe440000,0x3eedbf00,0x3eedbeb5,0xbe443eb5,0xbeed3eb5,0x3e44beb5,
0x3e150000,0xbef53f00,0x3e71beb5,0x3ee2beb5,0x3ec6be8e,0xbea23ed5,0xbd49bdc8,0x3effbefb,0x3effbeed,0xbd493e44,0xbea23e44,0x3ec6beed,0x3ee2befb,0x3e71bdc8,0xbef53ed5,0x3e15be8e,
0x3efbbf00,0x3dc80000,0xbdc80000,0x3efbbf00,0x3ed5beed,0x3e8ebe44,0xbe8e3e44,0x3ed5beed,0x3e8ebeb5,0x3ed5beb5,0xbed53eb5,0x3e8ebeb5,0x3dc8be44,0x3efbbeed,0xbefb3eed,0x3dc8be44,
0xbd490000,0x3effbf00,0xbec63eb5,0x3ea2beb5,0xbe153dc8,0x3ef5befb,0xbee23ed5,0x3e71be8e,0xbe713e44,0x3ee2beed,0xbef53eed,0x3e15be44,0xbea23e8e,0x3ec6bed5,0xbeff3efb,0x3d49bdc8,
0x3f800000,0x0,0x3f800000,0x0,0x3f800000,0x0,0x3f800000,0x0,0x3f800000,0x0,0x3f800000,0x0,0x3f800000,0x0,0x3f800000,0x0,
0x3f800000,0x0,0x3f7ffec4,0xbbc90f88,0x3f7ffb11,0xbc490e90,0x3f7ff4e6,0xbc96c9b6,0x3f7fec43,0xbcc90ab0,0x3f7fe129,0xbcfb49ba,0x3f7fd397,0xbd16c32c,0x3f7fc38f,0xbd2fe007,
0x3f800000,0x0,0x3f7ffb11,0xbc490e90,0x3f7fec43,0xbcc90ab0,0x3f7fd397,0xbd16c32c,0x3f7fb10f,0xbd48fb30,0x3f7f84ab,0xbd7b2b74,0x3f7f4e6d,0xbd96a905,0x3f7f0e58,0xbdafb680,
0x3f800000,0x0,0x3f7ff4e6,0xbc96c9b6,0x3f7fd397,0xbd16c32c,0x3f7f9c18,0xbd621469,0x3f7f4e6d,0xbd96a905,0x3f7eea9d,0xbdbc3ac3,0x3f7e70b0,0xbde1bc2e,0x3f7de0b1,0xbe039502,
0x3f800000,0x0,0x3f7fec43,0xbcc90ab0,0x3f7fb10f,0xbd48fb30,0x3f7f4e6d,0xbd96a905,0x3f7ec46d,0xbdc8bd36,0x3f7e1324,0xbdfab273,0x3f7d3aac,0xbe164083,0x3f7c3b28,0xbe2f10a2,
0x3f800000,0x0,0x3f7fe129,0xbcfb49ba,0x3f7f84ab,0xbd7b2b74,0x3f7eea9d,0xbdbc3ac3,0x3f7e1324,0xbdfab273,0x3f7cfe73,0xbe1c76de,0x3f7baccd,0xbe3b6ecf,0x3f7a1e84,0xbe5a3997,
0x3f800000,0x0,0x3f7fd397,0xbd16c32c,0x3f7f4e6d,0xbd96a905,0x3f7e70b0,0xbde1bc2e,0x3f7d3aac,0xbe164083,0x3f7baccd,0xbe3b6ecf,0x3f79c79d,0xbe605c13,0x3f778bc5,0xbe827dc0,
0x3f800000,0x0,0x3f7fc38f,0xbd2fe007,0x3f7f0e58,0xbdafb680,0x3f7de0b1,0xbe039502,0x3f7c3b28,0xbe2f10a2,0x3f7a1e84,0xbe5a3997,0x3f778bc5,0xbe827dc0,0x3f748422,0xbe97a117,
0x3f800000,0x0,0x3f7fb10f,0xbd48fb30,0x3f7ec46d,0xbdc8bd36,0x3f7d3aac,0xbe164083,0x3f7b14be,0xbe47c5c2,0x3f7853f8,0xbe78cfcc,0x3f74fa0b,0xbe94a031,0x3f710908,0xbeac7cd4,
0x3f800000,0x0,0x3f7f9c18,0xbd621469,0x3f7e70b0,0xbde1bc2e,0x3f7c7eb0,0xbe28defc,0x3f79c79d,0xbe605c13,0x3f764d97,0xbe8b9507,0x3f721352,0xbea68f12,0x3f6d1c1d,0xbec1071e,
0x3f800000,0x0,0x3f7f84ab,0xbd7b2b74,0x3f7e1324,0xbdfab273,0x3f7baccd,0xbe3b6ecf,0x3f7853f8,0xbe78cfcc,0x3f740bdd,0xbe9aa086,0x3f6ed89e,0xbeb8442a,0x3f68bf3c,0xbed53641,
0x3f800000,0x0,0x3f7f6ac7,0xbd8a200a,0x3f7dabcc,0xbe09cf86,0x3f7ac516,0xbe4dee60,0x3f76ba07,0xbe888e93,0x3f718f57,0xbea986c4,0x3f6b4b0c,0xbec9b953,0x3f63f473,0xbee900b7,
0x3f800000,0x0,0x3f7f4e6d,0xbd96a905,0x3f7d3aac,0xbe164083,0x3f79c79d,0xbe605c13,0x3f74fa0b,0xbe94a031,0x3f6ed89e,0xbeb8442a,0x3f676bd8,0xbedae880,0x3f5ebe05,0xbefc5d27,
0x3f800000,0x0,0x3f7f2f9d,0xbda3308c,0x3f7cbfc9,0xbe22abb6,0x3f78b47b,0xbe72b651,0x3f731447,0xbea09ae5,0x3f6be858,0xbec6d529,0x3f633c5a,0xbeebcbbb,0x3f591e6a,0xbf07a136,
0x3f800000,0x0,0x3f7f0e58,0xbdafb680,0x3f7c3b28,0xbe2f10a2,0x3f778bc5,0xbe827dc0,0x3f710908,0xbeac7cd4,0x3f68bf3c,0xbed53641,0x3f5ebe05,0xbefc5d27,0x3f531849,0xbf10d3cd,
0x3f800000,0x0,0x3f7eea9d,0xbdbc3ac3,0x3f7baccd,0xbe3b6ecf,0x3f764d97,0xbe8b9507,0x3f6ed89e,0xbeb8442a,0x3f655e0b,0xbee363fa,0x3f59f26a,0xbf064b82,0x3f4cae79,0xbf19c200,
0x3f800000,0x0,0x3f7ec46d,0xbdc8bd36,0x3f7b14be,0xbe47c5c2,0x3f74fa0b,0xbe94a031,0x3f6c835e,0xbec3ef15,0x3f61c598,0xbef15aea,0x3f54db31,0xbf0e39da,0x3f45e403,0xbf226799,
0x3f800000,0x0,0x3f7e9bc9,0xbdd53db9,0x3f7a7302,0xbe541501,0x3f73913f,0xbe9d9e78,0x3f6a09a7,0xbecf7bca,0x3f5df6be,0xbeff17b2,0x3f4f7a1f,0xbf15f6d9,0x3f3ebc1b,0xbf2ac082,
0x3f800000,0x0,0x3f7e70b0,0xbde1bc2e,0x3f79c79d,0xbe605c13,0x3f721352,0xbea68f12,0x3f676bd8,0xbedae880,0x3f59f26a,0xbf064b82,0x3f49d112,0xbf1d7fd1,0x3f373a23,0xbf32c8c9,
0x3f800000,0x0,0x3f7e4323,0xbdee3876,0x3f791298,0xbe6c9a7f,0x3f708066,0xbeaf713a,0x3f64aa59,0xbee63375,0x3f55b993,0xbf0cead0,0x3f43e200,0xbf24d225,0x3f2f61a5,0xbf3a7ca4,
0x3f800000,0x0,0x3f7e1324,0xbdfab273,0x3f7853f8,0xbe78cfcc,0x3f6ed89e,0xbeb8442a,0x3f61c598,0xbef15aea,0x3f514d3d,0xbf13682a,0x3f3daef9,0xbf2beb4a,0x3f273656,0xbf41d870,
0x3f800000,0x0,0x3f7de0b1,0xbe039502,0x3f778bc5,0xbe827dc0,0x3f6d1c1d,0xbec1071e,0x3f5ebe05,0xbefc5d27,0x3f4cae79,0xbf19c200,0x3f373a23,0xbf32c8c9,0x3f1ebc12,0xbf48d8b3,
0x3f800000,0x0,0x3f7dabcc,0xbe09cf86,0x3f76ba07,0xbe888e93,0x3f6b4b0c,0xbec9b953,0x3f5b941a,0xbf039c3d,0x3f47de65,0xbf1ff6cb,0x3f3085bb,0xbf396842,0x3f15f6d9,0xbf4f7a1f,
0x3f800000,0x0,0x3f7d7474,0xbe1008b7,0x3f75dec6,0xbe8e9a22,0x3f696591,0xbed25a09,0x3f584853,0xbf08f59b,0x3f42de29,0xbf26050a,0x3f299415,0xbf3fc767,0x3f0cead0,0xbf55b993,
0x3f800000,0x0,0x3f7d3aac,0xbe164083,0x3f74fa0b,0xbe94a031,0x3f676bd8,0xbedae880,0x3f54db31,0xbf0e39da,0x3f3daef9,0xbf2beb4a,0x3f226799,0xbf45e403,0x3f039c3d,0xbf5b941a,
0x3f800000,0x0,0x3f7cfe73,0xbe1c76de,0x3f740bdd,0xbe9aa086,0x3f655e0b,0xbee363fa,0x3f514d3d,0xbf13682a,0x3f385216,0xbf31a81d,0x3f1b02c6,0xbf4bbbf8,0x3ef41f07,0xbf6106f2,
0x3f800000,0x0,0x3f7cbfc9,0xbe22abb6,0x3f731447,0xbea09ae5,0x3f633c5a,0xbeebcbbb,0x3f4d9f02,0xbf187fc0,0x3f32c8c9,0xbf373a23,0x3f13682a,0xbf514d3d,0x3ee0924f,0xbf660f88,
0x3f800000,0x0,0x3f7c7eb0,0xbe28defc,0x3f721352,0xbea68f12,0x3f6106f2,0xbef41f07,0x3f49d112,0xbf1d7fd1,0x3f2d1469,0xbf3ca003,0x3f0b9a6b,0xbf5695e5,0x3ecc9b8b,0xbf6aab7b,
0x3f800000,0x0,0x3f7c3b28,0xbe2f10a2,0x3f710908,0xbeac7cd4,0x3f5ebe05,0xbefc5d27,0x3f45e403,0xbf226799,0x3f273656,0xbf41d870,0x3f039c3d,0xbf5b941a,0x3eb8442a,0xbf6ed89e,
0x3f800000,0x0,0x3f7bf531,0xbe354098,0x3f6ff573,0xbeb263ef,0x3f5c61c7,0xbf0242b1,0x3f41d870,0xbf273656,0x3f212ff9,0xbf46e22a,0x3ef6e0cb,0xbf604621,0x3ea395c5,0xbf7294f8,
0x3f800000,0x0,0x3f7baccd,0xbe3b6ecf,0x3f6ed89e,0xbeb8442a,0x3f59f26a,0xbf064b82,0x3f3daef9,0xbf2beb4a,0x3f1b02c6,0xbf4bbbf8,0x3ee63375,0xbf64aa59,0x3e8e9a22,0xbf75dec6,
0x3f800000,0x0,0x3f7b61fc,0xbe419b37,0x3f6db293,0xbebe1d4a,0x3f577026,0xbf0a48ad,0x3f396842,0xbf3085bb,0x3f14b039,0xbf5064af,0x3ed53641,0xbf68bf3c,0x3e72b651,0xbf78b47b,
0x3f800000,0x0,0x3f800000,0x0,0x3f800000,0x0,0x3f800000,0x0,0x3f800000,0x0,0x3f800000,0x0,0x3f800000,0x0,0x3f800000,0x0,
0x3f7fb10f,0xbd48fb30,0x3f7f9c18,0xbd621469,0x3f7f84ab,0xbd7b2b74,0x3f7f6ac7,0xbd8a200a,0x3f7f4e6d,0xbd96a905,0x3f7f2f9d,0xbda3308c,0x3f7f0e58,0xbdafb680,0x3f7eea9d,0xbdbc3ac3,
0x3f7ec46d,0xbdc8bd36,0x3f7e70b0,0xbde1bc2e,0x3f7e1324,0xbdfab273,0x3f7dabcc,0xbe09cf86,0x3f7d3aac,0xbe164083,0x3f7cbfc9,0xbe22abb6,0x3f7c3b28,0xbe2f10a2,0x3f7baccd,0xbe3b6ecf,
0x3f7d3aac,0xbe164083,0x3f7c7eb0,0xbe28defc,0x3f7baccd,0xbe3b6ecf,0x3f7ac516,0xbe4dee60,0x3f79c79d,0xbe605c13,0x3f78b47b,0xbe72b651,0x3f778bc5,0xbe827dc0,0x3f764d97,0xbe8b9507,
0x3f7b14be,0xbe47c5c2,0x3f79c79d,0xbe605c13,0x3f7853f8,0xbe78cfcc,0x3f76ba07,0xbe888e93,0x3f74fa0b,0xbe94a031,0x3f731447,0xbea09ae5,0x3f710908,0xbeac7cd4,0x3f6ed89e,0xbeb8442a,
0x3f7853f8,0xbe78cfcc,0x3f764d97,0xbe8b9507,0x3f740bdd,0xbe9aa086,0x3f718f57,0xbea986c4,0x3f6ed89e,0xbeb8442a,0x3f6be858,0xbec6d529,0x3f68bf3c,0xbed53641,0x3f655e0b,0xbee363fa,
0x3f74fa0b,0xbe94a031,0x3f721352,0xbea68f12,0x3f6ed89e,0xbeb8442a,0x3f6b4b0c,0xbec9b953,0x3f676bd8,0xbedae880,0x3f633c5a,0xbeebcbbb,0x3f5ebe05,0xbefc5d27,0x3f59f26a,0xbf064b82,
0x3f710908,0xbeac7cd4,0x3f6d1c1d,0xbec1071e,0x3f68bf3c,0xbed53641,0x3f63f473,0xbee900b7,0x3f5ebe05,0xbefc5d27,0x3f591e6a,0xbf07a136,0x3f531849,0xbf10d3cd,0x3f4cae79,0xbf19c200,
0x3f6c835e,0xbec3ef15,0x3f676bd8,0xbedae880,0x3f61c598,0xbef15aea,0x3f5b941a,0xbf039c3d,0x3f54db31,0xbf0e39da,0x3f4d9f02,0xbf187fc0,0x3f45e403,0xbf226799,0x3f3daef9,0xbf2beb4a,
0x3f676bd8,0xbedae880,0x3f6106f2,0xbef41f07,0x3f59f26a,0xbf064b82,0x3f5233c6,0xbf121eb0,0x3f49d112,0xbf1d7fd1,0x3f40d0da,0xbf286605,0x3f373a23,0xbf32c8c9,0x3f2d1469,0xbf3ca003,
0x3f61c598,0xbef15aea,0x3f59f26a,0xbf064b82,0x3f514d3d,0xbf13682a,0x3f47de65,0xbf1ff6cb,0x3f3daef9,0xbf2beb4a,0x3f32c8c9,0xbf373a23,0x3f273656,0xbf41d870,0x3f1b02c6,0xbf4bbbf8,
0x3f5b941a,0xbf039c3d,0x3f5233c6,0xbf121eb0,0x3f47de65,0xbf1ff6cb,0x3f3ca003,0xbf2d1469,0x3f3085bb,0xbf396842,0x3f239da9,0xbf44e3f5,0x3f15f6d9,0xbf4f7a1f,0x3f07a136,0xbf591e6a,
0x3f54db31,0xbf0e39da,0x3f49d112,0xbf1d7fd1,0x3f3daef9,0xbf2beb4a,0x3f3085bb,0xbf396842,0x3f226799,0xbf45e403,0x3f13682a,0xbf514d3d,0x3f039c3d,0xbf5b941a,0x3ee63375,0xbf64aa59,
0x3f4d9f02,0xbf187fc0,0x3f40d0da,0xbf286605,0x3f32c8c9,0xbf373a23,0x3f239da9,0xbf44e3f5,0x3f13682a,0xbf514d3d,0x3f0242b1,0xbf5c61c7,0x3ee0924f,0xbf660f88,0x3ebb31a0,0xbf6e46be,
0x3f45e403,0xbf226799,0x3f373a23,0xbf32c8c9,0x3f273656,0xbf41d870,0x3f15f6d9,0xbf4f7a1f,0x3f039c3d,0xbf5b941a,0x3ee0924f,0xbf660f88,0x3eb8442a,0xbf6ed89e,0x3e8e9a22,0xbf75dec6,
0x3f3daef9,0xbf2beb4a,0x3f2d1469,0xbf3ca003,0x3f1b02c6,0xbf4bbbf8,0x3f07a136,0xbf591e6a,0x3ee63375,0xbf64aa59,0x3ebb31a0,0xbf6e46be,0x3e8e9a22,0xbf75dec6,0x3e419b37,0xbf7b61fc,
0x3f3504f3,0xbf3504f3,0x3f226799,0xbf45e403,0x3f0e39da,0xbf54db31,0x3ef15aea,0xbf61c598,0x3ec3ef15,0xbf6c835e,0x3e94a031,0xbf74fa0b,0x3e47c5c2,0xbf7b14be,0x3dc8bd36,0xbf7ec46d,
0x3f2beb4a,0xbf3daef9,0x3f173c07,0xbf4e8d90,0x3f00e7e4,0xbf5d2d53,0x3ed25a09,0xbf696591,0x3ea09ae5,0xbf731447,0x3e5a3997,0xbf7a1e84,0x3de1bc2e,0xbf7e70b0,0x3bc90f88,0xbf7ffec4,
0x3f226799,0xbf45e403,0x3f0b9a6b,0xbf5695e5,0x3ee63375,0xbf64aa59,0x3eb263ef,0xbf6ff573,0x3e78cfcc,0xbf7853f8,0x3e09cf86,0xbf7dabcc,0x3cc90ab0,0xbf7fec43,0xbdafb680,0xbf7f0e58,
0x3f187fc0,0xbf4d9f02,0x3eff17b2,0xbf5df6be,0x3ec9b953,0xbf6b4b0c,0x3e919ddd,0xbf756d97,0x3e2f10a2,0xbf7c3b28,0x3d621469,0xbf7f9c18,0xbd7b2b74,0xbf7f84ab,0xbe354098,0xbf7bf531,
0x3f0e39da,0xbf54db31,0x3ee63375,0xbf64aa59,0x3eac7cd4,0xbf710908,0x3e605c13,0xbf79c79d,0x3dc8bd36,0xbf7ec46d,0xbcc90ab0,0xbf7fec43,0xbe164083,0xbf7d3aac,0xbe888e93,0xbf76ba07,
0x3f039c3d,0xbf5b941a,0x3ecc9b8b,0xbf6aab7b,0x3e8e9a22,0xbf75dec6,0x3e1c76de,0xbf7cfe73,0x3cc90ab0,0xbf7fec43,0xbdd53db9,0xbf7e9bc9,0xbe6c9a7f,0xbf791298,0xbeb554ec,0xbf6f6830,
0x3ef15aea,0xbf61c598,0x3eb263ef,0xbf6ff573,0x3e605c13,0xbf79c79d,0x3dafb680,0xbf7f0e58,0xbd48fb30,0xbf7fb10f,0xbe3b6ecf,0xbf7baccd,0xbea09ae5,0xbf731447,0xbee0924f,0xbf660f88,
0x3edae880,0xbf676bd8,0x3e97a117,0xbf748422,0x3e22abb6,0xbf7cbfc9,0x3c96c9b6,0xbf7ff4e6,0xbdfab273,0xbf7e1324,0xbe8586ce,0xbf772417,0xbec9b953,0xbf6b4b0c,0xbf04f484,0xbf5ac450,
0x3ec3ef15,0xbf6c835e,0x3e78cfcc,0xbf7853f8,0x3dc8bd36,0xbf7ec46d,0xbd48fb30,0xbf7fb10f,0xbe47c5c2,0xbf7b14be,0xbeac7cd4,0xbf710908,0xbef15aea,0xbf61c598,0xbf187fc0,0xbf4d9f02,
0x3eac7cd4,0xbf710908,0x3e419b37,0xbf7b61fc,0x3d16c32c,0xbf7fd397,0xbdee3876,0xbf7e4323,0xbe888e93,0xbf76ba07,0xbed25a09,0xbf696591,0xbf0b9a6b,0xbf5695e5,0xbf2ac082,0xbf3ebc1b,
0x3e94a031,0xbf74fa0b,0x3e09cf86,0xbf7dabcc,0xbcc90ab0,0xbf7fec43,0xbe3b6ecf,0xbf7baccd,0xbeac7cd4,0xbf710908,0xbef6e0cb,0xbf604621,0xbf1d7fd1,0xbf49d112,0xbf3b8f3b,0xbf2e3bde,
0x3e78cfcc,0xbf7853f8,0x3da3308c,0xbf7f2f9d,0xbdafb680,0xbf7f0e58,0xbe7ee6e1,0xbf77f110,0xbecf7bca,0xbf6a09a7,0xbf0cead0,0xbf55b993,0xbf2e3bde,0xbf3b8f3b,0xbf4ac77f,0xbf1c420c,
0x3e47c5c2,0xbf7b14be,0x3cc90ab0,0xbf7fec43,0xbe164083,0xbf7d3aac,0xbea09ae5,0xbf731447,0xbef15aea,0xbf61c598,0xbf1d7fd1,0xbf49d112,0xbf3daef9,0xbf2beb4a,0xbf584853,0xbf08f59b,
0x3e164083,0xbf7d3aac,0xbcfb49ba,0xbf7fe129,0xbe541501,0xbf7a7302,0xbec1071e,0xbf6d1c1d,0xbf08f59b,0xbf584853,0xbf2d1469,0xbf3ca003,0xbf4bbbf8,0xbf1b02c6,0xbf63f473,0xbee900b7,
0x3dc8bd36,0xbf7ec46d,0xbdafb680,0xbf7f0e58,0xbe888e93,0xbf76ba07,0xbee0924f,0xbf660f88,0xbf187fc0,0xbf4d9f02,0xbf3b8f3b,0xbf2e3bde,0xbf584853,0xbf08f59b,0xbf6db293,0xbebe1d4a,
0x3d48fb30,0xbf7fb10f,0xbe1008b7,0xbf7d7474,0xbea68f12,0xbf721352,0xbeff17b2,0xbf5df6be,0xbf273656,0xbf41d870,0xbf48d8b3,0xbf1ebc12,0xbf633c5a,0xbeebcbbb,0xbf756d97,0xbe919ddd,
0x3f800000,0x0,0x3f800000,0x0,0x3f800000,0x0,0x3f800000,0x0,0x3f800000,0x0,0x3f800000,0x0,0x3f800000,0x0,0x3f800000,0x0,
0x3f7ec46d,0xbdc8bd36,0x3f7e9bc9,0xbdd53db9,0x3f7e70b0,0xbde1bc2e,0x3f7e4323,0xbdee3876,0x3f7e1324,0xbdfab273,0x3f7de0b1,0xbe039502,0x3f7dabcc,0xbe09cf86,0x3f7d7474,0xbe1008b7,
0x3f7b14be,0xbe47c5c2,0x3f7a7302,0xbe541501,0x3f79c79d,0xbe605c13,0x3f791298,0xbe6c9a7f,0x3f7853f8,0xbe78cfcc,0x3f778bc5,0xbe827dc0,0x3f76ba07,0xbe888e93,0x3f75dec6,0xbe8e9a22,
0x3f74fa0b,0xbe94a031,0x3f73913f,0xbe9d9e78,0x3f721352,0xbea68f12,0x3f708066,0xbeaf713a,0x3f6ed89e,0xbeb8442a,0x3f6d1c1d,0xbec1071e,0x3f6b4b0c,0xbec9b953,0x3f696591,0xbed25a09,
0x3f6c835e,0xbec3ef15,0x3f6a09a7,0xbecf7bca,0x3f676bd8,0xbedae880,0x3f64aa59,0xbee63375,0x3f61c598,0xbef15aea,0x3f5ebe05,0xbefc5d27,0x3f5b941a,0xbf039c3d,0x3f584853,0xbf08f59b,
0x3f61c598,0xbef15aea,0x3f5df6be,0xbeff17b2,0x3f59f26a,0xbf064b82,0x3f55b993,0xbf0cead0,0x3f514d3d,0xbf13682a,0x3f4cae79,0xbf19c200,0x3f47de65,0xbf1ff6cb,0x3f42de29,0xbf26050a,
0x3f54db31,0xbf0e39da,0x3f4f7a1f,0xbf15f6d9,0x3f49d112,0xbf1d7fd1,0x3f43e200,0xbf24d225,0x3f3daef9,0xbf2beb4a,0x3f373a23,0xbf32c8c9,0x3f3085bb,0xbf396842,0x3f299415,0xbf3fc767,
0x3f45e403,0xbf226799,0x3f3ebc1b,0xbf2ac082,0x3f373a23,0xbf32c8c9,0x3f2f61a5,0xbf3a7ca4,0x3f273656,0xbf41d870,0x3f1ebc12,0xbf48d8b3,0x3f15f6d9,0xbf4f7a1f,0x3f0cead0,0xbf55b993,
0x3f3504f3,0xbf3504f3,0x3f2beb4a,0xbf3daef9,0x3f226799,0xbf45e403,0x3f187fc0,0xbf4d9f02,0x3f0e39da,0xbf54db31,0x3f039c3d,0xbf5b941a,0x3ef15aea,0xbf61c598,0x3edae880,0xbf676bd8,
0x3f226799,0xbf45e403,0x3f173c07,0xbf4e8d90,0x3f0b9a6b,0xbf5695e5,0x3eff17b2,0xbf5df6be,0x3ee63375,0xbf64aa59,0x3ecc9b8b,0xbf6aab7b,0x3eb263ef,0xbf6ff573,0x3e97a117,0xbf748422,
0x3f0e39da,0xbf54db31,0x3f00e7e4,0xbf5d2d53,0x3ee63375,0xbf64aa59,0x3ec9b953,0xbf6b4b0c,0x3eac7cd4,0xbf710908,0x3e8e9a22,0xbf75dec6,0x3e605c13,0xbf79c79d,0x3e22abb6,0xbf7cbfc9,
0x3ef15aea,0xbf61c598,0x3ed25a09,0xbf696591,0x3eb263ef,0xbf6ff573,0x3e919ddd,0xbf756d97,0x3e605c13,0xbf79c79d,0x3e1c76de,0xbf7cfe73,0x3dafb680,0xbf7f0e58,0x3c96c9b6,0xbf7ff4e6,
0x3ec3ef15,0xbf6c835e,0x3ea09ae5,0xbf731447,0x3e78cfcc,0xbf7853f8,0x3e2f10a2,0xbf7c3b28,0x3dc8bd36,0xbf7ec46d,0x3cc90ab0,0xbf7fec43,0xbd48fb30,0xbf7fb10f,0xbdfab273,0xbf7e1324,
0x3e94a031,0xbf74fa0b,0x3e5a3997,0xbf7a1e84,0x3e09cf86,0xbf7dabcc,0x3d621469,0xbf7f9c18,0xbcc90ab0,0xbf7fec43,0xbdd53db9,0xbf7e9bc9,0xbe3b6ecf,0xbf7baccd,0xbe8586ce,0xbf772417,
0x3e47c5c2,0xbf7b14be,0x3de1bc2e,0xbf7e70b0,0x3cc90ab0,0xbf7fec43,0xbd7b2b74,0xbf7f84ab,0xbe164083,0xbf7d3aac,0xbe6c9a7f,0xbf791298,0xbea09ae5,0xbf731447,0xbec9b953,0xbf6b4b0c,
0x3dc8bd36,0xbf7ec46d,0x3bc90f88,0xbf7ffec4,0xbdafb680,0xbf7f0e58,0xbe354098,0xbf7bf531,0xbe888e93,0xbf76ba07,0xbeb554ec,0xbf6f6830,0xbee0924f,0xbf660f88,0xbf04f484,0xbf5ac450,
0x0,0xbf800000,0xbdc8bd36,0xbf7ec46d,0xbe47c5c2,0xbf7b14be,0xbe94a031,0xbf74fa0b,0xbec3ef15,0xbf6c835e,0xbef15aea,0xbf61c598,0xbf0e39da,0xbf54db31,0xbf226799,0xbf45e403,
0xbdc8bd36,0xbf7ec46d,0xbe4dee60,0xbf7ac516,0xbe9aa086,0xbf740bdd,0xbecc9b8b,0xbf6aab7b,0xbefc5d27,0xbf5ebe05,0xbf14b039,0xbf5064af,0xbf299415,0xbf3fc767,0xbf3ca003,0xbf2d1469,
0xbe47c5c2,0xbf7b14be,0xbe9aa086,0xbf740bdd,0xbecf7bca,0xbf6a09a7,0xbf00e7e4,0xbf5d2d53,0xbf187fc0,0xbf4d9f02,0xbf2e3bde,0xbf3b8f3b,0xbf41d870,0xbf273656,0xbf531849,0xbf10d3cd,
0xbe94a031,0xbf74fa0b,0xbecc9b8b,0xbf6aab7b,0xbf00e7e4,0xbf5d2d53,0xbf19c200,0xbf4cae79,0xbf3085bb,0xbf396842,0xbf44e3f5,0xbf239da9,0xbf5695e5,0xbf0b9a6b,0xbf655e0b,0xbee363fa,
0xbec3ef15,0xbf6c835e,0xbefc5d27,0xbf5ebe05,0xbf187fc0,0xbf4d9f02,0xbf3085bb,0xbf396842,0xbf45e403,0xbf226799,0xbf584853,0xbf08f59b,0xbf676bd8,0xbedae880,0xbf731447,0xbea09ae5,
0xbef15aea,0xbf61c598,0xbf14b039,0xbf5064af,0xbf2e3bde,0xbf3b8f3b,0xbf44e3f5,0xbf239da9,0xbf584853,0xbf08f59b,0xbf6816a8,0xbed8106b,0xbf740bdd,0xbe9aa086,0xbf7bf531,0xbe354098,
0xbf0e39da,0xbf54db31,0xbf299415,0xbf3fc767,0xbf41d870,0xbf273656,0xbf5695e5,0xbf0b9a6b,0xbf676bd8,0xbedae880,0xbf740bdd,0xbe9aa086,0xbf7c3b28,0xbe2f10a2,0xbf7fd397,0xbd16c32c,
0xbf226799,0xbf45e403,0xbf3ca003,0xbf2d1469,0xbf531849,0xbf10d3cd,0xbf655e0b,0xbee363fa,0xbf731447,0xbea09ae5,0xbf7bf531,0xbe354098,0xbf7fd397,0xbd16c32c,0xbf7e9bc9,0x3dd53db9,
0xbf3504f3,0xbf3504f3,0xbf4d9f02,0xbf187fc0,0xbf61c598,0xbef15aea,0xbf710908,0xbeac7cd4,0xbf7b14be,0xbe47c5c2,0xbf7fb10f,0xbd48fb30,0xbf7ec46d,0x3dc8bd36,0xbf7853f8,0x3e78cfcc,
0xbf45e403,0xbf226799,0xbf5c61c7,0xbf0242b1,0xbf6db293,0xbebe1d4a,0xbf796e4e,0xbe667c66,0xbf7f4e6d,0xbd96a905,0xbf7f2f9d,0x3da3308c,0xbf791298,0x3e6c9a7f,0xbf6d1c1d,0x3ec1071e,
0xbf54db31,0xbf0e39da,0xbf68bf3c,0xbed53641,0xbf76ba07,0xbe888e93,0xbf7e70b0,0xbde1bc2e,0xbf7fb10f,0x3d48fb30,0xbf7a7302,0x3e541501,0xbf6ed89e,0x3eb8442a,0xbf5d2d53,0x3f00e7e4,
0xbf61c598,0xbef15aea,0xbf7294f8,0xbea395c5,0xbf7cbfc9,0xbe22abb6,0xbf7ffec4,0x3bc90f88,0xbf7c3b28,0x3e2f10a2,0xbf718f57,0x3ea986c4,0xbf604621,0x3ef6e0cb,0xbf48d8b3,0x3f1ebc12,
0xbf6c835e,0xbec3ef15,0xbf79c79d,0xbe605c13,0xbf7fb10f,0xbd48fb30,0xbf7e1324,0x3dfab273,0xbf74fa0b,0x3e94a031,0xbf64aa59,0x3ee63375,0xbf4d9f02,0x3f187fc0,0xbf3085bb,0x3f396842,
0xbf74fa0b,0xbe94a031,0xbf7e4323,0xbdee3876,0xbf7f84ab,0x3d7b2b74,0xbf78b47b,0x3e72b651,0xbf6a09a7,0x3ecf7bca,0xbf53fac3,0x3f0f8784,0xbf373a23,0x3f32c8c9,0xbf14b039,0x3f5064af,
0xbf7b14be,0xbe47c5c2,0xbf7ffb11,0xbc490e90,0xbf7c3b28,0x3e2f10a2,0xbf6ff573,0x3eb263ef,0xbf5b941a,0x3f039c3d,0xbf3fc767,0x3f299415,0xbf1d7fd1,0x3f49d112,0xbeebcbbb,0x3f633c5a,
0xbf7ec46d,0xbdc8bd36,0xbf7eea9d,0x3dbc3ac3,0xbf75dec6,0x3e8e9a22,0xbf63f473,0x3ee900b7,0xbf49d112,0x3f1d7fd1,0xbf286605,0x3f40d0da,0xbf00e7e4,0x3f5d2d53,0xbea986c4,0x3f718f57,
0x3f800000,0x0,0x3f800000,0x0,0x3f800000,0x0,0x3f800000,0x0,0x3f800000,0x0,0x3f800000,0x0,0x3f800000,0x0,0x3f800000,0x0,
0x3f7d3aac,0xbe164083,0x3f7cfe73,0xbe1c76de,0x3f7cbfc9,0xbe22abb6,0x3f7c7eb0,0xbe28defc,0x3f7c3b28,0xbe2f10a2,0x3f7bf531,0xbe354098,0x3f7baccd,0xbe3b6ecf,0x3f7b61fc,0xbe419b37,
0x3f74fa0b,0xbe94a031,0x3f740bdd,0xbe9aa086,0x3f731447,0xbea09ae5,0x3f721352,0xbea68f12,0x3f710908,0xbeac7cd4,0x3f6ff573,0xbeb263ef,0x3f6ed89e,0xbeb8442a,0x3f6db293,0xbebe1d4a,
0x3f676bd8,0xbedae880,0x3f655e0b,0xbee363fa,0x3f633c5a,0xbeebcbbb,0x3f6106f2,0xbef41f07,0x3f5ebe05,0xbefc5d27,0x3f5c61c7,0xbf0242b1,0x3f59f26a,0xbf064b82,0x3f577026,0xbf0a48ad,
0x3f54db31,0xbf0e39da,0x3f514d3d,0xbf13682a,0x3f4d9f02,0xbf187fc0,0x3f49d112,0xbf1d7fd1,0x3f45e403,0xbf226799,0x3f41d870,0xbf273656,0x3f3daef9,0xbf2beb4a,0x3f396842,0xbf3085bb,
0x3f3daef9,0xbf2beb4a,0x3f385216,0xbf31a81d,0x3f32c8c9,0xbf373a23,0x3f2d1469,0xbf3ca003,0x3f273656,0xbf41d870,0x3f212ff9,0xbf46e22a,0x3f1b02c6,0xbf4bbbf8,0x3f14b039,0xbf5064af,
0x3f226799,0xbf45e403,0x3f1b02c6,0xbf4bbbf8,0x3f13682a,0xbf514d3d,0x3f0b9a6b,0xbf5695e5,0x3f039c3d,0xbf5b941a,0x3ef6e0cb,0xbf604621,0x3ee63375,0xbf64aa59,0x3ed53641,0xbf68bf3c,
0x3f039c3d,0xbf5b941a,0x3ef41f07,0xbf6106f2,0x3ee0924f,0xbf660f88,0x3ecc9b8b,0xbf6aab7b,0x3eb8442a,0xbf6ed89e,0x3ea395c5,0xbf7294f8,0x3e8e9a22,0xbf75dec6,0x3e72b651,0xbf78b47b,
0x3ec3ef15,0xbf6c835e,0x3eac7cd4,0xbf710908,0x3e94a031,0xbf74fa0b,0x3e78cfcc,0xbf7853f8,0x3e47c5c2,0xbf7b14be,0x3e164083,0xbf7d3aac,0x3dc8bd36,0xbf7ec46d,0x3d48fb30,0xbf7fb10f,
0x3e78cfcc,0xbf7853f8,0x3e419b37,0xbf7b61fc,0x3e09cf86,0xbf7dabcc,0x3da3308c,0xbf7f2f9d,0x3cc90ab0,0xbf7fec43,0xbcfb49ba,0xbf7fe129,0xbdafb680,0xbf7f0e58,0xbe1008b7,0xbf7d7474,
0x3dc8bd36,0xbf7ec46d,0x3d16c32c,0xbf7fd397,0xbcc90ab0,0xbf7fec43,0xbdafb680,0xbf7f0e58,0xbe164083,0xbf7d3aac,0xbe541501,0xbf7a7302,0xbe888e93,0xbf76ba07,0xbea68f12,0xbf721352,
0xbd48fb30,0xbf7fb10f,0xbdee3876,0xbf7e4323,0xbe3b6ecf,0xbf7baccd,0xbe7ee6e1,0xbf77f110,0xbea09ae5,0xbf731447,0xbec1071e,0xbf6d1c1d,0xbee0924f,0xbf660f88,0xbeff17b2,0xbf5df6be,
0xbe47c5c2,0xbf7b14be,0xbe888e93,0xbf76ba07,0xbeac7cd4,0xbf710908,0xbecf7bca,0xbf6a09a7,0xbef15aea,0xbf61c598,0xbf08f59b,0xbf584853,0xbf187fc0,0xbf4d9f02,0xbf273656,0xbf41d870,
0xbeac7cd4,0xbf710908,0xbed25a09,0xbf696591,0xbef6e0cb,0xbf604621,0xbf0cead0,0xbf55b993,0xbf1d7fd1,0xbf49d112,0xbf2d1469,0xbf3ca003,0xbf3b8f3b,0xbf2e3bde,0xbf48d8b3,0xbf1ebc12,
0xbef15aea,0xbf61c598,0xbf0b9a6b,0xbf5695e5,0xbf1d7fd1,0xbf49d112,0xbf2e3bde,0xbf3b8f3b,0xbf3daef9,0xbf2beb4a,0xbf4bbbf8,0xbf1b02c6,0xbf584853,0xbf08f59b,0xbf633c5a,0xbeebcbbb,
0xbf187fc0,0xbf4d9f02,0xbf2ac082,0xbf3ebc1b,0xbf3b8f3b,0xbf2e3bde,0xbf4ac77f,0xbf1c420c,0xbf584853,0xbf08f59b,0xbf63f473,0xbee900b7,0xbf6db293,0xbebe1d4a,0xbf756d97,0xbe919ddd,
0xbf3504f3,0xbf3504f3,0xbf45e403,0xbf226799,0xbf54db31,0xbf0e39da,0xbf61c598,0xbef15aea,0xbf6c835e,0xbec3ef15,0xbf74fa0b,0xbe94a031,0xbf7b14be,0xbe47c5c2,0xbf7ec46d,0xbdc8bd36,
0xbf4d9f02,0xbf187fc0,0xbf5c61c7,0xbf0242b1,0xbf68bf3c,0xbed53641,0xbf7294f8,0xbea395c5,0xbf79c79d,0xbe605c13,0xbf7e4323,0xbdee3876,0xbf7ffb11,0xbc490e90,0xbf7eea9d,0x3dbc3ac3,
0xbf61c598,0xbef15aea,0xbf6db293,0xbebe1d4a,0xbf76ba07,0xbe888e93,0xbf7cbfc9,0xbe22abb6,0xbf7fb10f,0xbd48fb30,0xbf7f84ab,0x3d7b2b74,0xbf7c3b28,0x3e2f10a2,0xbf75dec6,0x3e8e9a22,
0xbf710908,0xbeac7cd4,0xbf796e4e,0xbe667c66,0xbf7e70b0,0xbde1bc2e,0xbf7ffec4,0x3bc90f88,0xbf7e1324,0x3dfab273,0xbf78b47b,0x3e72b651,0xbf6ff573,0x3eb263ef,0xbf63f473,0x3ee900b7,
0xbf7b14be,0xbe47c5c2,0xbf7f4e6d,0xbd96a905,0xbf7fb10f,0x3d48fb30,0xbf7c3b28,0x3e2f10a2,0xbf74fa0b,0x3e94a031,0xbf6a09a7,0x3ecf7bca,0xbf5b941a,0x3f039c3d,0xbf49d112,0x3f1d7fd1,
0xbf7fb10f,0xbd48fb30,0xbf7f2f9d,0x3da3308c,0xbf7a7302,0x3e541501,0xbf718f57,0x3ea986c4,0xbf64aa59,0x3ee63375,0xbf53fac3,0x3f0f8784,0xbf3fc767,0x3f299415,0xbf286605,0x3f40d0da,
0xbf7ec46d,0x3dc8bd36,0xbf791298,0x3e6c9a7f,0xbf6ed89e,0x3eb8442a,0xbf604621,0x3ef6e0cb,0xbf4d9f02,0x3f187fc0,0xbf373a23,0x3f32c8c9,0xbf1d7fd1,0x3f49d112,0xbf00e7e4,0x3f5d2d53,
0xbf7853f8,0x3e78cfcc,0xbf6d1c1d,0x3ec1071e,0xbf5d2d53,0x3f00e7e4,0xbf48d8b3,0x3f1ebc12,0xbf3085bb,0x3f396842,0xbf14b039,0x3f5064af,0xbeebcbbb,0x3f633c5a,0xbea986c4,0x3f718f57,
0xbf6c835e,0x3ec3ef15,0xbf5b941a,0x3f039c3d,0xbf45e403,0x3f226799,0xbf2beb4a,0x3f3daef9,0xbf0e39da,0x3f54db31,0xbedae880,0x3f676bd8,0xbe94a031,0x3f74fa0b,0xbe164083,0x3f7d3aac,
0xbf5b941a,0x3f039c3d,0xbf44e3f5,0x3f239da9,0xbf299415,0x3f3fc767,0xbf0a48ad,0x3f577026,0xbecf7bca,0x3f6a09a7,0xbe8586ce,0x3f772417,0xbde1bc2e,0x3f7e70b0,0x3d2fe007,0x3f7fc38f,
0xbf45e403,0x3f226799,0xbf299415,0x3f3fc767,0xbf08f59b,0x3f584853,0xbec9b953,0x3f6b4b0c,0xbe78cfcc,0x3f7853f8,0xbdafb680,0x3f7f0e58,0x3d96a905,0x3f7f4e6d,0x3e6c9a7f,0x3f791298,
0xbf2beb4a,0x3f3daef9,0xbf0a48ad,0x3f577026,0xbec9b953,0x3f6b4b0c,0xbe72b651,0x3f78b47b,0xbd96a905,0x3f7f4e6d,0x3dbc3ac3,0x3f7eea9d,0x3e827dc0,0x3f778bc5,0x3ed25a09,0x3f696591,
0xbf0e39da,0x3f54db31,0xbecf7bca,0x3f6a09a7,0xbe78cfcc,0x3f7853f8,0xbd96a905,0x3f7f4e6d,0x3dc8bd36,0x3f7ec46d,0x3e888e93,0x3f76ba07,0x3edae880,0x3f676bd8,0x3f13682a,0x3f514d3d,
0xbedae880,0x3f676bd8,0xbe8586ce,0x3f772417,0xbdafb680,0x3f7f0e58,0x3dbc3ac3,0x3f7eea9d,0x3e888e93,0x3f76ba07,0x3eddbe79,0x3f66becc,0x3f15f6d9,0x3f4f7a1f,0x3f385216,0x3f31a81d,
0xbe94a031,0x3f74fa0b,0xbde1bc2e,0x3f7e70b0,0x3d96a905,0x3f7f4e6d,0x3e827dc0,0x3f778bc5,0x3edae880,0x3f676bd8,0x3f15f6d9,0x3f4f7a1f,0x3f396842,0x3f3085bb,0x3f5695e5,0x3f0b9a6b,
0xbe164083,0x3f7d3aac,0x3d2fe007,0x3f7fc38f,0x3e6c9a7f,0x3f791298,0x3ed25a09,0x3f696591,0x3f13682a,0x3f514d3d,0x3f385216,0x3f31a81d,0x3f5695e5,0x3f0b9a6b,0x3f6d1c1d,0x3ec1071e,
0xbd803d80,0x80003e00,0x80003e00,0x80003e00,0x80003e00,0x80003e00,0x80003e00,0x80003e00,0x80003e00,0x80003e00,0x80003e00,0x80003e00,0x80003e00,0x80003e00,0x80003e00,0x80003e00,
0x3d803d80,0x3cc83dfb,0x3e000000,0x3dfbbcc8,0x3d443ded,0x3d8e3dd5,0x3dedbd44,0x3dd5bd8e,0x3db53db5,0x3dd53d8e,0x3db5bdb5,0x3d8ebdd5,0x3ded3d44,0x3dfb3cc8,0x3d44bded,0x3cc8bdfb,
0xbd803d80,0x3d443ded,0x8000be00,0xbd44bded,0x3db53db5,0x3ded3d44,0xbdb5bdb5,0xbdedbd44,0x3e000000,0x3dedbd44,0xbe000000,0xbded3d44,0x3db5bdb5,0x3d44bded,0xbdb53db5,0xbd443ded,
0x3d803d80,0x3d8e3dd5,0xbe000000,0xbdd53d8e,0x3ded3d44,0x3dfbbcc8,0xbd443ded,0x3cc83dfb,0x3db5bdb5,0x3cc8bdfb,0x3db53db5,0x3dfb3cc8,0xbd44bded,0xbdd5bd8e,0x3dedbd44,0x3d8ebdd5,
0xbd803d80,0x3db53db5,0x80003e00,0x3db53db5,0x3e000000,0x3db5bdb5,0x3e000000,0x3db5bdb5,0x8000be00,0xbdb5bdb5,0x8000be00,0xbdb5bdb5,0xbe000000,0xbdb53db5,0xbe000000,0xbdb53db5,
0x3d803d80,0x3dd53d8e,0x3e000000,0x3d8ebdd5,0x3dedbd44,0x3cc8bdfb,0xbd44bded,0xbdfbbcc8,0xbdb5bdb5,0xbdfb3cc8,0xbdb53db5,0x3cc83dfb,0xbd443ded,0x3d8e3dd5,0x3ded3d44,0x3dd5bd8e,
0xbd803d80,0x3ded3d44,0x8000be00,0xbdedbd44,0x3db5bdb5,0xbd44bded,0xbdb53db5,0x3d443ded,0xbe000000,0xbd443ded,0x3e000000,0x3d44bded,0x3db53db5,0x3dedbd44,0xbdb5bdb5,0xbded3d44,
0x3d803d80,0x3dfb3cc8,0xbe000000,0xbcc83dfb,0x3d44bded,0xbdd5bd8e,0x3ded3d44,0x3d8ebdd5,0xbdb53db5,0x3d8e3dd5,0xbdb5bdb5,0xbdd53d8e,0x3dedbd44,0xbcc8bdfb,0x3d443ded,0x3dfbbcc8,
0xbd803d80,0x3e000000,0x80003e00,0x3e000000,0x8000be00,0xbe000000,0x8000be00,0xbe000000,0x80003e00,0x3e000000,0x80003e00,0x3e000000,0x8000be00,0xbe000000,0x8000be00,0xbe000000,
0x3d803d80,0x3dfbbcc8,0x3e000000,0xbcc8bdfb,0xbd44bded,0xbdd53d8e,0xbded3d44,0x3d8e3dd5,0x3db53db5,0x3d8ebdd5,0x3db5bdb5,0xbdd5bd8e,0xbdedbd44,0xbcc83dfb,0xbd443ded,0x3dfb3cc8,
0xbd803d80,0x3dedbd44,0x8000be00,0xbded3d44,0xbdb5bdb5,0xbd443ded,0x3db53db5,0x3d44bded,0x3e000000,0xbd44bded,0xbe000000,0x3d443ded,0xbdb53db5,0x3ded3d44,0x3db5bdb5,0xbdedbd44,
0x3d803d80,0x3dd5bd8e,0xbe000000,0x3d8e3dd5,0xbdedbd44,0x3cc83dfb,0x3d44bded,0xbdfb3cc8,0x3db5bdb5,0xbdfbbcc8,0x3db53db5,0x3cc8bdfb,0x3d443ded,0x3d8ebdd5,0xbded3d44,0x3dd53d8e,
0xbd803d80,0x3db5bdb5,0x80003e00,0x3db5bdb5,0xbe000000,0x3db53db5,0xbe000000,0x3db53db5,0x8000be00,0xbdb53db5,0x8000be00,0xbdb53db5,0x3e000000,0xbdb5bdb5,0x3e000000,0xbdb5bdb5,
0x3d803d80,0x3d8ebdd5,0x3e000000,0xbdd5bd8e,0xbded3d44,0x3dfb3cc8,0x3d443ded,0x3cc8bdfb,0xbdb5bdb5,0x3cc83dfb,0xbdb53db5,0x3dfbbcc8,0x3d44bded,0xbdd53d8e,0xbdedbd44,0x3d8e3dd5,
0xbd803d80,0x3d44bded,0x8000be00,0xbd443ded,0xbdb53db5,0x3dedbd44,0x3db5bdb5,0xbded3d44,0xbe000000,0x3ded3d44,0x3e000000,0xbdedbd44,0xbdb5bdb5,0x3d443ded,0x3db53db5,0xbd44bded,
0x3d803d80,0x3cc8bdfb,0xbe000000,0x3dfb3cc8,0xbd443ded,0x3d8ebdd5,0xbdedbd44,0x3dd53d8e,0xbdb53db5,0x3dd5bd8e,0xbdb5bdb5,0x3d8e3dd5,0xbded3d44,0x3dfbbcc8,0xbd44bded,0x3cc83dfb,
0xbd803d80,0x8000be00,0x80003e00,0x8000be00,0x80003e00,0x8000be00,0x80003e00,0x8000be00,0x80003e00,0x8000be00,0x80003e00,0x8000be00,0x80003e00,0x8000be00,0x80003e00,0x8000be00,
0x3d803d80,0xbcc8bdfb,0x3e000000,0xbdfb3cc8,0x3d443ded,0xbd8ebdd5,0x3dedbd44,0xbdd53d8e,0x3db53db5,0xbdd5bd8e,0x3db5bdb5,0xbd8e3dd5,0x3ded3d44,0xbdfbbcc8,0x3d44bded,0xbcc83dfb,
0xbd803d80,0xbd44bded,0x8000be00,0x3d443ded,0x3db53db5,0xbdedbd44,0xbdb5bdb5,0x3ded3d44,0x3e000000,0xbded3d44,0xbe000000,0x3dedbd44,0x3db5bdb5,0xbd443ded,0xbdb53db5,0x3d44bded,
0x3d803d80,0xbd8ebdd5,0xbe000000,0x3dd5bd8e,0x3ded3d44,0xbdfb3cc8,0xbd443ded,0xbcc8bdfb,0x3db5bdb5,0xbcc83dfb,0x3db53db5,0xbdfbbcc8,0xbd44bded,0x3dd53d8e,0x3dedbd44,0xbd8e3dd5,
0xbd803d80,0xbdb5bdb5,0x80003e00,0xbdb5bdb5,0x3e000000,0xbdb53db5,0x3e000000,0xbdb53db5,0x8000be00,0x3db53db5,0x8000be00,0x3db53db5,0xbe000000,0x3db5bdb5,0xbe000000,0x3db5bdb5,
0x3d803d80,0xbdd5bd8e,0x3e000000,0xbd8e3dd5,0x3dedbd44,0xbcc83dfb,0xbd44bded,0x3dfb3cc8,0xbdb5bdb5,0x3dfbbcc8,0xbdb53db5,0xbcc8bdfb,0xbd443ded,0xbd8ebdd5,0x3ded3d44,0xbdd53d8e,
0xbd803d80,0xbdedbd44,0x8000be00,0x3ded3d44,0x3db5bdb5,0x3d443ded,0xbdb53db5,0xbd44bded,0xbe000000,0x3d44bded,0x3e000000,0xbd443ded,0x3db53db5,0xbded3d44,0xbdb5bdb5,0x3dedbd44,
0x3d803d80,0xbdfbbcc8,0xbe000000,0x3cc8bdfb,0x3d44bded,0x3dd53d8e,0x3ded3d44,0xbd8e3dd5,0xbdb53db5,0xbd8ebdd5,0xbdb5bdb5,0x3dd5bd8e,0x3dedbd44,0x3cc83dfb,0x3d443ded,0xbdfb3cc8,
0xbd803d80,0xbe000000,0x80003e00,0xbe000000,0x8000be00,0x3e000000,0x8000be00,0x3e000000,0x80003e00,0xbe000000,0x80003e00,0xbe000000,0x8000be00,0x3e000000,0x8000be00,0x3e000000,
0x3d803d80,0xbdfb3cc8,0x3e000000,0x3cc83dfb,0xbd44bded,0x3dd5bd8e,0xbded3d44,0xbd8ebdd5,0x3db53db5,0xbd8e3dd5,0x3db5bdb5,0x3dd53d8e,0xbdedbd44,0x3cc8bdfb,0xbd443ded,0xbdfbbcc8,
0xbd803d80,0xbded3d44,0x8000be00,0x3dedbd44,0xbdb5bdb5,0x3d44bded,0x3db53db5,0xbd443ded,0x3e000000,0x3d443ded,0xbe000000,0xbd44bded,0xbdb53db5,0xbdedbd44,0x3db5bdb5,0x3ded3d44,
0x3d803d80,0xbdd53d8e,0xbe000000,0xbd8ebdd5,0xbdedbd44,0xbcc8bdfb,0x3d44bded,0x3dfbbcc8,0x3db5bdb5,0x3dfb3cc8,0x3db53db5,0xbcc83dfb,0x3d443ded,0xbd8e3dd5,0xbded3d44,0xbdd5bd8e,
0xbd803d80,0xbdb53db5,0x80003e00,0xbdb53db5,0xbe000000,0xbdb5bdb5,0xbe000000,0xbdb5bdb5,0x8000be00,0x3db5bdb5,0x8000be00,0x3db5bdb5,0x3e000000,0x3db53db5,0x3e000000,0x3db53db5,
0x3d803d80,0xbd8e3dd5,0x3e000000,0x3dd53d8e,0xbded3d44,0xbdfbbcc8,0x3d443ded,0xbcc83dfb,0xbdb5bdb5,0xbcc8bdfb,0xbdb53db5,0xbdfb3cc8,0x3d44bded,0x3dd5bd8e,0xbdedbd44,0xbd8ebdd5,
0xbd803d80,0xbd443ded,0x8000be00,0x3d44bded,0xbdb53db5,0xbded3d44,0x3db5bdb5,0x3dedbd44,0xbe000000,0xbdedbd44,0x3e000000,0x3ded3d44,0xbdb5bdb5,0xbd44bded,0x3db53db5,0x3d443ded,
0x3d803d80,0xbcc83dfb,0xbe000000,0xbdfbbcc8,0xbd443ded,0xbd8e3dd5,0xbdedbd44,0xbdd5bd8e,0xbdb53db5,0xbdd53d8e,0xbdb5bdb5,0xbd8ebdd5,0xbded3d44,0xbdfb3cc8,0xbd44bded,0xbcc8bdfb,
0x80003e00,0x80003e00,0x80003e00,0x80003e00,0x80003e00,0x80003e00,0x80003e00,0x80003e00,0x80003e00,0x80003e00,0x80003e00,0x80003e00,0x80003e00,0x80003e00,0x80003e00,0x80003e00,
0x3c493dff,0x3d153df5,0x3dffbc49,0x3df5bd15,0x3d713de2,0x3da23dc6,0x3de2bd71,0x3dc6bda2,0x3dc63da2,0x3de23d71,0x3da2bdc6,0x3d71bde2,0x3df53d15,0x3dff3c49,0x3d15bdf5,0x3c49bdff,
0x3cc83dfb,0x3d8e3dd5,0xbcc8bdfb,0xbd8ebdd5,0x3dd53d8e,0x3dfb3cc8,0xbdd5bd8e,0xbdfbbcc8,0x3dfbbcc8,0x3dd5bd8e,0xbdfb3cc8,0xbdd53d8e,0x3d8ebdd5,0x3cc8bdfb,0xbd8e3dd5,0xbcc83dfb,
0x3d153df5,0x3dc63da2,0xbdf53d15,0xbda23dc6,0x3dff3c49,0x3de2bd71,0xbc493dff,0x3d713de2,0x3d71bde2,0xbc49bdff,0x3de23d71,0x3dffbc49,0xbda2bdc6,0xbdf5bd15,0x3dc6bda2,0x3d15bdf5,
0x3d443ded,0x3ded3d44,0x3d443ded,0x3ded3d44,0x3dedbd44,0x3d44bded,0x3dedbd44,0x3d44bded,0xbd44bded,0xbdedbd44,0xbd44bded,0xbdedbd44,0xbded3d44,0xbd443ded,0xbded3d44,0xbd443ded,
0x3d713de2,0x3dff3c49,0x3de2bd71,0x3c49bdff,0x3da2bdc6,0xbd15bdf5,0xbdc6bda2,0xbdf53d15,0xbdf5bd15,0xbdc63da2,0xbd153df5,0x3da23dc6,0x3c493dff,0x3de23d71,0x3dffbc49,0x3d71bde2,
0x3d8e3dd5,0x3dfbbcc8,0xbd8ebdd5,0xbdfb3cc8,0x3cc8bdfb,0xbdd5bd8e,0xbcc83dfb,0x3dd53d8e,0xbdd53d8e,0x3cc83dfb,0x3dd5bd8e,0xbcc8bdfb,0x3dfb3cc8,0x3d8ebdd5,0xbdfbbcc8,0xbd8e3dd5,
0x3da23dc6,0x3de2bd71,0xbdc63da2,0x3d713de2,0xbd15bdf5,0xbdff3c49,0x3df5bd15,0xbc49bdff,0xbc493dff,0x3df53d15,0xbdffbc49,0xbd153df5,0x3d71bde2,0xbdc6bda2,0x3de23d71,0x3da2bdc6,
0x3db53db5,0x3db5bdb5,0x3db53db5,0x3db5bdb5,0xbdb5bdb5,0xbdb53db5,0xbdb5bdb5,0xbdb53db5,0x3db53db5,0x3db5bdb5,0x3db53db5,0x3db5bdb5,0xbdb5bdb5,0xbdb53db5,0xbdb5bdb5,0xbdb53db5,
0x3dc63da2,0x3d71bde2,0x3da2bdc6,0xbde2bd71,0xbdf5bd15,0xbc493dff,0xbd153df5,0x3dff3c49,0x3dffbc49,0xbd15bdf5,0xbc49bdff,0xbdf53d15,0xbde23d71,0x3da23dc6,0x3d713de2,0x3dc6bda2,
0x3dd53d8e,0x3cc8bdfb,0xbdd5bd8e,0xbcc83dfb,0xbdfb3cc8,0x3d8e3dd5,0x3dfbbcc8,0xbd8ebdd5,0x3d8ebdd5,0xbdfbbcc8,0xbd8e3dd5,0x3dfb3cc8,0x3cc83dfb,0x3dd5bd8e,0xbcc8bdfb,0xbdd53d8e,
0x3de23d71,0xbc49bdff,0xbd713de2,0x3dffbc49,0xbdc63da2,0x3df53d15,0xbda2bdc6,0xbd153df5,0xbd15bdf5,0xbda23dc6,0x3df5bd15,0xbdc6bda2,0x3dff3c49,0xbd71bde2,0xbc493dff,0x3de2bd71,
0x3ded3d44,0xbd44bded,0x3ded3d44,0xbd44bded,0xbd443ded,0x3dedbd44,0xbd443ded,0x3dedbd44,0xbdedbd44,0x3d443ded,0xbdedbd44,0x3d443ded,0x3d44bded,0xbded3d44,0x3d44bded,0xbded3d44,
0x3df53d15,0xbda2bdc6,0x3d15bdf5,0xbdc63da2,0x3c493dff,0x3d71bde2,0x3dffbc49,0xbde2bd71,0xbde23d71,0x3dff3c49,0x3d713de2,0x3c49bdff,0xbdc6bda2,0x3d153df5,0xbda23dc6,0x3df5bd15,
0x3dfb3cc8,0xbdd5bd8e,0xbdfbbcc8,0x3dd53d8e,0x3d8e3dd5,0xbcc8bdfb,0xbd8ebdd5,0x3cc83dfb,0xbcc83dfb,0x3d8ebdd5,0x3cc8bdfb,0xbd8e3dd5,0xbdd53d8e,0x3dfbbcc8,0x3dd5bd8e,0xbdfb3cc8,
0x3dff3c49,0xbdf5bd15,0xbc493dff,0x3d15bdf5,0x3de23d71,0xbdc6bda2,0xbd713de2,0x3da2bdc6,0x3da23dc6,0xbd71bde2,0xbdc63da2,0x3de2bd71,0x3d153df5,0xbc49bdff,0xbdf53d15,0x3dffbc49,
0x3e000000,0xbe000000,0x3e000000,0xbe000000,0x3e000000,0xbe000000,0x3e000000,0xbe000000,0x3e000000,0xbe000000,0x3e000000,0xbe000000,0x3e000000,0xbe000000,0x3e000000,0xbe000000,
0x3dffbc49,0xbdf53d15,0xbc49bdff,0x3d153df5,0x3de2bd71,0xbdc63da2,0xbd71bde2,0x3da23dc6,0x3da2bdc6,0xbd713de2,0xbdc6bda2,0x3de23d71,0x3d15bdf5,0xbc493dff,0xbdf5bd15,0x3dff3c49,
0x3dfbbcc8,0xbdd53d8e,0xbdfb3cc8,0x3dd5bd8e,0x3d8ebdd5,0xbcc83dfb,0xbd8e3dd5,0x3cc8bdfb,0xbcc8bdfb,0x3d8e3dd5,0x3cc83dfb,0xbd8ebdd5,0xbdd5bd8e,0x3dfb3cc8,0x3dd53d8e,0xbdfbbcc8,
0x3df5bd15,0xbda23dc6,0x3d153df5,0xbdc6bda2,0x3c49bdff,0x3d713de2,0x3dff3c49,0xbde23d71,0xbde2bd71,0x3dffbc49,0x3d71bde2,0x3c493dff,0xbdc63da2,0x3d15bdf5,0xbda2bdc6,0x3df53d15,
0x3dedbd44,0xbd443ded,0x3dedbd44,0xbd443ded,0xbd44bded,0x3ded3d44,0xbd44bded,0x3ded3d44,0xbded3d44,0x3d44bded,0xbded3d44,0x3d44bded,0x3d443ded,0xbdedbd44,0x3d443ded,0xbdedbd44,
0x3de2bd71,0xbc493dff,0xbd71bde2,0x3dff3c49,0xbdc6bda2,0x3df5bd15,0xbda23dc6,0xbd15bdf5,0xbd153df5,0xbda2bdc6,0x3df53d15,0xbdc63da2,0x3dffbc49,0xbd713de2,0xbc49bdff,0x3de23d71,
0x3dd5bd8e,0x3cc83dfb,0xbdd53d8e,0xbcc8bdfb,0xbdfbbcc8,0x3d8ebdd5,0x3dfb3cc8,0xbd8e3dd5,0x3d8e3dd5,0xbdfb3cc8,0xbd8ebdd5,0x3dfbbcc8,0x3cc8bdfb,0x3dd53d8e,0xbcc83dfb,0xbdd5bd8e,
0x3dc6bda2,0x3d713de2,0x3da23dc6,0xbde23d71,0xbdf53d15,0xbc49bdff,0xbd15bdf5,0x3dffbc49,0x3dff3c49,0xbd153df5,0xbc493dff,0xbdf5bd15,0xbde2bd71,0x3da2bdc6,0x3d71bde2,0x3dc63da2,
0x3db5bdb5,0x3db53db5,0x3db5bdb5,0x3db53db5,0xbdb53db5,0xbdb5bdb5,0xbdb53db5,0xbdb5bdb5,0x3db5bdb5,0x3db53db5,0x3db5bdb5,0x3db53db5,0xbdb53db5,0xbdb5bdb5,0xbdb53db5,0xbdb5bdb5,
0x3da2bdc6,0x3de23d71,0xbdc6bda2,0x3d71bde2,0xbd153df5,0xbdffbc49,0x3df53d15,0xbc493dff,0xbc49bdff,0x3df5bd15,0xbdff3c49,0xbd15bdf5,0x3d713de2,0xbdc63da2,0x3de2bd71,0x3da23dc6,
0x3d8ebdd5,0x3dfb3cc8,0xbd8e3dd5,0xbdfbbcc8,0x3cc83dfb,0xbdd53d8e,0xbcc8bdfb,0x3dd5bd8e,0xbdd5bd8e,0x3cc8bdfb,0x3dd53d8e,0xbcc83dfb,0x3dfbbcc8,0x3d8e3dd5,0xbdfb3cc8,0xbd8ebdd5,
0x3d71bde2,0x3dffbc49,0x3de23d71,0x3c493dff,0x3da23dc6,0xbd153df5,0xbdc63da2,0xbdf5bd15,0xbdf53d15,0xbdc6bda2,0xbd15bdf5,0x3da2bdc6,0x3c49bdff,0x3de2bd71,0x3dff3c49,0x3d713de2,
0x3d44bded,0x3dedbd44,0x3d44bded,0x3dedbd44,0x3ded3d44,0x3d443ded,0x3ded3d44,0x3d443ded,0xbd443ded,0xbded3d44,0xbd443ded,0xbded3d44,0xbdedbd44,0xbd44bded,0xbdedbd44,0xbd44bded,
0x3d15bdf5,0x3dc6bda2,0xbdf5bd15,0xbda2bdc6,0x3dffbc49,0x3de23d71,0xbc49bdff,0x3d71bde2,0x3d713de2,0xbc493dff,0x3de2bd71,0x3dff3c49,0xbda23dc6,0xbdf53d15,0x3dc63da2,0x3d153df5,
0x3cc8bdfb,0x3d8ebdd5,0xbcc83dfb,0xbd8e3dd5,0x3dd5bd8e,0x3dfbbcc8,0xbdd53d8e,0xbdfb3cc8,0x3dfb3cc8,0x3dd53d8e,0xbdfbbcc8,0xbdd5bd8e,0x3d8e3dd5,0x3cc83dfb,0xbd8ebdd5,0xbcc8bdfb,
0x3c49bdff,0x3d15bdf5,0x3dff3c49,0x3df53d15,0x3d71bde2,0x3da2bdc6,0x3de23d71,0x3dc63da2,0x3dc6bda2,0x3de2bd71,0x3da23dc6,0x3d713de2,0x3df5bd15,0x3dffbc49,0x3d153df5,0x3c493dff,
0x3f800000,0x0,0x3f800000,0x0,0x3f800000,0x0,0x3f800000,0x0,0x3f800000,0x0,0x3f800000,0x0,0x3f800000,0x0,0x3f800000,0x0,
0x3f800000,0x0,0x3f7ffb11,0xbc490e90,0x3f7fec43,0xbcc90ab0,0x3f7fd397,0xbd16c32c,0x3f7fb10f,0xbd48fb30,0x3f7f84ab,0xbd7b2b74,0x3f7f4e6d,0xbd96a905,0x3f7f0e58,0xbdafb680,
0x3f800000,0x0,0x3f7fec43,0xbcc90ab0,0x3f7fb10f,0xbd48fb30,0x3f7f4e6d,0xbd96a905,0x3f7ec46d,0xbdc8bd36,0x3f7e1324,0xbdfab273,0x3f7d3aac,0xbe164083,0x3f7c3b28,0xbe2f10a2,
0x3f800000,0x0,0x3f7fd397,0xbd16c32c,0x3f7f4e6d,0xbd96a905,0x3f7e70b0,0xbde1bc2e,0x3f7d3aac,0xbe164083,0x3f7baccd,0xbe3b6ecf,0x3f79c79d,0xbe605c13,0x3f778bc5,0xbe827dc0,
0x3f800000,0x0,0x3f7fb10f,0xbd48fb30,0x3f7ec46d,0xbdc8bd36,0x3f7d3aac,0xbe164083,0x3f7b14be,0xbe47c5c2,0x3f7853f8,0xbe78cfcc,0x3f74fa0b,0xbe94a031,0x3f710908,0xbeac7cd4,
0x3f800000,0x0,0x3f7f84ab,0xbd7b2b74,0x3f7e1324,0xbdfab273,0x3f7baccd,0xbe3b6ecf,0x3f7853f8,0xbe78cfcc,0x3f740bdd,0xbe9aa086,0x3f6ed89e,0xbeb8442a,0x3f68bf3c,0xbed53641,
0x3f800000,0x0,0x3f7f4e6d,0xbd96a905,0x3f7d3aac,0xbe164083,0x3f79c79d,0xbe605c13,0x3f74fa0b,0xbe94a031,0x3f6ed89e,0xbeb8442a,0x3f676bd8,0xbedae880,0x3f5ebe05,0xbefc5d27,
0x3f800000,0x0,0x3f7f0e58,0xbdafb680,0x3f7c3b28,0xbe2f10a2,0x3f778bc5,0xbe827dc0,0x3f710908,0xbeac7cd4,0x3f68bf3c,0xbed53641,0x3f5ebe05,0xbefc5d27,0x3f531849,0xbf10d3cd,
0x3f800000,0x0,0x3f7ec46d,0xbdc8bd36,0x3f7b14be,0xbe47c5c2,0x3f74fa0b,0xbe94a031,0x3f6c835e,0xbec3ef15,0x3f61c598,0xbef15aea,0x3f54db31,0xbf0e39da,0x3f45e403,0xbf226799,
0x3f800000,0x0,0x3f7e70b0,0xbde1bc2e,0x3f79c79d,0xbe605c13,0x3f721352,0xbea68f12,0x3f676bd8,0xbedae880,0x3f59f26a,0xbf064b82,0x3f49d112,0xbf1d7fd1,0x3f373a23,0xbf32c8c9,
0x3f800000,0x0,0x3f7e1324,0xbdfab273,0x3f7853f8,0xbe78cfcc,0x3f6ed89e,0xbeb8442a,0x3f61c598,0xbef15aea,0x3f514d3d,0xbf13682a,0x3f3daef9,0xbf2beb4a,0x3f273656,0xbf41d870,
0x3f800000,0x0,0x3f7dabcc,0xbe09cf86,0x3f76ba07,0xbe888e93,0x3f6b4b0c,0xbec9b953,0x3f5b941a,0xbf039c3d,0x3f47de65,0xbf1ff6cb,0x3f3085bb,0xbf396842,0x3f15f6d9,0xbf4f7a1f,
0x3f800000,0x0,0x3f7d3aac,0xbe164083,0x3f74fa0b,0xbe94a031,0x3f676bd8,0xbedae880,0x3f54db31,0xbf0e39da,0x3f3daef9,0xbf2beb4a,0x3f226799,0xbf45e403,0x3f039c3d,0xbf5b941a,
0x3f800000,0x0,0x3f7cbfc9,0xbe22abb6,0x3f731447,0xbea09ae5,0x3f633c5a,0xbeebcbbb,0x3f4d9f02,0xbf187fc0,0x3f32c8c9,0xbf373a23,0x3f13682a,0xbf514d3d,0x3ee0924f,0xbf660f88,
0x3f800000,0x0,0x3f7c3b28,0xbe2f10a2,0x3f710908,0xbeac7cd4,0x3f5ebe05,0xbefc5d27,0x3f45e403,0xbf226799,0x3f273656,0xbf41d870,0x3f039c3d,0xbf5b941a,0x3eb8442a,0xbf6ed89e,
0x3f800000,0x0,0x3f7baccd,0xbe3b6ecf,0x3f6ed89e,0xbeb8442a,0x3f59f26a,0xbf064b82,0x3f3daef9,0xbf2beb4a,0x3f1b02c6,0xbf4bbbf8,0x3ee63375,0xbf64aa59,0x3e8e9a22,0xbf75dec6,
0x3f800000,0x0,0x3f7b14be,0xbe47c5c2,0x3f6c835e,0xbec3ef15,0x3f54db31,0xbf0e39da,0x3f3504f3,0xbf3504f3,0x3f0e39da,0xbf54db31,0x3ec3ef15,0xbf6c835e,0x3e47c5c2,0xbf7b14be,
0x3f800000,0x0,0x3f7a7302,0xbe541501,0x3f6a09a7,0xbecf7bca,0x3f4f7a1f,0xbf15f6d9,0x3f2beb4a,0xbf3daef9,0x3f00e7e4,0xbf5d2d53,0x3ea09ae5,0xbf731447,0x3de1bc2e,0xbf7e70b0,
0x3f800000,0x0,0x3f79c79d,0xbe605c13,0x3f676bd8,0xbedae880,0x3f49d112,0xbf1d7fd1,0x3f226799,0xbf45e403,0x3ee63375,0xbf64aa59,0x3e78cfcc,0xbf7853f8,0x3cc90ab0,0xbf7fec43,
0x3f800000,0x0,0x3f791298,0xbe6c9a7f,0x3f64aa59,0xbee63375,0x3f43e200,0xbf24d225,0x3f187fc0,0xbf4d9f02,0x3ec9b953,0xbf6b4b0c,0x3e2f10a2,0xbf7c3b28,0xbd7b2b74,0xbf7f84ab,
0x3f800000,0x0,0x3f7853f8,0xbe78cfcc,0x3f61c598,0xbef15aea,0x3f3daef9,0xbf2beb4a,0x3f0e39da,0xbf54db31,0x3eac7cd4,0xbf710908,0x3dc8bd36,0xbf7ec46d,0xbe164083,0xbf7d3aac,
0x3f800000,0x0,0x3f778bc5,0xbe827dc0,0x3f5ebe05,0xbefc5d27,0x3f373a23,0xbf32c8c9,0x3f039c3d,0xbf5b941a,0x3e8e9a22,0xbf75dec6,0x3cc90ab0,0xbf7fec43,0xbe6c9a7f,0xbf791298,
0x3f800000,0x0,0x3f76ba07,0xbe888e93,0x3f5b941a,0xbf039c3d,0x3f3085bb,0xbf396842,0x3ef15aea,0xbf61c598,0x3e605c13,0xbf79c79d,0xbd48fb30,0xbf7fb10f,0xbea09ae5,0xbf731447,
0x3f800000,0x0,0x3f75dec6,0xbe8e9a22,0x3f584853,0xbf08f59b,0x3f299415,0xbf3fc767,0x3edae880,0xbf676bd8,0x3e22abb6,0xbf7cbfc9,0xbdfab273,0xbf7e1324,0xbec9b953,0xbf6b4b0c,
0x3f800000,0x0,0x3f74fa0b,0xbe94a031,0x3f54db31,0xbf0e39da,0x3f226799,0xbf45e403,0x3ec3ef15,0xbf6c835e,0x3dc8bd36,0xbf7ec46d,0xbe47c5c2,0xbf7b14be,0xbef15aea,0xbf61c598,
0x3f800000,0x0,0x3f740bdd,0xbe9aa086,0x3f514d3d,0xbf13682a,0x3f1b02c6,0xbf4bbbf8,0x3eac7cd4,0xbf710908,0x3d16c32c,0xbf7fd397,0xbe888e93,0xbf76ba07,0xbf0b9a6b,0xbf5695e5,
0x3f800000,0x0,0x3f731447,0xbea09ae5,0x3f4d9f02,0xbf187fc0,0x3f13682a,0xbf514d3d,0x3e94a031,0xbf74fa0b,0xbcc90ab0,0xbf7fec43,0xbeac7cd4,0xbf710908,0xbf1d7fd1,0xbf49d112,
0x3f800000,0x0,0x3f721352,0xbea68f12,0x3f49d112,0xbf1d7fd1,0x3f0b9a6b,0xbf5695e5,0x3e78cfcc,0xbf7853f8,0xbdafb680,0xbf7f0e58,0xbecf7bca,0xbf6a09a7,0xbf2e3bde,0xbf3b8f3b,
0x3f800000,0x0,0x3f710908,0xbeac7cd4,0x3f45e403,0xbf226799,0x3f039c3d,0xbf5b941a,0x3e47c5c2,0xbf7b14be,0xbe164083,0xbf7d3aac,0xbef15aea,0xbf61c598,0xbf3daef9,0xbf2beb4a,
0x3f800000,0x0,0x3f6ff573,0xbeb263ef,0x3f41d870,0xbf273656,0x3ef6e0cb,0xbf604621,0x3e164083,0xbf7d3aac,0xbe541501,0xbf7a7302,0xbf08f59b,0xbf584853,0xbf4bbbf8,0xbf1b02c6,
0x3f800000,0x0,0x3f6ed89e,0xbeb8442a,0x3f3daef9,0xbf2beb4a,0x3ee63375,0xbf64aa59,0x3dc8bd36,0xbf7ec46d,0xbe888e93,0xbf76ba07,0xbf187fc0,0xbf4d9f02,0xbf584853,0xbf08f59b,
0x3f800000,0x0,0x3f6db293,0xbebe1d4a,0x3f396842,0xbf3085bb,0x3ed53641,0xbf68bf3c,0x3d48fb30,0xbf7fb10f,0xbea68f12,0xbf721352,0xbf273656,0xbf41d870,0xbf633c5a,0xbeebcbbb,
0x3f800000,0x3f800000,0x3f800000,0x3f800000,0x3f800000,0x3f800000,0x3f800000,0x3f800000,0x3f800000,0xbf800000,0x3f800000,0xbf800000,0x3f800000,0xbf800000,0x3f800000,0xbf800000,
0x3f800000,0x3f3504f3,0x0,0xbf3504f3,0xbf800000,0xbf3504f3,0x0,0x3f3504f3,0x0,0xbf3504f3,0xbf800000,0xbf3504f3,0x0,0x3f3504f3,0x3f800000,0x3f3504f3,
0x3f800000,0x0,0xbf800000,0x0,0x3f800000,0x0,0xbf800000,0x0,0x0,0xbf800000,0x0,0x3f800000,0x0,0xbf800000,0x0,0x3f800000,
0x3f800000,0xbf3504f3,0x0,0x3f3504f3,0xbf800000,0x3f3504f3,0x0,0xbf3504f3,0x0,0xbf3504f3,0x3f800000,0xbf3504f3,0x0,0x3f3504f3,0xbf800000,0x3f3504f3,
0x3f800000,0x3f6c835e,0x3f3504f3,0x3ec3ef15,0x0,0xbec3ef15,0xbf3504f3,0xbf6c835e,0x0,0xbec3ef15,0xbf3504f3,0xbf6c835e,0xbf800000,0xbf6c835e,0xbf3504f3,0xbec3ef15,
0x3f800000,0x3ec3ef15,0xbf3504f3,0xbf6c835e,0x0,0x3f6c835e,0x3f3504f3,0xbec3ef15,0x0,0xbf6c835e,0xbf3504f3,0x3ec3ef15,0x3f800000,0x3ec3ef15,0xbf3504f3,0xbf6c835e,
0x3f800000,0xbec3ef15,0xbf3504f3,0x3f6c835e,0x0,0xbf6c835e,0x3f3504f3,0x3ec3ef15,0x0,0xbf6c835e,0x3f3504f3,0x3ec3ef15,0xbf800000,0x3ec3ef15,0x3f3504f3,0xbf6c835e,
0x3f800000,0xbf6c835e,0x3f3504f3,0xbec3ef15,0x0,0x3ec3ef15,0xbf3504f3,0x3f6c835e,0x0,0xbec3ef15,0x3f3504f3,0xbf6c835e,0x3f800000,0xbf6c835e,0x3f3504f3,0xbec3ef15,
};

struct Params {
    const __nv_bfloat16 *xb, *lre, *lim, *ldt, *dsk;
    float* out;
    int zero[8];
    uint64_t da[4];
    uint32_t unit[258];
};

struct Maps { CUtensorMap m[12]; };

struct cf { float x, y; };
__device__ __forceinline__ uint32_t smem_u32(const void* p) { return (uint32_t)__cvta_generic_to_shared(p); }
__device__ __forceinline__ void mbar_init(uint32_t a, uint32_t c) { asm volatile("mbarrier.init.shared::cta.b64 [%0], %1;" ::"r"(a), "r"(c) : "memory"); }
__device__ __forceinline__ void mbar_expect_tx(uint32_t a, uint32_t b) { asm volatile("mbarrier.arrive.expect_tx.shared::cta.b64 _, [%0], %1;" ::"r"(a), "r"(b) : "memory"); }
__device__ __forceinline__ void mbar_arrive(uint32_t a) { asm volatile("mbarrier.arrive.shared::cta.b64 _, [%0];" ::"r"(a) : "memory"); }
__device__ __forceinline__ void mbar_wait(uint32_t a, uint32_t ph) {
    asm volatile("{.reg .pred p; .reg .u32 n;\n"
                 "mov.u32 n, 0;\n"
                 "LOOP: mbarrier.try_wait.parity.shared::cta.b64 p, [%0], %1;\n"
                 "@p bra DONE;\n"
                 "add.u32 n, n, 1;\n"
                 "setp.lt.u32 p, n, %2;\n"
                 "@p bra LOOP;\n"
                 "DONE: }" ::"r"(a), "r"(ph), "n"(SPIN_LIMIT) : "memory");
}
__device__ __forceinline__ unsigned ld_rlx(const unsigned* p) { unsigned v; asm volatile("ld.relaxed.gpu.global.u32 %0, [%1];" : "=r"(v) : "l"(p) : "memory"); return v; }
__device__ __forceinline__ void wait_cnt(const unsigned* p, unsigned target) {
    unsigned n = 0;
    while ((int)(ld_rlx(p) - target) < 0 && ++n < SPIN_LIMIT) __nanosleep(20);
}
__device__ __forceinline__ void red_hint(unsigned* p) { asm volatile("red.relaxed.gpu.global.add.u32 [%0], 1;" ::"l"(p) : "memory"); }
__device__ __forceinline__ void fence_async() { asm volatile("fence.proxy.async.global;" ::: "memory"); }
__device__ __forceinline__ void fence_async_sm() { asm volatile("fence.proxy.async.shared::cta;" ::: "memory"); }
#define bar_sync(id, n) asm volatile("bar.sync %0, %1;" ::"n"(id), "n"(n) : "memory")
#define bar_arrive(id, n) asm volatile("bar.arrive %0, %1;" ::"n"(id), "n"(n) : "memory")
__device__ __forceinline__ bool elect_one() {
    uint32_t r;
    asm volatile("{.reg .pred p; elect.sync _|p, 0xffffffff; selp.u32 %0, 1, 0, p;}" : "=r"(r));
    return r != 0;
}

__device__ __forceinline__ void tma2d(uint32_t dst, const CUtensorMap* m, int c0, int c1, uint32_t bar) {
    asm volatile("cp.async.bulk.tensor.2d.shared::cluster.global.mbarrier::complete_tx::bytes [%0], [%1, {%3,%4}], [%2];" ::"r"(dst), "l"(m), "r"(bar), "r"(c0), "r"(c1) : "memory");
}
__device__ __forceinline__ void tma4d(uint32_t dst, const CUtensorMap* m, int c0, int c1, int c2, int c3, uint32_t bar) {
    asm volatile("cp.async.bulk.tensor.4d.shared::cluster.global.mbarrier::complete_tx::bytes [%0], [%1, {%3,%4,%5,%6}], [%2];" ::"r"(dst), "l"(m), "r"(bar), "r"(c0), "r"(c1), "r"(c2), "r"(c3) : "memory");
}
__device__ __forceinline__ void tma4d_mc(uint32_t dst, const CUtensorMap* m, int c0, int c3, uint32_t bar) {
    asm volatile("cp.async.bulk.tensor.4d.shared::cluster.global.mbarrier::complete_tx::bytes.multicast::cluster [%0], [%1, {%3,%6,%6,%4}], [%2], %5;" ::"r"(dst), "l"(m), "r"(bar), "r"(c0), "r"(c3), "h"((uint16_t)3), "r"(0) : "memory");
}
__device__ __forceinline__ void tma2d_st(const CUtensorMap* m, int c0, int c1, uint32_t src) {
    asm volatile("cp.async.bulk.tensor.2d.global.shared::cta.bulk_group [%0, {%2,%3}], [%1];" ::"l"(m), "r"(src), "r"(c0), "r"(c1) : "memory");
}
__device__ __forceinline__ void tma5d(uint32_t dst, const CUtensorMap* m, int c0, int c1, int c2, int c3, int c4, uint32_t bar) {
    asm volatile("cp.async.bulk.tensor.5d.shared::cluster.global.mbarrier::complete_tx::bytes [%0], [%1, {%3,%4,%5,%6,%7}], [%2];" ::"r"(dst), "l"(m), "r"(bar), "r"(c0), "r"(c1), "r"(c2), "r"(c3), "r"(c4) : "memory");
}
__device__ __forceinline__ void bulk_ld(uint32_t dst, const void* src, uint32_t n, uint32_t bar) {
    asm volatile("cp.async.bulk.shared::cluster.global.mbarrier::complete_tx::bytes [%0], [%1], %2, [%3];" ::"r"(dst), "l"(src), "r"(n), "r"(bar) : "memory");
}
__device__ __forceinline__ void pf_map(const CUtensorMap* m) { asm volatile("prefetch.tensormap [%0];" ::"l"(m) : "memory"); }
__device__ __forceinline__ void bulk_commit() { asm volatile("cp.async.bulk.commit_group;" ::: "memory"); }
template <int N> __device__ __forceinline__ void bulk_wait_read() { asm volatile("cp.async.bulk.wait_group.read %0;" ::"n"(N) : "memory"); }
__device__ __forceinline__ void stsm4(uint32_t a, uint32_t r0, uint32_t r1, uint32_t r2, uint32_t r3) {
    asm volatile("stmatrix.sync.aligned.m8n8.x4.shared.b16 [%0], {%1,%2,%3,%4};" ::"r"(a), "r"(r0), "r"(r1), "r"(r2), "r"(r3) : "memory");
}
__device__ __forceinline__ void sts128f(uint32_t a, cf u, cf v) {
    asm volatile("st.shared.v4.f32 [%0], {%1,%2,%3,%4};" ::"r"(a), "f"(u.x), "f"(u.y), "f"(v.x), "f"(v.y) : "memory");
}
__device__ __forceinline__ void stg128(const void* a, uint32_t r0, uint32_t r1, uint32_t r2, uint32_t r3) {
    asm volatile("st.global.v4.b32 [%0], {%1,%2,%3,%4};" ::"l"(a), "r"(r0), "r"(r1), "r"(r2), "r"(r3) : "memory");
}
__device__ __forceinline__ void lds128f(uint32_t a, float& x, float& y, float& z, float& u) { asm volatile("ld.shared.v4.f32 {%0,%1,%2,%3}, [%4];" : "=f"(x), "=f"(y), "=f"(z), "=f"(u) : "r"(a) : "memory"); }
__device__ __forceinline__ cf lds_cf(uint32_t a) { cf v; asm volatile("ld.shared.v2.f32 {%0,%1}, [%2];" : "=f"(v.x), "=f"(v.y) : "r"(a) : "memory"); return v; }
__device__ __forceinline__ uint4 ldtab(int word) { return __ldg((const uint4*)(g_tab + word)); }
__device__ __forceinline__ void load_tw(cf (&tw)[8], int k1) {
#pragma unroll
    for (int i = 0; i < 4; i++) {
        const uint4 v = ldtab(TAB_TW + k1 * 16 + i * 4);
        tw[2 * i] = {__uint_as_float(v.x), __uint_as_float(v.y)};
        tw[2 * i + 1] = {__uint_as_float(v.z), __uint_as_float(v.w)};
    }
}
__device__ __forceinline__ void load_T(cf (&T)[8], int t7) {
#pragma unroll
    for (int i = 0; i < 4; i++)
        asm volatile("ld.global.nc.v4.f32 {%0,%1,%2,%3}, [%4];" : "=f"(T[2 * i].x), "=f"(T[2 * i].y), "=f"(T[2 * i + 1].x), "=f"(T[2 * i + 1].y) : "l"(g_tab + TAB_T + i * 512 + t7 * 4));
}
__device__ __forceinline__ uint32_t lds_u16(uint32_t a) { uint32_t v; asm volatile("ld.shared.u16 %0, [%1];" : "=r"(v) : "r"(a)); return v; }
__device__ __forceinline__ float up(uint32_t v) { return __uint_as_float(v << 16); }
__device__ __forceinline__ unsigned get_epoch(uint32_t bars) {
    mbar_wait(bars + B_EP, 0);
    unsigned e;
    asm volatile("ld.shared.u32 %0, [%1];" : "=r"(e) : "r"(bars + B_EPOCH) : "memory");
    return e;
}
__device__ __forceinline__ void sts64f(uint32_t a, float x, float y) { asm volatile("st.shared.v2.f32 [%0], {%1,%2};" ::"r"(a), "f"(x), "f"(y) : "memory"); }
__device__ __forceinline__ uint32_t pk(float lo, float hi) { uint32_t r; asm("cvt.rn.bf16x2.f32 %0, %1, %2;" : "=r"(r) : "f"(hi), "f"(lo)); return r; }
__device__ __forceinline__ uint32_t bitsel(uint32_t a, uint32_t m, uint32_t b) {
    uint32_t r;
    asm("lop3.b32 %0, %1, %2, %3, 0xea;" : "=r"(r) : "r"(a), "r"(m), "r"(b));
    return r;
}

__host__ __device__ constexpr uint64_t mkdesc(uint32_t off, uint32_t lbo, uint32_t sbo, uint32_t swz) {
    return (uint64_t)((SB0 + off) >> 4) | ((uint64_t)(lbo >> 4) << 16) | ((uint64_t)(sbo >> 4) << 32) | ((uint64_t)swz << 62);
}
__device__ __forceinline__ void wg_fence() { asm volatile("wgmma.fence.sync.aligned;" ::: "memory"); }
__device__ __forceinline__ void wg_commit() { asm volatile("wgmma.commit_group.sync.aligned;" ::: "memory"); }
template <int N> __device__ __forceinline__ void wg_wait() { asm volatile("wgmma.wait_group.sync.aligned %0;" ::"n"(N) : "memory"); }
template <int N> __device__ __forceinline__ void pin(float (&d)[N]) {
#pragma unroll
    for (int i = 0; i < N; i++) asm volatile("" : "+f"(d[i])::"memory");
}
template <int N> __device__ __forceinline__ void pinu(uint32_t (&d)[N]) {
#pragma unroll
    for (int i = 0; i < N; i++) asm volatile("" : "+r"(d[i])::"memory");
}

#define R8(d, o) "+f"(d[o]), "+f"(d[o + 1]), "+f"(d[o + 2]), "+f"(d[o + 3]), "+f"(d[o + 4]), "+f"(d[o + 5]), "+f"(d[o + 6]), "+f"(d[o + 7])
#define L8 "%0,%1,%2,%3,%4,%5,%6,%7"
#define L24 L8 ",%8,%9,%10,%11,%12,%13,%14,%15,%16,%17,%18,%19,%20,%21,%22,%23"
#define L32 L24 ",%24,%25,%26,%27,%28,%29,%30,%31"
#define L64 L32 ",%32,%33,%34,%35,%36,%37,%38,%39,%40,%41,%42,%43,%44,%45,%46,%47,%48,%49,%50,%51,%52,%53,%54,%55,%56,%57,%58,%59,%60,%61,%62,%63"

template <int O, int TA, int TB, int SC, int N> __device__ __forceinline__ void mma128_ss(float (&d)[N], uint64_t da, uint64_t db) {
    asm volatile("wgmma.mma_async.sync.aligned.m64n128k16.f32.bf16.bf16 {" L64 "}, %64, %65, %66, 1, 1, %67, %68;"
                 : R8(d, O), R8(d, O + 8), R8(d, O + 16), R8(d, O + 24), R8(d, O + 32), R8(d, O + 40), R8(d, O + 48), R8(d, O + 56)
                 : "l"(da), "l"(db), "n"(SC), "n"(TA), "n"(TB));
}
#define W8(d, o) "=f"(d[o]), "=f"(d[o + 1]), "=f"(d[o + 2]), "=f"(d[o + 3]), "=f"(d[o + 4]), "=f"(d[o + 5]), "=f"(d[o + 6]), "=f"(d[o + 7])
__device__ __forceinline__ void mma128_first(float (&d)[64], uint64_t da, uint64_t db) {
    asm volatile("wgmma.mma_async.sync.aligned.m64n128k16.f32.bf16.bf16 {" L64 "}, %64, %65, 0, 1, 1, 0, 1;"
                 : W8(d, 0), W8(d, 8), W8(d, 16), W8(d, 24), W8(d, 32), W8(d, 40), W8(d, 48), W8(d, 56) : "l"(da), "l"(db));
}
template <int TB, int SC> __device__ __forceinline__ void mma128_rs(float (&d)[64], const uint32_t* a, uint64_t db) {
    asm volatile("wgmma.mma_async.sync.aligned.m64n128k16.f32.bf16.bf16 {" L64 "}, {%64,%65,%66,%67}, %68, %69, 1, 1, %70;"
                 : R8(d, 0), R8(d, 8), R8(d, 16), R8(d, 24), R8(d, 32), R8(d, 40), R8(d, 48), R8(d, 56)
                 : "r"(a[0]), "r"(a[1]), "r"(a[2]), "r"(a[3]), "l"(db), "n"(SC), "n"(TB));
}
template <int TB, int SC> __device__ __forceinline__ void mma64_rs(float (&d)[32], const uint32_t* a, uint64_t db) {
    asm volatile("wgmma.mma_async.sync.aligned.m64n64k16.f32.bf16.bf16 {" L32 "}, {%32,%33,%34,%35}, %36, %37, 1, 1, %38;"
                 : R8(d, 0), R8(d, 8), R8(d, 16), R8(d, 24)
                 : "r"(a[0]), "r"(a[1]), "r"(a[2]), "r"(a[3]), "l"(db), "n"(SC), "n"(TB));
}
template <int TA, int SC> __device__ __forceinline__ void mma64_ss(float (&d)[32], uint64_t da, uint64_t db) {
    asm volatile("wgmma.mma_async.sync.aligned.m64n64k16.f32.bf16.bf16 {" L32 "}, %32, %33, %34, 1, 1, %35, 1;"
                 : R8(d, 0), R8(d, 8), R8(d, 16), R8(d, 24)
                 : "l"(da), "l"(db), "n"(SC), "n"(TA));
}
template <int SC> __device__ __forceinline__ void mma48_ss(float (&d)[32], uint64_t da, uint64_t db) {
    asm volatile("wgmma.mma_async.sync.aligned.m64n48k16.f32.bf16.bf16 {" L24 "}, %24, %25, %26, 1, 1, 0, 1;"
                 : R8(d, 8), R8(d, 16), R8(d, 24)
                 : "l"(da), "l"(db), "n"(SC));
}
template <int SC> __device__ __forceinline__ void mma16_rs(float (&d)[32], uint32_t a0, uint32_t a1, uint32_t a2, uint32_t a3, uint64_t db) {
    asm volatile("wgmma.mma_async.sync.aligned.m64n16k16.f32.bf16.bf16 {" L8 "}, {%8,%9,%10,%11}, %12, %13, 1, 1, 1;"
                 : R8(d, 0)
                 : "r"(a0), "r"(a1), "r"(a2), "r"(a3), "l"(db), "n"(SC));
}

__device__ __forceinline__ cf cmul(cf a, cf b) { return {fmaf(a.x, b.x, -a.y * b.y), fmaf(a.x, b.y, a.y * b.x)}; }
__device__ __forceinline__ cf csq(cf a) { return {fmaf(a.x, a.x, -a.y * a.y), (a.x + a.x) * a.y}; }
__device__ __forceinline__ cf cmulc(cf a, cf b) { return {fmaf(a.x, b.x, a.y * b.y), fmaf(a.y, b.x, -a.x * b.y)}; }
__device__ __forceinline__ cf cfma(cf a, cf b, cf c) { return {fmaf(a.x, b.x, fmaf(-a.y, b.y, c.x)), fmaf(a.x, b.y, fmaf(a.y, b.x, c.y))}; }
__device__ __forceinline__ cf csel(int c, cf a, cf b) {
    cf r;
    asm("{.reg .pred p; setp.ne.s32 p, %6, 0; selp.f32 %0, %2, %4, p; selp.f32 %1, %3, %5, p;}" : "=f"(r.x), "=f"(r.y) : "f"(a.x), "f"(a.y), "f"(b.x), "f"(b.y), "r"(c));
    return r;
}
__device__ __forceinline__ cf cadd(cf a, cf b) { return {a.x + b.x, a.y + b.y}; }
__device__ __forceinline__ cf csub(cf a, cf b) { return {a.x - b.x, a.y - b.y}; }
__device__ __forceinline__ cf twice_minus(cf a, cf s) { return {fmaf(2.f, a.x, -s.x), fmaf(2.f, a.y, -s.y)}; }
struct v2 { float a, b; };
struct c2 { v2 x, y; };
#define OP2(name, args, txt, ...) \
    __device__ __forceinline__ v2 name args { v2 r; asm volatile(txt : "=f"(r.a) : __VA_ARGS__(a)); asm volatile(txt : "=f"(r.b) : __VA_ARGS__(b)); return r; }
#define A_XY(e) "f"(x.e), "f"(y.e)
#define A_XYZ(e) "f"(x.e), "f"(y.e), "f"(z.e)
OP2(add2, (v2 x, v2 y), "add.rn.f32 %0, %1, %2;", A_XY)
OP2(sub2, (v2 x, v2 y), "sub.rn.f32 %0, %1, %2;", A_XY)
OP2(mul2, (v2 x, v2 y), "mul.rn.f32 %0, %1, %2;", A_XY)
OP2(tw2, (v2 x, v2 y), "{.reg .f32 n; neg.f32 n, %2; fma.rn.f32 %0, %1, 0f40000000, n;}", A_XY)
OP2(fma2, (v2 x, v2 y, v2 z), "fma.rn.f32 %0, %1, %2, %3;", A_XYZ)
OP2(fms2, (v2 x, v2 y, v2 z), "{.reg .f32 n; neg.f32 n, %3; fma.rn.f32 %0, %1, %2, n;}", A_XYZ)
OP2(fnm2, (v2 x, v2 y, v2 z), "{.reg .f32 n; neg.f32 n, %1; fma.rn.f32 %0, n, %2, %3;}", A_XYZ)
__device__ __forceinline__ c2 both(cf a) { return {{a.x, a.x}, {a.y, a.y}}; }
__device__ __forceinline__ c2 tw2(c2 a, c2 s) { c2 r; r.x = tw2(a.x, s.x); r.y = tw2(a.y, s.y); return r; }
template <bool CJ> __device__ __forceinline__ c2 cmul2(c2 a, c2 t) {
    const v2 p = mul2(a.y, t.y), q = mul2(a.x, t.y);
    c2 r;
    r.x = CJ ? fma2(a.x, t.x, p) : fms2(a.x, t.x, p);
    r.y = CJ ? fms2(a.y, t.x, q) : fma2(a.y, t.x, q);
    return r;
}
template <bool CJ> __device__ __forceinline__ c2 cfma2(c2 a, c2 t, c2 c) {
    const v2 p = CJ ? fma2(a.y, t.y, c.x) : fnm2(a.y, t.y, c.x), q = CJ ? fnm2(a.x, t.y, c.y) : fma2(a.x, t.y, c.y);
    c2 r;
    r.x = fma2(a.x, t.x, p);
    r.y = fma2(a.y, t.x, q);
    return r;
}
__device__ __forceinline__ void bfly2(c2 a, c2 b, c2& s, c2& d) { s.x = add2(a.x, b.x); d.x = sub2(a.x, b.x); s.y = add2(a.y, b.y); d.y = sub2(a.y, b.y); }
__device__ __forceinline__ void bflyi2(c2 a, c2 b, c2& s, c2& d) { s.x = add2(a.x, b.y); d.x = sub2(a.x, b.y); s.y = sub2(a.y, b.x); d.y = add2(a.y, b.x); }
__device__ __forceinline__ uint32_t pkv(float lo, float hi) { uint32_t r; asm volatile("cvt.rn.bf16x2.f32 %0, %1, %2;" : "=r"(r) : "f"(hi), "f"(lo)); return r; }
__device__ __forceinline__ uint32_t pkv(v2 v) { return pkv(v.a, v.b); }
__device__ __forceinline__ float upv(uint32_t v) { float r; asm volatile("shl.b32 %0, %1, 16;" : "=f"(r) : "r"(v)); return r; }
__device__ __forceinline__ cf twid(int m, int M) {
    int r = ((m + M / 2) & (M - 1)) - M / 2;
    float s, c;
    __sincosf((float)r * (-6.283185307179586f / (float)M), &s, &c);
    return {c, s};
}
template <int YL, class F> __device__ __forceinline__ void dft8_end(const c2 (&e)[4], c2 a4, c2 a5, c2 a6, c2 a7, F out) {
    const v2 s = {0.70710678118654752f, 0.70710678118654752f};
    c2 o0, o1, o2, o3, u, v;
    bfly2(a4, a6, o0, o2);
    bfly2(e[0], o0, u, v);
    out(0, u, v);
    YLD(YL, 2);
    bflyi2(e[2], o2, u, v);
    out(2, u, v);
    bflyi2(a5, a7, o1, o3);
    YLD(YL, 1);
    o0.x = add2(o1.y, o1.x); o0.y = sub2(o1.y, o1.x);
    u.x = fma2(o0.x, s, e[1].x); v.x = fnm2(o0.x, s, e[1].x); u.y = fma2(o0.y, s, e[1].y); v.y = fnm2(o0.y, s, e[1].y);
    out(1, u, v);
    YLD(YL, 2);
    o2.x = sub2(o3.y, o3.x); o2.y = add2(o3.y, o3.x);
    u.x = fma2(o2.x, s, e[3].x); v.x = fnm2(o2.x, s, e[3].x); u.y = fnm2(o2.y, s, e[3].y); v.y = fma2(o2.y, s, e[3].y);
    out(3, u, v);
    YLD(YL, 1);
}

__device__ __forceinline__ void bid2tile(int b, int& tc, int& cb) {
    const int c = b >> 1, e = c - 36, t7 = (e * 37) >> 8;
    int g;
    asm("{.reg .pred p, q; setp.lt.s32 p, %2, 4; setp.lt.s32 q, %2, 36; selp.s32 %0, %3, %4, q; selp.s32 %1, %5, %6, q; selp.s32 %0, 0, %0, p; selp.s32 %1, %7, %1, p;}"
        : "=&r"(g), "=&r"(cb) : "r"(c), "r"((c + 4) & 7), "r"(1 + e - 7 * t7), "r"((c - 4) >> 3), "r"(4 + t7), "r"(4 + c));
    tc = 2 * g + (b & 1);
}
__host__ __device__ __forceinline__ int pos_of(int n) { return (n & 24) + 4 * (n & 1) + ((n >> 1) & 3); }
static int kappa_of(int b, int gi) {
    const int r = b >> 4, k1 = 2 * ((b & 15) ^ (4 * gi)) + gi;
    return b >= 128 ? gi * 256 : (k1 || r < 4 ? k1 + 64 * r : 64 * r - 224);
}
static int slot3_of(int kap, int& cj) {
    int m = kap & 15;
    cj = (m > 8) || ((m & 7) == 0 && kap > 256);
    const int kk = cj ? 512 - kap : kap;
    m = kk & 15;
    return kk == 256 ? 0 : (m & 1) * 128 + (m & 6) * 16 + pos_of((kk >> 4) + 2 * (m & 8));
}

__device__ __forceinline__ uint32_t tag_bad(uint32_t a, uint32_t tag) {
    uint32_t v;
    asm volatile("ld.shared.u32 %0, [%1];" : "=r"(v) : "r"(a) : "memory");
    return (v ^ tag) & 1;
}
__device__ __forceinline__ bool wg_all_ok(uint32_t bad, int id) {
    uint32_t ok;
    asm volatile("{.reg .pred p, q; setp.eq.u32 q, %1, 0; barrier.red.and.aligned.pred p, %2, 128, q; selp.u32 %0, 1, 0, p;}" : "=r"(ok) : "r"(bad), "r"(id) : "memory");
    return __all_sync(~0u, ok);
}

__device__ __forceinline__ uint32_t lines_bad(uint32_t va, uint32_t tag, uint32_t bit) {
    uint32_t bad;
    asm volatile("{.reg .b32 a, b, c, d;\n"
                 "ld.shared.u32 a, [%1]; ld.shared.u32 b, [%1+4096]; ld.shared.u32 c, [%1+8192]; ld.shared.u32 d, [%1+12288];\n"
                 "lop3.b32 a, a, b, %2, 0x7e; lop3.b32 c, c, d, %2, 0x7e; lop3.b32 %0, a, c, %3, 0xa8;}"
                 : "=r"(bad) : "r"(va), "r"(tag), "r"(bit) : "memory");
    return bad;
}
__device__ __forceinline__ void load_w(uint32_t sb, const CUtensorMap* m, int kap, uint32_t more) {
    mbar_expect_tx(sb + OFF_BAR + B_WIN, 16 * WPITCH + more);
#pragma unroll 1
    for (int i = 0; i < 4; i++) {
        if (i) __nanosleep(PACE_W);
        tma2d(sb + OFF_W + i * (4 * WPITCH), m + (i & 1), ((i & 2 ? (512 - kap) & 511 : kap) * 1026 >> 4) * 2, 0, sb + OFF_BAR + B_WIN);
    }
}
__device__ __forceinline__ void carry_poll(unsigned __int128 (&f)[4], const uint4* a, int n, uint32_t tag) {
    f[0] = f[1] = f[2] = f[3] = tag;
    asm volatile("{.reg .pred p<4>;\n"
                 "setp.ge.s32 p0, %5, 0; setp.ge.s32 p1, %5, 4; setp.ge.s32 p2, %5, 8; setp.ge.s32 p3, %5, 12;\n"
                 "@p0 ld.relaxed.gpu.global.b128 %0, [%4];\n"
                 "@p1 ld.relaxed.gpu.global.b128 %1, [%4+-32768];\n"
                 "@p2 ld.relaxed.gpu.global.b128 %2, [%4+-65536];\n"
                 "@p3 ld.relaxed.gpu.global.b128 %3, [%4+-98304];}"
                 : "+q"(f[0]), "+q"(f[1]), "+q"(f[2]), "+q"(f[3]) : "l"(a), "r"(n) : "memory");
}
__device__ __forceinline__ uint32_t carry_sum(const unsigned __int128 (&f)[4], const cf (&m4)[2], uint32_t tag, cf (&P)[2]) {
#pragma unroll
    for (int h = 0; h < 2; h++)
#pragma unroll
        for (int a = 3; a >= 0; a--) {
            const cf v = {__uint_as_float((uint32_t)(f[a] >> (64 * h))), __uint_as_float((uint32_t)(f[a] >> (64 * h + 32)))};
            P[h] = a == 3 ? v : cfma(m4[h], P[h], v);
        }
    return (((uint32_t)f[0] ^ tag) | ((uint32_t)f[1] ^ tag) | ((uint32_t)f[2] ^ tag) | ((uint32_t)f[3] ^ tag)) & 15u;
}

struct Ring {
    uint32_t full, rel;
    uint32_t ph, bh;
    uint64_t da;
    bool sig;
    uint32_t k;
};
__device__ __forceinline__ void ring_release(const Ring& r, int slot) {
    if (r.sig) asm volatile("mbarrier.arrive.shared::cluster.b64 _, [%0];" ::"r"(r.rel + 8 * slot) : "memory");
}
__device__ __forceinline__ void ring_wait(Ring& r, int slot) {
    if (slot == 0) r.ph ^= 1;
    mbar_wait(r.full + 8 * slot, r.ph);
}
template <int SLOT, int TA, int HF, int J> __device__ __forceinline__ void mma_g(float (&d)[128], const Ring& r, int sc) {
    constexpr int O = 64 * HF;
    asm volatile("{.reg .b64 da, db; .reg .b32 l; .reg .pred p; setp.ne.s32 p, %67, 0; add.u64 da, %64, %69; mov.b32 l, %65; mov.b64 db, {l,%66};\n"
                 "wgmma.mma_async.sync.aligned.m64n128k16.f32.bf16.bf16 {" L64 "}, da, db, p, 1, 1, %68, 0;}"
                 : R8(d, O), R8(d, O + 8), R8(d, O + 16), R8(d, O + 24), R8(d, O + 32), R8(d, O + 40), R8(d, O + 48), R8(d, O + 56)
                 : "l"(r.da), "n"((uint32_t)mkdesc(SLOT * 32768 + 16384 + J * 32, 16, 0, 0)), "r"(r.bh), "r"(sc), "n"(TA),
                   "n"(1 + SLOT * 2048 + (TA ? HF * 64 + J * 256 : HF * 512 + J * 2)));
}
static_assert((GRP >> HAND & 1) && (GRP >> 7 & 1), "hand-over at the end of a group");
template <int SLOT, int TA, int I, int BAR> __device__ __forceinline__ void gemm_mmas(float (&d)[128], Ring& r, int sc, bool last) {
    mma_g<SLOT, TA, I & 1, I / 2>(d, r, I < 2 ? sc : 1);
    if (GRP >> I & 1) {
        wg_commit();
        if (BAR && I == HAND) asm volatile("{.reg .pred p; setp.ne.s32 p, %1, 0; @p bar.arrive %0, 256;}" ::"n"(BAR), "r"((int)last) : "memory");
        wg_wait<1>();
        if ((GRP & (1 << I) - 1) == 0 && sc) ring_release(r, (SLOT + NST - 1) % NST);
    }
    if constexpr (I < 7) gemm_mmas<SLOT, TA, I + 1, BAR>(d, r, sc, last);
}
template <int SLOT, int TA, int BAR = 0> __device__ __forceinline__ void gemm_step(float (&d)[128], Ring& r, int sc, bool last = false) {
    ring_wait(r, SLOT);
    wg_fence();
    gemm_mmas<SLOT, TA, 0, BAR>(d, r, sc, last);
}
template <int K, int HF> __device__ __forceinline__ void gemm_half(float (&d)[128], Ring& r) {
    if (HF == 0) { ring_wait(r, K % NST); wg_fence(); }
    mma_g<K % NST, 1, HF, 0>(d, r, 1); mma_g<K % NST, 1, HF, 1>(d, r, 1); mma_g<K % NST, 1, HF, 2>(d, r, 1); mma_g<K % NST, 1, HF, 3>(d, r, 1);
    if constexpr (HF == 0 && K < 64 - SKEW) { mma_g<K % NST, 1, 1, 0>(d, r, 1); mma_g<K % NST, 1, 1, 1>(d, r, 1); mma_g<K % NST, 1, 1, 2>(d, r, 1); mma_g<K % NST, 1, 1, 3>(d, r, 1); }
    if constexpr (K < 63) gemm_half<K + 1, HF>(d, r);
}
struct Prod {
    uint32_t b0, b1, b2, b3, b4, dbase;
    unsigned* prof;
    __device__ __forceinline__ Prod(uint32_t sb, int slot, uint32_t off) {
        const uint32_t bars = sb + OFF_BAR;
        b0 = bars + slot % NST * 8; b1 = bars + (slot + 1) % NST * 8; b2 = bars + (slot + 2) % NST * 8; b3 = bars + (slot + 3) % NST * 8; b4 = bars + (slot + 4) % NST * 8;
        dbase = sb + off - bars * 4096;
    }
    __device__ __forceinline__ uint32_t dst() const { return b0 * 4096 + dbase; }
    __device__ __forceinline__ void next() { const uint32_t t = b0; b0 = b1; b1 = b2; b2 = b3; b3 = b4; b4 = t; }
};
__device__ __forceinline__ void load_shared(Prod& r, uint32_t ph, const CUtensorMap* m, int c0, int c3) {
    mbar_wait(r.b0 + B_EMPTY, ph);
    tma4d_mc(r.dst(), m, c0, c3, r.b0);
    r.next();
}
__host__ __device__ constexpr uint64_t phases_from(int k) {
    uint64_t v = 0;
    for (int i = 0; i < 64; i++) v |= (uint64_t)((k + i) / NST & 1) << i;
    return v;
}
__device__ __forceinline__ uint32_t phases(int k, int n) { return ((uint32_t)(phases_from(0) >> k) & ((1u << n) - 1)) | 1u << n; }

__global__ void __cluster_dims__(2, 1, 1) __launch_bounds__(512, 1)
fused_kernel(const __grid_constant__ Maps tm, const __grid_constant__ Params p) {
    const CUtensorMap &tmX = tm.m[0], &tmBre = tm.m[1], &tmBim = tm.m[2], &tmXA = tm.m[5], &tmUst = tm.m[6], &tmVst = tm.m[7], &tmWr = tm.m[8], &tmVld = tm.m[10];
    extern __shared__ __align__(1024) uint8_t smraw[];
    const uint32_t sb = smem_u32(smraw);
    const uint32_t bars = sb + OFF_BAR;
    const int bid = blockIdx.x;
    const bool extra = bid >= 128;
    if (threadIdx.x == 480) RECL(0);
    int tc, cb;
    if (threadIdx.x < 32) {
        if (elect_one()) {
            pf_map(&tmX);
            pf_map(&tmBre);
            pf_map(&tmBim);
#pragma unroll
            for (int s = 0; s < NST; s++) mbar_init(bars + B_FULL + s * 8, 33);
            asm volatile("fence.mbarrier_init.release.cluster;" ::: "memory");
            bid2tile(bid, tc, cb);
            mbar_expect_tx(bars + B_FULL, 32768);
            tma5d(sb + 16384, &tmX, 0, 0, 0, 0, tc, bars + B_FULL);
            tma4d(sb, &tmBre, 0, 0, 0, cb * 4, bars + B_FULL);
            tma4d(sb + 8192, &tmBim, 0, 0, 0, cb * 4, bars + B_FULL);
            asm volatile("mbarrier.arrive.shared::cta.b64 _, [%0], 32;" ::"r"(bars + B_FULL) : "memory");
            STAMP(56);
        }
        __syncwarp();
    }
    const int wid = __shfl_sync(~0u, threadIdx.x >> 5, 0);
    if (wid == 1) {
        if (elect_one()) {
#pragma unroll
            for (int o = B_EMPTY; o < B_END; o += 8) mbar_init(bars + o, o < B_STGU ? 2 : (o == B_STGU ? 8 : (o < B_EP ? 4 : 1)));
            asm volatile("fence.mbarrier_init.release.cluster;" ::: "memory");
        }
        __syncwarp();
    }
    const int wg = ((wid >> 2) + 3) & 3, w = wid & 3;
    const int fb = bid >> 5, fcb = bid & 31, fpos = pos_of(fcb);
    const int vrow = ((bid & ~3) | (bid & 1) << 1 | (bid >> 1 & 1)) * 256;
    bid2tile(bid, tc, cb);
    asm volatile("barrier.cluster.arrive.relaxed.aligned;" ::: "memory");

    if (wg == 3) {
        asm volatile("setmaxnreg.dec.sync.aligned.u32 24;");
        if (w == 0) {
            if (extra) mbar_wait(bars + B_FULL, 0);
            else if (KMC > 1 && elect_one()) {
#pragma unroll 1
                for (int k = 1 + (bid >> 8); k < KMC; k++) {
                    mbar_expect_tx(bars + B_FULL + k * 8, 32768);
                    tma5d(sb + k * 32768 + 16384, &tmX, k * 64, 0, 0, 0, tc, bars + B_FULL + k * 8);
                    tma4d(sb + k * 32768, &tmBre, k * 64, 0, 0, cb * 4, bars + B_FULL + k * 8);
                    tma4d(sb + k * 32768 + 8192, &tmBim, k * 64, 0, 0, cb * 4, bars + B_FULL + k * 8);
                    asm volatile("mbarrier.arrive.shared::cta.b64 _, [%0], 32;" ::"r"(bars + B_FULL + k * 8) : "memory");
                }
                STAMP(28);
            }
            __syncwarp();
        }
        asm volatile("barrier.cluster.wait.aligned;" ::: "memory");
        if (bid == 129 || (sb & 0x3FFFF) != SB0) return;
        if (w < 2) {
            if (extra || !elect_one()) return;
            const int rank = bid & 1;
            if (w == 0) {
                Prod r(sb, KMC, 16384);
                int c0 = 64 * KMC;
#pragma unroll 1
                for (uint32_t pat = phases(NST + KMC, 32 - KMC); pat != 1; pat >>= 1) {
                    mbar_wait(r.b0 + B_EMPTY, pat);
                    if (c0 >= 0) tma5d(r.dst(), &tmX, c0, 0, 0, 0, tc, r.b0);
                    mbar_expect_tx(r.b0, c0 >= 0 ? 32768 : 16384);
                    asm volatile("mbarrier.arrive.shared::cta.b64 _, [%0], 32;" ::"r"(r.b0) : "memory");
                    c0 = c0 == 960 ? -64 * NST : c0 + 64;
                    r.next();
                }
                r.dbase -= 16384;
                const uint8_t* src = g_H + (size_t)tc * (32 * 16384);
                uint32_t all = (uint32_t)phases_from(32 - NST);
#pragma unroll 1
                for (int hh = 0; hh < 4; hh++) {
                    uint32_t pat = (all & 255) | 256;
                    all >>= 8;
                    mbar_wait(bars + B_HGO + 8 * hh, 0);
                    STAMPR(45 + hh);
#pragma unroll 1
                    do {
                        mbar_wait(r.b0 + B_EMPTY, pat);
                        bulk_ld(r.dst(), src, 16384, r.b0 + B_HLD);
                        mbar_expect_tx(r.b0 + B_HLD, 16384);
                        mbar_expect_tx(r.b0, 16384);
                        src += 16384;
                        r.next();
                        pat >>= 1;
                    } while (pat != 1);
                }
            } else {
                Prod r(sb, KMC, rank * 8192);
                int c = 64 * KMC;
#pragma unroll 1
                for (uint32_t pat = phases(NST + KMC, 32 - KMC); pat != 1; pat >>= 1) {
                    load_shared(r, pat, &tmBre + rank, c & 1023, cb * 4 + ((c >> 5) & 64));
                    c += c == 960 ? 2112 - 64 * NST : 64;
                }
                r.dbase += 16384;
                uint32_t pat = (uint32_t)phases_from(32 - NST);
#pragma unroll 1
                for (c = 0; c != 1024; c += 64) {
                    load_shared(r, pat, &tmBre + 2, c, cb * 8 + rank * 4);
                    load_shared(r, pat >> 1, &tmBre + 3, c, cb * 8 + rank * 4);
                    pat >>= 2;
                }
                mbar_arrive(bars + B_LDONE);
            }
        } else if (w == 2) {
            if (!elect_one()) return;
            STAMP5(39);
            if (!extra) {
                mbar_expect_tx(bars + B_XIN, 16384);
                mbar_expect_tx(bars + B_XIN + 8, 16384);
#pragma unroll 1
                for (int i = 0; i < 8; i++) {
                    const int k = i - XA_FIRST + XA_AT;
                    if (i >= XA_FIRST) mbar_wait(bars + B_EMPTY + (k < NST ? k : k - NST) * 8, k >= NST);
                    tma4d(sb + OFF_P + i * 2048, &tmXA, fcb * 32, 0, ((2 * i) & 7) + (i >> 2), fb, bars + B_XIN + (i & 4) * 2);
                    tma4d(sb + OFF_P + 16384 + i * 2048, &tmXA, fcb * 32 + 16, 0, ((2 * i) & 7) + (i >> 2), fb, bars + B_XIN + (i & 4) * 2);
                    if (!i) STAMP5(30);
                    STAMP5(31);
                }
            }
            pf_map(&tmWr);
            pf_map(&tmWr + 1);
            const unsigned ep = get_epoch(bars);
            if (!extra) mbar_wait(bars + B_XIN + 8, 0);
            STAMP5(32);
            load_w(sb, &tmWr, p.unit[2 * bid] & 0xffff, 8192);
            pf_map(&tmUst);
            if (!extra) mbar_wait(bars + B_STGU, 0);
            STAMP(21);
#pragma unroll 1
            for (int gi = 0; gi < 2; gi++) {
                if (!extra) {
#pragma unroll 1
                    for (int r = 128 * gi; r < 128 * gi + 128; r += UBOX) {
                        if (gi) __nanosleep(PACE_U);
                        tma2d_st(&tmUst, fb * 2048 + fpos * 64, r, sb + OFF_P + r * 128);
                        bulk_commit();
                    }
                    bulk_wait_read<HINT_U>();
                    red_hint(g_cnt + gi * 32);
                }
                if (!gi) bulk_ld(sb + OFF_F, g_tab + TAB_FG, 8192, bars + B_WIN);
                bulk_wait_read<0>();
                STAMPR(40 + gi);
                wait_cnt(g_cnt + 32 * gi, 128 * ep - (gi ? 0 : EARLY_U));
                {
                    if (gi) __nanosleep(UDELAY);
                    else STAMP(42);
                    mbar_expect_tx(bars + B_UIN + 8 * gi, 16384);
                    bulk_ld(sb + OFF_P + gi * 16384, g_U + (size_t)(extra ? 0 : bid + 128 * gi) * 16384, 16384, bars + B_UIN + 8 * gi);
                }
            }
            pf_map(&tmBre + 2); pf_map(&tmBre + 3); pf_map(&tmVst); pf_map(&tmVld);
            mbar_wait(bars + B_WFREE, 0);
            load_w(sb, &tmWr, p.unit[2 * bid + 1] & 0xffff, 0);
#pragma unroll 1
            for (int gi = 0; gi < 2; gi++) {
                const int vc = ((p.unit[2 * bid + gi] >> 16) & 255) * 64, go = vc >> 13;
                const uint32_t src = extra ? sb + 32768 : sb + OFF_P + gi * 16384;
                mbar_wait(bars + B_STG, gi);
                STAMPR(23 + gi);
                if (extra && !gi) continue;
                if (bid + gi != 0) {
#pragma unroll 1
                    for (int r = 0; r < 128; r += 32) {
                        if (r && !gi) __nanosleep(PACE_V);
                        tma2d_st(&tmVst, vc, r, src + r * 128);
                        bulk_commit();
                    }
                }
                bulk_wait_read<HINT_V>();
                red_hint(g_cnt + 64 + 32 * go);
                bulk_wait_read<0>();
                STAMP(49);
                if (extra) break;
                wait_cnt(g_cnt + 64 + 32 * gi, (129 - gi) * ep - gi * EARLY_V);
                {
                    STAMPR(43 + gi);
#pragma unroll
                    for (int h = 0; h < 2; h++) {
                        mbar_expect_tx(bars + B_VIN + gi * 16 + h * 8, 8192);
                        tma2d(src + h * 8192, &tmVld, h * 32, vrow + gi * 128, bars + B_VIN + gi * 16 + h * 8);
                    }
                }
                if (XT && !gi) {
                    mbar_wait(bars + B_WFREE, 1);
                    mbar_expect_tx(bars + B_WIN, 16384);
#pragma unroll 1
                    for (int i = 0; i < 4; i++) {
                        tma2d(sb + OFF_W + i * 4096, tm.m + 11, cb * 128, tc * 128 + 32 * i + 16, bars + B_WIN);
                    }
                }
            }
        } else {
            const uint32_t tag = ld_rlx(g_epoch + bid * 8) + 1;
            __syncwarp();
            if (elect_one()) {
                asm volatile("st.shared.u32 [%0], %1;" ::"r"(bars + B_EPOCH), "r"(tag) : "memory");
                mbar_arrive(bars + B_EP);
                asm volatile("st.relaxed.gpu.global.u32 [%0], %1;" ::"l"(g_epoch + bid * 8), "r"(tag) : "memory");
            }
            __syncwarp();
            if (extra) return;
            const int lane = (threadIdx.x + p.zero[0]) & 31;
            Prod r(sb, 32, 0);
            uint32_t va = (lane & 3) * 516 + (lane >> 4) * 2048 + (lane & 12) * 32 + (lane >> 2) * 16 + r.dbase;
            asm volatile("" : "+r"(va));
            uint32_t n = 0;
#pragma unroll 1
            for (int half = 0; half < 2; half++) {
#pragma unroll 1
                for (uint32_t pat = phases(16 * half, 16); pat != 1; pat >>= 1) {
                    mbar_wait(r.b0 + B_HLD, pat);
                    bool bad = lines_bad(r.b0 * 4096 + va, tag, 1);
                    if (!bad) mbar_arrive(r.b0);
#pragma unroll 1
                    while (__any_sync(~0u, bad)) {
                        const int kk = __shfl_sync(~0u, pat, 0);
                        if (elect_one()) {
                            mbar_expect_tx(bars + B_HRTY, 16384);
                            bulk_ld(r.dst(), g_H + (uint32_t)(tc * 32 + half * 16 + __clz(kk) - 15) * 16384, 16384, bars + B_HRTY);
                        }
                        __syncwarp();
                        mbar_wait(bars + B_HRTY, n++);
                        if (bad && !lines_bad(r.b0 * 4096 + va, tag, n < SPIN_LIMIT)) { bad = false; mbar_arrive(r.b0); }
                        __syncwarp();
                    }
                    if (pat >> 16) STAMPR(6 + 23 * half);
                    r.next();
                }
            }
        }
    } else {
        asm volatile("setmaxnreg.inc.sync.aligned.u32 152;");
        asm volatile("barrier.cluster.wait.aligned;" ::: "memory");
        STAMP(55);
        if ((extra && (wg != 2 || bid == 129)) || (sb & 0x3FFFF) != SB0) return;
        const int hf = wg - 1;
#define INDICES(i) const int t7 = (threadIdx.x + p.zero[i]) & 127, lane = t7 & 31, g = lane >> 2, q = lane & 3, k1 = t7 >> 2, mi = lane >> 3, gl = lane & 7; \
                   const uint32_t tmask = q == 0 ? ~1u : ~0u;
        if (wg == 1) {
            INDICES(1)
            const int ch = (t7 >> 6) * 512 + (t7 & 8) * 32 + cb * 32 + ((t7 >> 1) & 24) + (t7 & 7);
            const float lr = __bfloat162float(p.lre[ch]), li = __bfloat162float(p.lim[ch]);
            const float dt = __bfloat162float(__float2bfloat16(expf(__bfloat162float(p.ldt[ch]))));
            float sn, cs;
            sincospif(dt * li * 0.31830988618379067f, &sn, &cs);
            const float ex = expf(dt * lr), br = ex * cs, bi = ex * sn;
            const float inv = __fdividef(2.0f, lr * lr + li * li);
            const cf lam = {br, -bi}, gam = {((br - 1.f) * lr + bi * li) * inv, -(bi * lr - (br - 1.f) * li) * inv};
            const cf l32 = csq(csq(csq(csq(csq(lam))))), l64 = csq(l32), m1 = csq(l64), m2 = csq(m1), g2 = cmul(gam, l64);
            sts128f(sb + OFF_T1 + t7 * 16, lam, l32);
            sts128f(sb + OFF_TL + t7 * 32, gam, cmul(gam, l32));
            sts128f(sb + OFF_TL + t7 * 32 + 16, g2, cmul(g2, l32));
            sts128f(sb + OFF_TM + t7 * 32, csq(m2), m1);
            sts128f(sb + OFF_TM + t7 * 32 + 16, m2, cmul(m2, m1));
            __syncwarp();
            if (lane == 0) mbar_arrive(bars + B_LAM);
        }
        if (wg != 0 && !extra) {
            INDICES(2)
            uint32_t f1[16];
#pragma unroll
            for (int j = 0; j < 4; j++) { const uint4 v = ldtab(TAB_F1 + j * 512 + t7 * 4); f1[4 * j] = v.x; f1[4 * j + 1] = v.y; f1[4 * j + 2] = v.z; f1[4 * j + 3] = v.w; }
            cf tw[8];
            load_tw(tw, k1);
            const uint32_t tbit = get_epoch(bars) & ~tmask;
            const uint64_t dx = mkdesc(OFF_P, 2048, 256, 3) + hf * 1024;
            const int gr = gl & 1, jr = (gl >> 1) + 4 * ((w ^ gl) & 1);
            const uint32_t a0 = w + gl ? sb + OFF_P + (gr * 128 + 8 * (w >> 1) + jr + 64 * (mi >> 1)) * 128 : sb + OFF_F + 2048;
            const uint32_t rs = w + gl ? 2048 : 0;
            const uint32_t scr = sb + OFF_F + hf * 1024;
            float acc[32];
            c2 ev[2][4];
            uint4 fx0, fx1;
#pragma unroll 1
            for (int od = 0;; od++) {
                if (od) STAMP5(33 + hf);
                mbar_wait(bars + B_XIN + od * 8, 0);
                if (od) STAMP(20);
                pinu(f1);
                wg_fence();
                mma64_rs<1, 0>(acc, f1, dx + od * 512);
                mma64_rs<1, 1>(acc, f1 + 4, dx + od * 512 + 32);
                mma64_rs<1, 1>(acc, f1 + 8, dx + od * 512 + 64);
                mma64_rs<1, 1>(acc, f1 + 12, dx + od * 512 + 96);
                wg_commit();
                wg_wait<0>();
                pin(acc);
                pinu(f1);
                if (od) STAMP5(35);
                if (k1 == 0) {
#pragma unroll
                    for (int i = 0; i < 8; i++) sts128f(scr + (i >> 1) * 256 + od * 128 + (i & 1) * 64 + q * 16, {acc[4 * i], acc[4 * i + 1]}, {acc[4 * i + 2], acc[4 * i + 3]});
                }
                if (od) break;
                asm volatile("ld.global.nc.v4.b32 {%0,%1,%2,%3}, [%4];" : "=r"(fx0.x), "=r"(fx0.y), "=r"(fx0.z), "=r"(fx0.w) : "l"(g_tab + TAB_FX + (t7 & 120)));
                asm volatile("ld.global.nc.v4.b32 {%0,%1,%2,%3}, [%4];" : "=r"(fx1.x), "=r"(fx1.y), "=r"(fx1.z), "=r"(fx1.w) : "l"(g_tab + TAB_FX + (t7 & 120) + 4));
#pragma unroll
                for (int cl = 0; cl < 2; cl++) {
                    auto in = [&](int n) { const int i = 4 * (n + cl); return c2{{acc[i], acc[i + 1]}, {acc[i + 2], acc[i + 3]}}; };
                    const c2 a0 = cfma2<false>(in(4), both(tw[4]), in(0)), a1 = tw2(in(0), a0);
                    YIELD();
                    const c2 t2 = cmul2<false>(in(2), both(tw[2]));
                    YIELD();
                    const c2 a2 = cfma2<false>(in(6), both(tw[6]), t2), a3 = tw2(t2, a2);
                    YIELD();
                    bfly2(a0, a2, ev[cl][0], ev[cl][2]);
                    YIELD();
                    bflyi2(a1, a3, ev[cl][1], ev[cl][3]);
                    YIELD();
                }
            }
#pragma unroll
            for (int cl = 0; cl < 2; cl++) {
                auto in = [&](int n) { const int i = 4 * (n - 1 + cl); return c2{{acc[i], acc[i + 1]}, {acc[i + 2], acc[i + 3]}}; };
                const c2 t1 = cmul2<false>(in(1), both(tw[1]));
                YLD(YF1, 2);
                const c2 a4 = cfma2<false>(in(5), both(tw[5]), t1), a5 = tw2(t1, a4);
                YLD(YF1, 3);
                cf sx[8];
                if (cl == 0) {
                    bar_sync(6, 256);
                    STAMP5(36);
#pragma unroll
                    for (int n = 0; n < 8; n++) sx[n] = lds_cf(scr + n * 128 + gl * 16 + (w >> 1) * 8);
                }
                const c2 t3 = cmul2<false>(in(3), both(tw[3]));
                YLD(YF1, 1);
                const c2 a6 = cfma2<false>(in(7), both(tw[7]), t3), a7 = tw2(t3, a6);
                YLD(YF1, 2);
                const uint32_t a1 = a0 + (((((mi & 1) << 2) | ((2 * hf + cl) ^ (fpos & 3))) ^ jr) << 4);
                dft8_end<YF1>(ev[cl], a4, a5, a6, a7, [&](int r, c2 u, c2 v) {
                    uint32_t o0 = pkv(u.x), o1 = pkv(u.y), o2 = pkv(v.x), o3 = pkv(v.y);
                    if (cl == 0) { o0 = bitsel(o0, tmask, tbit); o1 = bitsel(o1, tmask, tbit); o2 = bitsel(o2, tmask, tbit); o3 = bitsel(o3, tmask, tbit); }
                    stsm4(a1 + r * rs, o0, o1, o2, o3);
                });
                if (cl == 0) {
                    YLD(YF1, 2);
                    float s0 = 0.f, s1 = 0.f;
#pragma unroll
                    for (int n = 0; n < 8; n++) {
                        const float c = __uint_as_float(n < 4 ? (n == 0 ? fx0.x : n == 1 ? fx0.y : n == 2 ? fx0.z : fx0.w) : (n == 4 ? fx1.x : n == 5 ? fx1.y : n == 6 ? fx1.z : fx1.w));
                        s0 = fmaf(c, sx[n].x, s0); s1 = fmaf(c, sx[n].y, s1);
                    }
                    asm volatile("st.shared.b32 [%0], %1;" ::"r"(sb + OFF_P + (t7 >> 4) * 2048 + (((mi & 1) * 4 + ((2 * hf + (g & 1)) ^ (fpos & 3))) << 4) + q * 4), "r"(bitsel(pk(s0, s1), tmask, tbit)) : "memory");
                    YLD(YF1, 1);
                }
            }
            fence_async_sm();
            __syncwarp();
            if (lane == 0) mbar_arrive(bars + B_STGU);
        }
        if (wg != 2) {
        if (wg == 0) bar_sync(4, 128);
        asm volatile("setmaxnreg.inc.sync.aligned.u32 168;");
        float d[128];
        Ring rg;
        rg.full = bars + B_FULL;
        asm("mapa.shared::cluster.u32 %0, %1, %2;" : "=r"(rg.rel) : "r"(bars + B_EMPTY), "r"(w & 1));
        rg.sig = ((threadIdx.x + p.zero[7]) & 95) == 0;
        rg.bh = (uint32_t)(mkdesc(0, 0, 1024, 1) >> 32) + p.zero[0];
        rg.da = p.da[0];
        rg.ph = 1;
        rg.k = 130 * 66 + bid * 66 + 16 * wg;
        if (wg == 0) {
            STAMP(0);
            gemm_step<0, 0>(d, rg, 0);
        } else {
            bar_sync(1, 256);
            STAMP(10);
        }
        rg.da = p.da[1];
#pragma unroll 1
        for (int i = 0; i < 3; i++) {
            gemm_step<1, 0>(d, rg, i >= wg);
            gemm_step<2, 0>(d, rg, 1);
            gemm_step<3, 0>(d, rg, 1);
            gemm_step<4, 0>(d, rg, 1);
            gemm_step<0, 0, 1>(d, rg, 1, i - wg == 2);
        }
        if (wg != p.zero[1]) {
            rg.da = p.da[0];
            gemm_step<1, 0, 2>(d, rg, 1, true);
        }
        {
            INDICES(3)
            cf lam[2], l32[2], l2[2];
            const uint32_t ta = sb + (wg * 64 + 16 * w + g) * 16;
            mbar_wait(bars + B_LAM, 0);
            const unsigned ep = get_epoch(bars), tag = ep & 15u;
            lds128f(ta + OFF_T1, lam[0].x, lam[0].y, l32[0].x, l32[0].y);
            lds128f(ta + OFF_T1 + 128, lam[1].x, lam[1].y, l32[1].x, l32[1].y);
            const uint4* cpub = g_carry + (uint32_t)(wg * 256 + cb * 32 + 8 * w + tc * 512 + g);
            l2[0] = csq(lam[0]);
            l2[1] = csq(lam[1]);
            asm volatile("pmevent 0;" : "+l"(cpub), "+f"(l2[0].x), "+f"(l2[0].y), "+f"(l2[1].x), "+f"(l2[1].y));
            wg_wait<0>();
            ring_release(rg, wg);
            pin(d);
            STAMPW(1, 11);
            cf f[2];
#pragma unroll
            for (int h = 0; h < 2; h++) {
                c2 c = {{d[2 * h], d[2 * h + 1]}, {d[64 + 2 * h], d[65 + 2 * h]}};
#pragma unroll
                for (int i = 1; i < 16; i++) {
                    const int r = 4 * i + 2 * h;
#define P1A "fma.rn.f32 a0, %2, %9, %4; fma.rn.f32 a1, %3, %9, %5;\n"
#define P1B "fma.rn.f32 b0, %0, n, %6; fma.rn.f32 b1, %1, n, %7;\n"
#define P1X "fma.rn.f32 %0, %0, %8, a0; fma.rn.f32 %1, %1, %8, a1;\n"
#define P1Y "fma.rn.f32 %2, %2, %8, b0; fma.rn.f32 %3, %3, %8, b1;\n"
#define P1ARG : "+f"(c.x.a), "+f"(c.x.b), "+f"(c.y.a), "+f"(c.y.b) : "f"(d[r]), "f"(d[r + 1]), "f"(d[64 + r]), "f"(d[65 + r]), "f"(l2[h].x), "f"(l2[h].y)
                    if (i & 1) asm volatile("{.reg .f32 a0, a1, b0, b1, n; neg.f32 n, %9;\n" P1A P1B P1X P1Y "}" P1ARG);
                    else asm volatile("{.reg .f32 a0, a1, b0, b1, n; neg.f32 n, %9;\n" P1B P1A P1Y P1X "}" P1ARG);
                    if (i % YS == 0) YIELD();
                    if (i == 12) lds128f(ta + OFF_T1 + 128 * h, lam[h].x, lam[h].y, l32[h].x, l32[h].y);
                }
                f[h] = cfma(lam[h], {c.x.a, -c.y.a}, {c.x.b, -c.y.b});
            }
            cf st[2], gam[2];
            gam[0] = lds_cf(2 * ta - sb + OFF_TL);
            gam[1] = lds_cf(2 * ta - sb + OFF_TL + 256);
            cf v0[2], v1[2], v2[2];
#pragma unroll
            for (int h = 0; h < 2; h++) {
                v0[h] = {__shfl_sync(~0u, f[h].x, 0, 4), __shfl_sync(~0u, f[h].y, 0, 4)};
                v1[h] = {__shfl_sync(~0u, f[h].x, 1, 4), __shfl_sync(~0u, f[h].y, 1, 4)};
                v2[h] = {__shfl_sync(~0u, f[h].x, 2, 4), __shfl_sync(~0u, f[h].y, 2, 4)};
            }
#pragma unroll
            for (int h = 0; h < 2; h++) {
                v1[h] = cfma(l32[h], v0[h], v1[h]);
                v2[h] = cfma(l32[h], v1[h], v2[h]);
                f[h] = cfma(l32[h], v2[h], f[h]);
            }
            asm volatile("{.reg .pred p; .reg .b64 a, b; .reg .b128 v; setp.eq.u32 p, %5, 3; mov.b64 a, {%1,%2}; mov.b64 b, {%3,%4}; mov.b128 v, {a, b};\n"
                         "@p st.relaxed.gpu.global.b128 [%0], v;}" ::"l"(cpub),
                         "r"(bitsel(__float_as_uint(f[0].x), ~15u, tag)), "r"(__float_as_uint(f[0].y)), "r"(__float_as_uint(f[1].x)), "r"(__float_as_uint(f[1].y)), "r"(q) : "memory");
            STAMPX(2, 12);
            YIELD();
#pragma unroll
            for (int h = 0; h < 2; h++) st[h] = cmul(gam[h], csel(q & 2, csel(q & 1, v2[h], v1[h]), csel(q & 1, v0[h], cf{0.f, 0.f})));
            const uint4* cget = cpub + (gl - g) - (1 + mi) * 512;
            const int nget = tc - 1 - mi;
            unsigned __int128 fq[4];
            auto prescale = [&](int i) {
                const int h = i >> 4, r = 4 * (i & 15) + 2 * h;
                asm volatile("{.reg .f32 s0, s1, n; neg.f32 n, %4; mul.f32 s0, %5, %1; mul.f32 s1, %5, %3; mul.f32 %1, n, %1; mul.f32 %3, n, %3;\n"
                             "fma.rn.f32 %1, %5, %0, %1; fma.rn.f32 %3, %5, %2, %3; fma.rn.f32 %0, %4, %0, s0; fma.rn.f32 %2, %4, %2, s1;}"
                             : "+f"(d[r]), "+f"(d[64 + r]), "+f"(d[r + 1]), "+f"(d[65 + r]) : "f"(gam[h].x), "f"(gam[h].y));
            };
#pragma unroll
            for (int i = 0; i < 32; i++) {
                if (i == POLL_AT) carry_poll(fq, cget, nget, tag);
                if (i % YS == 0) YIELD();
                prescale(i);
            }
            YIELD();
            const uint32_t tm = sb + OFF_TM + (wg * 64 + 16 * w) * 32;
            cf m4[2], mj[2], P[2], lq[2];
#pragma unroll
            for (int h = 0; h < 2; h++) {
                m4[h] = lds_cf(tm + gl * 32 + h * 256);
                mj[h] = lds_cf(tm + gl * 32 + h * 256 + mi * 8);
            }
            uint32_t bad = carry_sum(fq, m4, tag, P);
            unsigned n = 0;
            while (__any_sync(~0u, bad) && ++n < SPIN_LIMIT) {
                unsigned __int128 fr[4];
                carry_poll(fr, cget, nget, tag);
                bad = carry_sum(fr, m4, tag, P);
                YIELD();
                mj[0] = lds_cf(tm + gl * 32 + mi * 8);
                mj[1] = lds_cf(tm + gl * 32 + 256 + mi * 8);
            }
            STAMPX(53, 54);
            P[0] = csel(mi, cmul(P[0], mj[0]), P[0]);
            P[1] = csel(mi, cmul(P[1], mj[1]), P[1]);
            __syncwarp();
            sts128f(tm + lane * 16, P[0], P[1]);
#pragma unroll
            for (int h = 0; h < 2; h++) {
                lq[h] = lds_cf(2 * ta - sb + OFF_TL + h * 256 + q * 8);
                lam[h] = lds_cf(ta + OFF_T1 + h * 128);
            }
            __syncwarp();
            float ps[4][4];
#pragma unroll
            for (int j = 0; j < 4; j++) lds128f(tm + g * 16 + j * 128, ps[j][0], ps[j][1], ps[j][2], ps[j][3]);
            const uint8_t* hp = g_H + (uint32_t)((tc * 32 + wg * 16 + (cb & 6)) * 16384 + ((cb & 1) * 4 + w) * 2048 + g * 64 + ((q ^ (g >> 1)) << 4));
#pragma unroll
            for (int h = 0; h < 2; h++)
                st[h] = cfma(lq[h], {(ps[0][2 * h] + ps[1][2 * h]) + (ps[2][2 * h] + ps[3][2 * h]), (ps[0][2 * h + 1] + ps[1][2 * h + 1]) + (ps[2][2 * h + 1] + ps[3][2 * h + 1])}, st[h]);
            STAMPX(3, 13);
            uint32_t hv[32];
#pragma unroll
            for (int h = 0; h < 2; h++) {
                YIELD();
                cf c = st[h];
#pragma unroll
                for (int i = 0; i < 16; i++) {
                    const int r = 4 * i + 2 * h;
                    const cf a = cfma(lam[h], c, {d[r], d[64 + r]});
                    c = cfma(lam[h], a, {d[r + 1], d[65 + r]});
                    hv[i] = pk(a.x, c.x);
                    hv[16 + i] = pk(a.y, c.y);
                    if ((i & 3) == (i >> 2)) { hv[i] = bitsel(hv[i], ~1u, ep & 1); hv[16 + i] = bitsel(hv[16 + i], ~1u, ep & 1); }
                    if (h == 0 && (i & 3) == 3) {
                        stg128(hp + (i >> 2) * 512, hv[i - 3], hv[i - 2], hv[i - 1], hv[i]);
                        stg128(hp + 16384 + (i >> 2) * 512, hv[13 + i], hv[14 + i], hv[15 + i], hv[16 + i]);
                    }
                }
                if (h == 0) {
                    STAMPW(4, 14);
                    if (lane == 0) red_hint(g_hcnt + tc * 64 + wg * 32);
                }
            }
            YIELD();
            if (w == 0) {
                wait_cnt(g_hcnt + tc * 64 + wg * 32, 32 * ep - EARLY_H);
                if (lane < 4) mbar_arrive(bars + B_HGO + 16 * wg);
            } else mbar_wait(bars + B_HGO + 16 * wg, 0);
#pragma unroll
            for (int j = 0; j < 8; j++) {
                stg128(hp + (8 + (j >> 2)) * 16384 + (j & 3) * 512, hv[4 * j], hv[4 * j + 1], hv[4 * j + 2], hv[4 * j + 3]);
                if (j < 7) __nanosleep(PACE_H);
            }
            __syncwarp();
            if (lane == 0) mbar_arrive(bars + B_HGO + 16 * wg + 8);
            STAMPW(5, 15);
        }
        if (wg == p.zero[2]) {
            INDICES(1)
            float y[128];
            const uint32_t sa = sb + w * 4096 + g * 512 + q * 8;
            bar_sync(2, 256);
            STAMP(7);
            rg.da = p.da[2];
            rg.ph = 0;
            rg.k = 130 * 66 + bid * 66 + 32;
#pragma unroll 1
            for (int i = 0;; i++) {
                gemm_step<2, 1>(y, rg, i);
                gemm_step<3, 1>(y, rg, 1);
                gemm_step<4, 1>(y, rg, 1);
                if (i == 5) break;
                gemm_step<0, 1>(y, rg, 1);
                gemm_step<1, 1>(y, rg, 1);
            }
            rg.da = p.da[3];
            gemm_half<60, 0>(y, rg);
            wg_commit();
            gemm_half<64 - SKEW, 1>(y, rg);
            wg_commit();
#pragma unroll
            for (int r = 0; r < 4; r++) {
                if (r == 0) {
                    wg_wait<1>();
#pragma unroll
                    for (int i = 0; i < 64; i++) asm volatile("" : "+f"(y[i])::"memory");
                    STAMP(16);
                    bar_sync(4, 128);
                }
                if (r == 2) {
                    STAMP(18);
                    wg_wait<0>();
#pragma unroll
                    for (int i = 64; i < 128; i++) asm volatile("" : "+f"(y[i])::"memory");
                    STAMP(8);
                    bar_sync(4, 128);
                }
#pragma unroll
                for (int c = 0; c < 16; c++) {
                    const int yi = 64 * (r >> 1) + 4 * c + 2 * (r & 1);
                    sts64f(sa + (r < 2 ? (NST - 1) * 32768 : 0) + (r & 1) * 16384 + (c >> 2) * 128 + (((c ^ g) & 3) << 5), y[yi], y[yi + 1]);
                }
                if (r == 0) bar_arrive(9, 256);
                if (r == 1) bar_arrive(10, 256);
                if (r == 2) bar_arrive(11, 256);
                if (r == 3) bar_arrive(12, 256);
            }
            STAMP(19);
            return;
        }
        bar_sync(8, 128);
        asm volatile("setmaxnreg.dec.sync.aligned.u32 152;");
        } else {
            INDICES(4)
            cf T[8];
            load_T(T, t7);
            const uint32_t tag = get_epoch(bars) & 1;
            float acc[64];
            constexpr uint64_t dF = mkdesc(OFF_F, 16, 1024, 1);
            const uint32_t tga = sb + OFF_P + t7 * 128 + (((t7 & 1) ^ (g & 2)) << 4) + (g & 1) * 64;
            bool ok = false;
            mbar_wait(bars + B_WIN, 0);
#pragma unroll 1
            for (int gi = 0;; gi++) {
                const uint32_t un = p.unit[2 * bid + gi];
                const int kap = un & 0xffff;
                const uint32_t buf = sb + OFF_P + gi * 16384;
                STAMP3(39);
                float za[32], zb[32], ya[32], yb[32];
                const uint64_t dB = mkdesc(OFF_P, 4096, 512, 2) + gi * 1024;
                uint32_t ad, am, pa, pb;
                if (w == 2) {
                    ad = sb + OFF_W + (lane & 8) * 128;
                    am = ad + ((lane & 4) | (((kap ? 3 : 4) - lane) & 3)) * WPITCH + (8 * WPITCH + ((-2 * kap) & 15));
                    ad += gl * WPITCH + ((2 * kap) & 15);
                    asm volatile("" : "+r"(ad), "+r"(am));
                    mbar_wait(bars + B_WIN, gi);
                    pa = lds_u16(ad);
                    pb = lds_u16(am);
                }
#pragma unroll 1
                for (int n = gi; !ok && n < 4096; n++) {
                    if (n) bar_sync(3, 128);
                    if (n && w == 0 && elect_one()) { mbar_expect_tx(bars + B_UIN + gi * 8, 16384); bulk_ld(buf, g_U + (size_t)(extra ? 0 : bid + gi * 128) * 16384, 16384, bars + B_UIN + gi * 8); }
                    mbar_wait(bars + B_UIN + gi * 8, n & 1);
                    STAMP3(22);
                    wg_fence();
                    mma128_first(acc, dF, dB);
                    mma128_ss<0, 0, 1, 1>(acc, dF + 2, dB + 64);
                    mma128_ss<0, 0, 1, 1>(acc, dF + 4, dB + 128);
                    mma128_ss<0, 0, 1, 1>(acc, dF + 6, dB + 192);
                    wg_commit();
                    YIELD();
                    ok = wg_all_ok(tag_bad(tga + gi * 16384, tag), 3);
                    wg_wait<0>();
                    pin(acc);
                }
                STAMP3(30);
                uint32_t af[32];
#pragma unroll
                for (int b = 0; b < 4; b++) {
#pragma unroll
                    for (int c = 0; c < 4; c++) {
                        const int i = 4 * (4 * b + c);
                        cf x0 = cmul({acc[i], acc[i + 2]}, T[2 * c]), x1 = cmul({acc[i + 1], acc[i + 3]}, T[2 * c + 1]);
                        af[16 * (b >> 1) + 4 * c + (b & 1)] = pk(x0.x, x0.y);
                        af[16 * (b >> 1) + 4 * c + 2 + (b & 1)] = pk(x1.x, x1.y);
                        YLD(YF2, c == 3 ? 1 : (c == 1 ? 2 : 3));
                    }
                    if (b == 0 && w == 2) {
                        const uint32_t sg = (lane & 4) << 13, v = pk(0.5f * (up(pa) + up(pb ^ sg)), 0.f);
                        asm volatile("st.shared.u16 [%0], %1;" ::"r"(ad), "r"(v) : "memory");
                        asm volatile("st.shared.u16 [%0], %1;" ::"r"(am), "r"(v ^ sg) : "memory");
                    }
                    if (b == 1) {
                        wg_fence();
                        mma64_rs<0, 0>(za, af, dF); mma64_rs<0, 1>(za, af + 4, dF + 2); mma64_rs<0, 1>(za, af + 8, dF + 4); mma64_rs<0, 1>(za, af + 12, dF + 6);
                        wg_commit();
                    }
                }
                wg_fence();
                mma64_rs<0, 0>(zb, af + 16, dF); mma64_rs<0, 1>(zb, af + 20, dF + 2); mma64_rs<0, 1>(zb, af + 24, dF + 4); mma64_rs<0, 1>(zb, af + 28, dF + 6);
                wg_commit();
                STAMP3(31);
                int kq;
                asm volatile("mad.lo.s32 %0, %1, 512, %2;" : "=r"(kq) : "r"(q), "r"(kap));
                uint32_t wad[4];
#pragma unroll
                for (int j = 0; j < 4; j++) wad[j] = sb + OFF_W + ((j + (kq >> 9)) & 3) * WPITCH + ((2 * kap) & 15) + 2 * k1 + 128 * q;
                if (gi) fence_async_sm();
                bar_sync(3, 128);
                if (lane < gi) mbar_arrive(bars + B_STG);
                uint32_t wn[16];
#pragma unroll
                for (int j = 0; j < 16; j++) wn[j] = lds_u16(wad[j >> 2] + (j & 1) * 64 + (j & 2) * (2 * WPITCH));
                const cf be1 = twid(kq, 2048), be2 = cmul(be1, be1), be3 = cmul(be1, be2);
                YLD(YF2, 1);
                wg_wait<0>();
                pin(za);
                pin(zb);
                pinu(af);
                STAMP3(32);
                c2 z[4];
                auto pack = [&](int jb, int b) {
                    af[16 * (b >> 1) + 4 * jb + (b & 1)] = pkv(z[b].x);
                    af[16 * (b >> 1) + 4 * jb + 2 + (b & 1)] = pkv(z[b].y);
                };
#pragma unroll
                for (int jb = 0; jb < 4; jb++) {
                    if (jb == 2) STAMP3(37);
                    if (jb == 1) {
#pragma unroll
                        for (int j = 0; j < 4; j++)
                            wad[j] = sb + OFF_W + (8 + (((kap ? 3 : 4) - j - q) & 3)) * WPITCH + ((-2 * kap) & 15) + 1024 - 2 * k1 - 128 * q;
                    }
                    c2 W[4];
                    auto next = [&](int j) {
                        W[j] = {{upv(wn[4 * j]), upv(wn[4 * j + 1])}, {upv(wn[4 * j + 2]), upv(wn[4 * j + 3])}};
                        if (jb < 3) {
#pragma unroll
                            for (int n = 0; n < 4; n++) wn[4 * j + n] = lds_u16(wad[j] + (jb ? 512 - 512 * jb - (n & 1) * 64 : 512 + (n & 1) * 64) + (n & 2) * (2 * WPITCH));
                        }
                    };
                    const int i = 8 * jb;
                    const c2 z0 = {{za[i], za[i + 1]}, {za[i + 4], za[i + 5]}};
                    if (jb) pack(jb - 1, 1);
                    next(0);
                    c2 s0 = cfma2<false>({{zb[i], zb[i + 1]}, {zb[i + 4], zb[i + 5]}}, both(be2), z0), s1 = tw2(z0, s0);
                    YLD(YF2, 2);
                    if (jb) pack(jb - 1, 3);
                    if (jb == 3) load_T(T, t7);
                    next(1);
                    const c2 z1 = cmul2<false>({{za[i + 2], za[i + 3]}, {za[i + 6], za[i + 7]}}, both(be1));
                    YLD(YF2, 3);
                    c2 s2 = cfma2<false>({{zb[i + 2], zb[i + 3]}, {zb[i + 6], zb[i + 7]}}, both(be3), z1), s3 = tw2(z1, s2);
                    YLD(YF2, 1);
                    c2 x0, x1, x2, x3;
                    next(2);
                    bfly2(s0, s2, x0, x2);
                    const c2 y0 = jb < 2 ? cmul2<false>(x0, W[0]) : cmul2<true>(x0, W[0]);
                    YLD(YF2, 2);
                    next(3);
                    bflyi2(s1, s3, x1, x3);
                    const c2 y1 = jb < 2 ? cmul2<false>(x1, W[1]) : cmul2<true>(x1, W[1]);
                    YLD(YF2, 1);
                    s0 = jb < 2 ? cfma2<false>(x2, W[2], y0) : cfma2<true>(x2, W[2], y0);
                    s1 = tw2(y0, s0);
                    YLD(YF2, 3);
                    s2 = jb < 2 ? cfma2<false>(x3, W[3], y1) : cfma2<true>(x3, W[3], y1);
                    s3 = tw2(y1, s2);
                    YLD(YF2, 2);
                    bfly2(s0, s2, z[0], x2);
                    z[2] = cmul2<true>(x2, both(be2));
                    pack(jb, 0);
                    YLD(YF2, 1);
                    bflyi2(s1, s3, x3, x1);
                    pack(jb, 2);
                    z[1] = cmul2<true>(x1, both(be1));
                    YLD(YF2, 3);
                    z[3] = cmul2<true>(x3, both(be3));
                    YLD(YF2, 1);
                }
                pack(3, 1);
                pack(3, 3);
                pinu(af);
                wg_fence();
                mma64_rs<1, 0>(ya, af, dF); mma64_rs<1, 1>(ya, af + 4, dF + 128); mma64_rs<1, 1>(ya, af + 8, dF + 256); mma64_rs<1, 1>(ya, af + 12, dF + 384);
                wg_commit();
                mma64_rs<1, 0>(yb, af + 16, dF); mma64_rs<1, 1>(yb, af + 20, dF + 128); mma64_rs<1, 1>(yb, af + 24, dF + 256); mma64_rs<1, 1>(yb, af + 28, dF + 384);
                wg_commit();
                STAMP3(33);
                if (w == 2) fence_async_sm();
                __syncwarp();
                if (lane == 0) mbar_arrive(bars + B_WFREE);
                {
                    const uint32_t a0 = buf + (mi & 1) * 4096 + (16 * w + 8 * (mi >> 1) + gl) * 64;
#pragma unroll
                    for (int u = 0; u < 2; u++)
#pragma unroll
                        for (int c = 0; c < 4; c++) {
                            if (c == 0) {
                                if (u == 0) { wg_wait<1>(); pin(ya); STAMP3(34); }
                                else { wg_wait<0>(); pin(yb); pinu(af); }
                            }
                            const int i = 8 * c;
                            const float(&yy)[32] = u ? yb : ya;
                            const cf x0 = cmulc({yy[i], yy[i + 1]}, T[2 * c]), x1 = cmulc({yy[i + 4], yy[i + 5]}, T[2 * c + 1]);
                            const uint32_t o0 = pk(x0.x, x1.x), o2 = pk(x0.y, x1.y);
                            YLD(YF2, 3);
                            const cf y0 = cmulc({yy[i + 2], yy[i + 3]}, T[2 * c]), y1 = cmulc({yy[i + 6], yy[i + 7]}, T[2 * c + 1]);
                            stsm4(a0 + u * 8192 + ((c ^ (gl >> 1)) << 4), o0, pk(y0.x, y1.x), o2, pk(y0.y, y1.y));
                            YLD(YF2, 2 - (c & 1));
                        }
                }
                STAMP3(38);
                const uint32_t flip = ((g & 1) && !(un >> 24)) ? 0x80008000u : 0u, flipt = flip | (tag & ~tmask);
                const int rw = 8 * w + (gl & 4) + 2 * (mi & 1) + ((gl >> 1) & 1);
                const uint32_t a0 = (extra ? ((gl & 1) == gi ? sb + 32768 : sb + 65536) : buf) + rw * 128 +
                                    (((((gl & 1) << 1) | ((mi >> 1) ^ ((un >> 17) & 1))) ^ (rw & 7)) << 4);
                auto put = [&](const float (&v)[32], uint32_t a) {
#pragma unroll
                    for (int i = 0; i < 32; i += 8)
                        stsm4((a ^ ((i & 8) * 8)) + (i >> 4) * 4096, (pk(v[i], v[i + 1]) & tmask) ^ flipt, (pk(v[i + 2], v[i + 3]) & tmask) ^ flipt,
                              pk(v[i + 4], v[i + 5]) ^ flip, pk(v[i + 6], v[i + 7]) ^ flip);
                };
                fence_async_sm();
                bar_sync(3, 128);
                float va[32], vb[32];
                wg_fence();
                mma64_ss<1, 0>(va, dF, dB); mma64_ss<1, 0>(vb, dF, dB + 512);
                mma64_ss<1, 1>(va, dF + 128, dB + 64); mma64_ss<1, 1>(vb, dF + 128, dB + 576);
                mma64_ss<1, 1>(va, dF + 256, dB + 128); mma64_ss<1, 1>(vb, dF + 256, dB + 640);
                mma64_ss<1, 1>(va, dF + 384, dB + 192); mma64_ss<1, 1>(vb, dF + 384, dB + 704);
                wg_commit();
                STAMP3(35);
                uint32_t bad = 0;
                if (!gi) {
                    mbar_wait(bars + B_UIN + 8, 0);
                    bad = tag_bad(tga + 16384, tag);
                }
                wg_wait<0>();
                pin(va);
                pin(vb);
                STAMP3(36);
                ok = wg_all_ok(bad, 3);
                put(va, a0);
                if (gi) {
                    put(vb, a0 + 8192);
                    fence_async_sm();
                    __syncwarp();
                    if (lane == 0) mbar_arrive(bars + B_STG);
                    break;
                }
                constexpr uint64_t dN = mkdesc(OFF_P + 16384, 4096, 512, 2);
                wg_fence();
                mma128_first(acc, dF, dN);
                mma128_ss<0, 0, 1, 1>(acc, dF + 2, dN + 64);
                mma128_ss<0, 0, 1, 1>(acc, dF + 4, dN + 128);
                mma128_ss<0, 0, 1, 1>(acc, dF + 6, dN + 192);
                wg_commit();
                put(vb, a0 + 8192);
                wg_wait<0>();
                pin(acc);
            }
            if (extra) return;
        }
        uint2 xd[16], dd;
        auto skip = [&]() {
            const int lane = (threadIdx.x + p.zero[2]) & 31;
            const uint2* xp = (const uint2*)(p.xb + (uint32_t)((tc * 128 + 64 * (w & 1) + 32 * hf + 8 * (w >> 1)) * 1024 + cb * 128)) + lane;
            dd = __ldg((const uint2*)(p.dsk + cb * 128) + lane);
#pragma unroll
            for (int j = 0; j < (XT ? 8 : 16); j++) {
                asm volatile("ld.global.nc.L1::no_allocate.v2.b32 {%0,%1}, [%2];" : "=r"(xd[j].x), "=r"(xd[j].y) : "l"(xp + ((j >> 3) * 16 + (j & 7)) * 256));
            }
        };
        auto skip2 = [&]() {
            if (XT) {
                const uint32_t xa = sb + OFF_W + (2 * (w & 1) + hf) * 4096 + (w >> 1) * 2048 + ((threadIdx.x + p.zero[3]) & 31) * 8;
                mbar_wait(bars + B_WIN, 0);
#pragma unroll
                for (int j = 0; j < 8; j++) asm volatile("ld.shared.v2.b32 {%0,%1}, [%2];" : "=r"(xd[8 + j].x), "=r"(xd[8 + j].y) : "r"(xa + j * 256) : "memory");
            }
#pragma unroll
            for (int j = 0; j < 16; j++) {
                if (j % 4 == 0) YIELD();
                asm volatile("fma.rn.bf16x2 %0, %0, %1, %2;" : "+r"(xd[j].x) : "r"(dd.x), "r"(0x80008000u));
                asm volatile("fma.rn.bf16x2 %0, %0, %1, %2;" : "+r"(xd[j].y) : "r"(dd.y), "r"(0x80008000u));
            }
            YIELD();
        };
        {
            INDICES(5)
            uint32_t sp[8];
#pragma unroll
            for (int j = 0; j < 2; j++) { const uint4 v = ldtab(TAB_SP + j * 512 + t7 * 4); sp[4 * j] = v.x; sp[4 * j + 1] = v.y; sp[4 * j + 2] = v.z; sp[4 * j + 3] = v.w; }
            cf tw[8];
            load_tw(tw, k1);
            tw[4].x *= 2.f; tw[4].y *= 2.f;
            const uint32_t tag = get_epoch(bars) & 1;
            const uint32_t in = sb + OFF_P + hf * 8192;
            constexpr uint64_t dF = mkdesc(OFF_F, 16, 1024, 1);
            const uint64_t dB = mkdesc(OFF_P, 2048, 256, 3) + hf * 512;
            float ae[32], ao[32];
            c2 ev[2][4];
            auto blk = [&](const float (&a)[32], int i) { return c2{{a[i], a[i + 1]}, {a[i + 2], a[i + 3]}}; };
            auto unfold = [&](c2 a, c2 u, int n, c2& zn, c2& zm, int yl) {
                const float wc = n == 1 ? 0.92387953251128674f : (n == 2 ? 0.70710678118654752f : 0.38268343236508977f);
                const float ws = n == 3 ? 0.92387953251128674f : (n == 2 ? 0.70710678118654752f : 0.38268343236508977f);
                const v2 c = {wc, wc}, s = {ws, ws}, two = {2.f, 2.f};
                const c2 y = cmul2<false>(a, both(tw[n])), t = both(tw[8 - n]);
                c2 E;
                E.x = fnm2(u.y, t.y, y.x); E.y = fnm2(u.x, t.y, y.y); E.x = fma2(u.x, t.x, E.x); E.y = fnm2(u.y, t.x, E.y);
                YLD(yl, 2);
                const c2 D = tw2(y, E);
                zn.x = fnm2(D.y, c, E.x); zn.y = fma2(D.y, s, E.y); zn.x = fma2(D.x, s, zn.x); zn.y = fma2(D.x, c, zn.y);
                zm.x = tw2(E.x, zn.x); zm.y = fnm2(E.y, two, zn.y);
                YLD(yl, 1);
            };
#pragma unroll
            for (int rgn = 0; rgn < 2; rgn++) {
#pragma unroll 1
                for (int n = 0; n < 4096; n++) {
                    mbar_wait(bars + B_VIN + rgn * 16 + hf * 8, n & 1);
                    if (rgn) STAMP(25);
                    if (rgn == 0) {
                        pinu(sp);
                        wg_fence();
                        mma48_ss<0>(ae, dF, dB + 128); mma16_rs<0>(ae, sp[0], 0u, sp[1], 0u, dB);
                        mma48_ss<1>(ae, dF + 2, dB + 160); mma16_rs<1>(ae, sp[2], 0u, sp[3], 0u, dB + 32);
                        mma48_ss<1>(ae, dF + 4, dB + 192); mma16_rs<1>(ae, 0u, sp[4], 0u, sp[5], dB + 64);
                        mma48_ss<1>(ae, dF + 6, dB + 224); mma16_rs<1>(ae, 0u, sp[6], 0u, sp[7], dB + 96);
                    } else {
                        wg_fence();
                        mma64_ss<0, 0>(ao, dF, dB + 1024);
                        mma64_ss<0, 1>(ao, dF + 2, dB + 1056);
                        mma64_ss<0, 1>(ao, dF + 4, dB + 1088);
                        mma64_ss<0, 1>(ao, dF + 6, dB + 1120);
                    }
                    wg_commit();
                    const bool ok = wg_all_ok(tag_bad(in + rgn * 16384 + t7 * 64 + (t7 & 6) * 8, tag), hf ? 3 : 8);
                    wg_wait<0>();
                    if (rgn) pin(ao);
                    else { pin(ae); pinu(sp); }
                    if (ok) break;
                    wg_all_ok(0, hf ? 3 : 8);
                    if (w == 0 && elect_one()) {
                        mbar_expect_tx(bars + B_VIN + rgn * 16 + hf * 8, 8192);
                        tma2d(in + rgn * 16384, &tmVld, hf * 32, vrow + rgn * 128, bars + B_VIN + rgn * 16 + hf * 8);
                    }
                }
                if (rgn == 0) {
#pragma unroll
                    for (int cl = 0; cl < 2; cl++) {
                        const c2 b = blk(ae, 4 * cl), z0 = {add2(b.x, b.y), sub2(b.x, b.y)};
                        const c2 a0 = cfma2<false>(blk(ae, 16 + 4 * cl), both(tw[4]), z0), a1 = tw2(z0, a0);
                        YIELD();
                        c2 z2, z6, a2, a3;
                        unfold(blk(ae, 8 + 4 * cl), blk(ae, 24 + 4 * cl), 2, z2, z6, 2);
                        bfly2(z2, z6, a2, a3);
                        bfly2(a0, a2, ev[cl][0], ev[cl][2]);
                        YIELD();
                        bflyi2(a1, a3, ev[cl][1], ev[cl][3]);
                    }
                    YIELD();
                }
            }
            skip();
            const uint32_t a0 = in + (8 * w + (gl ^ (2 * hf)) + 32 * (mi & 1)) * 32 + (mi >> 1) * 16384 + (gl & 4) * 4;
#pragma unroll
            for (int cl = 0; cl < 2; cl++) {
                c2 z1, z3, z5, z7, a4, a5, a6, a7;
                unfold(blk(ao, 4 * cl), blk(ao, 24 + 4 * cl), 1, z1, z7, YF3);
                if (cl == 0) wg_all_ok(0, hf ? 3 : 8);
                unfold(blk(ao, 8 + 4 * cl), blk(ao, 16 + 4 * cl), 3, z3, z5, YF3);
                bfly2(z1, z5, a4, a5);
                bfly2(z3, z7, a6, a7);
                YLD(YF3, 2);
                dft8_end<YF3>(ev[cl], a4, a5, a6, a7, [&](int r, c2 u, c2 v) { stsm4((a0 ^ (cl * 16)) + r * 2048, pkv(u.x), pkv(u.y), pkv(v.x), pkv(v.y)); });
            }
            bar_sync(7, 256);
            STAMP(26);
        }
        INDICES(6)
        const int t0 = tc * 128 + 64 * (w & 1) + 32 * hf + 8 * (w >> 1);
        {
            const int n0 = 16 * hf + 4 * w + mi;
            uint32_t la = sb + OFF_P + (((gl >> 2) * 8256) ^ (n0 * 32)) + ((((gl >> 1) & 1) ^ (w & 1)) << 4) + (gl & 1) * 8;
            const float* op = p.out + (uint32_t)((4 * n0 + fb) * 2048 + fcb * 32 + gl * 4);
#pragma unroll 1
            for (int it = 0; it < 4; it++) {
                uint32_t u[8];
#pragma unroll
                for (int i = 0; i < 4; i++) asm volatile("ld.shared.v2.b32 {%0,%1}, [%2];" : "=r"(u[2 * i]), "=r"(u[2 * i + 1]) : "r"(la + i * 1024) : "memory");
#pragma unroll
                for (int i = 0; i < 4; i++) {
                    stg128(op + i * 128 * 2048, u[2 * i] << 16, u[2 * i] & 0xffff0000u, u[2 * i + 1] << 16, u[2 * i + 1] & 0xffff0000u);
                    if (TRYP >> i & 1) asm volatile("{.reg .pred p; mbarrier.try_wait.parity.shared::cta.b64 p, [%0], 0, %1; @p pmevent 0;}" ::"r"(bars + B_LDONE), "r"(PACE_O) : "memory");
                }
                la += it == 1 ? 12288 : 4096;
                op += 4 * 128 * 2048;
            }
            STAMP(27);
        }
        skip2();
        const uint32_t ra = sb + hf * 16384 + w * 4096;
        float* ob = p.out + (size_t)t0 * 2048 + 1024 + cb * 128 + lane * 4;
#pragma unroll
        for (int mb = 0; mb < 2; mb++) {
            if (hf == 0) { if (mb == 0) bar_sync(9, 256); else bar_sync(11, 256); }
            else { if (mb == 0) bar_sync(10, 256); else bar_sync(12, 256); }
            if (mb == 0) STAMP(17);
            float v[8][4];
#pragma unroll
            for (int j = 0; j < 8; j++) lds128f(ra + (mb ? 0 : (NST - 1) * 32768) + j * 512 + ((lane * 16) ^ ((j & 3) * 32)), v[j][0], v[j][1], v[j][2], v[j][3]);
#pragma unroll
            for (int j = 0; j < 8; j++) {
                const uint2 s = xd[8 * mb + j];
                stg128(ob + (16 * mb + j) * 2048, __float_as_uint(v[j][0] + up(s.x)), __float_as_uint(v[j][1] + __uint_as_float(s.x & 0xffff0000u)),
                       __float_as_uint(v[j][2] + up(s.y)), __float_as_uint(v[j][3] + __uint_as_float(s.y & 0xffff0000u)));
            }
        }
        STAMP(9);
        if (threadIdx.x == 480) RECL(2);
    }
}

typedef CUresult (*EncodeFn)(CUtensorMap*, CUtensorMapDataType, cuuint32_t, void*, const cuuint64_t*, const cuuint64_t*, const cuuint32_t*,
                             const cuuint32_t*, CUtensorMapInterleave, CUtensorMapSwizzle, CUtensorMapL2promotion, CUtensorMapFloatOOBfill);

static CUtensorMap make_map(EncodeFn enc, const void* ptr, int rank, const cuuint64_t* dims, const cuuint64_t* strides, const cuuint32_t* box,
                            CUtensorMapSwizzle swz, CUtensorMapL2promotion promo, CUtensorMapDataType dt = CU_TENSOR_MAP_DATA_TYPE_BFLOAT16) {
    CUtensorMap m;
    const cuuint32_t es[5] = {1, 1, 1, 1, 1};
    enc(&m, dt, rank, const_cast<void*>(ptr), dims, strides, box, es, CU_TENSOR_MAP_INTERLEAVE_NONE, swz, promo,
        CU_TENSOR_MAP_FLOAT_OOB_FILL_NONE);
    return m;
}

extern "C" void kernel_launch(void* const* d_in, const int* in_sizes, int n_in, void* d_out, int out_size) {
    void* fn = nullptr;
    cudaDriverEntryPointQueryResult qr;
    cudaGetDriverEntryPoint("cuTensorMapEncodeTiled", &fn, cudaEnableDefault, &qr);
    EncodeFn enc = (EncodeFn)fn;
    void *pU, *pV;
    cudaGetSymbolAddress(&pU, g_U);
    cudaGetSymbolAddress(&pV, g_V);
    const CUtensorMapL2promotion P256 = CU_TENSOR_MAP_L2_PROMOTION_L2_256B, P0 = CU_TENSOR_MAP_L2_PROMOTION_NONE;

    const cuuint64_t dX[5] = {1024, 2, 4, 16, 16}, sX[4] = {2048, 32 * 2048, 2 * 2048, 128 * 2048};
    const cuuint32_t bX[5] = {64, 2, 4, 16, 1};
    CUtensorMap tmX = make_map(enc, d_in[3], 5, dX, sX, bX, CU_TENSOR_MAP_SWIZZLE_128B, CU_TENSOR_MAP_L2_PROMOTION_L2_128B);
    const cuuint64_t dB[4] = {1024, 8, 2, 96}, sB[3] = {2048, 256 * 2048, 8 * 2048}, dC[4] = {1024, 8, 2, 64}, sC[3] = {2048, 8 * 2048, 16 * 2048};
    const cuuint32_t bB[4] = {64, 8, 2, 4};
    CUtensorMap tmBre = make_map(enc, d_in[6], 4, dB, sB, bB, CU_TENSOR_MAP_SWIZZLE_128B, P256);
    CUtensorMap tmBim = make_map(enc, d_in[7], 4, dB, sB, bB, CU_TENSOR_MAP_SWIZZLE_128B, P256);
    CUtensorMap tmCre = make_map(enc, d_in[8], 4, dC, sC, bB, CU_TENSOR_MAP_SWIZZLE_128B, P256);
    CUtensorMap tmCim = make_map(enc, d_in[9], 4, dC, sC, bB, CU_TENSOR_MAP_SWIZZLE_128B, P256);

    const cuuint64_t dU[2] = {8192, 256}, sU[1] = {16384};
    const cuuint32_t bS[2] = {64, UBOX};
    CUtensorMap tmUst = make_map(enc, pU, 2, dU, sU, bS, CU_TENSOR_MAP_SWIZZLE_128B, P0);
    const cuuint64_t dV[2] = {16384, 128}, sV[1] = {32768}, dL[2] = {64, 32768}, sL[1] = {128};
    const cuuint32_t bL[2] = {32, 128};
    CUtensorMap tmVst = make_map(enc, pV, 2, dV, sV, bS, CU_TENSOR_MAP_SWIZZLE_128B, P0);
    CUtensorMap tmVld = make_map(enc, pV, 2, dL, sL, bL, CU_TENSOR_MAP_SWIZZLE_NONE, P0);
    const cuuint64_t dR[2] = {1024, 2048}, sR[1] = {2048};
    const cuuint32_t bR[2] = {128, 16};
    CUtensorMap tmXR = make_map(enc, d_in[3], 2, dR, sR, bR, CU_TENSOR_MAP_SWIZZLE_NONE, P0);
    const cuuint64_t dA[4] = {1024, 64, 8, 4}, sA[3] = {32 * 2048, 4 * 2048, 2048};
    const cuuint32_t bA[4] = {16, 64, 1, 1};
    CUtensorMap tmXA = make_map(enc, d_in[0], 4, dA, sA, bA, CU_TENSOR_MAP_SWIZZLE_32B, CU_TENSOR_MAP_L2_PROMOTION_L2_128B);
    const cuuint64_t dF[2] = {512 * 1026 / 8, 4}, sF[1] = {512 * 1026};
    const cuuint32_t bF[2] = {WPITCH / 8, 4};
    CUtensorMap tmWr = make_map(enc, d_in[1], 2, dF, sF, bF, CU_TENSOR_MAP_SWIZZLE_NONE, P0, CU_TENSOR_MAP_DATA_TYPE_UINT64);
    CUtensorMap tmWi = make_map(enc, d_in[2], 2, dF, sF, bF, CU_TENSOR_MAP_SWIZZLE_NONE, P0, CU_TENSOR_MAP_DATA_TYPE_UINT64);

    Params p = {};
    p.xb = (const __nv_bfloat16*)d_in[3];
    p.lre = (const __nv_bfloat16*)d_in[4];
    p.lim = (const __nv_bfloat16*)d_in[5];
    p.ldt = (const __nv_bfloat16*)d_in[10];
    p.dsk = (const __nv_bfloat16*)d_in[11];
    p.out = (float*)d_out;
    p.da[0] = p.da[1] = mkdesc(0, 16, 1024, 1) - 1;
    p.da[2] = p.da[3] = mkdesc(0, 512, 2048, 2) - 1;
    for (int i = 0; i < 258; i++) {
        int cj;
        const int kap = kappa_of(i >> 1, i & 1), s3 = slot3_of(kap, cj);
        p.unit[i] = kap | s3 << 16 | cj << 24;
    }
    cudaFuncSetAttribute(fused_kernel, cudaFuncAttributeMaxDynamicSharedMemorySize, SMEM_BYTES);
    fused_kernel<<<130, 512, SMEM_BYTES>>>(Maps{{tmX, tmBre, tmBim, tmCre, tmCim, tmXA, tmUst, tmVst, tmWr, tmWi, tmVld, tmXR}}, p);
}
```

```cpp
#include <cuda_runtime.h>
#include <cuda.h>
#include <cuda_bf16.h>
#include <stdint.h>

#define NST 5
#define SB0 1024
#define WPITCH 1056
#define OFF_P (NST * 32768)
#define OFF_F (OFF_P + 32768)
#define OFF_W (OFF_F + 8192)
#define OFF_TL (OFF_W + 16 * WPITCH)
#define OFF_TM (OFF_TL + 4096)
#define OFF_T1 (OFF_TM + 4096)
#define OFF_BAR (OFF_T1 + 2048)
#define OFF_STAMP (OFF_BAR + 384)
#define SMEM_BYTES (OFF_BAR + 512)
#define B_FULL 0
#define B_EMPTY 40
#define B_STGU 80
#define B_HGO 88
#define B_LAM 120
#define B_STG 128
#define B_WFREE 136
#define B_EP 144
#define B_LDONE 152
#define B_UIN 160
#define B_WIN 176
#define B_XIN 184
#define B_VIN 200
#define B_HRTY 232
#define B_HLD 240
#define B_END 280
#define B_EPOCH 280

#define PACE_U 250
#define PACE_V 120
#define PACE_O 250
#define PACE_H 120
#define HAND 1
#define POLL_AT 24
#define XA_FIRST 3
#define XA_AT 0
#define YS 3
#define UDELAY 250
#define PACE_W 120
#define HINT_U 0
#define HINT_V 2
#define GRP 0x92
#define EARLY_U 24
#define EARLY_V 16
#define EARLY_H 4
#define KMC 4
#define HOIST 1
#define TRYP 10
#define XT 1
#define UBOX 32
#define SKEW 4
#define SPIN_LIMIT 32768

#define YIELD() asm volatile("pmevent 0;")
#define YF1 2
#define YF2 2
#define YF3 2
#define YLD(level, n) do { if ((level) >= (n)) YIELD(); } while (0)

__device__ __align__(1024) uint8_t g_U[4 << 20];
__device__ __align__(1024) uint8_t g_V[4 << 20];
__device__ __align__(1024) uint8_t g_H[8 << 20];
__device__ __align__(1024) uint4 g_carry[16 * 512];
__device__ __align__(1024) unsigned g_hcnt[16 * 64];
__device__ __align__(128) unsigned g_cnt[128];
__device__ __align__(128) unsigned g_epoch[129 * 8];

#define RECL(i) do { } while (0)
#define STAMP(i) do { } while (0)
#define STAMPR(i) do { } while (0)
#define STAMPW(a, b) do { } while (0)
#define STAMPX(a, b) do { } while (0)
#define STAMP5(i) do { } while (0)
#define STAMP3(i) do { } while (0)

#define TAB_FG 0
#define TAB_F1 2048
#define TAB_T 4096
#define TAB_SP 6144
#define TAB_TW 7168
#define TAB_FX 7680
__device__ __align__(1024) const uint32_t g_tab[7808] = {
0x80003d80,0x80003d80,0x80003d80,0x80003d80,0x80003d80,0x80003d80,0x80003d80,0x80003d80,0x80003d80,0x80003d80,0x80003d80,0x80003d80,0x80003d80,0x80003d80,0x80003d80,0x80003d80,
0x80003d80,0x80003d80,0x80003d80,0x80003d80,0x80003d80,0x80003d80,0x80003d80,0x80003d80,0x80003d80,0x80003d80,0x80003d80,0x80003d80,0x80003d80,0x80003d80,0x80003d80,0x80003d80,
0x3c483d7b,0x3d0e3d55,0x3d553d0e,0x3d7b3c48,0x80003d80,0x3cc43d6d,0x3d353d35,0x3d6d3cc4,0x3d7bbc48,0x3d55bd0e,0x3d0ebd55,0x3c48bd7b,0x3d800000,0x3d6dbcc4,0x3d35bd35,0x3cc4bd6d,
0xbc48bd7b,0xbd0ebd55,0xbd55bd0e,0xbd7bbc48,0x8000bd80,0xbcc4bd6d,0xbd35bd35,0xbd6dbcc4,0xbd7b3c48,0xbd553d0e,0xbd0e3d55,0xbc483d7b,0xbd800000,0xbd6d3cc4,0xbd353d35,0xbcc43d6d,
0x8000bd80,0xbd35bd35,0xbd800000,0xbd353d35,0xbcc4bd6d,0xbd6dbcc4,0xbd6d3cc4,0xbcc43d6d,0x80003d80,0x3d353d35,0x3d800000,0x3d35bd35,0x3cc43d6d,0x3d6d3cc4,0x3d6dbcc4,0x3cc4bd6d,
0x8000bd80,0xbd35bd35,0xbd800000,0xbd353d35,0xbcc4bd6d,0xbd6dbcc4,0xbd6d3cc4,0xbcc43d6d,0x80003d80,0x3d353d35,0x3d800000,0x3d35bd35,0x3cc43d6d,0x3d6d3cc4,0x3d6dbcc4,0x3cc4bd6d,
0xbd553d0e,0x3c483d7b,0x3d7b3c48,0x3d0ebd55,0xbd800000,0xbcc43d6d,0x3d353d35,0x3d6dbcc4,0x3d0e3d55,0x3d7bbc48,0x3c48bd7b,0xbd55bd0e,0x80003d80,0x3d6d3cc4,0x3d35bd35,0xbcc4bd6d,
0x3d55bd0e,0xbc48bd7b,0xbd7bbc48,0xbd0e3d55,0x3d800000,0x3cc4bd6d,0xbd35bd35,0xbd6d3cc4,0xbd0ebd55,0xbd7b3c48,0xbc483d7b,0x3d553d0e,0x8000bd80,0xbd6dbcc4,0xbd353d35,0x3cc43d6d,
0x80003d80,0x3d800000,0x8000bd80,0xbd800000,0x3d353d35,0x3d35bd35,0xbd35bd35,0xbd353d35,0x80003d80,0x3d800000,0x8000bd80,0xbd800000,0x3d353d35,0x3d35bd35,0xbd35bd35,0xbd353d35,
0x80003d80,0x3d800000,0x8000bd80,0xbd800000,0x3d353d35,0x3d35bd35,0xbd35bd35,0xbd353d35,0x80003d80,0x3d800000,0x8000bd80,0xbd800000,0x3d353d35,0x3d35bd35,0xbd35bd35,0xbd353d35,
0xbd55bd0e,0xbc483d7b,0x3d7bbc48,0xbd0ebd55,0x8000bd80,0xbd6d3cc4,0x3d353d35,0x3cc4bd6d,0xbd0e3d55,0x3d7b3c48,0xbc48bd7b,0xbd553d0e,0xbd800000,0x3cc43d6d,0x3d35bd35,0xbd6dbcc4,
0x3d553d0e,0x3c48bd7b,0xbd7b3c48,0x3d0e3d55,0x80003d80,0x3d6dbcc4,0xbd35bd35,0xbcc43d6d,0x3d0ebd55,0xbd7bbc48,0x3c483d7b,0x3d55bd0e,0x3d800000,0xbcc4bd6d,0xbd353d35,0x3d6d3cc4,
0x8000bd80,0xbd353d35,0x3d800000,0xbd35bd35,0xbd6dbcc4,0x3cc43d6d,0x3cc4bd6d,0xbd6d3cc4,0x80003d80,0x3d35bd35,0xbd800000,0x3d353d35,0x3d6d3cc4,0xbcc4bd6d,0xbcc43d6d,0x3d6dbcc4,
0x8000bd80,0xbd353d35,0x3d800000,0xbd35bd35,0xbd6dbcc4,0x3cc43d6d,0x3cc4bd6d,0xbd6d3cc4,0x80003d80,0x3d35bd35,0xbd800000,0x3d353d35,0x3d6d3cc4,0xbcc4bd6d,0xbcc43d6d,0x3d6dbcc4,
0x3c48bd7b,0xbd0e3d55,0x3d55bd0e,0xbd7b3c48,0x3d800000,0xbd6dbcc4,0x3d353d35,0xbcc4bd6d,0xbd7bbc48,0x3d553d0e,0xbd0ebd55,0x3c483d7b,0x8000bd80,0xbcc43d6d,0x3d35bd35,0xbd6d3cc4,
0xbc483d7b,0x3d0ebd55,0xbd553d0e,0x3d7bbc48,0xbd800000,0x3d6d3cc4,0xbd35bd35,0x3cc43d6d,0x3d7b3c48,0xbd55bd0e,0x3d0e3d55,0xbc48bd7b,0x80003d80,0x3cc4bd6d,0xbd353d35,0x3d6dbcc4,
0x3d800000,0x3d800000,0x3d800000,0x3d800000,0x3d800000,0x3d800000,0x3d800000,0x3d800000,0x3d800000,0x3d800000,0x3d800000,0x3d800000,0x3d800000,0x3d800000,0x3d800000,0x3d800000,
0x3d800000,0x3d800000,0x3d800000,0x3d800000,0x3d800000,0x3d800000,0x3d800000,0x3d800000,0x3d800000,0x3d800000,0x3d800000,0x3d800000,0x3d800000,0x3d800000,0x3d800000,0x3d800000,
0x3d7bbc48,0x3d55bd0e,0x3d0ebd55,0x3c48bd7b,0x3d800000,0x3d6dbcc4,0x3d35bd35,0x3cc4bd6d,0xbc48bd7b,0xbd0ebd55,0xbd55bd0e,0xbd7bbc48,0xbd80,0xbcc4bd6d,0xbd35bd35,0xbd6dbcc4,
0xbd7b3c48,0xbd553d0e,0xbd0e3d55,0xbc483d7b,0xbd800000,0xbd6d3cc4,0xbd353d35,0xbcc43d6d,0x3c483d7b,0x3d0e3d55,0x3d553d0e,0x3d7b3c48,0x3d80,0x3cc43d6d,0x3d353d35,0x3d6d3cc4,
0xbd800000,0xbd353d35,0x3d80,0x3d353d35,0xbd6d3cc4,0xbcc43d6d,0x3cc43d6d,0x3d6d3cc4,0x3d800000,0x3d35bd35,0xbd80,0xbd35bd35,0x3d6dbcc4,0x3cc4bd6d,0xbcc4bd6d,0xbd6dbcc4,
0xbd800000,0xbd353d35,0x3d80,0x3d353d35,0xbd6d3cc4,0xbcc43d6d,0x3cc43d6d,0x3d6d3cc4,0x3d800000,0x3d35bd35,0xbd80,0xbd35bd35,0x3d6dbcc4,0x3cc4bd6d,0xbcc4bd6d,0xbd6dbcc4,
0x3d0e3d55,0x3d7bbc48,0x3c48bd7b,0xbd55bd0e,0x3d80,0x3d6d3cc4,0x3d35bd35,0xbcc4bd6d,0x3d55bd0e,0xbc48bd7b,0xbd7bbc48,0xbd0e3d55,0x3d800000,0x3cc4bd6d,0xbd35bd35,0xbd6d3cc4,
0xbd0ebd55,0xbd7b3c48,0xbc483d7b,0x3d553d0e,0xbd80,0xbd6dbcc4,0xbd353d35,0x3cc43d6d,0xbd553d0e,0x3c483d7b,0x3d7b3c48,0x3d0ebd55,0xbd800000,0xbcc43d6d,0x3d353d35,0x3d6dbcc4,
0x3d800000,0xbd80,0xbd800000,0x3d80,0x3d35bd35,0xbd35bd35,0xbd353d35,0x3d353d35,0x3d800000,0xbd80,0xbd800000,0x3d80,0x3d35bd35,0xbd35bd35,0xbd353d35,0x3d353d35,
0x3d800000,0xbd80,0xbd800000,0x3d80,0x3d35bd35,0xbd35bd35,0xbd353d35,0x3d353d35,0x3d800000,0xbd80,0xbd800000,0x3d80,0x3d35bd35,0xbd35bd35,0xbd353d35,0x3d353d35,
0xbd0e3d55,0x3d7b3c48,0xbc48bd7b,0xbd553d0e,0xbd800000,0x3cc43d6d,0x3d35bd35,0xbd6dbcc4,0x3d553d0e,0x3c48bd7b,0xbd7b3c48,0x3d0e3d55,0x3d80,0x3d6dbcc4,0xbd35bd35,0xbcc43d6d,
0x3d0ebd55,0xbd7bbc48,0x3c483d7b,0x3d55bd0e,0x3d800000,0xbcc4bd6d,0xbd353d35,0x3d6d3cc4,0xbd55bd0e,0xbc483d7b,0x3d7bbc48,0xbd0ebd55,0xbd80,0xbd6d3cc4,0x3d353d35,0x3cc4bd6d,
0xbd800000,0x3d353d35,0xbd80,0xbd353d35,0xbcc43d6d,0x3d6dbcc4,0xbd6dbcc4,0x3cc43d6d,0x3d800000,0xbd35bd35,0x3d80,0x3d35bd35,0x3cc4bd6d,0xbd6d3cc4,0x3d6d3cc4,0xbcc4bd6d,
0xbd800000,0x3d353d35,0xbd80,0xbd353d35,0xbcc43d6d,0x3d6dbcc4,0xbd6dbcc4,0x3cc43d6d,0x3d800000,0xbd35bd35,0x3d80,0x3d35bd35,0x3cc4bd6d,0xbd6d3cc4,0x3d6d3cc4,0xbcc4bd6d,
0xbd7bbc48,0x3d553d0e,0xbd0ebd55,0x3c483d7b,0xbd80,0xbcc43d6d,0x3d35bd35,0xbd6d3cc4,0xbc483d7b,0x3d0ebd55,0xbd553d0e,0x3d7bbc48,0xbd800000,0x3d6d3cc4,0xbd35bd35,0x3cc43d6d,
0x3d7b3c48,0xbd55bd0e,0x3d0e3d55,0xbc48bd7b,0x3d80,0x3cc4bd6d,0xbd353d35,0x3d6dbcc4,0x3c48bd7b,0xbd0e3d55,0x3d55bd0e,0xbd7b3c48,0x3d800000,0xbd6dbcc4,0x3d353d35,0xbcc4bd6d,
0x80003d80,0x8000bd80,0x80003d80,0x8000bd80,0x3d800000,0xbd800000,0x3d800000,0xbd800000,0x80003d80,0x8000bd80,0x80003d80,0x8000bd80,0x3d800000,0xbd800000,0x3d800000,0xbd800000,
0x80003d80,0x8000bd80,0x80003d80,0x8000bd80,0x3d800000,0xbd800000,0x3d800000,0xbd800000,0x80003d80,0x8000bd80,0x80003d80,0x8000bd80,0x3d800000,0xbd800000,0x3d800000,0xbd800000,
0x3d7bbc48,0xbd553d0e,0x3d0ebd55,0xbc483d7b,0x80003d80,0xbcc4bd6d,0x3d353d35,0xbd6dbcc4,0xbc48bd7b,0x3d0e3d55,0xbd55bd0e,0x3d7b3c48,0x3d800000,0xbd6d3cc4,0x3d35bd35,0xbcc43d6d,
0xbd7b3c48,0x3d55bd0e,0xbd0e3d55,0x3c48bd7b,0x8000bd80,0x3cc43d6d,0xbd35bd35,0x3d6d3cc4,0x3c483d7b,0xbd0ebd55,0x3d553d0e,0xbd7bbc48,0xbd800000,0x3d6dbcc4,0xbd353d35,0x3cc4bd6d,
0x8000bd80,0x3d353d35,0xbd800000,0x3d35bd35,0xbd6d3cc4,0x3cc4bd6d,0x3cc43d6d,0xbd6dbcc4,0x80003d80,0xbd35bd35,0x3d800000,0xbd353d35,0x3d6dbcc4,0xbcc43d6d,0xbcc4bd6d,0x3d6d3cc4,
0x8000bd80,0x3d353d35,0xbd800000,0x3d35bd35,0xbd6d3cc4,0x3cc4bd6d,0x3cc43d6d,0xbd6dbcc4,0x80003d80,0xbd35bd35,0x3d800000,0xbd353d35,0x3d6dbcc4,0xbcc43d6d,0xbcc4bd6d,0x3d6d3cc4,
0x3d0e3d55,0xbd7b3c48,0x3c48bd7b,0x3d553d0e,0xbd800000,0x3cc4bd6d,0x3d353d35,0xbd6d3cc4,0x3d55bd0e,0x3c483d7b,0xbd7bbc48,0x3d0ebd55,0x80003d80,0xbd6dbcc4,0x3d35bd35,0x3cc43d6d,
0xbd0ebd55,0x3d7bbc48,0xbc483d7b,0xbd55bd0e,0x3d800000,0xbcc43d6d,0xbd35bd35,0x3d6dbcc4,0xbd553d0e,0xbc48bd7b,0x3d7b3c48,0xbd0e3d55,0x8000bd80,0x3d6d3cc4,0xbd353d35,0xbcc4bd6d,
0x80003d80,0xbd800000,0x8000bd80,0x3d800000,0x3d35bd35,0x3d353d35,0xbd353d35,0xbd35bd35,0x80003d80,0xbd800000,0x8000bd80,0x3d800000,0x3d35bd35,0x3d353d35,0xbd353d35,0xbd35bd35,
0x80003d80,0xbd800000,0x8000bd80,0x3d800000,0x3d35bd35,0x3d353d35,0xbd353d35,0xbd35bd35,0x80003d80,0xbd800000,0x8000bd80,0x3d800000,0x3d35bd35,0x3d353d35,0xbd353d35,0xbd35bd35,
0xbd0e3d55,0xbd7bbc48,0xbc48bd7b,0x3d55bd0e,0x8000bd80,0x3d6dbcc4,0x3d353d35,0xbcc43d6d,0x3d553d0e,0xbc483d7b,0xbd7b3c48,0xbd0ebd55,0xbd800000,0xbcc4bd6d,0x3d35bd35,0x3d6d3cc4,
0x3d0ebd55,0x3d7b3c48,0x3c483d7b,0xbd553d0e,0x80003d80,0xbd6d3cc4,0xbd35bd35,0x3cc4bd6d,0xbd55bd0e,0x3c48bd7b,0x3d7bbc48,0x3d0e3d55,0x3d800000,0x3cc43d6d,0xbd353d35,0xbd6dbcc4,
0x8000bd80,0x3d35bd35,0x3d800000,0x3d353d35,0xbcc43d6d,0xbd6d3cc4,0xbd6dbcc4,0xbcc4bd6d,0x80003d80,0xbd353d35,0xbd800000,0xbd35bd35,0x3cc4bd6d,0x3d6dbcc4,0x3d6d3cc4,0x3cc43d6d,
0x8000bd80,0x3d35bd35,0x3d800000,0x3d353d35,0xbcc43d6d,0xbd6d3cc4,0xbd6dbcc4,0xbcc4bd6d,0x80003d80,0xbd353d35,0xbd800000,0xbd35bd35,0x3cc4bd6d,0x3d6dbcc4,0x3d6d3cc4,0x3cc43d6d,
0xbd7bbc48,0xbd55bd0e,0xbd0ebd55,0xbc48bd7b,0x3d800000,0x3d6d3cc4,0x3d353d35,0x3cc43d6d,0xbc483d7b,0xbd0e3d55,0xbd553d0e,0xbd7b3c48,0x8000bd80,0x3cc4bd6d,0x3d35bd35,0x3d6dbcc4,
0x3d7b3c48,0x3d553d0e,0x3d0e3d55,0x3c483d7b,0xbd800000,0xbd6dbcc4,0xbd35bd35,0xbcc4bd6d,0x3c48bd7b,0x3d0ebd55,0x3d55bd0e,0x3d7bbc48,0x80003d80,0xbcc43d6d,0xbd353d35,0xbd6d3cc4,
0x3d800000,0xbd800000,0x3d800000,0xbd800000,0xbd80,0x3d80,0xbd80,0x3d80,0x3d800000,0xbd800000,0x3d800000,0xbd800000,0xbd80,0x3d80,0xbd80,0x3d80,
0x3d800000,0xbd800000,0x3d800000,0xbd800000,0xbd80,0x3d80,0xbd80,0x3d80,0x3d800000,0xbd800000,0x3d800000,0xbd800000,0xbd80,0x3d80,0xbd80,0x3d80,
0xbc48bd7b,0x3d0e3d55,0xbd55bd0e,0x3d7b3c48,0x3d800000,0xbd6d3cc4,0x3d35bd35,0xbcc43d6d,0xbd7b3c48,0x3d55bd0e,0xbd0e3d55,0x3c48bd7b,0xbd80,0x3cc43d6d,0xbd35bd35,0x3d6d3cc4,
0x3c483d7b,0xbd0ebd55,0x3d553d0e,0xbd7bbc48,0xbd800000,0x3d6dbcc4,0xbd353d35,0x3cc4bd6d,0x3d7bbc48,0xbd553d0e,0x3d0ebd55,0xbc483d7b,0x3d80,0xbcc4bd6d,0x3d353d35,0xbd6dbcc4,
0xbd800000,0x3d35bd35,0x3d80,0xbd35bd35,0x3cc43d6d,0xbd6dbcc4,0x3d6dbcc4,0xbcc43d6d,0x3d800000,0xbd353d35,0xbd80,0x3d353d35,0xbcc4bd6d,0x3d6d3cc4,0xbd6d3cc4,0x3cc4bd6d,
0xbd800000,0x3d35bd35,0x3d80,0xbd35bd35,0x3cc43d6d,0xbd6dbcc4,0x3d6dbcc4,0xbcc43d6d,0x3d800000,0xbd353d35,0xbd80,0x3d353d35,0xbcc4bd6d,0x3d6d3cc4,0xbd6d3cc4,0x3cc4bd6d,
0x3d55bd0e,0x3c483d7b,0xbd7bbc48,0x3d0ebd55,0x3d80,0xbd6dbcc4,0x3d35bd35,0x3cc43d6d,0xbd0ebd55,0x3d7bbc48,0xbc483d7b,0xbd55bd0e,0x3d800000,0xbcc43d6d,0xbd35bd35,0x3d6dbcc4,
0xbd553d0e,0xbc48bd7b,0x3d7b3c48,0xbd0e3d55,0xbd80,0x3d6d3cc4,0xbd353d35,0xbcc4bd6d,0x3d0e3d55,0xbd7b3c48,0x3c48bd7b,0x3d553d0e,0xbd800000,0x3cc4bd6d,0x3d353d35,0xbd6d3cc4,
0x3d800000,0x3d80,0xbd800000,0xbd80,0xbd35bd35,0x3d35bd35,0x3d353d35,0xbd353d35,0x3d800000,0x3d80,0xbd800000,0xbd80,0xbd35bd35,0x3d35bd35,0x3d353d35,0xbd353d35,
0x3d800000,0x3d80,0xbd800000,0xbd80,0xbd35bd35,0x3d35bd35,0x3d353d35,0xbd353d35,0x3d800000,0x3d80,0xbd800000,0xbd80,0xbd35bd35,0x3d35bd35,0x3d353d35,0xbd353d35,
0x3d553d0e,0xbc483d7b,0xbd7b3c48,0xbd0ebd55,0xbd800000,0xbcc4bd6d,0x3d35bd35,0x3d6d3cc4,0x3d0ebd55,0x3d7b3c48,0x3c483d7b,0xbd553d0e,0x3d80,0xbd6d3cc4,0xbd35bd35,0x3cc4bd6d,
0xbd55bd0e,0x3c48bd7b,0x3d7bbc48,0x3d0e3d55,0x3d800000,0x3cc43d6d,0xbd353d35,0xbd6dbcc4,0xbd0e3d55,0xbd7bbc48,0xbc48bd7b,0x3d55bd0e,0xbd80,0x3d6dbcc4,0x3d353d35,0xbcc43d6d,
0xbd800000,0xbd35bd35,0xbd80,0x3d35bd35,0x3d6d3cc4,0x3cc43d6d,0xbcc43d6d,0xbd6d3cc4,0x3d800000,0x3d353d35,0x3d80,0xbd353d35,0xbd6dbcc4,0xbcc4bd6d,0x3cc4bd6d,0x3d6dbcc4,
0xbd800000,0xbd35bd35,0xbd80,0x3d35bd35,0x3d6d3cc4,0x3cc43d6d,0xbcc43d6d,0xbd6d3cc4,0x3d800000,0x3d353d35,0x3d80,0xbd353d35,0xbd6dbcc4,0xbcc4bd6d,0x3cc4bd6d,0x3d6dbcc4,
0xbc483d7b,0xbd0e3d55,0xbd553d0e,0xbd7b3c48,0xbd80,0x3cc4bd6d,0x3d35bd35,0x3d6dbcc4,0x3d7b3c48,0x3d553d0e,0x3d0e3d55,0x3c483d7b,0xbd800000,0xbd6dbcc4,0xbd35bd35,0xbcc4bd6d,
0x3c48bd7b,0x3d0ebd55,0x3d55bd0e,0x3d7bbc48,0x3d80,0xbcc43d6d,0xbd353d35,0xbd6d3cc4,0xbd7bbc48,0xbd55bd0e,0xbd0ebd55,0xbc48bd7b,0x3d800000,0x3d6d3cc4,0x3d353d35,0x3cc43d6d,
0x80003d80,0x80003d80,0x80003d80,0x80003d80,0x8000bd80,0x8000bd80,0x8000bd80,0x8000bd80,0x80003d80,0x80003d80,0x80003d80,0x80003d80,0x8000bd80,0x8000bd80,0x8000bd80,0x8000bd80,
0x80003d80,0x80003d80,0x80003d80,0x80003d80,0x8000bd80,0x8000bd80,0x8000bd80,0x8000bd80,0x80003d80,0x80003d80,0x80003d80,0x80003d80,0x8000bd80,0x8000bd80,0x8000bd80,0x8000bd80,
0xbc48bd7b,0xbd0ebd55,0xbd55bd0e,0xbd7bbc48,0x80003d80,0x3cc43d6d,0x3d353d35,0x3d6d3cc4,0xbd7b3c48,0xbd553d0e,0xbd0e3d55,0xbc483d7b,0x3d800000,0x3d6dbcc4,0x3d35bd35,0x3cc4bd6d,
0x3c483d7b,0x3d0e3d55,0x3d553d0e,0x3d7b3c48,0x8000bd80,0xbcc4bd6d,0xbd35bd35,0xbd6dbcc4,0x3d7bbc48,0x3d55bd0e,0x3d0ebd55,0x3c48bd7b,0xbd800000,0xbd6d3cc4,0xbd353d35,0xbcc43d6d,
0x8000bd80,0xbd35bd35,0xbd800000,0xbd353d35,0x3cc43d6d,0x3d6d3cc4,0x3d6dbcc4,0x3cc4bd6d,0x80003d80,0x3d353d35,0x3d800000,0x3d35bd35,0xbcc4bd6d,0xbd6dbcc4,0xbd6d3cc4,0xbcc43d6d,
0x8000bd80,0xbd35bd35,0xbd800000,0xbd353d35,0x3cc43d6d,0x3d6d3cc4,0x3d6dbcc4,0x3cc4bd6d,0x80003d80,0x3d353d35,0x3d800000,0x3d35bd35,0xbcc4bd6d,0xbd6dbcc4,0xbd6d3cc4,0xbcc43d6d,
0x3d55bd0e,0xbc48bd7b,0xbd7bbc48,0xbd0e3d55,0xbd800000,0xbcc43d6d,0x3d353d35,0x3d6dbcc4,0xbd0ebd55,0xbd7b3c48,0xbc483d7b,0x3d553d0e,0x80003d80,0x3d6d3cc4,0x3d35bd35,0xbcc4bd6d,
0xbd553d0e,0x3c483d7b,0x3d7b3c48,0x3d0ebd55,0x3d800000,0x3cc4bd6d,0xbd35bd35,0xbd6d3cc4,0x3d0e3d55,0x3d7bbc48,0x3c48bd7b,0xbd55bd0e,0x8000bd80,0xbd6dbcc4,0xbd353d35,0x3cc43d6d,
0x80003d80,0x3d800000,0x8000bd80,0xbd800000,0xbd35bd35,0xbd353d35,0x3d353d35,0x3d35bd35,0x80003d80,0x3d800000,0x8000bd80,0xbd800000,0xbd35bd35,0xbd353d35,0x3d353d35,0x3d35bd35,
0x80003d80,0x3d800000,0x8000bd80,0xbd800000,0xbd35bd35,0xbd353d35,0x3d353d35,0x3d35bd35,0x80003d80,0x3d800000,0x8000bd80,0xbd800000,0xbd35bd35,0xbd353d35,0x3d353d35,0x3d35bd35,
0x3d553d0e,0x3c48bd7b,0xbd7b3c48,0x3d0e3d55,0x8000bd80,0xbd6d3cc4,0x3d353d35,0x3cc4bd6d,0x3d0ebd55,0xbd7bbc48,0x3c483d7b,0x3d55bd0e,0xbd800000,0x3cc43d6d,0x3d35bd35,0xbd6dbcc4,
0xbd55bd0e,0xbc483d7b,0x3d7bbc48,0xbd0ebd55,0x80003d80,0x3d6dbcc4,0xbd35bd35,0xbcc43d6d,0xbd0e3d55,0x3d7b3c48,0xbc48bd7b,0xbd553d0e,0x3d800000,0xbcc4bd6d,0xbd353d35,0x3d6d3cc4,
0x8000bd80,0xbd353d35,0x3d800000,0xbd35bd35,0x3d6d3cc4,0xbcc4bd6d,0xbcc43d6d,0x3d6dbcc4,0x80003d80,0x3d35bd35,0xbd800000,0x3d353d35,0xbd6dbcc4,0x3cc43d6d,0x3cc4bd6d,0xbd6d3cc4,
0x8000bd80,0xbd353d35,0x3d800000,0xbd35bd35,0x3d6d3cc4,0xbcc4bd6d,0xbcc43d6d,0x3d6dbcc4,0x80003d80,0x3d35bd35,0xbd800000,0x3d353d35,0xbd6dbcc4,0x3cc43d6d,0x3cc4bd6d,0xbd6d3cc4,
0xbc483d7b,0x3d0ebd55,0xbd553d0e,0x3d7bbc48,0x3d800000,0xbd6dbcc4,0x3d353d35,0xbcc4bd6d,0x3d7b3c48,0xbd55bd0e,0x3d0e3d55,0xbc48bd7b,0x8000bd80,0xbcc43d6d,0x3d35bd35,0xbd6d3cc4,
0x3c48bd7b,0xbd0e3d55,0x3d55bd0e,0xbd7b3c48,0xbd800000,0x3d6d3cc4,0xbd35bd35,0x3cc43d6d,0xbd7bbc48,0x3d553d0e,0xbd0ebd55,0x3c483d7b,0x80003d80,0x3cc4bd6d,0xbd353d35,0x3d6dbcc4,
0x3d800000,0x3d800000,0x3d800000,0x3d800000,0xbd800000,0xbd800000,0xbd800000,0xbd800000,0x3d800000,0x3d800000,0x3d800000,0x3d800000,0xbd800000,0xbd800000,0xbd800000,0xbd800000,
0x3d800000,0x3d800000,0x3d800000,0x3d800000,0xbd800000,0xbd800000,0xbd800000,0xbd800000,0x3d800000,0x3d800000,0x3d800000,0x3d800000,0xbd800000,0xbd800000,0xbd800000,0xbd800000,
0xbd7b3c48,0xbd553d0e,0xbd0e3d55,0xbc483d7b,0x3d800000,0x3d6dbcc4,0x3d35bd35,0x3cc4bd6d,0x3c483d7b,0x3d0e3d55,0x3d553d0e,0x3d7b3c48,0xbd80,0xbcc4bd6d,0xbd35bd35,0xbd6dbcc4,
0x3d7bbc48,0x3d55bd0e,0x3d0ebd55,0x3c48bd7b,0xbd800000,0xbd6d3cc4,0xbd353d35,0xbcc43d6d,0xbc48bd7b,0xbd0ebd55,0xbd55bd0e,0xbd7bbc48,0x3d80,0x3cc43d6d,0x3d353d35,0x3d6d3cc4,
0xbd800000,0xbd353d35,0x3d80,0x3d353d35,0x3d6dbcc4,0x3cc4bd6d,0xbcc4bd6d,0xbd6dbcc4,0x3d800000,0x3d35bd35,0xbd80,0xbd35bd35,0xbd6d3cc4,0xbcc43d6d,0x3cc43d6d,0x3d6d3cc4,
0xbd800000,0xbd353d35,0x3d80,0x3d353d35,0x3d6dbcc4,0x3cc4bd6d,0xbcc4bd6d,0xbd6dbcc4,0x3d800000,0x3d35bd35,0xbd80,0xbd35bd35,0xbd6d3cc4,0xbcc43d6d,0x3cc43d6d,0x3d6d3cc4,
0xbd0ebd55,0xbd7b3c48,0xbc483d7b,0x3d553d0e,0x3d80,0x3d6d3cc4,0x3d35bd35,0xbcc4bd6d,0xbd553d0e,0x3c483d7b,0x3d7b3c48,0x3d0ebd55,0x3d800000,0x3cc4bd6d,0xbd35bd35,0xbd6d3cc4,
0x3d0e3d55,0x3d7bbc48,0x3c48bd7b,0xbd55bd0e,0xbd80,0xbd6dbcc4,0xbd353d35,0x3cc43d6d,0x3d55bd0e,0xbc48bd7b,0xbd7bbc48,0xbd0e3d55,0xbd800000,0xbcc43d6d,0x3d353d35,0x3d6dbcc4,
0x3d800000,0xbd80,0xbd800000,0x3d80,0xbd353d35,0x3d353d35,0x3d35bd35,0xbd35bd35,0x3d800000,0xbd80,0xbd800000,0x3d80,0xbd353d35,0x3d353d35,0x3d35bd35,0xbd35bd35,
0x3d800000,0xbd80,0xbd800000,0x3d80,0xbd353d35,0x3d353d35,0x3d35bd35,0xbd35bd35,0x3d800000,0xbd80,0xbd800000,0x3d80,0xbd353d35,0x3d353d35,0x3d35bd35,0xbd35bd35,
0x3d0ebd55,0xbd7bbc48,0x3c483d7b,0x3d55bd0e,0xbd800000,0x3cc43d6d,0x3d35bd35,0xbd6dbcc4,0xbd55bd0e,0xbc483d7b,0x3d7bbc48,0xbd0ebd55,0x3d80,0x3d6dbcc4,0xbd35bd35,0xbcc43d6d,
0xbd0e3d55,0x3d7b3c48,0xbc48bd7b,0xbd553d0e,0x3d800000,0xbcc4bd6d,0xbd353d35,0x3d6d3cc4,0x3d553d0e,0x3c48bd7b,0xbd7b3c48,0x3d0e3d55,0xbd80,0xbd6d3cc4,0x3d353d35,0x3cc4bd6d,
0xbd800000,0x3d353d35,0xbd80,0xbd353d35,0x3cc4bd6d,0xbd6d3cc4,0x3d6d3cc4,0xbcc4bd6d,0x3d800000,0xbd35bd35,0x3d80,0x3d35bd35,0xbcc43d6d,0x3d6dbcc4,0xbd6dbcc4,0x3cc43d6d,
0xbd800000,0x3d353d35,0xbd80,0xbd353d35,0x3cc4bd6d,0xbd6d3cc4,0x3d6d3cc4,0xbcc4bd6d,0x3d800000,0xbd35bd35,0x3d80,0x3d35bd35,0xbcc43d6d,0x3d6dbcc4,0xbd6dbcc4,0x3cc43d6d,
0x3d7b3c48,0xbd55bd0e,0x3d0e3d55,0xbc48bd7b,0xbd80,0xbcc43d6d,0x3d35bd35,0xbd6d3cc4,0x3c48bd7b,0xbd0e3d55,0x3d55bd0e,0xbd7b3c48,0xbd800000,0x3d6d3cc4,0xbd35bd35,0x3cc43d6d,
0xbd7bbc48,0x3d553d0e,0xbd0ebd55,0x3c483d7b,0x3d80,0x3cc4bd6d,0xbd353d35,0x3d6dbcc4,0xbc483d7b,0x3d0ebd55,0xbd553d0e,0x3d7bbc48,0x3d800000,0xbd6dbcc4,0x3d353d35,0xbcc4bd6d,
0x80003d80,0x8000bd80,0x80003d80,0x8000bd80,0xbd800000,0x3d800000,0xbd800000,0x3d800000,0x80003d80,0x8000bd80,0x80003d80,0x8000bd80,0xbd800000,0x3d800000,0xbd800000,0x3d800000,
0x80003d80,0x8000bd80,0x80003d80,0x8000bd80,0xbd800000,0x3d800000,0xbd800000,0x3d800000,0x80003d80,0x8000bd80,0x80003d80,0x8000bd80,0xbd800000,0x3d800000,0xbd800000,0x3d800000,
0xbd7b3c48,0x3d55bd0e,0xbd0e3d55,0x3c48bd7b,0x80003d80,0xbcc4bd6d,0x3d353d35,0xbd6dbcc4,0x3c483d7b,0xbd0ebd55,0x3d553d0e,0xbd7bbc48,0x3d800000,0xbd6d3cc4,0x3d35bd35,0xbcc43d6d,
0x3d7bbc48,0xbd553d0e,0x3d0ebd55,0xbc483d7b,0x8000bd80,0x3cc43d6d,0xbd35bd35,0x3d6d3cc4,0xbc48bd7b,0x3d0e3d55,0xbd55bd0e,0x3d7b3c48,0xbd800000,0x3d6dbcc4,0xbd353d35,0x3cc4bd6d,
0x8000bd80,0x3d353d35,0xbd800000,0x3d35bd35,0x3d6dbcc4,0xbcc43d6d,0xbcc4bd6d,0x3d6d3cc4,0x80003d80,0xbd35bd35,0x3d800000,0xbd353d35,0xbd6d3cc4,0x3cc4bd6d,0x3cc43d6d,0xbd6dbcc4,
0x8000bd80,0x3d353d35,0xbd800000,0x3d35bd35,0x3d6dbcc4,0xbcc43d6d,0xbcc4bd6d,0x3d6d3cc4,0x80003d80,0xbd35bd35,0x3d800000,0xbd353d35,0xbd6d3cc4,0x3cc4bd6d,0x3cc43d6d,0xbd6dbcc4,
0xbd0ebd55,0x3d7bbc48,0xbc483d7b,0xbd55bd0e,0xbd800000,0x3cc4bd6d,0x3d353d35,0xbd6d3cc4,0xbd553d0e,0xbc48bd7b,0x3d7b3c48,0xbd0e3d55,0x80003d80,0xbd6dbcc4,0x3d35bd35,0x3cc43d6d,
0x3d0e3d55,0xbd7b3c48,0x3c48bd7b,0x3d553d0e,0x3d800000,0xbcc43d6d,0xbd35bd35,0x3d6dbcc4,0x3d55bd0e,0x3c483d7b,0xbd7bbc48,0x3d0ebd55,0x8000bd80,0x3d6d3cc4,0xbd353d35,0xbcc4bd6d,
0x80003d80,0xbd800000,0x8000bd80,0x3d800000,0xbd353d35,0xbd35bd35,0x3d35bd35,0x3d353d35,0x80003d80,0xbd800000,0x8000bd80,0x3d800000,0xbd353d35,0xbd35bd35,0x3d35bd35,0x3d353d35,
0x80003d80,0xbd800000,0x8000bd80,0x3d800000,0xbd353d35,0xbd35bd35,0x3d35bd35,0x3d353d35,0x80003d80,0xbd800000,0x8000bd80,0x3d800000,0xbd353d35,0xbd35bd35,0x3d35bd35,0x3d353d35,
0x3d0ebd55,0x3d7b3c48,0x3c483d7b,0xbd553d0e,0x8000bd80,0x3d6dbcc4,0x3d353d35,0xbcc43d6d,0xbd55bd0e,0x3c48bd7b,0x3d7bbc48,0x3d0e3d55,0xbd800000,0xbcc4bd6d,0x3d35bd35,0x3d6d3cc4,
0xbd0e3d55,0xbd7bbc48,0xbc48bd7b,0x3d55bd0e,0x80003d80,0xbd6d3cc4,0xbd35bd35,0x3cc4bd6d,0x3d553d0e,0xbc483d7b,0xbd7b3c48,0xbd0ebd55,0x3d800000,0x3cc43d6d,0xbd353d35,0xbd6dbcc4,
0x8000bd80,0x3d35bd35,0x3d800000,0x3d353d35,0x3cc4bd6d,0x3d6dbcc4,0x3d6d3cc4,0x3cc43d6d,0x80003d80,0xbd353d35,0xbd800000,0xbd35bd35,0xbcc43d6d,0xbd6d3cc4,0xbd6dbcc4,0xbcc4bd6d,
0x8000bd80,0x3d35bd35,0x3d800000,0x3d353d35,0x3cc4bd6d,0x3d6dbcc4,0x3d6d3cc4,0x3cc43d6d,0x80003d80,0xbd353d35,0xbd800000,0xbd35bd35,0xbcc43d6d,0xbd6d3cc4,0xbd6dbcc4,0xbcc4bd6d,
0x3d7b3c48,0x3d553d0e,0x3d0e3d55,0x3c483d7b,0x3d800000,0x3d6d3cc4,0x3d353d35,0x3cc43d6d,0x3c48bd7b,0x3d0ebd55,0x3d55bd0e,0x3d7bbc48,0x8000bd80,0x3cc4bd6d,0x3d35bd35,0x3d6dbcc4,
0xbd7bbc48,0xbd55bd0e,0xbd0ebd55,0xbc48bd7b,0xbd800000,0xbd6dbcc4,0xbd35bd35,0xbcc4bd6d,0xbc483d7b,0xbd0e3d55,0xbd553d0e,0xbd7b3c48,0x80003d80,0xbcc43d6d,0xbd353d35,0xbd6d3cc4,
0x3d800000,0xbd800000,0x3d800000,0xbd800000,0x3d80,0xbd80,0x3d80,0xbd80,0x3d800000,0xbd800000,0x3d800000,0xbd800000,0x3d80,0xbd80,0x3d80,0xbd80,
0x3d800000,0xbd800000,0x3d800000,0xbd800000,0x3d80,0xbd80,0x3d80,0xbd80,0x3d800000,0xbd800000,0x3d800000,0xbd800000,0x3d80,0xbd80,0x3d80,0xbd80,
0x3c483d7b,0xbd0ebd55,0x3d553d0e,0xbd7bbc48,0x3d800000,0xbd6d3cc4,0x3d35bd35,0xbcc43d6d,0x3d7bbc48,0xbd553d0e,0x3d0ebd55,0xbc483d7b,0xbd80,0x3cc43d6d,0xbd35bd35,0x3d6d3cc4,
0xbc48bd7b,0x3d0e3d55,0xbd55bd0e,0x3d7b3c48,0xbd800000,0x3d6dbcc4,0xbd353d35,0x3cc4bd6d,0xbd7b3c48,0x3d55bd0e,0xbd0e3d55,0x3c48bd7b,0x3d80,0xbcc4bd6d,0x3d353d35,0xbd6dbcc4,
0xbd800000,0x3d35bd35,0x3d80,0xbd35bd35,0xbcc4bd6d,0x3d6d3cc4,0xbd6d3cc4,0x3cc4bd6d,0x3d800000,0xbd353d35,0xbd80,0x3d353d35,0x3cc43d6d,0xbd6dbcc4,0x3d6dbcc4,0xbcc43d6d,
0xbd800000,0x3d35bd35,0x3d80,0xbd35bd35,0xbcc4bd6d,0x3d6d3cc4,0xbd6d3cc4,0x3cc4bd6d,0x3d800000,0xbd353d35,0xbd80,0x3d353d35,0x3cc43d6d,0xbd6dbcc4,0x3d6dbcc4,0xbcc43d6d,
0xbd553d0e,0xbc48bd7b,0x3d7b3c48,0xbd0e3d55,0x3d80,0xbd6dbcc4,0x3d35bd35,0x3cc43d6d,0x3d0e3d55,0xbd7b3c48,0x3c48bd7b,0x3d553d0e,0x3d800000,0xbcc43d6d,0xbd35bd35,0x3d6dbcc4,
0x3d55bd0e,0x3c483d7b,0xbd7bbc48,0x3d0ebd55,0xbd80,0x3d6d3cc4,0xbd353d35,0xbcc4bd6d,0xbd0ebd55,0x3d7bbc48,0xbc483d7b,0xbd55bd0e,0xbd800000,0x3cc4bd6d,0x3d353d35,0xbd6d3cc4,
0x3d800000,0x3d80,0xbd800000,0xbd80,0x3d353d35,0xbd353d35,0xbd35bd35,0x3d35bd35,0x3d800000,0x3d80,0xbd800000,0xbd80,0x3d353d35,0xbd353d35,0xbd35bd35,0x3d35bd35,
0x3d800000,0x3d80,0xbd800000,0xbd80,0x3d353d35,0xbd353d35,0xbd35bd35,0x3d35bd35,0x3d800000,0x3d80,0xbd800000,0xbd80,0x3d353d35,0xbd353d35,0xbd35bd35,0x3d35bd35,
0xbd55bd0e,0x3c48bd7b,0x3d7bbc48,0x3d0e3d55,0xbd800000,0xbcc4bd6d,0x3d35bd35,0x3d6d3cc4,0xbd0e3d55,0xbd7bbc48,0xbc48bd7b,0x3d55bd0e,0x3d80,0xbd6d3cc4,0xbd35bd35,0x3cc4bd6d,
0x3d553d0e,0xbc483d7b,0xbd7b3c48,0xbd0ebd55,0x3d800000,0x3cc43d6d,0xbd353d35,0xbd6dbcc4,0x3d0ebd55,0x3d7b3c48,0x3c483d7b,0xbd553d0e,0xbd80,0x3d6dbcc4,0x3d353d35,0xbcc43d6d,
0xbd800000,0xbd35bd35,0xbd80,0x3d35bd35,0xbd6dbcc4,0xbcc4bd6d,0x3cc4bd6d,0x3d6dbcc4,0x3d800000,0x3d353d35,0x3d80,0xbd353d35,0x3d6d3cc4,0x3cc43d6d,0xbcc43d6d,0xbd6d3cc4,
0xbd800000,0xbd35bd35,0xbd80,0x3d35bd35,0xbd6dbcc4,0xbcc4bd6d,0x3cc4bd6d,0x3d6dbcc4,0x3d800000,0x3d353d35,0x3d80,0xbd353d35,0x3d6d3cc4,0x3cc43d6d,0xbcc43d6d,0xbd6d3cc4,
0x3c48bd7b,0x3d0ebd55,0x3d55bd0e,0x3d7bbc48,0xbd80,0x3cc4bd6d,0x3d35bd35,0x3d6dbcc4,0xbd7bbc48,0xbd55bd0e,0xbd0ebd55,0xbc48bd7b,0xbd800000,0xbd6dbcc4,0xbd35bd35,0xbcc4bd6d,
0xbc483d7b,0xbd0e3d55,0xbd553d0e,0xbd7b3c48,0x3d80,0xbcc43d6d,0xbd353d35,0xbd6d3cc4,0x3d7b3c48,0x3d553d0e,0x3d0e3d55,0x3c483d7b,0x3d800000,0x3d6d3cc4,0x3d353d35,0x3cc43d6d,
0x3f003f00,0xbf003f00,0x3f003f00,0xbf003f00,0x3f003f00,0xbf003f00,0x3f003f00,0xbf003f00,0x3f003f00,0xbf003f00,0x3f003f00,0xbf003f00,0x3f003f00,0xbf003f00,0x3f003f00,0xbf003f00,
0x3eff3f00,0xbd490000,0x3ea23eb5,0xbec6beb5,0x3ef53efb,0xbe15bdc8,0x3e713e8e,0xbee2bed5,0x3ee23eed,0xbe71be44,0x3e153e44,0xbef5beed,0x3ec63ed5,0xbea2be8e,0x3d493dc8,0xbeffbefb,
0x3efb3f00,0xbdc80000,0xbdc80000,0xbefbbf00,0x3ed53eed,0xbe8ebe44,0xbe8ebe44,0xbed5beed,0x3e8e3eb5,0xbed5beb5,0xbed5beb5,0xbe8ebeb5,0x3dc83e44,0xbefbbeed,0xbefbbeed,0xbdc8be44,
0x3ef53f00,0xbe150000,0xbee2beb5,0xbe71beb5,0x3ea23ed5,0xbec6be8e,0xbeffbefb,0x3d49bdc8,0x3d493e44,0xbeffbeed,0xbec6beed,0x3ea23e44,0xbe71bdc8,0xbee2befb,0xbe15be8e,0x3ef53ed5,
0x3eed3f00,0xbe440000,0xbeedbf00,0x3e440000,0x3e443eb5,0xbeedbeb5,0xbe44beb5,0x3eed3eb5,0xbe440000,0xbeedbf00,0x3e440000,0x3eed3f00,0xbeedbeb5,0xbe44beb5,0x3eed3eb5,0x3e443eb5,
0x3ee23f00,0xbe710000,0xbe15beb5,0x3ef53eb5,0x3d493e8e,0xbeffbed5,0x3ea23dc8,0x3ec63efb,0xbec6be44,0xbea2beed,0x3eff3eed,0xbd493e44,0xbef5befb,0x3e15bdc8,0x3e713ed5,0xbee2be8e,
0x3ed53f00,0xbe8e0000,0x3e8e0000,0x3ed53f00,0xbdc83e44,0xbefbbeed,0x3efb3eed,0xbdc83e44,0xbefbbeb5,0xbdc8beb5,0x3dc83eb5,0xbefbbeb5,0xbe8ebeed,0x3ed53e44,0xbed5be44,0xbe8ebeed,
0x3ec63f00,0xbea20000,0x3eff3eb5,0x3d493eb5,0xbe713dc8,0xbee2befb,0x3e153ed5,0xbef5be8e,0xbef5beed,0x3e15be44,0xbee2be44,0xbe71beed,0x3d49be8e,0x3eff3ed5,0xbea2befb,0x3ec63dc8,
0x3eb53f00,0xbeb50000,0x3eb53f00,0xbeb50000,0xbeb50000,0xbeb5bf00,0xbeb50000,0xbeb5bf00,0xbeb5bf00,0x3eb50000,0xbeb5bf00,0x3eb50000,0x3eb50000,0x3eb53f00,0x3eb50000,0x3eb53f00,
0x3ea23f00,0xbec60000,0xbd493eb5,0xbeffbeb5,0xbee2bdc8,0xbe71befb,0xbef5bed5,0x3e15be8e,0xbe15beed,0x3ef53e44,0x3e71be44,0x3ee23eed,0x3eff3e8e,0x3d493ed5,0x3ec63efb,0xbea23dc8,
0x3e8e3f00,0xbed50000,0xbed50000,0xbe8ebf00,0xbefbbe44,0xbdc8beed,0xbdc8beed,0x3efb3e44,0x3dc8beb5,0x3efb3eb5,0x3efb3eb5,0xbdc83eb5,0x3ed53eed,0xbe8e3e44,0xbe8e3e44,0xbed5beed,
0x3e713f00,0xbee20000,0xbef5beb5,0x3e15beb5,0xbeffbe8e,0x3d49bed5,0x3ec6bdc8,0x3ea23efb,0x3ea2be44,0x3ec63eed,0x3d493eed,0xbeffbe44,0x3e153efb,0xbef5bdc8,0xbee2bed5,0x3e71be8e,
0x3e443f00,0xbeed0000,0xbe44bf00,0x3eed0000,0xbeedbeb5,0x3e44beb5,0x3eed3eb5,0xbe443eb5,0x3eed0000,0x3e443f00,0xbeed0000,0xbe44bf00,0xbe443eb5,0xbeedbeb5,0x3e44beb5,0x3eed3eb5,
0x3e153f00,0xbef50000,0x3e71beb5,0x3ee23eb5,0xbec6bed5,0x3ea2be8e,0x3d493efb,0xbeffbdc8,0x3eff3e44,0xbd493eed,0xbea2beed,0x3ec6be44,0xbee23dc8,0xbe71befb,0x3ef53e8e,0xbe153ed5,
0x3dc83f00,0xbefb0000,0x3efb0000,0x3dc83f00,0xbe8ebeed,0x3ed5be44,0xbed53e44,0xbe8ebeed,0x3ed53eb5,0xbe8e3eb5,0x3e8ebeb5,0x3ed53eb5,0xbefbbe44,0x3dc8beed,0xbdc83eed,0xbefbbe44,
0x3d493f00,0xbeff0000,0x3ec63eb5,0xbea23eb5,0xbe15befb,0x3ef5bdc8,0xbee2be8e,0x3e71bed5,0x3e713eed,0xbee23e44,0x3ef53e44,0xbe153eed,0xbea2bed5,0x3ec6be8e,0xbeffbdc8,0x3d49befb,
0x3f00,0xbf000000,0x3f00,0xbf000000,0xbf00,0x3f000000,0xbf00,0x3f000000,0x3f00,0xbf000000,0x3f00,0xbf000000,0xbf00,0x3f000000,0xbf00,0x3f000000,
0xbd493f00,0xbeff0000,0xbec63eb5,0xbea2beb5,0x3e15befb,0x3ef53dc8,0x3ee2be8e,0x3e713ed5,0xbe713eed,0xbee2be44,0xbef53e44,0xbe15beed,0x3ea2bed5,0x3ec63e8e,0x3effbdc8,0x3d493efb,
0xbdc83f00,0xbefb0000,0xbefb0000,0x3dc8bf00,0x3e8ebeed,0x3ed53e44,0x3ed53e44,0xbe8e3eed,0xbed53eb5,0xbe8ebeb5,0xbe8ebeb5,0x3ed5beb5,0x3efbbe44,0x3dc83eed,0x3dc83eed,0xbefb3e44,
0xbe153f00,0xbef50000,0xbe71beb5,0x3ee2beb5,0x3ec6bed5,0x3ea23e8e,0xbd493efb,0xbeff3dc8,0xbeff3e44,0xbd49beed,0x3ea2beed,0x3ec63e44,0x3ee23dc8,0xbe713efb,0xbef53e8e,0xbe15bed5,
0xbe443f00,0xbeed0000,0x3e44bf00,0x3eed0000,0x3eedbeb5,0x3e443eb5,0xbeed3eb5,0xbe44beb5,0xbeed0000,0x3e44bf00,0x3eed0000,0xbe443f00,0x3e443eb5,0xbeed3eb5,0xbe44beb5,0x3eedbeb5,
0xbe713f00,0xbee20000,0x3ef5beb5,0x3e153eb5,0x3effbe8e,0x3d493ed5,0xbec6bdc8,0x3ea2befb,0xbea2be44,0x3ec6beed,0xbd493eed,0xbeff3e44,0xbe153efb,0xbef53dc8,0x3ee2bed5,0x3e713e8e,
0xbe8e3f00,0xbed50000,0x3ed50000,0xbe8e3f00,0x3efbbe44,0xbdc83eed,0x3dc8beed,0x3efbbe44,0xbdc8beb5,0x3efbbeb5,0xbefb3eb5,0xbdc8beb5,0xbed53eed,0xbe8ebe44,0x3e8e3e44,0xbed53eed,
0xbea23f00,0xbec60000,0x3d493eb5,0xbeff3eb5,0x3ee2bdc8,0xbe713efb,0x3ef5bed5,0x3e153e8e,0x3e15beed,0x3ef5be44,0xbe71be44,0x3ee2beed,0xbeff3e8e,0x3d49bed5,0xbec63efb,0xbea2bdc8,
0xbeb53f00,0xbeb50000,0xbeb53f00,0xbeb50000,0x3eb50000,0xbeb53f00,0x3eb50000,0xbeb53f00,0x3eb5bf00,0x3eb50000,0x3eb5bf00,0x3eb50000,0xbeb50000,0x3eb5bf00,0xbeb50000,0x3eb5bf00,
0xbec63f00,0xbea20000,0xbeff3eb5,0x3d49beb5,0x3e713dc8,0xbee23efb,0xbe153ed5,0xbef53e8e,0x3ef5beed,0x3e153e44,0x3ee2be44,0xbe713eed,0xbd49be8e,0x3effbed5,0x3ea2befb,0x3ec6bdc8,
0xbed53f00,0xbe8e0000,0xbe8e0000,0x3ed5bf00,0x3dc83e44,0xbefb3eed,0xbefb3eed,0xbdc8be44,0x3efbbeb5,0xbdc83eb5,0xbdc83eb5,0xbefb3eb5,0x3e8ebeed,0x3ed5be44,0x3ed5be44,0xbe8e3eed,
0xbee23f00,0xbe710000,0x3e15beb5,0x3ef5beb5,0xbd493e8e,0xbeff3ed5,0xbea23dc8,0x3ec6befb,0x3ec6be44,0xbea23eed,0xbeff3eed,0xbd49be44,0x3ef5befb,0x3e153dc8,0xbe713ed5,0xbee23e8e,
0xbeed3f00,0xbe440000,0x3eedbf00,0x3e440000,0xbe443eb5,0xbeed3eb5,0x3e44beb5,0x3eedbeb5,0x3e440000,0xbeed3f00,0xbe440000,0x3eedbf00,0x3eedbeb5,0xbe443eb5,0xbeed3eb5,0x3e44beb5,
0xbef53f00,0xbe150000,0x3ee2beb5,0xbe713eb5,0xbea23ed5,0xbec63e8e,0x3effbefb,0x3d493dc8,0xbd493e44,0xbeff3eed,0x3ec6beed,0x3ea2be44,0x3e71bdc8,0xbee23efb,0x3e15be8e,0x3ef5bed5,
0xbefb3f00,0xbdc80000,0x3dc80000,0xbefb3f00,0xbed53eed,0xbe8e3e44,0x3e8ebe44,0xbed53eed,0xbe8e3eb5,0xbed53eb5,0x3ed5beb5,0xbe8e3eb5,0xbdc83e44,0xbefb3eed,0x3efbbeed,0xbdc83e44,
0xbeff3f00,0xbd490000,0xbea23eb5,0xbec63eb5,0xbef53efb,0xbe153dc8,0xbe713e8e,0xbee23ed5,0xbee23eed,0xbe713e44,0xbe153e44,0xbef53eed,0xbec63ed5,0xbea23e8e,0xbd493dc8,0xbeff3efb,
0x3f003f00,0xbf003f00,0x3f003f00,0xbf003f00,0x3f003f00,0xbf003f00,0x3f003f00,0xbf003f00,0x3f003f00,0xbf003f00,0x3f003f00,0xbf003f00,0x3f003f00,0xbf003f00,0x3f003f00,0xbf003f00,
0xbd490000,0xbeffbf00,0xbec6beb5,0xbea2beb5,0xbe15bdc8,0xbef5befb,0xbee2bed5,0xbe71be8e,0xbe71be44,0xbee2beed,0xbef5beed,0xbe15be44,0xbea2be8e,0xbec6bed5,0xbeffbefb,0xbd49bdc8,
0xbefbbf00,0x3dc80000,0x3dc80000,0x3efb3f00,0xbed5beed,0x3e8e3e44,0x3e8e3e44,0x3ed53eed,0xbe8ebeb5,0x3ed53eb5,0x3ed53eb5,0x3e8e3eb5,0xbdc8be44,0x3efb3eed,0x3efb3eed,0x3dc83e44,
0x3e150000,0x3ef53f00,0x3e713eb5,0xbee2beb5,0x3ec63e8e,0x3ea23ed5,0xbd493dc8,0xbeffbefb,0x3eff3eed,0x3d493e44,0xbea2be44,0xbec6beed,0x3ee23efb,0xbe71bdc8,0xbef5bed5,0xbe15be8e,
0x3eed3f00,0xbe440000,0xbeedbf00,0x3e440000,0x3e443eb5,0xbeedbeb5,0xbe44beb5,0x3eed3eb5,0xbe440000,0xbeedbf00,0x3e440000,0x3eed3f00,0xbeedbeb5,0xbe44beb5,0x3eed3eb5,0x3e443eb5,
0xbe710000,0xbee2bf00,0x3ef53eb5,0x3e153eb5,0xbeffbed5,0xbd49be8e,0x3ec63efb,0xbea2bdc8,0xbea2beed,0x3ec63e44,0xbd493e44,0xbeffbeed,0x3e15bdc8,0x3ef53efb,0xbee2be8e,0xbe71bed5,
0xbed5bf00,0x3e8e0000,0xbe8e0000,0xbed5bf00,0x3dc8be44,0x3efb3eed,0xbefbbeed,0x3dc8be44,0x3efb3eb5,0x3dc83eb5,0xbdc8beb5,0x3efb3eb5,0x3e8e3eed,0xbed5be44,0x3ed53e44,0x3e8e3eed,
0x3ea20000,0x3ec63f00,0xbd49beb5,0x3eff3eb5,0x3ee23efb,0xbe713dc8,0x3ef53e8e,0x3e153ed5,0xbe153e44,0xbef5beed,0x3e713eed,0xbee2be44,0xbeffbed5,0x3d49be8e,0xbec6bdc8,0xbea2befb,
0x3eb53f00,0xbeb50000,0x3eb53f00,0xbeb50000,0xbeb50000,0xbeb5bf00,0xbeb50000,0xbeb5bf00,0xbeb5bf00,0x3eb50000,0xbeb5bf00,0x3eb50000,0x3eb50000,0x3eb53f00,0x3eb50000,0x3eb53f00,
0xbec60000,0xbea2bf00,0xbeffbeb5,0x3d49beb5,0xbe71befb,0x3ee23dc8,0x3e15be8e,0x3ef53ed5,0x3ef53e44,0x3e153eed,0x3ee23eed,0xbe713e44,0x3d493ed5,0xbeffbe8e,0xbea23dc8,0xbec6befb,
0xbe8ebf00,0x3ed50000,0x3ed50000,0x3e8e3f00,0x3efb3e44,0x3dc83eed,0x3dc83eed,0xbefbbe44,0xbdc83eb5,0xbefbbeb5,0xbefbbeb5,0x3dc8beb5,0xbed5beed,0x3e8ebe44,0x3e8ebe44,0x3ed53eed,
0x3ee20000,0x3e713f00,0xbe153eb5,0xbef5beb5,0xbd493ed5,0xbeffbe8e,0xbea2befb,0x3ec6bdc8,0xbec6beed,0x3ea2be44,0x3eff3e44,0x3d493eed,0x3ef53dc8,0x3e153efb,0xbe713e8e,0xbee2bed5,
0x3e443f00,0xbeed0000,0xbe44bf00,0x3eed0000,0xbeedbeb5,0x3e44beb5,0x3eed3eb5,0xbe443eb5,0x3eed0000,0x3e443f00,0xbeed0000,0xbe44bf00,0xbe443eb5,0xbeedbeb5,0x3e44beb5,0x3eed3eb5,
0xbef50000,0xbe15bf00,0x3ee23eb5,0xbe713eb5,0x3ea2be8e,0x3ec63ed5,0xbeffbdc8,0xbd49befb,0xbd493eed,0xbeffbe44,0x3ec6be44,0x3ea23eed,0xbe71befb,0x3ee2bdc8,0xbe153ed5,0xbef5be8e,
0xbdc8bf00,0x3efb0000,0xbefb0000,0xbdc8bf00,0x3e8e3eed,0xbed53e44,0x3ed5be44,0x3e8e3eed,0xbed5beb5,0x3e8ebeb5,0xbe8e3eb5,0xbed5beb5,0x3efb3e44,0xbdc83eed,0x3dc8beed,0x3efb3e44,
0x3eff0000,0x3d493f00,0x3ea2beb5,0x3ec63eb5,0xbef53dc8,0xbe15befb,0xbe713ed5,0xbee2be8e,0x3ee2be44,0x3e713eed,0x3e15beed,0x3ef53e44,0xbec63e8e,0xbea2bed5,0xbd493efb,0xbeffbdc8,
0x3f00,0xbf000000,0x3f00,0xbf000000,0xbf00,0x3f000000,0xbf00,0x3f000000,0x3f00,0xbf000000,0x3f00,0xbf000000,0xbf00,0x3f000000,0xbf00,0x3f000000,
0xbeff0000,0x3d49bf00,0xbea2beb5,0x3ec6beb5,0x3ef53dc8,0xbe153efb,0x3e713ed5,0xbee23e8e,0xbee2be44,0x3e71beed,0xbe15beed,0x3ef5be44,0x3ec63e8e,0xbea23ed5,0x3d493efb,0xbeff3dc8,
0x3dc8bf00,0x3efb0000,0x3efb0000,0xbdc83f00,0xbe8e3eed,0xbed5be44,0xbed5be44,0x3e8ebeed,0x3ed5beb5,0x3e8e3eb5,0x3e8e3eb5,0xbed53eb5,0xbefb3e44,0xbdc8beed,0xbdc8beed,0x3efbbe44,
0x3ef50000,0xbe153f00,0xbee23eb5,0xbe71beb5,0xbea2be8e,0x3ec6bed5,0x3effbdc8,0xbd493efb,0x3d493eed,0xbeff3e44,0xbec6be44,0x3ea2beed,0x3e71befb,0x3ee23dc8,0x3e153ed5,0xbef53e8e,
0xbe443f00,0xbeed0000,0x3e44bf00,0x3eed0000,0x3eedbeb5,0x3e443eb5,0xbeed3eb5,0xbe44beb5,0xbeed0000,0x3e44bf00,0x3eed0000,0xbe443f00,0x3e443eb5,0xbeed3eb5,0xbe44beb5,0x3eedbeb5,
0xbee20000,0x3e71bf00,0x3e153eb5,0xbef53eb5,0x3d493ed5,0xbeff3e8e,0x3ea2befb,0x3ec63dc8,0x3ec6beed,0x3ea23e44,0xbeff3e44,0x3d49beed,0xbef53dc8,0x3e15befb,0x3e713e8e,0xbee23ed5,
0x3e8ebf00,0x3ed50000,0xbed50000,0x3e8ebf00,0xbefb3e44,0x3dc8beed,0xbdc83eed,0xbefb3e44,0x3dc83eb5,0xbefb3eb5,0x3efbbeb5,0x3dc83eb5,0x3ed5beed,0x3e8e3e44,0xbe8ebe44,0x3ed5beed,
0x3ec60000,0xbea23f00,0x3effbeb5,0x3d493eb5,0x3e71befb,0x3ee2bdc8,0xbe15be8e,0x3ef5bed5,0xbef53e44,0x3e15beed,0xbee23eed,0xbe71be44,0xbd493ed5,0xbeff3e8e,0x3ea23dc8,0xbec63efb,
0xbeb53f00,0xbeb50000,0xbeb53f00,0xbeb50000,0x3eb50000,0xbeb53f00,0x3eb50000,0xbeb53f00,0x3eb5bf00,0x3eb50000,0x3eb5bf00,0x3eb50000,0xbeb50000,0x3eb5bf00,0xbeb50000,0x3eb5bf00,
0xbea20000,0x3ec6bf00,0x3d49beb5,0x3effbeb5,0xbee23efb,0xbe71bdc8,0xbef53e8e,0x3e15bed5,0x3e153e44,0xbef53eed,0xbe713eed,0xbee23e44,0x3effbed5,0x3d493e8e,0x3ec6bdc8,0xbea23efb,
0x3ed5bf00,0x3e8e0000,0x3e8e0000,0xbed53f00,0xbdc8be44,0x3efbbeed,0x3efbbeed,0x3dc83e44,0xbefb3eb5,0x3dc8beb5,0x3dc8beb5,0x3efbbeb5,0xbe8e3eed,0xbed53e44,0xbed53e44,0x3e8ebeed,
0x3e710000,0xbee23f00,0xbef53eb5,0x3e15beb5,0x3effbed5,0xbd493e8e,0xbec63efb,0xbea23dc8,0x3ea2beed,0x3ec6be44,0x3d493e44,0xbeff3eed,0xbe15bdc8,0x3ef5befb,0x3ee2be8e,0xbe713ed5,
0xbeed3f00,0xbe440000,0x3eedbf00,0x3e440000,0xbe443eb5,0xbeed3eb5,0x3e44beb5,0x3eedbeb5,0x3e440000,0xbeed3f00,0xbe440000,0x3eedbf00,0x3eedbeb5,0xbe443eb5,0xbeed3eb5,0x3e44beb5,
0xbe150000,0x3ef5bf00,0xbe713eb5,0xbee23eb5,0xbec63e8e,0x3ea2bed5,0x3d493dc8,0xbeff3efb,0xbeff3eed,0x3d49be44,0x3ea2be44,0xbec63eed,0xbee23efb,0xbe713dc8,0x3ef5bed5,0xbe153e8e,
0x3efbbf00,0x3dc80000,0xbdc80000,0x3efbbf00,0x3ed5beed,0x3e8ebe44,0xbe8e3e44,0x3ed5beed,0x3e8ebeb5,0x3ed5beb5,0xbed53eb5,0x3e8ebeb5,0x3dc8be44,0x3efbbeed,0xbefb3eed,0x3dc8be44,
0x3d490000,0xbeff3f00,0x3ec6beb5,0xbea23eb5,0x3e15bdc8,0xbef53efb,0x3ee2bed5,0xbe713e8e,0x3e71be44,0xbee23eed,0x3ef5beed,0xbe153e44,0x3ea2be8e,0xbec63ed5,0x3effbefb,0xbd493dc8,
0x3f003f00,0xbf003f00,0x3f003f00,0xbf003f00,0x3f003f00,0xbf003f00,0x3f003f00,0xbf003f00,0x3f003f00,0xbf003f00,0x3f003f00,0xbf003f00,0x3f003f00,0xbf003f00,0x3f003f00,0xbf003f00,
0xbeffbf00,0x3d490000,0xbea2beb5,0x3ec63eb5,0xbef5befb,0x3e153dc8,0xbe71be8e,0x3ee23ed5,0xbee2beed,0x3e713e44,0xbe15be44,0x3ef53eed,0xbec6bed5,0x3ea23e8e,0xbd49bdc8,0x3eff3efb,
0x3efb3f00,0xbdc80000,0xbdc80000,0xbefbbf00,0x3ed53eed,0xbe8ebe44,0xbe8ebe44,0xbed5beed,0x3e8e3eb5,0xbed5beb5,0xbed5beb5,0xbe8ebeb5,0x3dc83e44,0xbefbbeed,0xbefbbeed,0xbdc8be44,
0xbef5bf00,0x3e150000,0x3ee23eb5,0x3e713eb5,0xbea2bed5,0x3ec63e8e,0x3eff3efb,0xbd493dc8,0xbd49be44,0x3eff3eed,0x3ec63eed,0xbea2be44,0x3e713dc8,0x3ee23efb,0x3e153e8e,0xbef5bed5,
0x3eed3f00,0xbe440000,0xbeedbf00,0x3e440000,0x3e443eb5,0xbeedbeb5,0xbe44beb5,0x3eed3eb5,0xbe440000,0xbeedbf00,0x3e440000,0x3eed3f00,0xbeedbeb5,0xbe44beb5,0x3eed3eb5,0x3e443eb5,
0xbee2bf00,0x3e710000,0x3e153eb5,0xbef5beb5,0xbd49be8e,0x3eff3ed5,0xbea2bdc8,0xbec6befb,0x3ec63e44,0x3ea23eed,0xbeffbeed,0x3d49be44,0x3ef53efb,0xbe153dc8,0xbe71bed5,0x3ee23e8e,
0x3ed53f00,0xbe8e0000,0x3e8e0000,0x3ed53f00,0xbdc83e44,0xbefbbeed,0x3efb3eed,0xbdc83e44,0xbefbbeb5,0xbdc8beb5,0x3dc83eb5,0xbefbbeb5,0xbe8ebeed,0x3ed53e44,0xbed5be44,0xbe8ebeed,
0xbec6bf00,0x3ea20000,0xbeffbeb5,0xbd49beb5,0x3e71bdc8,0x3ee23efb,0xbe15bed5,0x3ef53e8e,0x3ef53eed,0xbe153e44,0x3ee23e44,0x3e713eed,0xbd493e8e,0xbeffbed5,0x3ea23efb,0xbec6bdc8,
0x3eb53f00,0xbeb50000,0x3eb53f00,0xbeb50000,0xbeb50000,0xbeb5bf00,0xbeb50000,0xbeb5bf00,0xbeb5bf00,0x3eb50000,0xbeb5bf00,0x3eb50000,0x3eb50000,0x3eb53f00,0x3eb50000,0x3eb53f00,
0xbea2bf00,0x3ec60000,0x3d49beb5,0x3eff3eb5,0x3ee23dc8,0x3e713efb,0x3ef53ed5,0xbe153e8e,0x3e153eed,0xbef5be44,0xbe713e44,0xbee2beed,0xbeffbe8e,0xbd49bed5,0xbec6befb,0x3ea2bdc8,
0x3e8e3f00,0xbed50000,0xbed50000,0xbe8ebf00,0xbefbbe44,0xbdc8beed,0xbdc8beed,0x3efb3e44,0x3dc8beb5,0x3efb3eb5,0x3efb3eb5,0xbdc83eb5,0x3ed53eed,0xbe8e3e44,0xbe8e3e44,0xbed5beed,
0xbe71bf00,0x3ee20000,0x3ef53eb5,0xbe153eb5,0x3eff3e8e,0xbd493ed5,0xbec63dc8,0xbea2befb,0xbea23e44,0xbec6beed,0xbd49beed,0x3eff3e44,0xbe15befb,0x3ef53dc8,0x3ee23ed5,0xbe713e8e,
0x3e443f00,0xbeed0000,0xbe44bf00,0x3eed0000,0xbeedbeb5,0x3e44beb5,0x3eed3eb5,0xbe443eb5,0x3eed0000,0x3e443f00,0xbeed0000,0xbe44bf00,0xbe443eb5,0xbeedbeb5,0x3e44beb5,0x3eed3eb5,
0xbe15bf00,0x3ef50000,0xbe713eb5,0xbee2beb5,0x3ec63ed5,0xbea23e8e,0xbd49befb,0x3eff3dc8,0xbeffbe44,0x3d49beed,0x3ea23eed,0xbec63e44,0x3ee2bdc8,0x3e713efb,0xbef5be8e,0x3e15bed5,
0x3dc83f00,0xbefb0000,0x3efb0000,0x3dc83f00,0xbe8ebeed,0x3ed5be44,0xbed53e44,0xbe8ebeed,0x3ed53eb5,0xbe8e3eb5,0x3e8ebeb5,0x3ed53eb5,0xbefbbe44,0x3dc8beed,0xbdc83eed,0xbefbbe44,
0xbd49bf00,0x3eff0000,0xbec6beb5,0x3ea2beb5,0x3e153efb,0xbef53dc8,0x3ee23e8e,0xbe713ed5,0xbe71beed,0x3ee2be44,0xbef5be44,0x3e15beed,0x3ea23ed5,0xbec63e8e,0x3eff3dc8,0xbd493efb,
0x3f00,0xbf000000,0x3f00,0xbf000000,0xbf00,0x3f000000,0xbf00,0x3f000000,0x3f00,0xbf000000,0x3f00,0xbf000000,0xbf00,0x3f000000,0xbf00,0x3f000000,
0x3d49bf00,0x3eff0000,0x3ec6beb5,0x3ea23eb5,0xbe153efb,0xbef5bdc8,0xbee23e8e,0xbe71bed5,0x3e71beed,0x3ee23e44,0x3ef5be44,0x3e153eed,0xbea23ed5,0xbec6be8e,0xbeff3dc8,0xbd49befb,
0xbdc83f00,0xbefb0000,0xbefb0000,0x3dc8bf00,0x3e8ebeed,0x3ed53e44,0x3ed53e44,0xbe8e3eed,0xbed53eb5,0xbe8ebeb5,0xbe8ebeb5,0x3ed5beb5,0x3efbbe44,0x3dc83eed,0x3dc83eed,0xbefb3e44,
0x3e15bf00,0x3ef50000,0x3e713eb5,0xbee23eb5,0xbec63ed5,0xbea2be8e,0x3d49befb,0x3effbdc8,0x3effbe44,0x3d493eed,0xbea23eed,0xbec6be44,0xbee2bdc8,0x3e71befb,0x3ef5be8e,0x3e153ed5,
0xbe443f00,0xbeed0000,0x3e44bf00,0x3eed0000,0x3eedbeb5,0x3e443eb5,0xbeed3eb5,0xbe44beb5,0xbeed0000,0x3e44bf00,0x3eed0000,0xbe443f00,0x3e443eb5,0xbeed3eb5,0xbe44beb5,0x3eedbeb5,
0x3e71bf00,0x3ee20000,0xbef53eb5,0xbe15beb5,0xbeff3e8e,0xbd49bed5,0x3ec63dc8,0xbea23efb,0x3ea23e44,0xbec63eed,0x3d49beed,0x3effbe44,0x3e15befb,0x3ef5bdc8,0xbee23ed5,0xbe71be8e,
0xbe8e3f00,0xbed50000,0x3ed50000,0xbe8e3f00,0x3efbbe44,0xbdc83eed,0x3dc8beed,0x3efbbe44,0xbdc8beb5,0x3efbbeb5,0xbefb3eb5,0xbdc8beb5,0xbed53eed,0xbe8ebe44,0x3e8e3e44,0xbed53eed,
0x3ea2bf00,0x3ec60000,0xbd49beb5,0x3effbeb5,0xbee23dc8,0x3e71befb,0xbef53ed5,0xbe15be8e,0xbe153eed,0xbef53e44,0x3e713e44,0xbee23eed,0x3effbe8e,0xbd493ed5,0x3ec6befb,0x3ea23dc8,
0xbeb53f00,0xbeb50000,0xbeb53f00,0xbeb50000,0x3eb50000,0xbeb53f00,0x3eb50000,0xbeb53f00,0x3eb5bf00,0x3eb50000,0x3eb5bf00,0x3eb50000,0xbeb50000,0x3eb5bf00,0xbeb50000,0x3eb5bf00,
0x3ec6bf00,0x3ea20000,0x3effbeb5,0xbd493eb5,0xbe71bdc8,0x3ee2befb,0x3e15bed5,0x3ef5be8e,0xbef53eed,0xbe15be44,0xbee23e44,0x3e71beed,0x3d493e8e,0xbeff3ed5,0xbea23efb,0xbec63dc8,
0xbed53f00,0xbe8e0000,0xbe8e0000,0x3ed5bf00,0x3dc83e44,0xbefb3eed,0xbefb3eed,0xbdc8be44,0x3efbbeb5,0xbdc83eb5,0xbdc83eb5,0xbefb3eb5,0x3e8ebeed,0x3ed5be44,0x3ed5be44,0xbe8e3eed,
0x3ee2bf00,0x3e710000,0xbe153eb5,0xbef53eb5,0x3d49be8e,0x3effbed5,0x3ea2bdc8,0xbec63efb,0xbec63e44,0x3ea2beed,0x3effbeed,0x3d493e44,0xbef53efb,0xbe15bdc8,0x3e71bed5,0x3ee2be8e,
0xbeed3f00,0xbe440000,0x3eedbf00,0x3e440000,0xbe443eb5,0xbeed3eb5,0x3e44beb5,0x3eedbeb5,0x3e440000,0xbeed3f00,0xbe440000,0x3eedbf00,0x3eedbeb5,0xbe443eb5,0xbeed3eb5,0x3e44beb5,
0x3ef5bf00,0x3e150000,0xbee23eb5,0x3e71beb5,0x3ea2bed5,0x3ec6be8e,0xbeff3efb,0xbd49bdc8,0x3d49be44,0x3effbeed,0xbec63eed,0xbea23e44,0xbe713dc8,0x3ee2befb,0xbe153e8e,0xbef53ed5,
0xbefb3f00,0xbdc80000,0x3dc80000,0xbefb3f00,0xbed53eed,0xbe8e3e44,0x3e8ebe44,0xbed53eed,0xbe8e3eb5,0xbed53eb5,0x3ed5beb5,0xbe8e3eb5,0xbdc83e44,0xbefb3eed,0x3efbbeed,0xbdc83e44,
0x3effbf00,0x3d490000,0x3ea2beb5,0x3ec6beb5,0x3ef5befb,0x3e15bdc8,0x3e71be8e,0x3ee2bed5,0x3ee2beed,0x3e71be44,0x3e15be44,0x3ef5beed,0x3ec6bed5,0x3ea2be8e,0x3d49bdc8,0x3effbefb,
0x3f003f00,0xbf003f00,0x3f003f00,0xbf003f00,0x3f003f00,0xbf003f00,0x3f003f00,0xbf003f00,0x3f003f00,0xbf003f00,0x3f003f00,0xbf003f00,0x3f003f00,0xbf003f00,0x3f003f00,0xbf003f00,
0x3d490000,0x3eff3f00,0x3ec63eb5,0x3ea23eb5,0x3e153dc8,0x3ef53efb,0x3ee23ed5,0x3e713e8e,0x3e713e44,0x3ee23eed,0x3ef53eed,0x3e153e44,0x3ea23e8e,0x3ec63ed5,0x3eff3efb,0x3d493dc8,
0xbefbbf00,0x3dc80000,0x3dc80000,0x3efb3f00,0xbed5beed,0x3e8e3e44,0x3e8e3e44,0x3ed53eed,0xbe8ebeb5,0x3ed53eb5,0x3ed53eb5,0x3e8e3eb5,0xbdc8be44,0x3efb3eed,0x3efb3eed,0x3dc83e44,
0xbe150000,0xbef5bf00,0xbe71beb5,0x3ee23eb5,0xbec6be8e,0xbea2bed5,0x3d49bdc8,0x3eff3efb,0xbeffbeed,0xbd49be44,0x3ea23e44,0x3ec63eed,0xbee2befb,0x3e713dc8,0x3ef53ed5,0x3e153e8e,
0x3eed3f00,0xbe440000,0xbeedbf00,0x3e440000,0x3e443eb5,0xbeedbeb5,0xbe44beb5,0x3eed3eb5,0xbe440000,0xbeedbf00,0x3e440000,0x3eed3f00,0xbeedbeb5,0xbe44beb5,0x3eed3eb5,0x3e443eb5,
0x3e710000,0x3ee23f00,0xbef5beb5,0xbe15beb5,0x3eff3ed5,0x3d493e8e,0xbec6befb,0x3ea23dc8,0x3ea23eed,0xbec6be44,0x3d49be44,0x3eff3eed,0xbe153dc8,0xbef5befb,0x3ee23e8e,0x3e713ed5,
0xbed5bf00,0x3e8e0000,0xbe8e0000,0xbed5bf00,0x3dc8be44,0x3efb3eed,0xbefbbeed,0x3dc8be44,0x3efb3eb5,0x3dc83eb5,0xbdc8beb5,0x3efb3eb5,0x3e8e3eed,0xbed5be44,0x3ed53e44,0x3e8e3eed,
0xbea20000,0xbec6bf00,0x3d493eb5,0xbeffbeb5,0xbee2befb,0x3e71bdc8,0xbef5be8e,0xbe15bed5,0x3e15be44,0x3ef53eed,0xbe71beed,0x3ee23e44,0x3eff3ed5,0xbd493e8e,0x3ec63dc8,0x3ea23efb,
0x3eb53f00,0xbeb50000,0x3eb53f00,0xbeb50000,0xbeb50000,0xbeb5bf00,0xbeb50000,0xbeb5bf00,0xbeb5bf00,0x3eb50000,0xbeb5bf00,0x3eb50000,0x3eb50000,0x3eb53f00,0x3eb50000,0x3eb53f00,
0x3ec60000,0x3ea23f00,0x3eff3eb5,0xbd493eb5,0x3e713efb,0xbee2bdc8,0xbe153e8e,0xbef5bed5,0xbef5be44,0xbe15beed,0xbee2beed,0x3e71be44,0xbd49bed5,0x3eff3e8e,0x3ea2bdc8,0x3ec63efb,
0xbe8ebf00,0x3ed50000,0x3ed50000,0x3e8e3f00,0x3efb3e44,0x3dc83eed,0x3dc83eed,0xbefbbe44,0xbdc83eb5,0xbefbbeb5,0xbefbbeb5,0x3dc8beb5,0xbed5beed,0x3e8ebe44,0x3e8ebe44,0x3ed53eed,
0xbee20000,0xbe71bf00,0x3e15beb5,0x3ef53eb5,0x3d49bed5,0x3eff3e8e,0x3ea23efb,0xbec63dc8,0x3ec63eed,0xbea23e44,0xbeffbe44,0xbd49beed,0xbef5bdc8,0xbe15befb,0x3e71be8e,0x3ee23ed5,
0x3e443f00,0xbeed0000,0xbe44bf00,0x3eed0000,0xbeedbeb5,0x3e44beb5,0x3eed3eb5,0xbe443eb5,0x3eed0000,0x3e443f00,0xbeed0000,0xbe44bf00,0xbe443eb5,0xbeedbeb5,0x3e44beb5,0x3eed3eb5,
0x3ef50000,0x3e153f00,0xbee2beb5,0x3e71beb5,0xbea23e8e,0xbec6bed5,0x3eff3dc8,0x3d493efb,0x3d49beed,0x3eff3e44,0xbec63e44,0xbea2beed,0x3e713efb,0xbee23dc8,0x3e15bed5,0x3ef53e8e,
0xbdc8bf00,0x3efb0000,0xbefb0000,0xbdc8bf00,0x3e8e3eed,0xbed53e44,0x3ed5be44,0x3e8e3eed,0xbed5beb5,0x3e8ebeb5,0xbe8e3eb5,0xbed5beb5,0x3efb3e44,0xbdc83eed,0x3dc8beed,0x3efb3e44,
0xbeff0000,0xbd49bf00,0xbea23eb5,0xbec6beb5,0x3ef5bdc8,0x3e153efb,0x3e71bed5,0x3ee23e8e,0xbee23e44,0xbe71beed,0xbe153eed,0xbef5be44,0x3ec6be8e,0x3ea23ed5,0x3d49befb,0x3eff3dc8,
0x3f00,0xbf000000,0x3f00,0xbf000000,0xbf00,0x3f000000,0xbf00,0x3f000000,0x3f00,0xbf000000,0x3f00,0xbf000000,0xbf00,0x3f000000,0xbf00,0x3f000000,
0x3eff0000,0xbd493f00,0x3ea23eb5,0xbec63eb5,0xbef5bdc8,0x3e15befb,0xbe71bed5,0x3ee2be8e,0x3ee23e44,0xbe713eed,0x3e153eed,0xbef53e44,0xbec6be8e,0x3ea2bed5,0xbd49befb,0x3effbdc8,
0x3dc8bf00,0x3efb0000,0x3efb0000,0xbdc83f00,0xbe8e3eed,0xbed5be44,0xbed5be44,0x3e8ebeed,0x3ed5beb5,0x3e8e3eb5,0x3e8e3eb5,0xbed53eb5,0xbefb3e44,0xbdc8beed,0xbdc8beed,0x3efbbe44,
0xbef50000,0x3e15bf00,0x3ee2beb5,0x3e713eb5,0x3ea23e8e,0xbec63ed5,0xbeff3dc8,0x3d49befb,0xbd49beed,0x3effbe44,0x3ec63e44,0xbea23eed,0xbe713efb,0xbee2bdc8,0xbe15bed5,0x3ef5be8e,
0xbe443f00,0xbeed0000,0x3e44bf00,0x3eed0000,0x3eedbeb5,0x3e443eb5,0xbeed3eb5,0xbe44beb5,0xbeed0000,0x3e44bf00,0x3eed0000,0xbe443f00,0x3e443eb5,0xbeed3eb5,0xbe44beb5,0x3eedbeb5,
0x3ee20000,0xbe713f00,0xbe15beb5,0x3ef5beb5,0xbd49bed5,0x3effbe8e,0xbea23efb,0xbec6bdc8,0xbec63eed,0xbea2be44,0x3effbe44,0xbd493eed,0x3ef5bdc8,0xbe153efb,0xbe71be8e,0x3ee2bed5,
0x3e8ebf00,0x3ed50000,0xbed50000,0x3e8ebf00,0xbefb3e44,0x3dc8beed,0xbdc83eed,0xbefb3e44,0x3dc83eb5,0xbefb3eb5,0x3efbbeb5,0x3dc83eb5,0x3ed5beed,0x3e8e3e44,0xbe8ebe44,0x3ed5beed,
0xbec60000,0x3ea2bf00,0xbeff3eb5,0xbd49beb5,0xbe713efb,0xbee23dc8,0x3e153e8e,0xbef53ed5,0x3ef5be44,0xbe153eed,0x3ee2beed,0x3e713e44,0x3d49bed5,0x3effbe8e,0xbea2bdc8,0x3ec6befb,
0xbeb53f00,0xbeb50000,0xbeb53f00,0xbeb50000,0x3eb50000,0xbeb53f00,0x3eb50000,0xbeb53f00,0x3eb5bf00,0x3eb50000,0x3eb5bf00,0x3eb50000,0xbeb50000,0x3eb5bf00,0xbeb50000,0x3eb5bf00,
0x3ea20000,0xbec63f00,0xbd493eb5,0xbeff3eb5,0x3ee2befb,0x3e713dc8,0x3ef5be8e,0xbe153ed5,0xbe15be44,0x3ef5beed,0x3e71beed,0x3ee2be44,0xbeff3ed5,0xbd49be8e,0xbec63dc8,0x3ea2befb,
0x3ed5bf00,0x3e8e0000,0x3e8e0000,0xbed53f00,0xbdc8be44,0x3efbbeed,0x3efbbeed,0x3dc83e44,0xbefb3eb5,0x3dc8beb5,0x3dc8beb5,0x3efbbeb5,0xbe8e3eed,0xbed53e44,0xbed53e44,0x3e8ebeed,
0xbe710000,0x3ee2bf00,0x3ef5beb5,0xbe153eb5,0xbeff3ed5,0x3d49be8e,0x3ec6befb,0x3ea2bdc8,0xbea23eed,0xbec63e44,0xbd49be44,0x3effbeed,0x3e153dc8,0xbef53efb,0xbee23e8e,0x3e71bed5,
0xbeed3f00,0xbe440000,0x3eedbf00,0x3e440000,0xbe443eb5,0xbeed3eb5,0x3e44beb5,0x3eedbeb5,0x3e440000,0xbeed3f00,0xbe440000,0x3eedbf00,0x3eedbeb5,0xbe443eb5,0xbeed3eb5,0x3e44beb5,
0x3e150000,0xbef53f00,0x3e71beb5,0x3ee2beb5,0x3ec6be8e,0xbea23ed5,0xbd49bdc8,0x3effbefb,0x3effbeed,0xbd493e44,0xbea23e44,0x3ec6beed,0x3ee2befb,0x3e71bdc8,0xbef53ed5,0x3e15be8e,
0x3efbbf00,0x3dc80000,0xbdc80000,0x3efbbf00,0x3ed5beed,0x3e8ebe44,0xbe8e3e44,0x3ed5beed,0x3e8ebeb5,0x3ed5beb5,0xbed53eb5,0x3e8ebeb5,0x3dc8be44,0x3efbbeed,0xbefb3eed,0x3dc8be44,
0xbd490000,0x3effbf00,0xbec63eb5,0x3ea2beb5,0xbe153dc8,0x3ef5befb,0xbee23ed5,0x3e71be8e,0xbe713e44,0x3ee2beed,0xbef53eed,0x3e15be44,0xbea23e8e,0x3ec6bed5,0xbeff3efb,0x3d49bdc8,
0x3f800000,0x0,0x3f800000,0x0,0x3f800000,0x0,0x3f800000,0x0,0x3f800000,0x0,0x3f800000,0x0,0x3f800000,0x0,0x3f800000,0x0,
0x3f800000,0x0,0x3f7ffec4,0xbbc90f88,0x3f7ffb11,0xbc490e90,0x3f7ff4e6,0xbc96c9b6,0x3f7fec43,0xbcc90ab0,0x3f7fe129,0xbcfb49ba,0x3f7fd397,0xbd16c32c,0x3f7fc38f,0xbd2fe007,
0x3f800000,0x0,0x3f7ffb11,0xbc490e90,0x3f7fec43,0xbcc90ab0,0x3f7fd397,0xbd16c32c,0x3f7fb10f,0xbd48fb30,0x3f7f84ab,0xbd7b2b74,0x3f7f4e6d,0xbd96a905,0x3f7f0e58,0xbdafb680,
0x3f800000,0x0,0x3f7ff4e6,0xbc96c9b6,0x3f7fd397,0xbd16c32c,0x3f7f9c18,0xbd621469,0x3f7f4e6d,0xbd96a905,0x3f7eea9d,0xbdbc3ac3,0x3f7e70b0,0xbde1bc2e,0x3f7de0b1,0xbe039502,
0x3f800000,0x0,0x3f7fec43,0xbcc90ab0,0x3f7fb10f,0xbd48fb30,0x3f7f4e6d,0xbd96a905,0x3f7ec46d,0xbdc8bd36,0x3f7e1324,0xbdfab273,0x3f7d3aac,0xbe164083,0x3f7c3b28,0xbe2f10a2,
0x3f800000,0x0,0x3f7fe129,0xbcfb49ba,0x3f7f84ab,0xbd7b2b74,0x3f7eea9d,0xbdbc3ac3,0x3f7e1324,0xbdfab273,0x3f7cfe73,0xbe1c76de,0x3f7baccd,0xbe3b6ecf,0x3f7a1e84,0xbe5a3997,
0x3f800000,0x0,0x3f7fd397,0xbd16c32c,0x3f7f4e6d,0xbd96a905,0x3f7e70b0,0xbde1bc2e,0x3f7d3aac,0xbe164083,0x3f7baccd,0xbe3b6ecf,0x3f79c79d,0xbe605c13,0x3f778bc5,0xbe827dc0,
0x3f800000,0x0,0x3f7fc38f,0xbd2fe007,0x3f7f0e58,0xbdafb680,0x3f7de0b1,0xbe039502,0x3f7c3b28,0xbe2f10a2,0x3f7a1e84,0xbe5a3997,0x3f778bc5,0xbe827dc0,0x3f748422,0xbe97a117,
0x3f800000,0x0,0x3f7fb10f,0xbd48fb30,0x3f7ec46d,0xbdc8bd36,0x3f7d3aac,0xbe164083,0x3f7b14be,0xbe47c5c2,0x3f7853f8,0xbe78cfcc,0x3f74fa0b,0xbe94a031,0x3f710908,0xbeac7cd4,
0x3f800000,0x0,0x3f7f9c18,0xbd621469,0x3f7e70b0,0xbde1bc2e,0x3f7c7eb0,0xbe28defc,0x3f79c79d,0xbe605c13,0x3f764d97,0xbe8b9507,0x3f721352,0xbea68f12,0x3f6d1c1d,0xbec1071e,
0x3f800000,0x0,0x3f7f84ab,0xbd7b2b74,0x3f7e1324,0xbdfab273,0x3f7baccd,0xbe3b6ecf,0x3f7853f8,0xbe78cfcc,0x3f740bdd,0xbe9aa086,0x3f6ed89e,0xbeb8442a,0x3f68bf3c,0xbed53641,
0x3f800000,0x0,0x3f7f6ac7,0xbd8a200a,0x3f7dabcc,0xbe09cf86,0x3f7ac516,0xbe4dee60,0x3f76ba07,0xbe888e93,0x3f718f57,0xbea986c4,0x3f6b4b0c,0xbec9b953,0x3f63f473,0xbee900b7,
0x3f800000,0x0,0x3f7f4e6d,0xbd96a905,0x3f7d3aac,0xbe164083,0x3f79c79d,0xbe605c13,0x3f74fa0b,0xbe94a031,0x3f6ed89e,0xbeb8442a,0x3f676bd8,0xbedae880,0x3f5ebe05,0xbefc5d27,
0x3f800000,0x0,0x3f7f2f9d,0xbda3308c,0x3f7cbfc9,0xbe22abb6,0x3f78b47b,0xbe72b651,0x3f731447,0xbea09ae5,0x3f6be858,0xbec6d529,0x3f633c5a,0xbeebcbbb,0x3f591e6a,0xbf07a136,
0x3f800000,0x0,0x3f7f0e58,0xbdafb680,0x3f7c3b28,0xbe2f10a2,0x3f778bc5,0xbe827dc0,0x3f710908,0xbeac7cd4,0x3f68bf3c,0xbed53641,0x3f5ebe05,0xbefc5d27,0x3f531849,0xbf10d3cd,
0x3f800000,0x0,0x3f7eea9d,0xbdbc3ac3,0x3f7baccd,0xbe3b6ecf,0x3f764d97,0xbe8b9507,0x3f6ed89e,0xbeb8442a,0x3f655e0b,0xbee363fa,0x3f59f26a,0xbf064b82,0x3f4cae79,0xbf19c200,
0x3f800000,0x0,0x3f7ec46d,0xbdc8bd36,0x3f7b14be,0xbe47c5c2,0x3f74fa0b,0xbe94a031,0x3f6c835e,0xbec3ef15,0x3f61c598,0xbef15aea,0x3f54db31,0xbf0e39da,0x3f45e403,0xbf226799,
0x3f800000,0x0,0x3f7e9bc9,0xbdd53db9,0x3f7a7302,0xbe541501,0x3f73913f,0xbe9d9e78,0x3f6a09a7,0xbecf7bca,0x3f5df6be,0xbeff17b2,0x3f4f7a1f,0xbf15f6d9,0x3f3ebc1b,0xbf2ac082,
0x3f800000,0x0,0x3f7e70b0,0xbde1bc2e,0x3f79c79d,0xbe605c13,0x3f721352,0xbea68f12,0x3f676bd8,0xbedae880,0x3f59f26a,0xbf064b82,0x3f49d112,0xbf1d7fd1,0x3f373a23,0xbf32c8c9,
0x3f800000,0x0,0x3f7e4323,0xbdee3876,0x3f791298,0xbe6c9a7f,0x3f708066,0xbeaf713a,0x3f64aa59,0xbee63375,0x3f55b993,0xbf0cead0,0x3f43e200,0xbf24d225,0x3f2f61a5,0xbf3a7ca4,
0x3f800000,0x0,0x3f7e1324,0xbdfab273,0x3f7853f8,0xbe78cfcc,0x3f6ed89e,0xbeb8442a,0x3f61c598,0xbef15aea,0x3f514d3d,0xbf13682a,0x3f3daef9,0xbf2beb4a,0x3f273656,0xbf41d870,
0x3f800000,0x0,0x3f7de0b1,0xbe039502,0x3f778bc5,0xbe827dc0,0x3f6d1c1d,0xbec1071e,0x3f5ebe05,0xbefc5d27,0x3f4cae79,0xbf19c200,0x3f373a23,0xbf32c8c9,0x3f1ebc12,0xbf48d8b3,
0x3f800000,0x0,0x3f7dabcc,0xbe09cf86,0x3f76ba07,0xbe888e93,0x3f6b4b0c,0xbec9b953,0x3f5b941a,0xbf039c3d,0x3f47de65,0xbf1ff6cb,0x3f3085bb,0xbf396842,0x3f15f6d9,0xbf4f7a1f,
0x3f800000,0x0,0x3f7d7474,0xbe1008b7,0x3f75dec6,0xbe8e9a22,0x3f696591,0xbed25a09,0x3f584853,0xbf08f59b,0x3f42de29,0xbf26050a,0x3f299415,0xbf3fc767,0x3f0cead0,0xbf55b993,
0x3f800000,0x0,0x3f7d3aac,0xbe164083,0x3f74fa0b,0xbe94a031,0x3f676bd8,0xbedae880,0x3f54db31,0xbf0e39da,0x3f3daef9,0xbf2beb4a,0x3f226799,0xbf45e403,0x3f039c3d,0xbf5b941a,
0x3f800000,0x0,0x3f7cfe73,0xbe1c76de,0x3f740bdd,0xbe9aa086,0x3f655e0b,0xbee363fa,0x3f514d3d,0xbf13682a,0x3f385216,0xbf31a81d,0x3f1b02c6,0xbf4bbbf8,0x3ef41f07,0xbf6106f2,
0x3f800000,0x0,0x3f7cbfc9,0xbe22abb6,0x3f731447,0xbea09ae5,0x3f633c5a,0xbeebcbbb,0x3f4d9f02,0xbf187fc0,0x3f32c8c9,0xbf373a23,0x3f13682a,0xbf514d3d,0x3ee0924f,0xbf660f88,
0x3f800000,0x0,0x3f7c7eb0,0xbe28defc,0x3f721352,0xbea68f12,0x3f6106f2,0xbef41f07,0x3f49d112,0xbf1d7fd1,0x3f2d1469,0xbf3ca003,0x3f0b9a6b,0xbf5695e5,0x3ecc9b8b,0xbf6aab7b,
0x3f800000,0x0,0x3f7c3b28,0xbe2f10a2,0x3f710908,0xbeac7cd4,0x3f5ebe05,0xbefc5d27,0x3f45e403,0xbf226799,0x3f273656,0xbf41d870,0x3f039c3d,0xbf5b941a,0x3eb8442a,0xbf6ed89e,
0x3f800000,0x0,0x3f7bf531,0xbe354098,0x3f6ff573,0xbeb263ef,0x3f5c61c7,0xbf0242b1,0x3f41d870,0xbf273656,0x3f212ff9,0xbf46e22a,0x3ef6e0cb,0xbf604621,0x3ea395c5,0xbf7294f8,
0x3f800000,0x0,0x3f7baccd,0xbe3b6ecf,0x3f6ed89e,0xbeb8442a,0x3f59f26a,0xbf064b82,0x3f3daef9,0xbf2beb4a,0x3f1b02c6,0xbf4bbbf8,0x3ee63375,0xbf64aa59,0x3e8e9a22,0xbf75dec6,
0x3f800000,0x0,0x3f7b61fc,0xbe419b37,0x3f6db293,0xbebe1d4a,0x3f577026,0xbf0a48ad,0x3f396842,0xbf3085bb,0x3f14b039,0xbf5064af,0x3ed53641,0xbf68bf3c,0x3e72b651,0xbf78b47b,
0x3f800000,0x0,0x3f800000,0x0,0x3f800000,0x0,0x3f800000,0x0,0x3f800000,0x0,0x3f800000,0x0,0x3f800000,0x0,0x3f800000,0x0,
0x3f7fb10f,0xbd48fb30,0x3f7f9c18,0xbd621469,0x3f7f84ab,0xbd7b2b74,0x3f7f6ac7,0xbd8a200a,0x3f7f4e6d,0xbd96a905,0x3f7f2f9d,0xbda3308c,0x3f7f0e58,0xbdafb680,0x3f7eea9d,0xbdbc3ac3,
0x3f7ec46d,0xbdc8bd36,0x3f7e70b0,0xbde1bc2e,0x3f7e1324,0xbdfab273,0x3f7dabcc,0xbe09cf86,0x3f7d3aac,0xbe164083,0x3f7cbfc9,0xbe22abb6,0x3f7c3b28,0xbe2f10a2,0x3f7baccd,0xbe3b6ecf,
0x3f7d3aac,0xbe164083,0x3f7c7eb0,0xbe28defc,0x3f7baccd,0xbe3b6ecf,0x3f7ac516,0xbe4dee60,0x3f79c79d,0xbe605c13,0x3f78b47b,0xbe72b651,0x3f778bc5,0xbe827dc0,0x3f764d97,0xbe8b9507,
0x3f7b14be,0xbe47c5c2,0x3f79c79d,0xbe605c13,0x3f7853f8,0xbe78cfcc,0x3f76ba07,0xbe888e93,0x3f74fa0b,0xbe94a031,0x3f731447,0xbea09ae5,0x3f710908,0xbeac7cd4,0x3f6ed89e,0xbeb8442a,
0x3f7853f8,0xbe78cfcc,0x3f764d97,0xbe8b9507,0x3f740bdd,0xbe9aa086,0x3f718f57,0xbea986c4,0x3f6ed89e,0xbeb8442a,0x3f6be858,0xbec6d529,0x3f68bf3c,0xbed53641,0x3f655e0b,0xbee363fa,
0x3f74fa0b,0xbe94a031,0x3f721352,0xbea68f12,0x3f6ed89e,0xbeb8442a,0x3f6b4b0c,0xbec9b953,0x3f676bd8,0xbedae880,0x3f633c5a,0xbeebcbbb,0x3f5ebe05,0xbefc5d27,0x3f59f26a,0xbf064b82,
0x3f710908,0xbeac7cd4,0x3f6d1c1d,0xbec1071e,0x3f68bf3c,0xbed53641,0x3f63f473,0xbee900b7,0x3f5ebe05,0xbefc5d27,0x3f591e6a,0xbf07a136,0x3f531849,0xbf10d3cd,0x3f4cae79,0xbf19c200,
0x3f6c835e,0xbec3ef15,0x3f676bd8,0xbedae880,0x3f61c598,0xbef15aea,0x3f5b941a,0xbf039c3d,0x3f54db31,0xbf0e39da,0x3f4d9f02,0xbf187fc0,0x3f45e403,0xbf226799,0x3f3daef9,0xbf2beb4a,
0x3f676bd8,0xbedae880,0x3f6106f2,0xbef41f07,0x3f59f26a,0xbf064b82,0x3f5233c6,0xbf121eb0,0x3f49d112,0xbf1d7fd1,0x3f40d0da,0xbf286605,0x3f373a23,0xbf32c8c9,0x3f2d1469,0xbf3ca003,
0x3f61c598,0xbef15aea,0x3f59f26a,0xbf064b82,0x3f514d3d,0xbf13682a,0x3f47de65,0xbf1ff6cb,0x3f3daef9,0xbf2beb4a,0x3f32c8c9,0xbf373a23,0x3f273656,0xbf41d870,0x3f1b02c6,0xbf4bbbf8,
0x3f5b941a,0xbf039c3d,0x3f5233c6,0xbf121eb0,0x3f47de65,0xbf1ff6cb,0x3f3ca003,0xbf2d1469,0x3f3085bb,0xbf396842,0x3f239da9,0xbf44e3f5,0x3f15f6d9,0xbf4f7a1f,0x3f07a136,0xbf591e6a,
0x3f54db31,0xbf0e39da,0x3f49d112,0xbf1d7fd1,0x3f3daef9,0xbf2beb4a,0x3f3085bb,0xbf396842,0x3f226799,0xbf45e403,0x3f13682a,0xbf514d3d,0x3f039c3d,0xbf5b941a,0x3ee63375,0xbf64aa59,
0x3f4d9f02,0xbf187fc0,0x3f40d0da,0xbf286605,0x3f32c8c9,0xbf373a23,0x3f239da9,0xbf44e3f5,0x3f13682a,0xbf514d3d,0x3f0242b1,0xbf5c61c7,0x3ee0924f,0xbf660f88,0x3ebb31a0,0xbf6e46be,
0x3f45e403,0xbf226799,0x3f373a23,0xbf32c8c9,0x3f273656,0xbf41d870,0x3f15f6d9,0xbf4f7a1f,0x3f039c3d,0xbf5b941a,0x3ee0924f,0xbf660f88,0x3eb8442a,0xbf6ed89e,0x3e8e9a22,0xbf75dec6,
0x3f3daef9,0xbf2beb4a,0x3f2d1469,0xbf3ca003,0x3f1b02c6,0xbf4bbbf8,0x3f07a136,0xbf591e6a,0x3ee63375,0xbf64aa59,0x3ebb31a0,0xbf6e46be,0x3e8e9a22,0xbf75dec6,0x3e419b37,0xbf7b61fc,
0x3f3504f3,0xbf3504f3,0x3f226799,0xbf45e403,0x3f0e39da,0xbf54db31,0x3ef15aea,0xbf61c598,0x3ec3ef15,0xbf6c835e,0x3e94a031,0xbf74fa0b,0x3e47c5c2,0xbf7b14be,0x3dc8bd36,0xbf7ec46d,
0x3f2beb4a,0xbf3daef9,0x3f173c07,0xbf4e8d90,0x3f00e7e4,0xbf5d2d53,0x3ed25a09,0xbf696591,0x3ea09ae5,0xbf731447,0x3e5a3997,0xbf7a1e84,0x3de1bc2e,0xbf7e70b0,0x3bc90f88,0xbf7ffec4,
0x3f226799,0xbf45e403,0x3f0b9a6b,0xbf5695e5,0x3ee63375,0xbf64aa59,0x3eb263ef,0xbf6ff573,0x3e78cfcc,0xbf7853f8,0x3e09cf86,0xbf7dabcc,0x3cc90ab0,0xbf7fec43,0xbdafb680,0xbf7f0e58,
0x3f187fc0,0xbf4d9f02,0x3eff17b2,0xbf5df6be,0x3ec9b953,0xbf6b4b0c,0x3e919ddd,0xbf756d97,0x3e2f10a2,0xbf7c3b28,0x3d621469,0xbf7f9c18,0xbd7b2b74,0xbf7f84ab,0xbe354098,0xbf7bf531,
0x3f0e39da,0xbf54db31,0x3ee63375,0xbf64aa59,0x3eac7cd4,0xbf710908,0x3e605c13,0xbf79c79d,0x3dc8bd36,0xbf7ec46d,0xbcc90ab0,0xbf7fec43,0xbe164083,0xbf7d3aac,0xbe888e93,0xbf76ba07,
0x3f039c3d,0xbf5b941a,0x3ecc9b8b,0xbf6aab7b,0x3e8e9a22,0xbf75dec6,0x3e1c76de,0xbf7cfe73,0x3cc90ab0,0xbf7fec43,0xbdd53db9,0xbf7e9bc9,0xbe6c9a7f,0xbf791298,0xbeb554ec,0xbf6f6830,
0x3ef15aea,0xbf61c598,0x3eb263ef,0xbf6ff573,0x3e605c13,0xbf79c79d,0x3dafb680,0xbf7f0e58,0xbd48fb30,0xbf7fb10f,0xbe3b6ecf,0xbf7baccd,0xbea09ae5,0xbf731447,0xbee0924f,0xbf660f88,
0x3edae880,0xbf676bd8,0x3e97a117,0xbf748422,0x3e22abb6,0xbf7cbfc9,0x3c96c9b6,0xbf7ff4e6,0xbdfab273,0xbf7e1324,0xbe8586ce,0xbf772417,0xbec9b953,0xbf6b4b0c,0xbf04f484,0xbf5ac450,
0x3ec3ef15,0xbf6c835e,0x3e78cfcc,0xbf7853f8,0x3dc8bd36,0xbf7ec46d,0xbd48fb30,0xbf7fb10f,0xbe47c5c2,0xbf7b14be,0xbeac7cd4,0xbf710908,0xbef15aea,0xbf61c598,0xbf187fc0,0xbf4d9f02,
0x3eac7cd4,0xbf710908,0x3e419b37,0xbf7b61fc,0x3d16c32c,0xbf7fd397,0xbdee3876,0xbf7e4323,0xbe888e93,0xbf76ba07,0xbed25a09,0xbf696591,0xbf0b9a6b,0xbf5695e5,0xbf2ac082,0xbf3ebc1b,
0x3e94a031,0xbf74fa0b,0x3e09cf86,0xbf7dabcc,0xbcc90ab0,0xbf7fec43,0xbe3b6ecf,0xbf7baccd,0xbeac7cd4,0xbf710908,0xbef6e0cb,0xbf604621,0xbf1d7fd1,0xbf49d112,0xbf3b8f3b,0xbf2e3bde,
0x3e78cfcc,0xbf7853f8,0x3da3308c,0xbf7f2f9d,0xbdafb680,0xbf7f0e58,0xbe7ee6e1,0xbf77f110,0xbecf7bca,0xbf6a09a7,0xbf0cead0,0xbf55b993,0xbf2e3bde,0xbf3b8f3b,0xbf4ac77f,0xbf1c420c,
0x3e47c5c2,0xbf7b14be,0x3cc90ab0,0xbf7fec43,0xbe164083,0xbf7d3aac,0xbea09ae5,0xbf731447,0xbef15aea,0xbf61c598,0xbf1d7fd1,0xbf49d112,0xbf3daef9,0xbf2beb4a,0xbf584853,0xbf08f59b,
0x3e164083,0xbf7d3aac,0xbcfb49ba,0xbf7fe129,0xbe541501,0xbf7a7302,0xbec1071e,0xbf6d1c1d,0xbf08f59b,0xbf584853,0xbf2d1469,0xbf3ca003,0xbf4bbbf8,0xbf1b02c6,0xbf63f473,0xbee900b7,
0x3dc8bd36,0xbf7ec46d,0xbdafb680,0xbf7f0e58,0xbe888e93,0xbf76ba07,0xbee0924f,0xbf660f88,0xbf187fc0,0xbf4d9f02,0xbf3b8f3b,0xbf2e3bde,0xbf584853,0xbf08f59b,0xbf6db293,0xbebe1d4a,
0x3d48fb30,0xbf7fb10f,0xbe1008b7,0xbf7d7474,0xbea68f12,0xbf721352,0xbeff17b2,0xbf5df6be,0xbf273656,0xbf41d870,0xbf48d8b3,0xbf1ebc12,0xbf633c5a,0xbeebcbbb,0xbf756d97,0xbe919ddd,
0x3f800000,0x0,0x3f800000,0x0,0x3f800000,0x0,0x3f800000,0x0,0x3f800000,0x0,0x3f800000,0x0,0x3f800000,0x0,0x3f800000,0x0,
0x3f7ec46d,0xbdc8bd36,0x3f7e9bc9,0xbdd53db9,0x3f7e70b0,0xbde1bc2e,0x3f7e4323,0xbdee3876,0x3f7e1324,0xbdfab273,0x3f7de0b1,0xbe039502,0x3f7dabcc,0xbe09cf86,0x3f7d7474,0xbe1008b7,
0x3f7b14be,0xbe47c5c2,0x3f7a7302,0xbe541501,0x3f79c79d,0xbe605c13,0x3f791298,0xbe6c9a7f,0x3f7853f8,0xbe78cfcc,0x3f778bc5,0xbe827dc0,0x3f76ba07,0xbe888e93,0x3f75dec6,0xbe8e9a22,
0x3f74fa0b,0xbe94a031,0x3f73913f,0xbe9d9e78,0x3f721352,0xbea68f12,0x3f708066,0xbeaf713a,0x3f6ed89e,0xbeb8442a,0x3f6d1c1d,0xbec1071e,0x3f6b4b0c,0xbec9b953,0x3f696591,0xbed25a09,
0x3f6c835e,0xbec3ef15,0x3f6a09a7,0xbecf7bca,0x3f676bd8,0xbedae880,0x3f64aa59,0xbee63375,0x3f61c598,0xbef15aea,0x3f5ebe05,0xbefc5d27,0x3f5b941a,0xbf039c3d,0x3f584853,0xbf08f59b,
0x3f61c598,0xbef15aea,0x3f5df6be,0xbeff17b2,0x3f59f26a,0xbf064b82,0x3f55b993,0xbf0cead0,0x3f514d3d,0xbf13682a,0x3f4cae79,0xbf19c200,0x3f47de65,0xbf1ff6cb,0x3f42de29,0xbf26050a,
0x3f54db31,0xbf0e39da,0x3f4f7a1f,0xbf15f6d9,0x3f49d112,0xbf1d7fd1,0x3f43e200,0xbf24d225,0x3f3daef9,0xbf2beb4a,0x3f373a23,0xbf32c8c9,0x3f3085bb,0xbf396842,0x3f299415,0xbf3fc767,
0x3f45e403,0xbf226799,0x3f3ebc1b,0xbf2ac082,0x3f373a23,0xbf32c8c9,0x3f2f61a5,0xbf3a7ca4,0x3f273656,0xbf41d870,0x3f1ebc12,0xbf48d8b3,0x3f15f6d9,0xbf4f7a1f,0x3f0cead0,0xbf55b993,
0x3f3504f3,0xbf3504f3,0x3f2beb4a,0xbf3daef9,0x3f226799,0xbf45e403,0x3f187fc0,0xbf4d9f02,0x3f0e39da,0xbf54db31,0x3f039c3d,0xbf5b941a,0x3ef15aea,0xbf61c598,0x3edae880,0xbf676bd8,
0x3f226799,0xbf45e403,0x3f173c07,0xbf4e8d90,0x3f0b9a6b,0xbf5695e5,0x3eff17b2,0xbf5df6be,0x3ee63375,0xbf64aa59,0x3ecc9b8b,0xbf6aab7b,0x3eb263ef,0xbf6ff573,0x3e97a117,0xbf748422,
0x3f0e39da,0xbf54db31,0x3f00e7e4,0xbf5d2d53,0x3ee63375,0xbf64aa59,0x3ec9b953,0xbf6b4b0c,0x3eac7cd4,0xbf710908,0x3e8e9a22,0xbf75dec6,0x3e605c13,0xbf79c79d,0x3e22abb6,0xbf7cbfc9,
0x3ef15aea,0xbf61c598,0x3ed25a09,0xbf696591,0x3eb263ef,0xbf6ff573,0x3e919ddd,0xbf756d97,0x3e605c13,0xbf79c79d,0x3e1c76de,0xbf7cfe73,0x3dafb680,0xbf7f0e58,0x3c96c9b6,0xbf7ff4e6,
0x3ec3ef15,0xbf6c835e,0x3ea09ae5,0xbf731447,0x3e78cfcc,0xbf7853f8,0x3e2f10a2,0xbf7c3b28,0x3dc8bd36,0xbf7ec46d,0x3cc90ab0,0xbf7fec43,0xbd48fb30,0xbf7fb10f,0xbdfab273,0xbf7e1324,
0x3e94a031,0xbf74fa0b,0x3e5a3997,0xbf7a1e84,0x3e09cf86,0xbf7dabcc,0x3d621469,0xbf7f9c18,0xbcc90ab0,0xbf7fec43,0xbdd53db9,0xbf7e9bc9,0xbe3b6ecf,0xbf7baccd,0xbe8586ce,0xbf772417,
0x3e47c5c2,0xbf7b14be,0x3de1bc2e,0xbf7e70b0,0x3cc90ab0,0xbf7fec43,0xbd7b2b74,0xbf7f84ab,0xbe164083,0xbf7d3aac,0xbe6c9a7f,0xbf791298,0xbea09ae5,0xbf731447,0xbec9b953,0xbf6b4b0c,
0x3dc8bd36,0xbf7ec46d,0x3bc90f88,0xbf7ffec4,0xbdafb680,0xbf7f0e58,0xbe354098,0xbf7bf531,0xbe888e93,0xbf76ba07,0xbeb554ec,0xbf6f6830,0xbee0924f,0xbf660f88,0xbf04f484,0xbf5ac450,
0x0,0xbf800000,0xbdc8bd36,0xbf7ec46d,0xbe47c5c2,0xbf7b14be,0xbe94a031,0xbf74fa0b,0xbec3ef15,0xbf6c835e,0xbef15aea,0xbf61c598,0xbf0e39da,0xbf54db31,0xbf226799,0xbf45e403,
0xbdc8bd36,0xbf7ec46d,0xbe4dee60,0xbf7ac516,0xbe9aa086,0xbf740bdd,0xbecc9b8b,0xbf6aab7b,0xbefc5d27,0xbf5ebe05,0xbf14b039,0xbf5064af,0xbf299415,0xbf3fc767,0xbf3ca003,0xbf2d1469,
0xbe47c5c2,0xbf7b14be,0xbe9aa086,0xbf740bdd,0xbecf7bca,0xbf6a09a7,0xbf00e7e4,0xbf5d2d53,0xbf187fc0,0xbf4d9f02,0xbf2e3bde,0xbf3b8f3b,0xbf41d870,0xbf273656,0xbf531849,0xbf10d3cd,
0xbe94a031,0xbf74fa0b,0xbecc9b8b,0xbf6aab7b,0xbf00e7e4,0xbf5d2d53,0xbf19c200,0xbf4cae79,0xbf3085bb,0xbf396842,0xbf44e3f5,0xbf239da9,0xbf5695e5,0xbf0b9a6b,0xbf655e0b,0xbee363fa,
0xbec3ef15,0xbf6c835e,0xbefc5d27,0xbf5ebe05,0xbf187fc0,0xbf4d9f02,0xbf3085bb,0xbf396842,0xbf45e403,0xbf226799,0xbf584853,0xbf08f59b,0xbf676bd8,0xbedae880,0xbf731447,0xbea09ae5,
0xbef15aea,0xbf61c598,0xbf14b039,0xbf5064af,0xbf2e3bde,0xbf3b8f3b,0xbf44e3f5,0xbf239da9,0xbf584853,0xbf08f59b,0xbf6816a8,0xbed8106b,0xbf740bdd,0xbe9aa086,0xbf7bf531,0xbe354098,
0xbf0e39da,0xbf54db31,0xbf299415,0xbf3fc767,0xbf41d870,0xbf273656,0xbf5695e5,0xbf0b9a6b,0xbf676bd8,0xbedae880,0xbf740bdd,0xbe9aa086,0xbf7c3b28,0xbe2f10a2,0xbf7fd397,0xbd16c32c,
0xbf226799,0xbf45e403,0xbf3ca003,0xbf2d1469,0xbf531849,0xbf10d3cd,0xbf655e0b,0xbee363fa,0xbf731447,0xbea09ae5,0xbf7bf531,0xbe354098,0xbf7fd397,0xbd16c32c,0xbf7e9bc9,0x3dd53db9,
0xbf3504f3,0xbf3504f3,0xbf4d9f02,0xbf187fc0,0xbf61c598,0xbef15aea,0xbf710908,0xbeac7cd4,0xbf7b14be,0xbe47c5c2,0xbf7fb10f,0xbd48fb30,0xbf7ec46d,0x3dc8bd36,0xbf7853f8,0x3e78cfcc,
0xbf45e403,0xbf226799,0xbf5c61c7,0xbf0242b1,0xbf6db293,0xbebe1d4a,0xbf796e4e,0xbe667c66,0xbf7f4e6d,0xbd96a905,0xbf7f2f9d,0x3da3308c,0xbf791298,0x3e6c9a7f,0xbf6d1c1d,0x3ec1071e,
0xbf54db31,0xbf0e39da,0xbf68bf3c,0xbed53641,0xbf76ba07,0xbe888e93,0xbf7e70b0,0xbde1bc2e,0xbf7fb10f,0x3d48fb30,0xbf7a7302,0x3e541501,0xbf6ed89e,0x3eb8442a,0xbf5d2d53,0x3f00e7e4,
0xbf61c598,0xbef15aea,0xbf7294f8,0xbea395c5,0xbf7cbfc9,0xbe22abb6,0xbf7ffec4,0x3bc90f88,0xbf7c3b28,0x3e2f10a2,0xbf718f57,0x3ea986c4,0xbf604621,0x3ef6e0cb,0xbf48d8b3,0x3f1ebc12,
0xbf6c835e,0xbec3ef15,0xbf79c79d,0xbe605c13,0xbf7fb10f,0xbd48fb30,0xbf7e1324,0x3dfab273,0xbf74fa0b,0x3e94a031,0xbf64aa59,0x3ee63375,0xbf4d9f02,0x3f187fc0,0xbf3085bb,0x3f396842,
0xbf74fa0b,0xbe94a031,0xbf7e4323,0xbdee3876,0xbf7f84ab,0x3d7b2b74,0xbf78b47b,0x3e72b651,0xbf6a09a7,0x3ecf7bca,0xbf53fac3,0x3f0f8784,0xbf373a23,0x3f32c8c9,0xbf14b039,0x3f5064af,
0xbf7b14be,0xbe47c5c2,0xbf7ffb11,0xbc490e90,0xbf7c3b28,0x3e2f10a2,0xbf6ff573,0x3eb263ef,0xbf5b941a,0x3f039c3d,0xbf3fc767,0x3f299415,0xbf1d7fd1,0x3f49d112,0xbeebcbbb,0x3f633c5a,
0xbf7ec46d,0xbdc8bd36,0xbf7eea9d,0x3dbc3ac3,0xbf75dec6,0x3e8e9a22,0xbf63f473,0x3ee900b7,0xbf49d112,0x3f1d7fd1,0xbf286605,0x3f40d0da,0xbf00e7e4,0x3f5d2d53,0xbea986c4,0x3f718f57,
0x3f800000,0x0,0x3f800000,0x0,0x3f800000,0x0,0x3f800000,0x0,0x3f800000,0x0,0x3f800000,0x0,0x3f800000,0x0,0x3f800000,0x0,
0x3f7d3aac,0xbe164083,0x3f7cfe73,0xbe1c76de,0x3f7cbfc9,0xbe22abb6,0x3f7c7eb0,0xbe28defc,0x3f7c3b28,0xbe2f10a2,0x3f7bf531,0xbe354098,0x3f7baccd,0xbe3b6ecf,0x3f7b61fc,0xbe419b37,
0x3f74fa0b,0xbe94a031,0x3f740bdd,0xbe9aa086,0x3f731447,0xbea09ae5,0x3f721352,0xbea68f12,0x3f710908,0xbeac7cd4,0x3f6ff573,0xbeb263ef,0x3f6ed89e,0xbeb8442a,0x3f6db293,0xbebe1d4a,
0x3f676bd8,0xbedae880,0x3f655e0b,0xbee363fa,0x3f633c5a,0xbeebcbbb,0x3f6106f2,0xbef41f07,0x3f5ebe05,0xbefc5d27,0x3f5c61c7,0xbf0242b1,0x3f59f26a,0xbf064b82,0x3f577026,0xbf0a48ad,
0x3f54db31,0xbf0e39da,0x3f514d3d,0xbf13682a,0x3f4d9f02,0xbf187fc0,0x3f49d112,0xbf1d7fd1,0x3f45e403,0xbf226799,0x3f41d870,0xbf273656,0x3f3daef9,0xbf2beb4a,0x3f396842,0xbf3085bb,
0x3f3daef9,0xbf2beb4a,0x3f385216,0xbf31a81d,0x3f32c8c9,0xbf373a23,0x3f2d1469,0xbf3ca003,0x3f273656,0xbf41d870,0x3f212ff9,0xbf46e22a,0x3f1b02c6,0xbf4bbbf8,0x3f14b039,0xbf5064af,
0x3f226799,0xbf45e403,0x3f1b02c6,0xbf4bbbf8,0x3f13682a,0xbf514d3d,0x3f0b9a6b,0xbf5695e5,0x3f039c3d,0xbf5b941a,0x3ef6e0cb,0xbf604621,0x3ee63375,0xbf64aa59,0x3ed53641,0xbf68bf3c,
0x3f039c3d,0xbf5b941a,0x3ef41f07,0xbf6106f2,0x3ee0924f,0xbf660f88,0x3ecc9b8b,0xbf6aab7b,0x3eb8442a,0xbf6ed89e,0x3ea395c5,0xbf7294f8,0x3e8e9a22,0xbf75dec6,0x3e72b651,0xbf78b47b,
0x3ec3ef15,0xbf6c835e,0x3eac7cd4,0xbf710908,0x3e94a031,0xbf74fa0b,0x3e78cfcc,0xbf7853f8,0x3e47c5c2,0xbf7b14be,0x3e164083,0xbf7d3aac,0x3dc8bd36,0xbf7ec46d,0x3d48fb30,0xbf7fb10f,
0x3e78cfcc,0xbf7853f8,0x3e419b37,0xbf7b61fc,0x3e09cf86,0xbf7dabcc,0x3da3308c,0xbf7f2f9d,0x3cc90ab0,0xbf7fec43,0xbcfb49ba,0xbf7fe129,0xbdafb680,0xbf7f0e58,0xbe1008b7,0xbf7d7474,
0x3dc8bd36,0xbf7ec46d,0x3d16c32c,0xbf7fd397,0xbcc90ab0,0xbf7fec43,0xbdafb680,0xbf7f0e58,0xbe164083,0xbf7d3aac,0xbe541501,0xbf7a7302,0xbe888e93,0xbf76ba07,0xbea68f12,0xbf721352,
0xbd48fb30,0xbf7fb10f,0xbdee3876,0xbf7e4323,0xbe3b6ecf,0xbf7baccd,0xbe7ee6e1,0xbf77f110,0xbea09ae5,0xbf731447,0xbec1071e,0xbf6d1c1d,0xbee0924f,0xbf660f88,0xbeff17b2,0xbf5df6be,
0xbe47c5c2,0xbf7b14be,0xbe888e93,0xbf76ba07,0xbeac7cd4,0xbf710908,0xbecf7bca,0xbf6a09a7,0xbef15aea,0xbf61c598,0xbf08f59b,0xbf584853,0xbf187fc0,0xbf4d9f02,0xbf273656,0xbf41d870,
0xbeac7cd4,0xbf710908,0xbed25a09,0xbf696591,0xbef6e0cb,0xbf604621,0xbf0cead0,0xbf55b993,0xbf1d7fd1,0xbf49d112,0xbf2d1469,0xbf3ca003,0xbf3b8f3b,0xbf2e3bde,0xbf48d8b3,0xbf1ebc12,
0xbef15aea,0xbf61c598,0xbf0b9a6b,0xbf5695e5,0xbf1d7fd1,0xbf49d112,0xbf2e3bde,0xbf3b8f3b,0xbf3daef9,0xbf2beb4a,0xbf4bbbf8,0xbf1b02c6,0xbf584853,0xbf08f59b,0xbf633c5a,0xbeebcbbb,
0xbf187fc0,0xbf4d9f02,0xbf2ac082,0xbf3ebc1b,0xbf3b8f3b,0xbf2e3bde,0xbf4ac77f,0xbf1c420c,0xbf584853,0xbf08f59b,0xbf63f473,0xbee900b7,0xbf6db293,0xbebe1d4a,0xbf756d97,0xbe919ddd,
0xbf3504f3,0xbf3504f3,0xbf45e403,0xbf226799,0xbf54db31,0xbf0e39da,0xbf61c598,0xbef15aea,0xbf6c835e,0xbec3ef15,0xbf74fa0b,0xbe94a031,0xbf7b14be,0xbe47c5c2,0xbf7ec46d,0xbdc8bd36,
0xbf4d9f02,0xbf187fc0,0xbf5c61c7,0xbf0242b1,0xbf68bf3c,0xbed53641,0xbf7294f8,0xbea395c5,0xbf79c79d,0xbe605c13,0xbf7e4323,0xbdee3876,0xbf7ffb11,0xbc490e90,0xbf7eea9d,0x3dbc3ac3,
0xbf61c598,0xbef15aea,0xbf6db293,0xbebe1d4a,0xbf76ba07,0xbe888e93,0xbf7cbfc9,0xbe22abb6,0xbf7fb10f,0xbd48fb30,0xbf7f84ab,0x3d7b2b74,0xbf7c3b28,0x3e2f10a2,0xbf75dec6,0x3e8e9a22,
0xbf710908,0xbeac7cd4,0xbf796e4e,0xbe667c66,0xbf7e70b0,0xbde1bc2e,0xbf7ffec4,0x3bc90f88,0xbf7e1324,0x3dfab273,0xbf78b47b,0x3e72b651,0xbf6ff573,0x3eb263ef,0xbf63f473,0x3ee900b7,
0xbf7b14be,0xbe47c5c2,0xbf7f4e6d,0xbd96a905,0xbf7fb10f,0x3d48fb30,0xbf7c3b28,0x3e2f10a2,0xbf74fa0b,0x3e94a031,0xbf6a09a7,0x3ecf7bca,0xbf5b941a,0x3f039c3d,0xbf49d112,0x3f1d7fd1,
0xbf7fb10f,0xbd48fb30,0xbf7f2f9d,0x3da3308c,0xbf7a7302,0x3e541501,0xbf718f57,0x3ea986c4,0xbf64aa59,0x3ee63375,0xbf53fac3,0x3f0f8784,0xbf3fc767,0x3f299415,0xbf286605,0x3f40d0da,
0xbf7ec46d,0x3dc8bd36,0xbf791298,0x3e6c9a7f,0xbf6ed89e,0x3eb8442a,0xbf604621,0x3ef6e0cb,0xbf4d9f02,0x3f187fc0,0xbf373a23,0x3f32c8c9,0xbf1d7fd1,0x3f49d112,0xbf00e7e4,0x3f5d2d53,
0xbf7853f8,0x3e78cfcc,0xbf6d1c1d,0x3ec1071e,0xbf5d2d53,0x3f00e7e4,0xbf48d8b3,0x3f1ebc12,0xbf3085bb,0x3f396842,0xbf14b039,0x3f5064af,0xbeebcbbb,0x3f633c5a,0xbea986c4,0x3f718f57,
0xbf6c835e,0x3ec3ef15,0xbf5b941a,0x3f039c3d,0xbf45e403,0x3f226799,0xbf2beb4a,0x3f3daef9,0xbf0e39da,0x3f54db31,0xbedae880,0x3f676bd8,0xbe94a031,0x3f74fa0b,0xbe164083,0x3f7d3aac,
0xbf5b941a,0x3f039c3d,0xbf44e3f5,0x3f239da9,0xbf299415,0x3f3fc767,0xbf0a48ad,0x3f577026,0xbecf7bca,0x3f6a09a7,0xbe8586ce,0x3f772417,0xbde1bc2e,0x3f7e70b0,0x3d2fe007,0x3f7fc38f,
0xbf45e403,0x3f226799,0xbf299415,0x3f3fc767,0xbf08f59b,0x3f584853,0xbec9b953,0x3f6b4b0c,0xbe78cfcc,0x3f7853f8,0xbdafb680,0x3f7f0e58,0x3d96a905,0x3f7f4e6d,0x3e6c9a7f,0x3f791298,
0xbf2beb4a,0x3f3daef9,0xbf0a48ad,0x3f577026,0xbec9b953,0x3f6b4b0c,0xbe72b651,0x3f78b47b,0xbd96a905,0x3f7f4e6d,0x3dbc3ac3,0x3f7eea9d,0x3e827dc0,0x3f778bc5,0x3ed25a09,0x3f696591,
0xbf0e39da,0x3f54db31,0xbecf7bca,0x3f6a09a7,0xbe78cfcc,0x3f7853f8,0xbd96a905,0x3f7f4e6d,0x3dc8bd36,0x3f7ec46d,0x3e888e93,0x3f76ba07,0x3edae880,0x3f676bd8,0x3f13682a,0x3f514d3d,
0xbedae880,0x3f676bd8,0xbe8586ce,0x3f772417,0xbdafb680,0x3f7f0e58,0x3dbc3ac3,0x3f7eea9d,0x3e888e93,0x3f76ba07,0x3eddbe79,0x3f66becc,0x3f15f6d9,0x3f4f7a1f,0x3f385216,0x3f31a81d,
0xbe94a031,0x3f74fa0b,0xbde1bc2e,0x3f7e70b0,0x3d96a905,0x3f7f4e6d,0x3e827dc0,0x3f778bc5,0x3edae880,0x3f676bd8,0x3f15f6d9,0x3f4f7a1f,0x3f396842,0x3f3085bb,0x3f5695e5,0x3f0b9a6b,
0xbe164083,0x3f7d3aac,0x3d2fe007,0x3f7fc38f,0x3e6c9a7f,0x3f791298,0x3ed25a09,0x3f696591,0x3f13682a,0x3f514d3d,0x3f385216,0x3f31a81d,0x3f5695e5,0x3f0b9a6b,0x3f6d1c1d,0x3ec1071e,
0xbd803d80,0x80003e00,0x80003e00,0x80003e00,0x80003e00,0x80003e00,0x80003e00,0x80003e00,0x80003e00,0x80003e00,0x80003e00,0x80003e00,0x80003e00,0x80003e00,0x80003e00,0x80003e00,
0x3d803d80,0x3cc83dfb,0x3e000000,0x3dfbbcc8,0x3d443ded,0x3d8e3dd5,0x3dedbd44,0x3dd5bd8e,0x3db53db5,0x3dd53d8e,0x3db5bdb5,0x3d8ebdd5,0x3ded3d44,0x3dfb3cc8,0x3d44bded,0x3cc8bdfb,
0xbd803d80,0x3d443ded,0x8000be00,0xbd44bded,0x3db53db5,0x3ded3d44,0xbdb5bdb5,0xbdedbd44,0x3e000000,0x3dedbd44,0xbe000000,0xbded3d44,0x3db5bdb5,0x3d44bded,0xbdb53db5,0xbd443ded,
0x3d803d80,0x3d8e3dd5,0xbe000000,0xbdd53d8e,0x3ded3d44,0x3dfbbcc8,0xbd443ded,0x3cc83dfb,0x3db5bdb5,0x3cc8bdfb,0x3db53db5,0x3dfb3cc8,0xbd44bded,0xbdd5bd8e,0x3dedbd44,0x3d8ebdd5,
0xbd803d80,0x3db53db5,0x80003e00,0x3db53db5,0x3e000000,0x3db5bdb5,0x3e000000,0x3db5bdb5,0x8000be00,0xbdb5bdb5,0x8000be00,0xbdb5bdb5,0xbe000000,0xbdb53db5,0xbe000000,0xbdb53db5,
0x3d803d80,0x3dd53d8e,0x3e000000,0x3d8ebdd5,0x3dedbd44,0x3cc8bdfb,0xbd44bded,0xbdfbbcc8,0xbdb5bdb5,0xbdfb3cc8,0xbdb53db5,0x3cc83dfb,0xbd443ded,0x3d8e3dd5,0x3ded3d44,0x3dd5bd8e,
0xbd803d80,0x3ded3d44,0x8000be00,0xbdedbd44,0x3db5bdb5,0xbd44bded,0xbdb53db5,0x3d443ded,0xbe000000,0xbd443ded,0x3e000000,0x3d44bded,0x3db53db5,0x3dedbd44,0xbdb5bdb5,0xbded3d44,
0x3d803d80,0x3dfb3cc8,0xbe000000,0xbcc83dfb,0x3d44bded,0xbdd5bd8e,0x3ded3d44,0x3d8ebdd5,0xbdb53db5,0x3d8e3dd5,0xbdb5bdb5,0xbdd53d8e,0x3dedbd44,0xbcc8bdfb,0x3d443ded,0x3dfbbcc8,
0xbd803d80,0x3e000000,0x80003e00,0x3e000000,0x8000be00,0xbe000000,0x8000be00,0xbe000000,0x80003e00,0x3e000000,0x80003e00,0x3e000000,0x8000be00,0xbe000000,0x8000be00,0xbe000000,
0x3d803d80,0x3dfbbcc8,0x3e000000,0xbcc8bdfb,0xbd44bded,0xbdd53d8e,0xbded3d44,0x3d8e3dd5,0x3db53db5,0x3d8ebdd5,0x3db5bdb5,0xbdd5bd8e,0xbdedbd44,0xbcc83dfb,0xbd443ded,0x3dfb3cc8,
0xbd803d80,0x3dedbd44,0x8000be00,0xbded3d44,0xbdb5bdb5,0xbd443ded,0x3db53db5,0x3d44bded,0x3e000000,0xbd44bded,0xbe000000,0x3d443ded,0xbdb53db5,0x3ded3d44,0x3db5bdb5,0xbdedbd44,
0x3d803d80,0x3dd5bd8e,0xbe000000,0x3d8e3dd5,0xbdedbd44,0x3cc83dfb,0x3d44bded,0xbdfb3cc8,0x3db5bdb5,0xbdfbbcc8,0x3db53db5,0x3cc8bdfb,0x3d443ded,0x3d8ebdd5,0xbded3d44,0x3dd53d8e,
0xbd803d80,0x3db5bdb5,0x80003e00,0x3db5bdb5,0xbe000000,0x3db53db5,0xbe000000,0x3db53db5,0x8000be00,0xbdb53db5,0x8000be00,0xbdb53db5,0x3e000000,0xbdb5bdb5,0x3e000000,0xbdb5bdb5,
0x3d803d80,0x3d8ebdd5,0x3e000000,0xbdd5bd8e,0xbded3d44,0x3dfb3cc8,0x3d443ded,0x3cc8bdfb,0xbdb5bdb5,0x3cc83dfb,0xbdb53db5,0x3dfbbcc8,0x3d44bded,0xbdd53d8e,0xbdedbd44,0x3d8e3dd5,
0xbd803d80,0x3d44bded,0x8000be00,0xbd443ded,0xbdb53db5,0x3dedbd44,0x3db5bdb5,0xbded3d44,0xbe000000,0x3ded3d44,0x3e000000,0xbdedbd44,0xbdb5bdb5,0x3d443ded,0x3db53db5,0xbd44bded,
0x3d803d80,0x3cc8bdfb,0xbe000000,0x3dfb3cc8,0xbd443ded,0x3d8ebdd5,0xbdedbd44,0x3dd53d8e,0xbdb53db5,0x3dd5bd8e,0xbdb5bdb5,0x3d8e3dd5,0xbded3d44,0x3dfbbcc8,0xbd44bded,0x3cc83dfb,
0xbd803d80,0x8000be00,0x80003e00,0x8000be00,0x80003e00,0x8000be00,0x80003e00,0x8000be00,0x80003e00,0x8000be00,0x80003e00,0x8000be00,0x80003e00,0x8000be00,0x80003e00,0x8000be00,
0x3d803d80,0xbcc8bdfb,0x3e000000,0xbdfb3cc8,0x3d443ded,0xbd8ebdd5,0x3dedbd44,0xbdd53d8e,0x3db53db5,0xbdd5bd8e,0x3db5bdb5,0xbd8e3dd5,0x3ded3d44,0xbdfbbcc8,0x3d44bded,0xbcc83dfb,
0xbd803d80,0xbd44bded,0x8000be00,0x3d443ded,0x3db53db5,0xbdedbd44,0xbdb5bdb5,0x3ded3d44,0x3e000000,0xbded3d44,0xbe000000,0x3dedbd44,0x3db5bdb5,0xbd443ded,0xbdb53db5,0x3d44bded,
0x3d803d80,0xbd8ebdd5,0xbe000000,0x3dd5bd8e,0x3ded3d44,0xbdfb3cc8,0xbd443ded,0xbcc8bdfb,0x3db5bdb5,0xbcc83dfb,0x3db53db5,0xbdfbbcc8,0xbd44bded,0x3dd53d8e,0x3dedbd44,0xbd8e3dd5,
0xbd803d80,0xbdb5bdb5,0x80003e00,0xbdb5bdb5,0x3e000000,0xbdb53db5,0x3e000000,0xbdb53db5,0x8000be00,0x3db53db5,0x8000be00,0x3db53db5,0xbe000000,0x3db5bdb5,0xbe000000,0x3db5bdb5,
0x3d803d80,0xbdd5bd8e,0x3e000000,0xbd8e3dd5,0x3dedbd44,0xbcc83dfb,0xbd44bded,0x3dfb3cc8,0xbdb5bdb5,0x3dfbbcc8,0xbdb53db5,0xbcc8bdfb,0xbd443ded,0xbd8ebdd5,0x3ded3d44,0xbdd53d8e,
0xbd803d80,0xbdedbd44,0x8000be00,0x3ded3d44,0x3db5bdb5,0x3d443ded,0xbdb53db5,0xbd44bded,0xbe000000,0x3d44bded,0x3e000000,0xbd443ded,0x3db53db5,0xbded3d44,0xbdb5bdb5,0x3dedbd44,
0x3d803d80,0xbdfbbcc8,0xbe000000,0x3cc8bdfb,0x3d44bded,0x3dd53d8e,0x3ded3d44,0xbd8e3dd5,0xbdb53db5,0xbd8ebdd5,0xbdb5bdb5,0x3dd5bd8e,0x3dedbd44,0x3cc83dfb,0x3d443ded,0xbdfb3cc8,
0xbd803d80,0xbe000000,0x80003e00,0xbe000000,0x8000be00,0x3e000000,0x8000be00,0x3e000000,0x80003e00,0xbe000000,0x80003e00,0xbe000000,0x8000be00,0x3e000000,0x8000be00,0x3e000000,
0x3d803d80,0xbdfb3cc8,0x3e000000,0x3cc83dfb,0xbd44bded,0x3dd5bd8e,0xbded3d44,0xbd8ebdd5,0x3db53db5,0xbd8e3dd5,0x3db5bdb5,0x3dd53d8e,0xbdedbd44,0x3cc8bdfb,0xbd443ded,0xbdfbbcc8,
0xbd803d80,0xbded3d44,0x8000be00,0x3dedbd44,0xbdb5bdb5,0x3d44bded,0x3db53db5,0xbd443ded,0x3e000000,0x3d443ded,0xbe000000,0xbd44bded,0xbdb53db5,0xbdedbd44,0x3db5bdb5,0x3ded3d44,
0x3d803d80,0xbdd53d8e,0xbe000000,0xbd8ebdd5,0xbdedbd44,0xbcc8bdfb,0x3d44bded,0x3dfbbcc8,0x3db5bdb5,0x3dfb3cc8,0x3db53db5,0xbcc83dfb,0x3d443ded,0xbd8e3dd5,0xbded3d44,0xbdd5bd8e,
0xbd803d80,0xbdb53db5,0x80003e00,0xbdb53db5,0xbe000000,0xbdb5bdb5,0xbe000000,0xbdb5bdb5,0x8000be00,0x3db5bdb5,0x8000be00,0x3db5bdb5,0x3e000000,0x3db53db5,0x3e000000,0x3db53db5,
0x3d803d80,0xbd8e3dd5,0x3e000000,0x3dd53d8e,0xbded3d44,0xbdfbbcc8,0x3d443ded,0xbcc83dfb,0xbdb5bdb5,0xbcc8bdfb,0xbdb53db5,0xbdfb3cc8,0x3d44bded,0x3dd5bd8e,0xbdedbd44,0xbd8ebdd5,
0xbd803d80,0xbd443ded,0x8000be00,0x3d44bded,0xbdb53db5,0xbded3d44,0x3db5bdb5,0x3dedbd44,0xbe000000,0xbdedbd44,0x3e000000,0x3ded3d44,0xbdb5bdb5,0xbd44bded,0x3db53db5,0x3d443ded,
0x3d803d80,0xbcc83dfb,0xbe000000,0xbdfbbcc8,0xbd443ded,0xbd8e3dd5,0xbdedbd44,0xbdd5bd8e,0xbdb53db5,0xbdd53d8e,0xbdb5bdb5,0xbd8ebdd5,0xbded3d44,0xbdfb3cc8,0xbd44bded,0xbcc8bdfb,
0x80003e00,0x80003e00,0x80003e00,0x80003e00,0x80003e00,0x80003e00,0x80003e00,0x80003e00,0x80003e00,0x80003e00,0x80003e00,0x80003e00,0x80003e00,0x80003e00,0x80003e00,0x80003e00,
0x3c493dff,0x3d153df5,0x3dffbc49,0x3df5bd15,0x3d713de2,0x3da23dc6,0x3de2bd71,0x3dc6bda2,0x3dc63da2,0x3de23d71,0x3da2bdc6,0x3d71bde2,0x3df53d15,0x3dff3c49,0x3d15bdf5,0x3c49bdff,
0x3cc83dfb,0x3d8e3dd5,0xbcc8bdfb,0xbd8ebdd5,0x3dd53d8e,0x3dfb3cc8,0xbdd5bd8e,0xbdfbbcc8,0x3dfbbcc8,0x3dd5bd8e,0xbdfb3cc8,0xbdd53d8e,0x3d8ebdd5,0x3cc8bdfb,0xbd8e3dd5,0xbcc83dfb,
0x3d153df5,0x3dc63da2,0xbdf53d15,0xbda23dc6,0x3dff3c49,0x3de2bd71,0xbc493dff,0x3d713de2,0x3d71bde2,0xbc49bdff,0x3de23d71,0x3dffbc49,0xbda2bdc6,0xbdf5bd15,0x3dc6bda2,0x3d15bdf5,
0x3d443ded,0x3ded3d44,0x3d443ded,0x3ded3d44,0x3dedbd44,0x3d44bded,0x3dedbd44,0x3d44bded,0xbd44bded,0xbdedbd44,0xbd44bded,0xbdedbd44,0xbded3d44,0xbd443ded,0xbded3d44,0xbd443ded,
0x3d713de2,0x3dff3c49,0x3de2bd71,0x3c49bdff,0x3da2bdc6,0xbd15bdf5,0xbdc6bda2,0xbdf53d15,0xbdf5bd15,0xbdc63da2,0xbd153df5,0x3da23dc6,0x3c493dff,0x3de23d71,0x3dffbc49,0x3d71bde2,
0x3d8e3dd5,0x3dfbbcc8,0xbd8ebdd5,0xbdfb3cc8,0x3cc8bdfb,0xbdd5bd8e,0xbcc83dfb,0x3dd53d8e,0xbdd53d8e,0x3cc83dfb,0x3dd5bd8e,0xbcc8bdfb,0x3dfb3cc8,0x3d8ebdd5,0xbdfbbcc8,0xbd8e3dd5,
0x3da23dc6,0x3de2bd71,0xbdc63da2,0x3d713de2,0xbd15bdf5,0xbdff3c49,0x3df5bd15,0xbc49bdff,0xbc493dff,0x3df53d15,0xbdffbc49,0xbd153df5,0x3d71bde2,0xbdc6bda2,0x3de23d71,0x3da2bdc6,
0x3db53db5,0x3db5bdb5,0x3db53db5,0x3db5bdb5,0xbdb5bdb5,0xbdb53db5,0xbdb5bdb5,0xbdb53db5,0x3db53db5,0x3db5bdb5,0x3db53db5,0x3db5bdb5,0xbdb5bdb5,0xbdb53db5,0xbdb5bdb5,0xbdb53db5,
0x3dc63da2,0x3d71bde2,0x3da2bdc6,0xbde2bd71,0xbdf5bd15,0xbc493dff,0xbd153df5,0x3dff3c49,0x3dffbc49,0xbd15bdf5,0xbc49bdff,0xbdf53d15,0xbde23d71,0x3da23dc6,0x3d713de2,0x3dc6bda2,
0x3dd53d8e,0x3cc8bdfb,0xbdd5bd8e,0xbcc83dfb,0xbdfb3cc8,0x3d8e3dd5,0x3dfbbcc8,0xbd8ebdd5,0x3d8ebdd5,0xbdfbbcc8,0xbd8e3dd5,0x3dfb3cc8,0x3cc83dfb,0x3dd5bd8e,0xbcc8bdfb,0xbdd53d8e,
0x3de23d71,0xbc49bdff,0xbd713de2,0x3dffbc49,0xbdc63da2,0x3df53d15,0xbda2bdc6,0xbd153df5,0xbd15bdf5,0xbda23dc6,0x3df5bd15,0xbdc6bda2,0x3dff3c49,0xbd71bde2,0xbc493dff,0x3de2bd71,
0x3ded3d44,0xbd44bded,0x3ded3d44,0xbd44bded,0xbd443ded,0x3dedbd44,0xbd443ded,0x3dedbd44,0xbdedbd44,0x3d443ded,0xbdedbd44,0x3d443ded,0x3d44bded,0xbded3d44,0x3d44bded,0xbded3d44,
0x3df53d15,0xbda2bdc6,0x3d15bdf5,0xbdc63da2,0x3c493dff,0x3d71bde2,0x3dffbc49,0xbde2bd71,0xbde23d71,0x3dff3c49,0x3d713de2,0x3c49bdff,0xbdc6bda2,0x3d153df5,0xbda23dc6,0x3df5bd15,
0x3dfb3cc8,0xbdd5bd8e,0xbdfbbcc8,0x3dd53d8e,0x3d8e3dd5,0xbcc8bdfb,0xbd8ebdd5,0x3cc83dfb,0xbcc83dfb,0x3d8ebdd5,0x3cc8bdfb,0xbd8e3dd5,0xbdd53d8e,0x3dfbbcc8,0x3dd5bd8e,0xbdfb3cc8,
0x3dff3c49,0xbdf5bd15,0xbc493dff,0x3d15bdf5,0x3de23d71,0xbdc6bda2,0xbd713de2,0x3da2bdc6,0x3da23dc6,0xbd71bde2,0xbdc63da2,0x3de2bd71,0x3d153df5,0xbc49bdff,0xbdf53d15,0x3dffbc49,
0x3e000000,0xbe000000,0x3e000000,0xbe000000,0x3e000000,0xbe000000,0x3e000000,0xbe000000,0x3e000000,0xbe000000,0x3e000000,0xbe000000,0x3e000000,0xbe000000,0x3e000000,0xbe000000,
0x3dffbc49,0xbdf53d15,0xbc49bdff,0x3d153df5,0x3de2bd71,0xbdc63da2,0xbd71bde2,0x3da23dc6,0x3da2bdc6,0xbd713de2,0xbdc6bda2,0x3de23d71,0x3d15bdf5,0xbc493dff,0xbdf5bd15,0x3dff3c49,
0x3dfbbcc8,0xbdd53d8e,0xbdfb3cc8,0x3dd5bd8e,0x3d8ebdd5,0xbcc83dfb,0xbd8e3dd5,0x3cc8bdfb,0xbcc8bdfb,0x3d8e3dd5,0x3cc83dfb,0xbd8ebdd5,0xbdd5bd8e,0x3dfb3cc8,0x3dd53d8e,0xbdfbbcc8,
0x3df5bd15,0xbda23dc6,0x3d153df5,0xbdc6bda2,0x3c49bdff,0x3d713de2,0x3dff3c49,0xbde23d71,0xbde2bd71,0x3dffbc49,0x3d71bde2,0x3c493dff,0xbdc63da2,0x3d15bdf5,0xbda2bdc6,0x3df53d15,
0x3dedbd44,0xbd443ded,0x3dedbd44,0xbd443ded,0xbd44bded,0x3ded3d44,0xbd44bded,0x3ded3d44,0xbded3d44,0x3d44bded,0xbded3d44,0x3d44bded,0x3d443ded,0xbdedbd44,0x3d443ded,0xbdedbd44,
0x3de2bd71,0xbc493dff,0xbd71bde2,0x3dff3c49,0xbdc6bda2,0x3df5bd15,0xbda23dc6,0xbd15bdf5,0xbd153df5,0xbda2bdc6,0x3df53d15,0xbdc63da2,0x3dffbc49,0xbd713de2,0xbc49bdff,0x3de23d71,
0x3dd5bd8e,0x3cc83dfb,0xbdd53d8e,0xbcc8bdfb,0xbdfbbcc8,0x3d8ebdd5,0x3dfb3cc8,0xbd8e3dd5,0x3d8e3dd5,0xbdfb3cc8,0xbd8ebdd5,0x3dfbbcc8,0x3cc8bdfb,0x3dd53d8e,0xbcc83dfb,0xbdd5bd8e,
0x3dc6bda2,0x3d713de2,0x3da23dc6,0xbde23d71,0xbdf53d15,0xbc49bdff,0xbd15bdf5,0x3dffbc49,0x3dff3c49,0xbd153df5,0xbc493dff,0xbdf5bd15,0xbde2bd71,0x3da2bdc6,0x3d71bde2,0x3dc63da2,
0x3db5bdb5,0x3db53db5,0x3db5bdb5,0x3db53db5,0xbdb53db5,0xbdb5bdb5,0xbdb53db5,0xbdb5bdb5,0x3db5bdb5,0x3db53db5,0x3db5bdb5,0x3db53db5,0xbdb53db5,0xbdb5bdb5,0xbdb53db5,0xbdb5bdb5,
0x3da2bdc6,0x3de23d71,0xbdc6bda2,0x3d71bde2,0xbd153df5,0xbdffbc49,0x3df53d15,0xbc493dff,0xbc49bdff,0x3df5bd15,0xbdff3c49,0xbd15bdf5,0x3d713de2,0xbdc63da2,0x3de2bd71,0x3da23dc6,
0x3d8ebdd5,0x3dfb3cc8,0xbd8e3dd5,0xbdfbbcc8,0x3cc83dfb,0xbdd53d8e,0xbcc8bdfb,0x3dd5bd8e,0xbdd5bd8e,0x3cc8bdfb,0x3dd53d8e,0xbcc83dfb,0x3dfbbcc8,0x3d8e3dd5,0xbdfb3cc8,0xbd8ebdd5,
0x3d71bde2,0x3dffbc49,0x3de23d71,0x3c493dff,0x3da23dc6,0xbd153df5,0xbdc63da2,0xbdf5bd15,0xbdf53d15,0xbdc6bda2,0xbd15bdf5,0x3da2bdc6,0x3c49bdff,0x3de2bd71,0x3dff3c49,0x3d713de2,
0x3d44bded,0x3dedbd44,0x3d44bded,0x3dedbd44,0x3ded3d44,0x3d443ded,0x3ded3d44,0x3d443ded,0xbd443ded,0xbded3d44,0xbd443ded,0xbded3d44,0xbdedbd44,0xbd44bded,0xbdedbd44,0xbd44bded,
0x3d15bdf5,0x3dc6bda2,0xbdf5bd15,0xbda2bdc6,0x3dffbc49,0x3de23d71,0xbc49bdff,0x3d71bde2,0x3d713de2,0xbc493dff,0x3de2bd71,0x3dff3c49,0xbda23dc6,0xbdf53d15,0x3dc63da2,0x3d153df5,
0x3cc8bdfb,0x3d8ebdd5,0xbcc83dfb,0xbd8e3dd5,0x3dd5bd8e,0x3dfbbcc8,0xbdd53d8e,0xbdfb3cc8,0x3dfb3cc8,0x3dd53d8e,0xbdfbbcc8,0xbdd5bd8e,0x3d8e3dd5,0x3cc83dfb,0xbd8ebdd5,0xbcc8bdfb,
0x3c49bdff,0x3d15bdf5,0x3dff3c49,0x3df53d15,0x3d71bde2,0x3da2bdc6,0x3de23d71,0x3dc63da2,0x3dc6bda2,0x3de2bd71,0x3da23dc6,0x3d713de2,0x3df5bd15,0x3dffbc49,0x3d153df5,0x3c493dff,
0x3f800000,0x0,0x3f800000,0x0,0x3f800000,0x0,0x3f800000,0x0,0x3f800000,0x0,0x3f800000,0x0,0x3f800000,0x0,0x3f800000,0x0,
0x3f800000,0x0,0x3f7ffb11,0xbc490e90,0x3f7fec43,0xbcc90ab0,0x3f7fd397,0xbd16c32c,0x3f7fb10f,0xbd48fb30,0x3f7f84ab,0xbd7b2b74,0x3f7f4e6d,0xbd96a905,0x3f7f0e58,0xbdafb680,
0x3f800000,0x0,0x3f7fec43,0xbcc90ab0,0x3f7fb10f,0xbd48fb30,0x3f7f4e6d,0xbd96a905,0x3f7ec46d,0xbdc8bd36,0x3f7e1324,0xbdfab273,0x3f7d3aac,0xbe164083,0x3f7c3b28,0xbe2f10a2,
0x3f800000,0x0,0x3f7fd397,0xbd16c32c,0x3f7f4e6d,0xbd96a905,0x3f7e70b0,0xbde1bc2e,0x3f7d3aac,0xbe164083,0x3f7baccd,0xbe3b6ecf,0x3f79c79d,0xbe605c13,0x3f778bc5,0xbe827dc0,
0x3f800000,0x0,0x3f7fb10f,0xbd48fb30,0x3f7ec46d,0xbdc8bd36,0x3f7d3aac,0xbe164083,0x3f7b14be,0xbe47c5c2,0x3f7853f8,0xbe78cfcc,0x3f74fa0b,0xbe94a031,0x3f710908,0xbeac7cd4,
0x3f800000,0x0,0x3f7f84ab,0xbd7b2b74,0x3f7e1324,0xbdfab273,0x3f7baccd,0xbe3b6ecf,0x3f7853f8,0xbe78cfcc,0x3f740bdd,0xbe9aa086,0x3f6ed89e,0xbeb8442a,0x3f68bf3c,0xbed53641,
0x3f800000,0x0,0x3f7f4e6d,0xbd96a905,0x3f7d3aac,0xbe164083,0x3f79c79d,0xbe605c13,0x3f74fa0b,0xbe94a031,0x3f6ed89e,0xbeb8442a,0x3f676bd8,0xbedae880,0x3f5ebe05,0xbefc5d27,
0x3f800000,0x0,0x3f7f0e58,0xbdafb680,0x3f7c3b28,0xbe2f10a2,0x3f778bc5,0xbe827dc0,0x3f710908,0xbeac7cd4,0x3f68bf3c,0xbed53641,0x3f5ebe05,0xbefc5d27,0x3f531849,0xbf10d3cd,
0x3f800000,0x0,0x3f7ec46d,0xbdc8bd36,0x3f7b14be,0xbe47c5c2,0x3f74fa0b,0xbe94a031,0x3f6c835e,0xbec3ef15,0x3f61c598,0xbef15aea,0x3f54db31,0xbf0e39da,0x3f45e403,0xbf226799,
0x3f800000,0x0,0x3f7e70b0,0xbde1bc2e,0x3f79c79d,0xbe605c13,0x3f721352,0xbea68f12,0x3f676bd8,0xbedae880,0x3f59f26a,0xbf064b82,0x3f49d112,0xbf1d7fd1,0x3f373a23,0xbf32c8c9,
0x3f800000,0x0,0x3f7e1324,0xbdfab273,0x3f7853f8,0xbe78cfcc,0x3f6ed89e,0xbeb8442a,0x3f61c598,0xbef15aea,0x3f514d3d,0xbf13682a,0x3f3daef9,0xbf2beb4a,0x3f273656,0xbf41d870,
0x3f800000,0x0,0x3f7dabcc,0xbe09cf86,0x3f76ba07,0xbe888e93,0x3f6b4b0c,0xbec9b953,0x3f5b941a,0xbf039c3d,0x3f47de65,0xbf1ff6cb,0x3f3085bb,0xbf396842,0x3f15f6d9,0xbf4f7a1f,
0x3f800000,0x0,0x3f7d3aac,0xbe164083,0x3f74fa0b,0xbe94a031,0x3f676bd8,0xbedae880,0x3f54db31,0xbf0e39da,0x3f3daef9,0xbf2beb4a,0x3f226799,0xbf45e403,0x3f039c3d,0xbf5b941a,
0x3f800000,0x0,0x3f7cbfc9,0xbe22abb6,0x3f731447,0xbea09ae5,0x3f633c5a,0xbeebcbbb,0x3f4d9f02,0xbf187fc0,0x3f32c8c9,0xbf373a23,0x3f13682a,0xbf514d3d,0x3ee0924f,0xbf660f88,
0x3f800000,0x0,0x3f7c3b28,0xbe2f10a2,0x3f710908,0xbeac7cd4,0x3f5ebe05,0xbefc5d27,0x3f45e403,0xbf226799,0x3f273656,0xbf41d870,0x3f039c3d,0xbf5b941a,0x3eb8442a,0xbf6ed89e,
0x3f800000,0x0,0x3f7baccd,0xbe3b6ecf,0x3f6ed89e,0xbeb8442a,0x3f59f26a,0xbf064b82,0x3f3daef9,0xbf2beb4a,0x3f1b02c6,0xbf4bbbf8,0x3ee63375,0xbf64aa59,0x3e8e9a22,0xbf75dec6,
0x3f800000,0x0,0x3f7b14be,0xbe47c5c2,0x3f6c835e,0xbec3ef15,0x3f54db31,0xbf0e39da,0x3f3504f3,0xbf3504f3,0x3f0e39da,0xbf54db31,0x3ec3ef15,0xbf6c835e,0x3e47c5c2,0xbf7b14be,
0x3f800000,0x0,0x3f7a7302,0xbe541501,0x3f6a09a7,0xbecf7bca,0x3f4f7a1f,0xbf15f6d9,0x3f2beb4a,0xbf3daef9,0x3f00e7e4,0xbf5d2d53,0x3ea09ae5,0xbf731447,0x3de1bc2e,0xbf7e70b0,
0x3f800000,0x0,0x3f79c79d,0xbe605c13,0x3f676bd8,0xbedae880,0x3f49d112,0xbf1d7fd1,0x3f226799,0xbf45e403,0x3ee63375,0xbf64aa59,0x3e78cfcc,0xbf7853f8,0x3cc90ab0,0xbf7fec43,
0x3f800000,0x0,0x3f791298,0xbe6c9a7f,0x3f64aa59,0xbee63375,0x3f43e200,0xbf24d225,0x3f187fc0,0xbf4d9f02,0x3ec9b953,0xbf6b4b0c,0x3e2f10a2,0xbf7c3b28,0xbd7b2b74,0xbf7f84ab,
0x3f800000,0x0,0x3f7853f8,0xbe78cfcc,0x3f61c598,0xbef15aea,0x3f3daef9,0xbf2beb4a,0x3f0e39da,0xbf54db31,0x3eac7cd4,0xbf710908,0x3dc8bd36,0xbf7ec46d,0xbe164083,0xbf7d3aac,
0x3f800000,0x0,0x3f778bc5,0xbe827dc0,0x3f5ebe05,0xbefc5d27,0x3f373a23,0xbf32c8c9,0x3f039c3d,0xbf5b941a,0x3e8e9a22,0xbf75dec6,0x3cc90ab0,0xbf7fec43,0xbe6c9a7f,0xbf791298,
0x3f800000,0x0,0x3f76ba07,0xbe888e93,0x3f5b941a,0xbf039c3d,0x3f3085bb,0xbf396842,0x3ef15aea,0xbf61c598,0x3e605c13,0xbf79c79d,0xbd48fb30,0xbf7fb10f,0xbea09ae5,0xbf731447,
0x3f800000,0x0,0x3f75dec6,0xbe8e9a22,0x3f584853,0xbf08f59b,0x3f299415,0xbf3fc767,0x3edae880,0xbf676bd8,0x3e22abb6,0xbf7cbfc9,0xbdfab273,0xbf7e1324,0xbec9b953,0xbf6b4b0c,
0x3f800000,0x0,0x3f74fa0b,0xbe94a031,0x3f54db31,0xbf0e39da,0x3f226799,0xbf45e403,0x3ec3ef15,0xbf6c835e,0x3dc8bd36,0xbf7ec46d,0xbe47c5c2,0xbf7b14be,0xbef15aea,0xbf61c598,
0x3f800000,0x0,0x3f740bdd,0xbe9aa086,0x3f514d3d,0xbf13682a,0x3f1b02c6,0xbf4bbbf8,0x3eac7cd4,0xbf710908,0x3d16c32c,0xbf7fd397,0xbe888e93,0xbf76ba07,0xbf0b9a6b,0xbf5695e5,
0x3f800000,0x0,0x3f731447,0xbea09ae5,0x3f4d9f02,0xbf187fc0,0x3f13682a,0xbf514d3d,0x3e94a031,0xbf74fa0b,0xbcc90ab0,0xbf7fec43,0xbeac7cd4,0xbf710908,0xbf1d7fd1,0xbf49d112,
0x3f800000,0x0,0x3f721352,0xbea68f12,0x3f49d112,0xbf1d7fd1,0x3f0b9a6b,0xbf5695e5,0x3e78cfcc,0xbf7853f8,0xbdafb680,0xbf7f0e58,0xbecf7bca,0xbf6a09a7,0xbf2e3bde,0xbf3b8f3b,
0x3f800000,0x0,0x3f710908,0xbeac7cd4,0x3f45e403,0xbf226799,0x3f039c3d,0xbf5b941a,0x3e47c5c2,0xbf7b14be,0xbe164083,0xbf7d3aac,0xbef15aea,0xbf61c598,0xbf3daef9,0xbf2beb4a,
0x3f800000,0x0,0x3f6ff573,0xbeb263ef,0x3f41d870,0xbf273656,0x3ef6e0cb,0xbf604621,0x3e164083,0xbf7d3aac,0xbe541501,0xbf7a7302,0xbf08f59b,0xbf584853,0xbf4bbbf8,0xbf1b02c6,
0x3f800000,0x0,0x3f6ed89e,0xbeb8442a,0x3f3daef9,0xbf2beb4a,0x3ee63375,0xbf64aa59,0x3dc8bd36,0xbf7ec46d,0xbe888e93,0xbf76ba07,0xbf187fc0,0xbf4d9f02,0xbf584853,0xbf08f59b,
0x3f800000,0x0,0x3f6db293,0xbebe1d4a,0x3f396842,0xbf3085bb,0x3ed53641,0xbf68bf3c,0x3d48fb30,0xbf7fb10f,0xbea68f12,0xbf721352,0xbf273656,0xbf41d870,0xbf633c5a,0xbeebcbbb,
0x3f800000,0x3f800000,0x3f800000,0x3f800000,0x3f800000,0x3f800000,0x3f800000,0x3f800000,0x3f800000,0xbf800000,0x3f800000,0xbf800000,0x3f800000,0xbf800000,0x3f800000,0xbf800000,
0x3f800000,0x3f3504f3,0x0,0xbf3504f3,0xbf800000,0xbf3504f3,0x0,0x3f3504f3,0x0,0xbf3504f3,0xbf800000,0xbf3504f3,0x0,0x3f3504f3,0x3f800000,0x3f3504f3,
0x3f800000,0x0,0xbf800000,0x0,0x3f800000,0x0,0xbf800000,0x0,0x0,0xbf800000,0x0,0x3f800000,0x0,0xbf800000,0x0,0x3f800000,
0x3f800000,0xbf3504f3,0x0,0x3f3504f3,0xbf800000,0x3f3504f3,0x0,0xbf3504f3,0x0,0xbf3504f3,0x3f800000,0xbf3504f3,0x0,0x3f3504f3,0xbf800000,0x3f3504f3,
0x3f800000,0x3f6c835e,0x3f3504f3,0x3ec3ef15,0x0,0xbec3ef15,0xbf3504f3,0xbf6c835e,0x0,0xbec3ef15,0xbf3504f3,0xbf6c835e,0xbf800000,0xbf6c835e,0xbf3504f3,0xbec3ef15,
0x3f800000,0x3ec3ef15,0xbf3504f3,0xbf6c835e,0x0,0x3f6c835e,0x3f3504f3,0xbec3ef15,0x0,0xbf6c835e,0xbf3504f3,0x3ec3ef15,0x3f800000,0x3ec3ef15,0xbf3504f3,0xbf6c835e,
0x3f800000,0xbec3ef15,0xbf3504f3,0x3f6c835e,0x0,0xbf6c835e,0x3f3504f3,0x3ec3ef15,0x0,0xbf6c835e,0x3f3504f3,0x3ec3ef15,0xbf800000,0x3ec3ef15,0x3f3504f3,0xbf6c835e,
0x3f800000,0xbf6c835e,0x3f3504f3,0xbec3ef15,0x0,0x3ec3ef15,0xbf3504f3,0x3f6c835e,0x0,0xbec3ef15,0x3f3504f3,0xbf6c835e,0x3f800000,0xbf6c835e,0x3f3504f3,0xbec3ef15,
};

struct Params {
    const __nv_bfloat16 *xb, *lre, *lim, *ldt, *dsk;
    float* out;
    int zero[8];
    uint64_t da[4];
    uint32_t unit[258];
};

struct Maps { CUtensorMap m[12]; };

struct cf { float x, y; };
__device__ __forceinline__ uint32_t smem_u32(const void* p) { return (uint32_t)__cvta_generic_to_shared(p); }
__device__ __forceinline__ void mbar_init(uint32_t a, uint32_t c) { asm volatile("mbarrier.init.shared::cta.b64 [%0], %1;" ::"r"(a), "r"(c) : "memory"); }
__device__ __forceinline__ void mbar_expect_tx(uint32_t a, uint32_t b) { asm volatile("mbarrier.arrive.expect_tx.shared::cta.b64 _, [%0], %1;" ::"r"(a), "r"(b) : "memory"); }
__device__ __forceinline__ void mbar_arrive(uint32_t a) { asm volatile("mbarrier.arrive.shared::cta.b64 _, [%0];" ::"r"(a) : "memory"); }
__device__ __forceinline__ void mbar_wait(uint32_t a, uint32_t ph) {
    asm volatile("{.reg .pred p; .reg .u32 n;\n"
                 "mov.u32 n, 0;\n"
                 "LOOP: mbarrier.try_wait.parity.shared::cta.b64 p, [%0], %1;\n"
                 "@p bra DONE;\n"
                 "add.u32 n, n, 1;\n"
                 "setp.lt.u32 p, n, %2;\n"
                 "@p bra LOOP;\n"
                 "DONE: }" ::"r"(a), "r"(ph), "n"(SPIN_LIMIT) : "memory");
}
__device__ __forceinline__ unsigned ld_rlx(const unsigned* p) { unsigned v; asm volatile("ld.relaxed.gpu.global.u32 %0, [%1];" : "=r"(v) : "l"(p) : "memory"); return v; }
__device__ __forceinline__ void wait_cnt(const unsigned* p, unsigned target) {
    unsigned n = 0;
    while ((int)(ld_rlx(p) - target) < 0 && ++n < SPIN_LIMIT) __nanosleep(20);
}
__device__ __forceinline__ void red_hint(unsigned* p) { asm volatile("red.relaxed.gpu.global.add.u32 [%0], 1;" ::"l"(p) : "memory"); }
__device__ __forceinline__ void fence_async() { asm volatile("fence.proxy.async.global;" ::: "memory"); }
__device__ __forceinline__ void fence_async_sm() { asm volatile("fence.proxy.async.shared::cta;" ::: "memory"); }
#define bar_sync(id, n) asm volatile("bar.sync %0, %1;" ::"n"(id), "n"(n) : "memory")
#define bar_arrive(id, n) asm volatile("bar.arrive %0, %1;" ::"n"(id), "n"(n) : "memory")
__device__ __forceinline__ bool elect_one() {
    uint32_t r;
    asm volatile("{.reg .pred p; elect.sync _|p, 0xffffffff; selp.u32 %0, 1, 0, p;}" : "=r"(r));
    return r != 0;
}

__device__ __forceinline__ void tma2d(uint32_t dst, const CUtensorMap* m, int c0, int c1, uint32_t bar) {
    asm volatile("cp.async.bulk.tensor.2d.shared::cluster.global.mbarrier::complete_tx::bytes [%0], [%1, {%3,%4}], [%2];" ::"r"(dst), "l"(m), "r"(bar), "r"(c0), "r"(c1) : "memory");
}
__device__ __forceinline__ void tma4d(uint32_t dst, const CUtensorMap* m, int c0, int c1, int c2, int c3, uint32_t bar) {
    asm volatile("cp.async.bulk.tensor.4d.shared::cluster.global.mbarrier::complete_tx::bytes [%0], [%1, {%3,%4,%5,%6}], [%2];" ::"r"(dst), "l"(m), "r"(bar), "r"(c0), "r"(c1), "r"(c2), "r"(c3) : "memory");
}
__device__ __forceinline__ void tma4d_mc(uint32_t dst, const CUtensorMap* m, int c0, int c3, uint32_t bar) {
    asm volatile("cp.async.bulk.tensor.4d.shared::cluster.global.mbarrier::complete_tx::bytes.multicast::cluster [%0], [%1, {%3,%6,%6,%4}], [%2], %5;" ::"r"(dst), "l"(m), "r"(bar), "r"(c0), "r"(c3), "h"((uint16_t)3), "r"(0) : "memory");
}
__device__ __forceinline__ void tma2d_st(const CUtensorMap* m, int c0, int c1, uint32_t src) {
    asm volatile("cp.async.bulk.tensor.2d.global.shared::cta.bulk_group [%0, {%2,%3}], [%1];" ::"l"(m), "r"(src), "r"(c0), "r"(c1) : "memory");
}
__device__ __forceinline__ void tma5d(uint32_t dst, const CUtensorMap* m, int c0, int c1, int c2, int c3, int c4, uint32_t bar) {
    asm volatile("cp.async.bulk.tensor.5d.shared::cluster.global.mbarrier::complete_tx::bytes [%0], [%1, {%3,%4,%5,%6,%7}], [%2];" ::"r"(dst), "l"(m), "r"(bar), "r"(c0), "r"(c1), "r"(c2), "r"(c3), "r"(c4) : "memory");
}
__device__ __forceinline__ void bulk_ld(uint32_t dst, const void* src, uint32_t n, uint32_t bar) {
    asm volatile("cp.async.bulk.shared::cluster.global.mbarrier::complete_tx::bytes [%0], [%1], %2, [%3];" ::"r"(dst), "l"(src), "r"(n), "r"(bar) : "memory");
}
__device__ __forceinline__ void pf_map(const CUtensorMap* m) { asm volatile("prefetch.tensormap [%0];" ::"l"(m) : "memory"); }
__device__ __forceinline__ void bulk_commit() { asm volatile("cp.async.bulk.commit_group;" ::: "memory"); }
template <int N> __device__ __forceinline__ void bulk_wait_read() { asm volatile("cp.async.bulk.wait_group.read %0;" ::"n"(N) : "memory"); }
__device__ __forceinline__ void stsm4(uint32_t a, uint32_t r0, uint32_t r1, uint32_t r2, uint32_t r3) {
    asm volatile("stmatrix.sync.aligned.m8n8.x4.shared.b16 [%0], {%1,%2,%3,%4};" ::"r"(a), "r"(r0), "r"(r1), "r"(r2), "r"(r3) : "memory");
}
__device__ __forceinline__ void sts128f(uint32_t a, cf u, cf v) {
    asm volatile("st.shared.v4.f32 [%0], {%1,%2,%3,%4};" ::"r"(a), "f"(u.x), "f"(u.y), "f"(v.x), "f"(v.y) : "memory");
}
__device__ __forceinline__ void stg128(const void* a, uint32_t r0, uint32_t r1, uint32_t r2, uint32_t r3) {
    asm volatile("st.global.v4.b32 [%0], {%1,%2,%3,%4};" ::"l"(a), "r"(r0), "r"(r1), "r"(r2), "r"(r3) : "memory");
}
__device__ __forceinline__ void lds128f(uint32_t a, float& x, float& y, float& z, float& u) { asm volatile("ld.shared.v4.f32 {%0,%1,%2,%3}, [%4];" : "=f"(x), "=f"(y), "=f"(z), "=f"(u) : "r"(a) : "memory"); }
__device__ __forceinline__ cf lds_cf(uint32_t a) { cf v; asm volatile("ld.shared.v2.f32 {%0,%1}, [%2];" : "=f"(v.x), "=f"(v.y) : "r"(a) : "memory"); return v; }
__device__ __forceinline__ uint4 ldtab(int word) { return __ldg((const uint4*)(g_tab + word)); }
__device__ __forceinline__ void load_tw(cf (&tw)[8], int k1) {
#pragma unroll
    for (int i = 0; i < 4; i++) {
        const uint4 v = ldtab(TAB_TW + k1 * 16 + i * 4);
        tw[2 * i] = {__uint_as_float(v.x), __uint_as_float(v.y)};
        tw[2 * i + 1] = {__uint_as_float(v.z), __uint_as_float(v.w)};
    }
}
__device__ __forceinline__ void load_T(cf (&T)[8], int t7) {
#pragma unroll
    for (int i = 0; i < 4; i++)
        asm volatile("ld.global.nc.v4.f32 {%0,%1,%2,%3}, [%4];" : "=f"(T[2 * i].x), "=f"(T[2 * i].y), "=f"(T[2 * i + 1].x), "=f"(T[2 * i + 1].y) : "l"(g_tab + TAB_T + i * 512 + t7 * 4));
}
__device__ __forceinline__ uint32_t lds_u16(uint32_t a) { uint32_t v; asm volatile("ld.shared.u16 %0, [%1];" : "=r"(v) : "r"(a)); return v; }
__device__ __forceinline__ float up(uint32_t v) { return __uint_as_float(v << 16); }
__device__ __forceinline__ unsigned get_epoch(uint32_t bars) {
    mbar_wait(bars + B_EP, 0);
    unsigned e;
    asm volatile("ld.shared.u32 %0, [%1];" : "=r"(e) : "r"(bars + B_EPOCH) : "memory");
    return e;
}
__device__ __forceinline__ void sts64f(uint32_t a, float x, float y) { asm volatile("st.shared.v2.f32 [%0], {%1,%2};" ::"r"(a), "f"(x), "f"(y) : "memory"); }
__device__ __forceinline__ uint32_t pk(float lo, float hi) { uint32_t r; asm("cvt.rn.bf16x2.f32 %0, %1, %2;" : "=r"(r) : "f"(hi), "f"(lo)); return r; }
__device__ __forceinline__ uint32_t bitsel(uint32_t a, uint32_t m, uint32_t b) {
    uint32_t r;
    asm("lop3.b32 %0, %1, %2, %3, 0xea;" : "=r"(r) : "r"(a), "r"(m), "r"(b));
    return r;
}

__host__ __device__ constexpr uint64_t mkdesc(uint32_t off, uint32_t lbo, uint32_t sbo, uint32_t swz) {
    return (uint64_t)((SB0 + off) >> 4) | ((uint64_t)(lbo >> 4) << 16) | ((uint64_t)(sbo >> 4) << 32) | ((uint64_t)swz << 62);
}
__device__ __forceinline__ void wg_fence() { asm volatile("wgmma.fence.sync.aligned;" ::: "memory"); }
__device__ __forceinline__ void wg_commit() { asm volatile("wgmma.commit_group.sync.aligned;" ::: "memory"); }
template <int N> __device__ __forceinline__ void wg_wait() { asm volatile("wgmma.wait_group.sync.aligned %0;" ::"n"(N) : "memory"); }
template <int N> __device__ __forceinline__ void pin(float (&d)[N]) {
#pragma unroll
    for (int i = 0; i < N; i++) asm volatile("" : "+f"(d[i])::"memory");
}
template <int N> __device__ __forceinline__ void pinu(uint32_t (&d)[N]) {
#pragma unroll
    for (int i = 0; i < N; i++) asm volatile("" : "+r"(d[i])::"memory");
}

#define R8(d, o) "+f"(d[o]), "+f"(d[o + 1]), "+f"(d[o + 2]), "+f"(d[o + 3]), "+f"(d[o + 4]), "+f"(d[o + 5]), "+f"(d[o + 6]), "+f"(d[o + 7])
#define L8 "%0,%1,%2,%3,%4,%5,%6,%7"
#define L24 L8 ",%8,%9,%10,%11,%12,%13,%14,%15,%16,%17,%18,%19,%20,%21,%22,%23"
#define L32 L24 ",%24,%25,%26,%27,%28,%29,%30,%31"
#define L64 L32 ",%32,%33,%34,%35,%36,%37,%38,%39,%40,%41,%42,%43,%44,%45,%46,%47,%48,%49,%50,%51,%52,%53,%54,%55,%56,%57,%58,%59,%60,%61,%62,%63"

template <int O, int TA, int TB, int SC, int N> __device__ __forceinline__ void mma128_ss(float (&d)[N], uint64_t da, uint64_t db) {
    asm volatile("wgmma.mma_async.sync.aligned.m64n128k16.f32.bf16.bf16 {" L64 "}, %64, %65, %66, 1, 1, %67, %68;"
                 : R8(d, O), R8(d, O + 8), R8(d, O + 16), R8(d, O + 24), R8(d, O + 32), R8(d, O + 40), R8(d, O + 48), R8(d, O + 56)
                 : "l"(da), "l"(db), "n"(SC), "n"(TA), "n"(TB));
}
#define W8(d, o) "=f"(d[o]), "=f"(d[o + 1]), "=f"(d[o + 2]), "=f"(d[o + 3]), "=f"(d[o + 4]), "=f"(d[o + 5]), "=f"(d[o + 6]), "=f"(d[o + 7])
__device__ __forceinline__ void mma128_first(float (&d)[64], uint64_t da, uint64_t db) {
    asm volatile("wgmma.mma_async.sync.aligned.m64n128k16.f32.bf16.bf16 {" L64 "}, %64, %65, 0, 1, 1, 0, 1;"
                 : W8(d, 0), W8(d, 8), W8(d, 16), W8(d, 24), W8(d, 32), W8(d, 40), W8(d, 48), W8(d, 56) : "l"(da), "l"(db));
}
template <int TB, int SC> __device__ __forceinline__ void mma128_rs(float (&d)[64], const uint32_t* a, uint64_t db) {
    asm volatile("wgmma.mma_async.sync.aligned.m64n128k16.f32.bf16.bf16 {" L64 "}, {%64,%65,%66,%67}, %68, %69, 1, 1, %70;"
                 : R8(d, 0), R8(d, 8), R8(d, 16), R8(d, 24), R8(d, 32), R8(d, 40), R8(d, 48), R8(d, 56)
                 : "r"(a[0]), "r"(a[1]), "r"(a[2]), "r"(a[3]), "l"(db), "n"(SC), "n"(TB));
}
template <int TB, int SC> __device__ __forceinline__ void mma64_rs(float (&d)[32], const uint32_t* a, uint64_t db) {
    asm volatile("wgmma.mma_async.sync.aligned.m64n64k16.f32.bf16.bf16 {" L32 "}, {%32,%33,%34,%35}, %36, %37, 1, 1, %38;"
                 : R8(d, 0), R8(d, 8), R8(d, 16), R8(d, 24)
                 : "r"(a[0]), "r"(a[1]), "r"(a[2]), "r"(a[3]), "l"(db), "n"(SC), "n"(TB));
}
template <int TA, int SC> __device__ __forceinline__ void mma64_ss(float (&d)[32], uint64_t da, uint64_t db) {
    asm volatile("wgmma.mma_async.sync.aligned.m64n64k16.f32.bf16.bf16 {" L32 "}, %32, %33, %34, 1, 1, %35, 1;"
                 : R8(d, 0), R8(d, 8), R8(d, 16), R8(d, 24)
                 : "l"(da), "l"(db), "n"(SC), "n"(TA));
}
template <int SC> __device__ __forceinline__ void mma48_ss(float (&d)[32], uint64_t da, uint64_t db) {
    asm volatile("wgmma.mma_async.sync.aligned.m64n48k16.f32.bf16.bf16 {" L24 "}, %24, %25, %26, 1, 1, 0, 1;"
                 : R8(d, 8), R8(d, 16), R8(d, 24)
                 : "l"(da), "l"(db), "n"(SC));
}
template <int SC> __device__ __forceinline__ void mma16_rs(float (&d)[32], uint32_t a0, uint32_t a1, uint32_t a2, uint32_t a3, uint64_t db) {
    asm volatile("wgmma.mma_async.sync.aligned.m64n16k16.f32.bf16.bf16 {" L8 "}, {%8,%9,%10,%11}, %12, %13, 1, 1, 1;"
                 : R8(d, 0)
                 : "r"(a0), "r"(a1), "r"(a2), "r"(a3), "l"(db), "n"(SC));
}

__device__ __forceinline__ cf cmul(cf a, cf b) { return {fmaf(a.x, b.x, -a.y * b.y), fmaf(a.x, b.y, a.y * b.x)}; }
__device__ __forceinline__ cf csq(cf a) { return {fmaf(a.x, a.x, -a.y * a.y), (a.x + a.x) * a.y}; }
__device__ __forceinline__ cf cmulc(cf a, cf b) { return {fmaf(a.x, b.x, a.y * b.y), fmaf(a.y, b.x, -a.x * b.y)}; }
__device__ __forceinline__ cf cfma(cf a, cf b, cf c) { return {fmaf(a.x, b.x, fmaf(-a.y, b.y, c.x)), fmaf(a.x, b.y, fmaf(a.y, b.x, c.y))}; }
__device__ __forceinline__ cf csel(int c, cf a, cf b) {
    cf r;
    asm("{.reg .pred p; setp.ne.s32 p, %6, 0; selp.f32 %0, %2, %4, p; selp.f32 %1, %3, %5, p;}" : "=f"(r.x), "=f"(r.y) : "f"(a.x), "f"(a.y), "f"(b.x), "f"(b.y), "r"(c));
    return r;
}
__device__ __forceinline__ cf cadd(cf a, cf b) { return {a.x + b.x, a.y + b.y}; }
__device__ __forceinline__ cf csub(cf a, cf b) { return {a.x - b.x, a.y - b.y}; }
__device__ __forceinline__ cf twice_minus(cf a, cf s) { return {fmaf(2.f, a.x, -s.x), fmaf(2.f, a.y, -s.y)}; }
struct v2 { float a, b; };
struct c2 { v2 x, y; };
#define OP2(name, args, txt, ...) \
    __device__ __forceinline__ v2 name args { v2 r; asm volatile(txt : "=f"(r.a) : __VA_ARGS__(a)); asm volatile(txt : "=f"(r.b) : __VA_ARGS__(b)); return r; }
#define A_XY(e) "f"(x.e), "f"(y.e)
#define A_XYZ(e) "f"(x.e), "f"(y.e), "f"(z.e)
OP2(add2, (v2 x, v2 y), "add.rn.f32 %0, %1, %2;", A_XY)
OP2(sub2, (v2 x, v2 y), "sub.rn.f32 %0, %1, %2;", A_XY)
OP2(mul2, (v2 x, v2 y), "mul.rn.f32 %0, %1, %2;", A_XY)
OP2(tw2, (v2 x, v2 y), "{.reg .f32 n; neg.f32 n, %2; fma.rn.f32 %0, %1, 0f40000000, n;}", A_XY)
OP2(fma2, (v2 x, v2 y, v2 z), "fma.rn.f32 %0, %1, %2, %3;", A_XYZ)
OP2(fms2, (v2 x, v2 y, v2 z), "{.reg .f32 n; neg.f32 n, %3; fma.rn.f32 %0, %1, %2, n;}", A_XYZ)
OP2(fnm2, (v2 x, v2 y, v2 z), "{.reg .f32 n; neg.f32 n, %1; fma.rn.f32 %0, n, %2, %3;}", A_XYZ)
__device__ __forceinline__ c2 both(cf a) { return {{a.x, a.x}, {a.y, a.y}}; }
__device__ __forceinline__ c2 tw2(c2 a, c2 s) { c2 r; r.x = tw2(a.x, s.x); r.y = tw2(a.y, s.y); return r; }
template <bool CJ> __device__ __forceinline__ c2 cmul2(c2 a, c2 t) {
    const v2 p = mul2(a.y, t.y), q = mul2(a.x, t.y);
    c2 r;
    r.x = CJ ? fma2(a.x, t.x, p) : fms2(a.x, t.x, p);
    r.y = CJ ? fms2(a.y, t.x, q) : fma2(a.y, t.x, q);
    return r;
}
template <bool CJ> __device__ __forceinline__ c2 cfma2(c2 a, c2 t, c2 c) {
    const v2 p = CJ ? fma2(a.y, t.y, c.x) : fnm2(a.y, t.y, c.x), q = CJ ? fnm2(a.x, t.y, c.y) : fma2(a.x, t.y, c.y);
    c2 r;
    r.x = fma2(a.x, t.x, p);
    r.y = fma2(a.y, t.x, q);
    return r;
}
__device__ __forceinline__ void bfly2(c2 a, c2 b, c2& s, c2& d) { s.x = add2(a.x, b.x); d.x = sub2(a.x, b.x); s.y = add2(a.y, b.y); d.y = sub2(a.y, b.y); }
__device__ __forceinline__ void bflyi2(c2 a, c2 b, c2& s, c2& d) { s.x = add2(a.x, b.y); d.x = sub2(a.x, b.y); s.y = sub2(a.y, b.x); d.y = add2(a.y, b.x); }
__device__ __forceinline__ uint32_t pkv(float lo, float hi) { uint32_t r; asm volatile("cvt.rn.bf16x2.f32 %0, %1, %2;" : "=r"(r) : "f"(hi), "f"(lo)); return r; }
__device__ __forceinline__ uint32_t pkv(v2 v) { return pkv(v.a, v.b); }
__device__ __forceinline__ float upv(uint32_t v) { float r; asm volatile("shl.b32 %0, %1, 16;" : "=f"(r) : "r"(v)); return r; }
__device__ __forceinline__ cf twid(int m, int M) {
    int r = ((m + M / 2) & (M - 1)) - M / 2;
    float s, c;
    __sincosf((float)r * (-6.283185307179586f / (float)M), &s, &c);
    return {c, s};
}
template <int YL, class F> __device__ __forceinline__ void dft8_end(const c2 (&e)[4], c2 a4, c2 a5, c2 a6, c2 a7, F out) {
    const v2 s = {0.70710678118654752f, 0.70710678118654752f};
    c2 o0, o1, o2, o3, u, v;
    bfly2(a4, a6, o0, o2);
    bfly2(e[0], o0, u, v);
    out(0, u, v);
    YLD(YL, 2);
    bflyi2(e[2], o2, u, v);
    out(2, u, v);
    bflyi2(a5, a7, o1, o3);
    YLD(YL, 1);
    o0.x = add2(o1.y, o1.x); o0.y = sub2(o1.y, o1.x);
    u.x = fma2(o0.x, s, e[1].x); v.x = fnm2(o0.x, s, e[1].x); u.y = fma2(o0.y, s, e[1].y); v.y = fnm2(o0.y, s, e[1].y);
    out(1, u, v);
    YLD(YL, 2);
    o2.x = sub2(o3.y, o3.x); o2.y = add2(o3.y, o3.x);
    u.x = fma2(o2.x, s, e[3].x); v.x = fnm2(o2.x, s, e[3].x); u.y = fnm2(o2.y, s, e[3].y); v.y = fma2(o2.y, s, e[3].y);
    out(3, u, v);
    YLD(YL, 1);
}

__device__ __forceinline__ void bid2tile(int b, int& tc, int& cb) {
    const int c = b >> 1, e = c - 36, t7 = (e * 37) >> 8;
    int g;
    asm("{.reg .pred p, q; setp.lt.s32 p, %2, 4; setp.lt.s32 q, %2, 36; selp.s32 %0, %3, %4, q; selp.s32 %1, %5, %6, q; selp.s32 %0, 0, %0, p; selp.s32 %1, %7, %1, p;}"
        : "=&r"(g), "=&r"(cb) : "r"(c), "r"((c + 4) & 7), "r"(1 + e - 7 * t7), "r"((c - 4) >> 3), "r"(4 + t7), "r"(4 + c));
    tc = 2 * g + (b & 1);
}
__host__ __device__ __forceinline__ int pos_of(int n) { return (n & 24) + 4 * (n & 1) + ((n >> 1) & 3); }
static int kappa_of(int b, int gi) {
    const int r = b >> 4, k1 = 2 * ((b & 15) ^ (4 * gi)) + gi;
    return b >= 128 ? gi * 256 : (k1 || r < 4 ? k1 + 64 * r : 64 * r - 224);
}
static int slot3_of(int kap, int& cj) {
    int m = kap & 15;
    cj = (m > 8) || ((m & 7) == 0 && kap > 256);
    const int kk = cj ? 512 - kap : kap;
    m = kk & 15;
    return kk == 256 ? 0 : (m & 1) * 128 + (m & 6) * 16 + pos_of((kk >> 4) + 2 * (m & 8));
}

__device__ __forceinline__ uint32_t tag_bad(uint32_t a, uint32_t tag) {
    uint32_t v;
    asm volatile("ld.shared.u32 %0, [%1];" : "=r"(v) : "r"(a) : "memory");
    return (v ^ tag) & 1;
}
__device__ __forceinline__ bool wg_all_ok(uint32_t bad, int id) {
    uint32_t ok;
    asm volatile("{.reg .pred p, q; setp.eq.u32 q, %1, 0; barrier.red.and.aligned.pred p, %2, 128, q; selp.u32 %0, 1, 0, p;}" : "=r"(ok) : "r"(bad), "r"(id) : "memory");
    return __all_sync(~0u, ok);
}

__device__ __forceinline__ uint32_t lines_bad(uint32_t va, uint32_t tag, uint32_t bit) {
    uint32_t bad;
    asm volatile("{.reg .b32 a, b, c, d;\n"
                 "ld.shared.u32 a, [%1]; ld.shared.u32 b, [%1+4096]; ld.shared.u32 c, [%1+8192]; ld.shared.u32 d, [%1+12288];\n"
                 "lop3.b32 a, a, b, %2, 0x7e; lop3.b32 c, c, d, %2, 0x7e; lop3.b32 %0, a, c, %3, 0xa8;}"
                 : "=r"(bad) : "r"(va), "r"(tag), "r"(bit) : "memory");
    return bad;
}
__device__ __forceinline__ void load_w(uint32_t sb, const CUtensorMap* m, int kap, uint32_t more) {
    mbar_expect_tx(sb + OFF_BAR + B_WIN, 16 * WPITCH + more);
#pragma unroll 1
    for (int i = 0; i < 4; i++) {
        if (i) __nanosleep(PACE_W);
        tma2d(sb + OFF_W + i * (4 * WPITCH), m + (i & 1), ((i & 2 ? (512 - kap) & 511 : kap) * 1026 >> 4) * 2, 0, sb + OFF_BAR + B_WIN);
    }
}
__device__ __forceinline__ void carry_poll(unsigned __int128 (&f)[4], const uint4* a, int n, uint32_t tag) {
    f[0] = f[1] = f[2] = f[3] = tag;
    asm volatile("{.reg .pred p<4>;\n"
                 "setp.ge.s32 p0, %5, 0; setp.ge.s32 p1, %5, 4; setp.ge.s32 p2, %5, 8; setp.ge.s32 p3, %5, 12;\n"
                 "@p0 ld.relaxed.gpu.global.b128 %0, [%4];\n"
                 "@p1 ld.relaxed.gpu.global.b128 %1, [%4+-32768];\n"
                 "@p2 ld.relaxed.gpu.global.b128 %2, [%4+-65536];\n"
                 "@p3 ld.relaxed.gpu.global.b128 %3, [%4+-98304];}"
                 : "+q"(f[0]), "+q"(f[1]), "+q"(f[2]), "+q"(f[3]) : "l"(a), "r"(n) : "memory");
}
__device__ __forceinline__ uint32_t carry_sum(const unsigned __int128 (&f)[4], const cf (&m4)[2], uint32_t tag, cf (&P)[2]) {
#pragma unroll
    for (int h = 0; h < 2; h++)
#pragma unroll
        for (int a = 3; a >= 0; a--) {
            const cf v = {__uint_as_float((uint32_t)(f[a] >> (64 * h))), __uint_as_float((uint32_t)(f[a] >> (64 * h + 32)))};
            P[h] = a == 3 ? v : cfma(m4[h], P[h], v);
        }
    return (((uint32_t)f[0] ^ tag) | ((uint32_t)f[1] ^ tag) | ((uint32_t)f[2] ^ tag) | ((uint32_t)f[3] ^ tag)) & 15u;
}

struct Ring {
    uint32_t full, rel;
    uint32_t ph, bh;
    uint64_t da;
    bool sig;
    uint32_t k;
};
__device__ __forceinline__ void ring_release(const Ring& r, int slot) {
    if (r.sig) asm volatile("mbarrier.arrive.shared::cluster.b64 _, [%0];" ::"r"(r.rel + 8 * slot) : "memory");
}
__device__ __forceinline__ void ring_wait(Ring& r, int slot) {
    if (slot == 0) r.ph ^= 1;
    mbar_wait(r.full + 8 * slot, r.ph);
}
template <int SLOT, int TA, int HF, int J> __device__ __forceinline__ void mma_g(float (&d)[128], const Ring& r, int sc) {
    constexpr int O = 64 * HF;
    asm volatile("{.reg .b64 da, db; .reg .b32 l; .reg .pred p; setp.ne.s32 p, %67, 0; add.u64 da, %64, %69; mov.b32 l, %65; mov.b64 db, {l,%66};\n"
                 "wgmma.mma_async.sync.aligned.m64n128k16.f32.bf16.bf16 {" L64 "}, da, db, p, 1, 1, %68, 0;}"
                 : R8(d, O), R8(d, O + 8), R8(d, O + 16), R8(d, O + 24), R8(d, O + 32), R8(d, O + 40), R8(d, O + 48), R8(d, O + 56)
                 : "l"(r.da), "n"((uint32_t)mkdesc(SLOT * 32768 + 16384 + J * 32, 16, 0, 0)), "r"(r.bh), "r"(sc), "n"(TA),
                   "n"(1 + SLOT * 2048 + (TA ? HF * 64 + J * 256 : HF * 512 + J * 2)));
}
static_assert((GRP >> HAND & 1) && (GRP >> 7 & 1), "hand-over at the end of a group");
template <int SLOT, int TA, int I, int BAR> __device__ __forceinline__ void gemm_mmas(float (&d)[128], Ring& r, int sc, bool last) {
    mma_g<SLOT, TA, I & 1, I / 2>(d, r, I < 2 ? sc : 1);
    if (GRP >> I & 1) {
        wg_commit();
        if (BAR && I == HAND) asm volatile("{.reg .pred p; setp.ne.s32 p, %1, 0; @p bar.arrive %0, 256;}" ::"n"(BAR), "r"((int)last) : "memory");
        wg_wait<1>();
        if ((GRP & (1 << I) - 1) == 0 && sc) ring_release(r, (SLOT + NST - 1) % NST);
    }
    if constexpr (I < 7) gemm_mmas<SLOT, TA, I + 1, BAR>(d, r, sc, last);
}
template <int SLOT, int TA, int BAR = 0> __device__ __forceinline__ void gemm_step(float (&d)[128], Ring& r, int sc, bool last = false) {
    ring_wait(r, SLOT);
    wg_fence();
    gemm_mmas<SLOT, TA, 0, BAR>(d, r, sc, last);
}
template <int K, int HF> __device__ __forceinline__ void gemm_half(float (&d)[128], Ring& r) {
    if (HF == 0) { ring_wait(r, K % NST); wg_fence(); }
    mma_g<K % NST, 1, HF, 0>(d, r, 1); mma_g<K % NST, 1, HF, 1>(d, r, 1); mma_g<K % NST, 1, HF, 2>(d, r, 1); mma_g<K % NST, 1, HF, 3>(d, r, 1);
    if constexpr (HF == 0 && K < 64 - SKEW) { mma_g<K % NST, 1, 1, 0>(d, r, 1); mma_g<K % NST, 1, 1, 1>(d, r, 1); mma_g<K % NST, 1, 1, 2>(d, r, 1); mma_g<K % NST, 1, 1, 3>(d, r, 1); }
    if constexpr (K < 63) gemm_half<K + 1, HF>(d, r);
}
struct Prod {
    uint32_t b0, b1, b2, b3, b4, dbase;
    unsigned* prof;
    __device__ __forceinline__ Prod(uint32_t sb, int slot, uint32_t off) {
        const uint32_t bars = sb + OFF_BAR;
        b0 = bars + slot % NST * 8; b1 = bars + (slot + 1) % NST * 8; b2 = bars + (slot + 2) % NST * 8; b3 = bars + (slot + 3) % NST * 8; b4 = bars + (slot + 4) % NST * 8;
        dbase = sb + off - bars * 4096;
    }
    __device__ __forceinline__ uint32_t dst() const { return b0 * 4096 + dbase; }
    __device__ __forceinline__ void next() { const uint32_t t = b0; b0 = b1; b1 = b2; b2 = b3; b3 = b4; b4 = t; }
};
__device__ __forceinline__ void load_shared(Prod& r, uint32_t ph, const CUtensorMap* m, int c0, int c3) {
    uint32_t dst = r.dst();
    if (HOIST) asm volatile("pmevent 0;" : "+r"(dst), "+r"(c0), "+r"(c3), "+l"(m));
    mbar_wait(r.b0 + B_EMPTY, ph);
    tma4d_mc(dst, m, c0, c3, r.b0);
    if (HOIST) YIELD();
    r.next();
}
__host__ __device__ constexpr uint64_t phases_from(int k) {
    uint64_t v = 0;
    for (int i = 0; i < 64; i++) v |= (uint64_t)((k + i) / NST & 1) << i;
    return v;
}
__device__ __forceinline__ uint32_t phases(int k, int n) { return ((uint32_t)(phases_from(0) >> k) & ((1u << n) - 1)) | 1u << n; }

__global__ void __cluster_dims__(2, 1, 1) __launch_bounds__(512, 1)
fused_kernel(const __grid_constant__ Maps tm, const __grid_constant__ Params p) {
    const CUtensorMap &tmX = tm.m[0], &tmBre = tm.m[1], &tmBim = tm.m[2], &tmXA = tm.m[5], &tmUst = tm.m[6], &tmVst = tm.m[7], &tmWr = tm.m[8], &tmVld = tm.m[10];
    extern __shared__ __align__(1024) uint8_t smraw[];
    const uint32_t sb = smem_u32(smraw);
    const uint32_t bars = sb + OFF_BAR;
    const int bid = blockIdx.x;
    const bool extra = bid >= 128;
    if (threadIdx.x == 480) RECL(0);
    int tc, cb;
    if (threadIdx.x < 32) {
        if (elect_one()) {
            pf_map(&tmX);
            pf_map(&tmBre);
            pf_map(&tmBim);
#pragma unroll
            for (int s = 0; s < NST; s++) mbar_init(bars + B_FULL + s * 8, 33);
            asm volatile("fence.mbarrier_init.release.cluster;" ::: "memory");
            bid2tile(bid, tc, cb);
            mbar_expect_tx(bars + B_FULL, 32768);
            tma5d(sb + 16384, &tmX, 0, 0, 0, 0, tc, bars + B_FULL);
            tma4d(sb, &tmBre, 0, 0, 0, cb * 4, bars + B_FULL);
            tma4d(sb + 8192, &tmBim, 0, 0, 0, cb * 4, bars + B_FULL);
            asm volatile("mbarrier.arrive.shared::cta.b64 _, [%0], 32;" ::"r"(bars + B_FULL) : "memory");
            STAMP(56);
        }
        __syncwarp();
    }
    const int wid = __shfl_sync(~0u, threadIdx.x >> 5, 0);
    if (wid == 1) {
        if (elect_one()) {
#pragma unroll
            for (int o = B_EMPTY; o < B_END; o += 8) mbar_init(bars + o, o < B_STGU ? 2 : (o == B_STGU ? 8 : (o < B_EP ? 4 : 1)));
            asm volatile("fence.mbarrier_init.release.cluster;" ::: "memory");
        }
        __syncwarp();
    }
    const int wg = ((wid >> 2) + 3) & 3, w = wid & 3;
    const int fb = bid >> 5, fcb = bid & 31, fpos = pos_of(fcb);
    const int vrow = ((bid & ~3) | (bid & 1) << 1 | (bid >> 1 & 1)) * 256;
    bid2tile(bid, tc, cb);
    asm volatile("barrier.cluster.arrive.relaxed.aligned;" ::: "memory");

    if (wg == 3) {
        asm volatile("setmaxnreg.dec.sync.aligned.u32 24;");
        if (w == 0) {
            if (extra) mbar_wait(bars + B_FULL, 0);
            else if (KMC > 1 && elect_one()) {
#pragma unroll 1
                for (int k = 1 + (bid >> 8); k < KMC; k++) {
                    mbar_expect_tx(bars + B_FULL + k * 8, 32768);
                    tma5d(sb + k * 32768 + 16384, &tmX, k * 64, 0, 0, 0, tc, bars + B_FULL + k * 8);
                    tma4d(sb + k * 32768, &tmBre, k * 64, 0, 0, cb * 4, bars + B_FULL + k * 8);
                    tma4d(sb + k * 32768 + 8192, &tmBim, k * 64, 0, 0, cb * 4, bars + B_FULL + k * 8);
                    asm volatile("mbarrier.arrive.shared::cta.b64 _, [%0], 32;" ::"r"(bars + B_FULL + k * 8) : "memory");
                }
                STAMP(28);
            }
            __syncwarp();
        }
        asm volatile("barrier.cluster.wait.aligned;" ::: "memory");
        if (bid == 129 || (sb & 0x3FFFF) != SB0) return;
        if (w < 2) {
            if (extra || !elect_one()) return;
            const int rank = bid & 1;
            if (w == 0) {
                Prod r(sb, KMC, 16384);
                int c0 = 64 * KMC;
#pragma unroll 1
                for (uint32_t pat = phases(NST + KMC, 32 - KMC); pat != 1; pat >>= 1) {
                    uint32_t dst = r.dst();
                    if (HOIST) asm volatile("pmevent 0;" : "+r"(dst));
                    mbar_wait(r.b0 + B_EMPTY, pat);
                    if (c0 >= 0) tma5d(dst, &tmX, c0, 0, 0, 0, tc, r.b0);
                    mbar_expect_tx(r.b0, c0 >= 0 ? 32768 : 16384);
                    asm volatile("mbarrier.arrive.shared::cta.b64 _, [%0], 32;" ::"r"(r.b0) : "memory");
                    c0 = c0 == 960 ? -64 * NST : c0 + 64;
                    r.next();
                }
                r.dbase -= 16384;
                const uint8_t* src = g_H + (size_t)tc * (32 * 16384);
                uint32_t all = (uint32_t)phases_from(32 - NST);
#pragma unroll 1
                for (int hh = 0; hh < 4; hh++) {
                    uint32_t pat = (all & 255) | 256;
                    all >>= 8;
                    mbar_wait(bars + B_HGO + 8 * hh, 0);
                    STAMPR(45 + hh);
#pragma unroll 1
                    do {
                        uint32_t dst = r.dst(), hb = r.b0 + B_HLD;
                        if (HOIST) asm volatile("pmevent 0;" : "+r"(dst), "+r"(hb));
                        mbar_wait(r.b0 + B_EMPTY, pat);
                        bulk_ld(dst, src, 16384, hb);
                        if (HOIST) YIELD();
                        mbar_expect_tx(r.b0 + B_HLD, 16384);
                        mbar_expect_tx(r.b0, 16384);
                        src += 16384;
                        r.next();
                        pat >>= 1;
                    } while (pat != 1);
                }
            } else {
                Prod r(sb, KMC, rank * 8192);
                int c = 64 * KMC;
#pragma unroll 1
                for (uint32_t pat = phases(NST + KMC, 32 - KMC); pat != 1; pat >>= 1) {
                    load_shared(r, pat, &tmBre + rank, c & 1023, cb * 4 + ((c >> 5) & 64));
                    c += c == 960 ? 2112 - 64 * NST : 64;
                }
                r.dbase += 16384;
                uint32_t pat = (uint32_t)phases_from(32 - NST);
#pragma unroll 1
                for (c = 0; c != 1024; c += 64) {
                    load_shared(r, pat, &tmBre + 2, c, cb * 8 + rank * 4);
                    load_shared(r, pat >> 1, &tmBre + 3, c, cb * 8 + rank * 4);
                    pat >>= 2;
                }
                mbar_arrive(bars + B_LDONE);
            }
        } else if (w == 2) {
            if (!elect_one()) return;
            STAMP5(39);
            if (!extra) {
                mbar_expect_tx(bars + B_XIN, 16384);
                mbar_expect_tx(bars + B_XIN + 8, 16384);
#pragma unroll 1
                for (int i = 0; i < 8; i++) {
                    const int k = i - XA_FIRST + XA_AT;
                    if (i >= XA_FIRST) mbar_wait(bars + B_EMPTY + (k < NST ? k : k - NST) * 8, k >= NST);
                    tma4d(sb + OFF_P + i * 2048, &tmXA, fcb * 32, 0, ((2 * i) & 7) + (i >> 2), fb, bars + B_XIN + (i & 4) * 2);
                    tma4d(sb + OFF_P + 16384 + i * 2048, &tmXA, fcb * 32 + 16, 0, ((2 * i) & 7) + (i >> 2), fb, bars + B_XIN + (i & 4) * 2);
                    if (!i) STAMP5(30);
                    STAMP5(31);
                }
            }
            pf_map(&tmWr);
            pf_map(&tmWr + 1);
            const unsigned ep = get_epoch(bars);
            if (!extra) mbar_wait(bars + B_XIN + 8, 0);
            STAMP5(32);
            load_w(sb, &tmWr, p.unit[2 * bid] & 0xffff, 8192);
            pf_map(&tmUst);
            if (!extra) mbar_wait(bars + B_STGU, 0);
            STAMP(21);
#pragma unroll 1
            for (int gi = 0; gi < 2; gi++) {
                if (!extra) {
#pragma unroll 1
                    for (int r = 128 * gi; r < 128 * gi + 128; r += UBOX) {
                        if (gi) __nanosleep(PACE_U);
                        tma2d_st(&tmUst, fb * 2048 + fpos * 64, r, sb + OFF_P + r * 128);
                        bulk_commit();
                    }
                    bulk_wait_read<HINT_U>();
                    red_hint(g_cnt + gi * 32);
                }
                if (!gi) bulk_ld(sb + OFF_F, g_tab + TAB_FG, 8192, bars + B_WIN);
                bulk_wait_read<0>();
                STAMPR(40 + gi);
                wait_cnt(g_cnt + 32 * gi, 128 * ep - (gi ? 0 : EARLY_U));
                {
                    if (gi) __nanosleep(UDELAY);
                    else STAMP(42);
                    mbar_expect_tx(bars + B_UIN + 8 * gi, 16384);
                    bulk_ld(sb + OFF_P + gi * 16384, g_U + (size_t)(extra ? 0 : bid + 128 * gi) * 16384, 16384, bars + B_UIN + 8 * gi);
                }
            }
            pf_map(&tmBre + 2); pf_map(&tmBre + 3); pf_map(&tmVst); pf_map(&tmVld);
            mbar_wait(bars + B_WFREE, 0);
            load_w(sb, &tmWr, p.unit[2 * bid + 1] & 0xffff, 0);
#pragma unroll 1
            for (int gi = 0; gi < 2; gi++) {
                const int vc = ((p.unit[2 * bid + gi] >> 16) & 255) * 64, go = vc >> 13;
                const uint32_t src = extra ? sb + 32768 : sb + OFF_P + gi * 16384;
                mbar_wait(bars + B_STG, gi);
                STAMPR(23 + gi);
                if (extra && !gi) continue;
                if (bid + gi != 0) {
#pragma unroll 1
                    for (int r = 0; r < 128; r += 32) {
                        if (r && !gi) __nanosleep(PACE_V);
                        tma2d_st(&tmVst, vc, r, src + r * 128);
                        bulk_commit();
                    }
                }
                bulk_wait_read<HINT_V>();
                red_hint(g_cnt + 64 + 32 * go);
                bulk_wait_read<0>();
                STAMP(49);
                if (extra) break;
                wait_cnt(g_cnt + 64 + 32 * gi, (129 - gi) * ep - gi * EARLY_V);
                {
                    STAMPR(43 + gi);
#pragma unroll
                    for (int h = 0; h < 2; h++) {
                        mbar_expect_tx(bars + B_VIN + gi * 16 + h * 8, 8192);
                        tma2d(src + h * 8192, &tmVld, h * 32, vrow + gi * 128, bars + B_VIN + gi * 16 + h * 8);
                    }
                }
                if (XT && !gi) {
                    mbar_wait(bars + B_WFREE, 1);
                    mbar_expect_tx(bars + B_WIN, 16384);
#pragma unroll 1
                    for (int i = 0; i < 4; i++) {
                        tma2d(sb + OFF_W + i * 4096, tm.m + 11, cb * 128, tc * 128 + 32 * i + 16, bars + B_WIN);
                    }
                }
            }
        } else {
            const uint32_t tag = ld_rlx(g_epoch + bid * 8) + 1;
            __syncwarp();
            if (elect_one()) {
                asm volatile("st.shared.u32 [%0], %1;" ::"r"(bars + B_EPOCH), "r"(tag) : "memory");
                mbar_arrive(bars + B_EP);
                asm volatile("st.relaxed.gpu.global.u32 [%0], %1;" ::"l"(g_epoch + bid * 8), "r"(tag) : "memory");
            }
            __syncwarp();
            if (extra) return;
            const int lane = (threadIdx.x + p.zero[0]) & 31;
            Prod r(sb, 32, 0);
            uint32_t va = (lane & 3) * 516 + (lane >> 4) * 2048 + (lane & 12) * 32 + (lane >> 2) * 16 + r.dbase;
            asm volatile("" : "+r"(va));
            uint32_t n = 0;
#pragma unroll 1
            for (int half = 0; half < 2; half++) {
#pragma unroll 1
                for (uint32_t pat = phases(16 * half, 16); pat != 1; pat >>= 1) {
                    uint32_t la = r.b0 * 4096 + va;
                    asm volatile("pmevent 0;" : "+r"(la));
                    mbar_wait(r.b0 + B_HLD, pat);
                    uint32_t bad = lines_bad(la, tag, 1);
                    if (!bad) mbar_arrive(r.b0);
                    asm volatile("pmevent 0;" : "+r"(bad));
#pragma unroll 1
                    while (__any_sync(~0u, bad)) {
                        const int kk = __shfl_sync(~0u, pat, 0);
                        if (elect_one()) {
                            mbar_expect_tx(bars + B_HRTY, 16384);
                            bulk_ld(r.dst(), g_H + (uint32_t)(tc * 32 + half * 16 + __clz(kk) - 15) * 16384, 16384, bars + B_HRTY);
                        }
                        __syncwarp();
                        mbar_wait(bars + B_HRTY, n++);
                        if (bad && !lines_bad(la, tag, n < SPIN_LIMIT)) { bad = 0; mbar_arrive(r.b0); }
                        __syncwarp();
                    }
                    if (pat >> 16) STAMPR(6 + 23 * half);
                    r.next();
                }
            }
        }
    } else {
        asm volatile("setmaxnreg.inc.sync.aligned.u32 152;");
        asm volatile("barrier.cluster.wait.aligned;" ::: "memory");
        STAMP(55);
        if ((extra && (wg != 2 || bid == 129)) || (sb & 0x3FFFF) != SB0) return;
        const int hf = wg - 1;
#define INDICES(i) const int t7 = (threadIdx.x + p.zero[i]) & 127, lane = t7 & 31, g = lane >> 2, q = lane & 3, k1 = t7 >> 2, mi = lane >> 3, gl = lane & 7; \
                   const uint32_t tmask = q == 0 ? ~1u : ~0u;
        if (wg == 1) {
            INDICES(1)
            const int ch = (t7 >> 6) * 512 + (t7 & 8) * 32 + cb * 32 + ((t7 >> 1) & 24) + (t7 & 7);
            const float lr = __bfloat162float(p.lre[ch]), li = __bfloat162float(p.lim[ch]);
            const float dt = __bfloat162float(__float2bfloat16(expf(__bfloat162float(p.ldt[ch]))));
            float sn, cs;
            sincospif(dt * li * 0.31830988618379067f, &sn, &cs);
            const float ex = expf(dt * lr), br = ex * cs, bi = ex * sn;
            const float inv = __fdividef(2.0f, lr * lr + li * li);
            const cf lam = {br, -bi}, gam = {((br - 1.f) * lr + bi * li) * inv, -(bi * lr - (br - 1.f) * li) * inv};
            const cf l32 = csq(csq(csq(csq(csq(lam))))), l64 = csq(l32), m1 = csq(l64), m2 = csq(m1), g2 = cmul(gam, l64);
            sts128f(sb + OFF_T1 + t7 * 16, lam, l32);
            sts128f(sb + OFF_TL + t7 * 32, gam, cmul(gam, l32));
            sts128f(sb + OFF_TL + t7 * 32 + 16, g2, cmul(g2, l32));
            sts128f(sb + OFF_TM + t7 * 32, csq(m2), m1);
            sts128f(sb + OFF_TM + t7 * 32 + 16, m2, cmul(m2, m1));
            __syncwarp();
            if (lane == 0) mbar_arrive(bars + B_LAM);
        }
        if (wg != 0 && !extra) {
            INDICES(2)
            uint32_t f1[16];
#pragma unroll
            for (int j = 0; j < 4; j++) { const uint4 v = ldtab(TAB_F1 + j * 512 + t7 * 4); f1[4 * j] = v.x; f1[4 * j + 1] = v.y; f1[4 * j + 2] = v.z; f1[4 * j + 3] = v.w; }
            cf tw[8];
            load_tw(tw, k1);
            const uint32_t tbit = get_epoch(bars) & ~tmask;
            const uint64_t dx = mkdesc(OFF_P, 2048, 256, 3) + hf * 1024;
            const int gr = gl & 1, jr = (gl >> 1) + 4 * ((w ^ gl) & 1);
            const uint32_t a0 = w + gl ? sb + OFF_P + (gr * 128 + 8 * (w >> 1) + jr + 64 * (mi >> 1)) * 128 : sb + OFF_F + 2048;
            const uint32_t rs = w + gl ? 2048 : 0;
            const uint32_t scr = sb + OFF_F + hf * 1024;
            float acc[32];
            c2 ev[2][4];
            uint4 fx0, fx1;
            float s0, s1;
#pragma unroll 1
            for (int od = 0;; od++) {
                if (od) STAMP5(33 + hf);
                mbar_wait(bars + B_XIN + od * 8, 0);
                if (od) STAMP(20);
                pinu(f1);
                wg_fence();
                mma64_rs<1, 0>(acc, f1, dx + od * 512);
                mma64_rs<1, 1>(acc, f1 + 4, dx + od * 512 + 32);
                mma64_rs<1, 1>(acc, f1 + 8, dx + od * 512 + 64);
                mma64_rs<1, 1>(acc, f1 + 12, dx + od * 512 + 96);
                wg_commit();
                wg_wait<0>();
                pin(acc);
                pinu(f1);
                if (od) STAMP5(35);
                if (k1 == 0) {
#pragma unroll
                    for (int i = 0; i < 8; i++) sts128f(scr + (i >> 1) * 256 + od * 128 + (i & 1) * 64 + q * 16, {acc[4 * i], acc[4 * i + 1]}, {acc[4 * i + 2], acc[4 * i + 3]});
                }
                if (od) break;
                asm volatile("ld.global.nc.v4.b32 {%0,%1,%2,%3}, [%4];" : "=r"(fx0.x), "=r"(fx0.y), "=r"(fx0.z), "=r"(fx0.w) : "l"(g_tab + TAB_FX + (t7 & 120)));
                asm volatile("ld.global.nc.v4.b32 {%0,%1,%2,%3}, [%4];" : "=r"(fx1.x), "=r"(fx1.y), "=r"(fx1.z), "=r"(fx1.w) : "l"(g_tab + TAB_FX + (t7 & 120) + 4));
#pragma unroll
                for (int cl = 0; cl < 2; cl++) {
                    auto in = [&](int n) { const int i = 4 * (n + cl); return c2{{acc[i], acc[i + 1]}, {acc[i + 2], acc[i + 3]}}; };
                    const c2 a0 = cfma2<false>(in(4), both(tw[4]), in(0)), a1 = tw2(in(0), a0);
                    YIELD();
                    const c2 t2 = cmul2<false>(in(2), both(tw[2]));
                    YIELD();
                    const c2 a2 = cfma2<false>(in(6), both(tw[6]), t2), a3 = tw2(t2, a2);
                    YIELD();
                    bfly2(a0, a2, ev[cl][0], ev[cl][2]);
                    YIELD();
                    bflyi2(a1, a3, ev[cl][1], ev[cl][3]);
                    YIELD();
                }
                wg_all_ok(0, hf ? 3 : 8);
                const uint32_t sa = scr + gl * 16 + (w >> 1) * 8;
                const cf x0 = lds_cf(sa), x2 = lds_cf(sa + 256), x4 = lds_cf(sa + 512), x6 = lds_cf(sa + 768);
                const float c0 = __uint_as_float(fx0.x), c2 = __uint_as_float(fx0.z), c4 = __uint_as_float(fx1.x), c6 = __uint_as_float(fx1.z);
                s0 = fmaf(c6, x6.x, fmaf(c4, x4.x, fmaf(c2, x2.x, c0 * x0.x)));
                s1 = fmaf(c6, x6.y, fmaf(c4, x4.y, fmaf(c2, x2.y, c0 * x0.y)));
            }
#pragma unroll
            for (int cl = 0; cl < 2; cl++) {
                auto in = [&](int n) { const int i = 4 * (n - 1 + cl); return c2{{acc[i], acc[i + 1]}, {acc[i + 2], acc[i + 3]}}; };
                const c2 t1 = cmul2<false>(in(1), both(tw[1]));
                YLD(YF1, 2);
                const c2 a4 = cfma2<false>(in(5), both(tw[5]), t1), a5 = tw2(t1, a4);
                YLD(YF1, 3);
                cf sx[8];
                if (cl == 0) {
                    bar_sync(6, 256);
                    STAMP5(36);
#pragma unroll
                    for (int n = 1; n < 8; n += 2) sx[n] = lds_cf(scr + n * 128 + gl * 16 + (w >> 1) * 8);
                }
                const c2 t3 = cmul2<false>(in(3), both(tw[3]));
                YLD(YF1, 1);
                const c2 a6 = cfma2<false>(in(7), both(tw[7]), t3), a7 = tw2(t3, a6);
                YLD(YF1, 2);
                const uint32_t a1 = a0 + (((((mi & 1) << 2) | ((2 * hf + cl) ^ (fpos & 3))) ^ jr) << 4);
                dft8_end<YF1>(ev[cl], a4, a5, a6, a7, [&](int r, c2 u, c2 v) {
                    uint32_t o0 = pkv(u.x), o1 = pkv(u.y), o2 = pkv(v.x), o3 = pkv(v.y);
                    if (cl == 0) { o0 = bitsel(o0, tmask, tbit); o2 = bitsel(o2, tmask, tbit); }
                    stsm4(a1 + r * rs, o0, o1, o2, o3);
                });
                if (cl == 0) {
                    YLD(YF1, 2);
#pragma unroll
                    for (int n = 1; n < 8; n += 2) {
                        const float c = __uint_as_float(n < 4 ? (n == 0 ? fx0.x : n == 1 ? fx0.y : n == 2 ? fx0.z : fx0.w) : (n == 4 ? fx1.x : n == 5 ? fx1.y : n == 6 ? fx1.z : fx1.w));
                        s0 = fmaf(c, sx[n].x, s0); s1 = fmaf(c, sx[n].y, s1);
                    }
                    asm volatile("st.shared.b32 [%0], %1;" ::"r"(sb + OFF_P + (t7 >> 4) * 2048 + (((mi & 1) * 4 + ((2 * hf + (g & 1)) ^ (fpos & 3))) << 4) + q * 4), "r"(bitsel(pk(s0, s1), tmask, tbit)) : "memory");
                    YLD(YF1, 1);
                }
            }
            fence_async_sm();
            __syncwarp();
            if (lane == 0) mbar_arrive(bars + B_STGU);
        }
        if (wg != 2) {
        if (wg == 0) bar_sync(4, 128);
        asm volatile("setmaxnreg.inc.sync.aligned.u32 168;");
        float d[128];
        Ring rg;
        rg.full = bars + B_FULL;
        asm("mapa.shared::cluster.u32 %0, %1, %2;" : "=r"(rg.rel) : "r"(bars + B_EMPTY), "r"(w & 1));
        rg.sig = ((threadIdx.x + p.zero[7]) & 95) == 0;
        rg.bh = (uint32_t)(mkdesc(0, 0, 1024, 1) >> 32) + p.zero[0];
        rg.da = p.da[0];
        rg.ph = 1;
        rg.k = 130 * 66 + bid * 66 + 16 * wg;
        if (wg == 0) {
            STAMP(0);
            gemm_step<0, 0>(d, rg, 0);
        } else {
            bar_sync(1, 256);
            STAMP(10);
        }
        rg.da = p.da[1];
#pragma unroll 1
        for (int i = 0; i < 3; i++) {
            gemm_step<1, 0>(d, rg, i >= wg);
            gemm_step<2, 0>(d, rg, 1);
            gemm_step<3, 0>(d, rg, 1);
            gemm_step<4, 0>(d, rg, 1);
            gemm_step<0, 0, 1>(d, rg, 1, i - wg == 2);
        }
        if (wg != p.zero[1]) {
            rg.da = p.da[0];
            gemm_step<1, 0, 2>(d, rg, 1, true);
        }
        {
            INDICES(3)
            cf lam[2], l32[2], l2[2];
            const uint32_t ta = sb + (wg * 64 + 16 * w + g) * 16;
            mbar_wait(bars + B_LAM, 0);
            const unsigned ep = get_epoch(bars), tag = ep & 15u;
            lds128f(ta + OFF_T1, lam[0].x, lam[0].y, l32[0].x, l32[0].y);
            lds128f(ta + OFF_T1 + 128, lam[1].x, lam[1].y, l32[1].x, l32[1].y);
            const uint4* cpub = g_carry + (uint32_t)(wg * 256 + cb * 32 + 8 * w + tc * 512 + g);
            l2[0] = csq(lam[0]);
            l2[1] = csq(lam[1]);
            asm volatile("pmevent 0;" : "+l"(cpub), "+f"(l2[0].x), "+f"(l2[0].y), "+f"(l2[1].x), "+f"(l2[1].y));
            wg_wait<0>();
            ring_release(rg, wg);
            pin(d);
            STAMPW(1, 11);
            cf f[2];
#pragma unroll
            for (int h = 0; h < 2; h++) {
                c2 c = {{d[2 * h], d[2 * h + 1]}, {d[64 + 2 * h], d[65 + 2 * h]}};
#pragma unroll
                for (int i = 1; i < 16; i++) {
                    const int r = 4 * i + 2 * h;
#define P1A "fma.rn.f32 a0, %2, %9, %4; fma.rn.f32 a1, %3, %9, %5;\n"
#define P1B "fma.rn.f32 b0, %0, n, %6; fma.rn.f32 b1, %1, n, %7;\n"
#define P1X "fma.rn.f32 %0, %0, %8, a0; fma.rn.f32 %1, %1, %8, a1;\n"
#define P1Y "fma.rn.f32 %2, %2, %8, b0; fma.rn.f32 %3, %3, %8, b1;\n"
#define P1ARG : "+f"(c.x.a), "+f"(c.x.b), "+f"(c.y.a), "+f"(c.y.b) : "f"(d[r]), "f"(d[r + 1]), "f"(d[64 + r]), "f"(d[65 + r]), "f"(l2[h].x), "f"(l2[h].y)
                    if (i & 1) asm volatile("{.reg .f32 a0, a1, b0, b1, n; neg.f32 n, %9;\n" P1A P1B P1X P1Y "}" P1ARG);
                    else asm volatile("{.reg .f32 a0, a1, b0, b1, n; neg.f32 n, %9;\n" P1B P1A P1Y P1X "}" P1ARG);
                    if (i % YS == 0) YIELD();
                    if (i == 12) lds128f(ta + OFF_T1 + 128 * h, lam[h].x, lam[h].y, l32[h].x, l32[h].y);
                }
                f[h] = cfma(lam[h], {c.x.a, -c.y.a}, {c.x.b, -c.y.b});
            }
            cf st[2], gam[2];
            gam[0] = lds_cf(2 * ta - sb + OFF_TL);
            gam[1] = lds_cf(2 * ta - sb + OFF_TL + 256);
            cf v0[2], v1[2], v2[2];
#pragma unroll
            for (int h = 0; h < 2; h++) {
                v0[h] = {__shfl_sync(~0u, f[h].x, 0, 4), __shfl_sync(~0u, f[h].y, 0, 4)};
                v1[h] = {__shfl_sync(~0u, f[h].x, 1, 4), __shfl_sync(~0u, f[h].y, 1, 4)};
                v2[h] = {__shfl_sync(~0u, f[h].x, 2, 4), __shfl_sync(~0u, f[h].y, 2, 4)};
            }
#pragma unroll
            for (int h = 0; h < 2; h++) {
                v1[h] = cfma(l32[h], v0[h], v1[h]);
                v2[h] = cfma(l32[h], v1[h], v2[h]);
                f[h] = cfma(l32[h], v2[h], f[h]);
            }
            asm volatile("{.reg .pred p; .reg .b64 a, b; .reg .b128 v; setp.eq.u32 p, %5, 3; mov.b64 a, {%1,%2}; mov.b64 b, {%3,%4}; mov.b128 v, {a, b};\n"
                         "@p st.relaxed.gpu.global.b128 [%0], v;}" ::"l"(cpub),
                         "r"(bitsel(__float_as_uint(f[0].x), ~15u, tag)), "r"(__float_as_uint(f[0].y)), "r"(__float_as_uint(f[1].x)), "r"(__float_as_uint(f[1].y)), "r"(q) : "memory");
            STAMPX(2, 12);
            YIELD();
#pragma unroll
            for (int h = 0; h < 2; h++) st[h] = cmul(gam[h], csel(q & 2, csel(q & 1, v2[h], v1[h]), csel(q & 1, v0[h], cf{0.f, 0.f})));
            const uint4* cget = cpub + (gl - g) - (1 + mi) * 512;
            const int nget = tc - 1 - mi;
            unsigned __int128 fq[4];
            auto prescale = [&](int i) {
                const int h = i >> 4, r = 4 * (i & 15) + 2 * h;
                asm volatile("{.reg .f32 s0, s1, n; neg.f32 n, %4; mul.f32 s0, %5, %1; mul.f32 s1, %5, %3; mul.f32 %1, n, %1; mul.f32 %3, n, %3;\n"
                             "fma.rn.f32 %1, %5, %0, %1; fma.rn.f32 %3, %5, %2, %3; fma.rn.f32 %0, %4, %0, s0; fma.rn.f32 %2, %4, %2, s1;}"
                             : "+f"(d[r]), "+f"(d[64 + r]), "+f"(d[r + 1]), "+f"(d[65 + r]) : "f"(gam[h].x), "f"(gam[h].y));
            };
#pragma unroll
            for (int i = 0; i < 32; i++) {
                if (i == POLL_AT) carry_poll(fq, cget, nget, tag);
                if (i % YS == 0) YIELD();
                prescale(i);
            }
            YIELD();
            const uint32_t tm = sb + OFF_TM + (wg * 64 + 16 * w) * 32;
            cf m4[2], mj[2], P[2], lq[2];
#pragma unroll
            for (int h = 0; h < 2; h++) {
                m4[h] = lds_cf(tm + gl * 32 + h * 256);
                mj[h] = lds_cf(tm + gl * 32 + h * 256 + mi * 8);
            }
            uint32_t bad = carry_sum(fq, m4, tag, P);
            unsigned n = 0;
            while (__any_sync(~0u, bad) && ++n < SPIN_LIMIT) {
                unsigned __int128 fr[4];
                carry_poll(fr, cget, nget, tag);
                bad = carry_sum(fr, m4, tag, P);
                YIELD();
                mj[0] = lds_cf(tm + gl * 32 + mi * 8);
                mj[1] = lds_cf(tm + gl * 32 + 256 + mi * 8);
            }
            STAMPX(53, 54);
            P[0] = csel(mi, cmul(P[0], mj[0]), P[0]);
            P[1] = csel(mi, cmul(P[1], mj[1]), P[1]);
            __syncwarp();
            sts128f(tm + lane * 16, P[0], P[1]);
#pragma unroll
            for (int h = 0; h < 2; h++) {
                lq[h] = lds_cf(2 * ta - sb + OFF_TL + h * 256 + q * 8);
                lam[h] = lds_cf(ta + OFF_T1 + h * 128);
            }
            __syncwarp();
            float ps[4][4];
#pragma unroll
            for (int j = 0; j < 4; j++) lds128f(tm + g * 16 + j * 128, ps[j][0], ps[j][1], ps[j][2], ps[j][3]);
            const uint8_t* hp = g_H + (uint32_t)((tc * 32 + wg * 16 + (cb & 6)) * 16384 + ((cb & 1) * 4 + w) * 2048 + g * 64 + ((q ^ (g >> 1)) << 4));
#pragma unroll
            for (int h = 0; h < 2; h++)
                st[h] = cfma(lq[h], {(ps[0][2 * h] + ps[1][2 * h]) + (ps[2][2 * h] + ps[3][2 * h]), (ps[0][2 * h + 1] + ps[1][2 * h + 1]) + (ps[2][2 * h + 1] + ps[3][2 * h + 1])}, st[h]);
            STAMPX(3, 13);
            uint32_t hv[32];
#pragma unroll
            for (int h = 0; h < 2; h++) {
                YIELD();
                cf c = st[h];
#pragma unroll
                for (int i = 0; i < 16; i++) {
                    const int r = 4 * i + 2 * h;
                    const cf a = cfma(lam[h], c, {d[r], d[64 + r]});
                    c = cfma(lam[h], a, {d[r + 1], d[65 + r]});
                    hv[i] = pk(a.x, c.x);
                    hv[16 + i] = pk(a.y, c.y);
                    if ((i & 3) == (i >> 2)) { hv[i] = bitsel(hv[i], ~1u, ep & 1); hv[16 + i] = bitsel(hv[16 + i], ~1u, ep & 1); }
                    if (h == 0 && (i & 3) == 3) {
                        stg128(hp + (i >> 2) * 512, hv[i - 3], hv[i - 2], hv[i - 1], hv[i]);
                        stg128(hp + 16384 + (i >> 2) * 512, hv[13 + i], hv[14 + i], hv[15 + i], hv[16 + i]);
                    }
                }
                if (h == 0) {
                    STAMPW(4, 14);
                    if (lane == 0) red_hint(g_hcnt + tc * 64 + wg * 32);
                }
            }
            YIELD();
            if (w == 0) {
                wait_cnt(g_hcnt + tc * 64 + wg * 32, 32 * ep - EARLY_H);
                if (lane < 4) mbar_arrive(bars + B_HGO + 16 * wg);
            } else mbar_wait(bars + B_HGO + 16 * wg, 0);
#pragma unroll
            for (int j = 0; j < 8; j++) {
                stg128(hp + (8 + (j >> 2)) * 16384 + (j & 3) * 512, hv[4 * j], hv[4 * j + 1], hv[4 * j + 2], hv[4 * j + 3]);
                if (j < 7) __nanosleep(PACE_H);
            }
            __syncwarp();
            if (lane == 0) mbar_arrive(bars + B_HGO + 16 * wg + 8);
            STAMPW(5, 15);
        }
        if (wg == p.zero[2]) {
            INDICES(1)
            float y[128];
            const uint32_t sa = sb + w * 4096 + g * 512 + q * 8;
            bar_sync(2, 256);
            STAMP(7);
            rg.da = p.da[2];
            rg.ph = 0;
            rg.k = 130 * 66 + bid * 66 + 32;
#pragma unroll 1
            for (int i = 0;; i++) {
                gemm_step<2, 1>(y, rg, i);
                gemm_step<3, 1>(y, rg, 1);
                gemm_step<4, 1>(y, rg, 1);
                if (i == 5) break;
                gemm_step<0, 1>(y, rg, 1);
                gemm_step<1, 1>(y, rg, 1);
            }
            rg.da = p.da[3];
            gemm_half<60, 0>(y, rg);
            wg_commit();
            gemm_half<64 - SKEW, 1>(y, rg);
            wg_commit();
#pragma unroll
            for (int r = 0; r < 4; r++) {
                if (r == 0) {
                    wg_wait<1>();
#pragma unroll
                    for (int i = 0; i < 64; i++) asm volatile("" : "+f"(y[i])::"memory");
                    STAMP(16);
                    bar_sync(4, 128);
                }
                if (r == 2) {
                    STAMP(18);
                    wg_wait<0>();
#pragma unroll
                    for (int i = 64; i < 128; i++) asm volatile("" : "+f"(y[i])::"memory");
                    STAMP(8);
                    bar_sync(4, 128);
                }
#pragma unroll
                for (int c = 0; c < 16; c++) {
                    const int yi = 64 * (r >> 1) + 4 * c + 2 * (r & 1);
                    sts64f(sa + (r < 2 ? (NST - 1) * 32768 : 0) + (r & 1) * 16384 + (c >> 2) * 128 + (((c ^ g) & 3) << 5), y[yi], y[yi + 1]);
                }
                if (r == 0) bar_arrive(9, 256);
                if (r == 1) bar_arrive(10, 256);
                if (r == 2) bar_arrive(11, 256);
                if (r == 3) bar_arrive(12, 256);
            }
            STAMP(19);
            return;
        }
        bar_sync(8, 128);
        asm volatile("setmaxnreg.dec.sync.aligned.u32 152;");
        } else {
            INDICES(4)
            cf T[8];
            load_T(T, t7);
            const uint32_t tag = get_epoch(bars) & 1;
            float acc[64];
            constexpr uint64_t dF = mkdesc(OFF_F, 16, 1024, 1);
            const uint32_t tga = sb + OFF_P + t7 * 128 + (((t7 & 1) ^ (g & 2)) << 4);
            bool ok = false;
            mbar_wait(bars + B_WIN, 0);
#pragma unroll 1
            for (int gi = 0;; gi++) {
                const uint32_t un = p.unit[2 * bid + gi];
                const int kap = un & 0xffff;
                const uint32_t buf = sb + OFF_P + gi * 16384;
                STAMP3(39);
                float za[32], zb[32], ya[32], yb[32];
                const uint64_t dB = mkdesc(OFF_P, 4096, 512, 2) + gi * 1024;
                uint32_t ad, am, pa, pb;
                if (w == 2) {
                    ad = sb + OFF_W + (lane & 8) * 128;
                    am = ad + ((lane & 4) | (((kap ? 3 : 4) - lane) & 3)) * WPITCH + (8 * WPITCH + ((-2 * kap) & 15));
                    ad += gl * WPITCH + ((2 * kap) & 15);
                    asm volatile("" : "+r"(ad), "+r"(am));
                    mbar_wait(bars + B_WIN, gi);
                    pa = lds_u16(ad);
                    pb = lds_u16(am);
                }
#pragma unroll 1
                for (int n = gi; !ok && n < 4096; n++) {
                    if (n) bar_sync(3, 128);
                    if (n && w == 0 && elect_one()) { mbar_expect_tx(bars + B_UIN + gi * 8, 16384); bulk_ld(buf, g_U + (size_t)(extra ? 0 : bid + gi * 128) * 16384, 16384, bars + B_UIN + gi * 8); }
                    mbar_wait(bars + B_UIN + gi * 8, n & 1);
                    STAMP3(22);
                    wg_fence();
                    mma128_first(acc, dF, dB);
                    mma128_ss<0, 0, 1, 1>(acc, dF + 2, dB + 64);
                    mma128_ss<0, 0, 1, 1>(acc, dF + 4, dB + 128);
                    mma128_ss<0, 0, 1, 1>(acc, dF + 6, dB + 192);
                    wg_commit();
                    YIELD();
                    ok = wg_all_ok(tag_bad(tga + gi * 16384, tag), 3);
                    wg_wait<0>();
                    pin(acc);
                }
                STAMP3(30);
                uint32_t af[32];
#pragma unroll
                for (int b = 0; b < 4; b++) {
#pragma unroll
                    for (int c = 0; c < 4; c++) {
                        const int i = 4 * (4 * b + c);
                        cf x0 = cmul({acc[i], acc[i + 2]}, T[2 * c]), x1 = cmul({acc[i + 1], acc[i + 3]}, T[2 * c + 1]);
                        af[16 * (b >> 1) + 4 * c + (b & 1)] = pk(x0.x, x0.y);
                        af[16 * (b >> 1) + 4 * c + 2 + (b & 1)] = pk(x1.x, x1.y);
                        YLD(YF2, c == 3 ? 1 : (c == 1 ? 2 : 3));
                    }
                    if (b == 0 && w == 2) {
                        const uint32_t sg = (lane & 4) << 13, v = pk(0.5f * (up(pa) + up(pb ^ sg)), 0.f);
                        asm volatile("st.shared.u16 [%0], %1;" ::"r"(ad), "r"(v) : "memory");
                        asm volatile("st.shared.u16 [%0], %1;" ::"r"(am), "r"(v ^ sg) : "memory");
                    }
                    if (b == 1) {
                        wg_fence();
                        mma64_rs<0, 0>(za, af, dF); mma64_rs<0, 1>(za, af + 4, dF + 2); mma64_rs<0, 1>(za, af + 8, dF + 4); mma64_rs<0, 1>(za, af + 12, dF + 6);
                        wg_commit();
                    }
                }
                wg_fence();
                mma64_rs<0, 0>(zb, af + 16, dF); mma64_rs<0, 1>(zb, af + 20, dF + 2); mma64_rs<0, 1>(zb, af + 24, dF + 4); mma64_rs<0, 1>(zb, af + 28, dF + 6);
                wg_commit();
                STAMP3(31);
                int kq;
                asm volatile("mad.lo.s32 %0, %1, 512, %2;" : "=r"(kq) : "r"(q), "r"(kap));
                uint32_t wad[4];
#pragma unroll
                for (int j = 0; j < 4; j++) wad[j] = sb + OFF_W + ((j + (kq >> 9)) & 3) * WPITCH + ((2 * kap) & 15) + 2 * k1 + 128 * q;
                if (gi) fence_async_sm();
                bar_sync(3, 128);
                if (lane < gi) mbar_arrive(bars + B_STG);
                uint32_t wn[16];
#pragma unroll
                for (int j = 0; j < 16; j++) wn[j] = lds_u16(wad[j >> 2] + (j & 1) * 64 + (j & 2) * (2 * WPITCH));
                const cf be1 = twid(kq, 2048), be2 = cmul(be1, be1), be3 = cmul(be1, be2);
                YLD(YF2, 1);
                wg_wait<0>();
                pin(za);
                pin(zb);
                pinu(af);
                STAMP3(32);
                c2 z[4];
                auto pack = [&](int jb, int b) {
                    af[16 * (b >> 1) + 4 * jb + (b & 1)] = pkv(z[b].x);
                    af[16 * (b >> 1) + 4 * jb + 2 + (b & 1)] = pkv(z[b].y);
                };
#pragma unroll
                for (int jb = 0; jb < 4; jb++) {
                    if (jb == 2) STAMP3(37);
                    if (jb == 1) {
#pragma unroll
                        for (int j = 0; j < 4; j++)
                            wad[j] = sb + OFF_W + (8 + (((kap ? 3 : 4) - j - q) & 3)) * WPITCH + ((-2 * kap) & 15) + 1024 - 2 * k1 - 128 * q;
                    }
                    c2 W[4];
                    auto next = [&](int j) {
                        W[j] = {{upv(wn[4 * j]), upv(wn[4 * j + 1])}, {upv(wn[4 * j + 2]), upv(wn[4 * j + 3])}};
                        if (jb < 3) {
#pragma unroll
                            for (int n = 0; n < 4; n++) wn[4 * j + n] = lds_u16(wad[j] + (jb ? 512 - 512 * jb - (n & 1) * 64 : 512 + (n & 1) * 64) + (n & 2) * (2 * WPITCH));
                        }
                    };
                    const int i = 8 * jb;
                    const c2 z0 = {{za[i], za[i + 1]}, {za[i + 4], za[i + 5]}};
                    if (jb) pack(jb - 1, 1);
                    next(0);
                    c2 s0 = cfma2<false>({{zb[i], zb[i + 1]}, {zb[i + 4], zb[i + 5]}}, both(be2), z0), s1 = tw2(z0, s0);
                    YLD(YF2, 2);
                    if (jb) pack(jb - 1, 3);
                    if (jb == 3) load_T(T, t7);
                    next(1);
                    const c2 z1 = cmul2<false>({{za[i + 2], za[i + 3]}, {za[i + 6], za[i + 7]}}, both(be1));
                    YLD(YF2, 3);
                    c2 s2 = cfma2<false>({{zb[i + 2], zb[i + 3]}, {zb[i + 6], zb[i + 7]}}, both(be3), z1), s3 = tw2(z1, s2);
                    YLD(YF2, 1);
                    c2 x0, x1, x2, x3;
                    next(2);
                    bfly2(s0, s2, x0, x2);
                    const c2 y0 = jb < 2 ? cmul2<false>(x0, W[0]) : cmul2<true>(x0, W[0]);
                    YLD(YF2, 2);
                    next(3);
                    bflyi2(s1, s3, x1, x3);
                    const c2 y1 = jb < 2 ? cmul2<false>(x1, W[1]) : cmul2<true>(x1, W[1]);
                    YLD(YF2, 1);
                    s0 = jb < 2 ? cfma2<false>(x2, W[2], y0) : cfma2<true>(x2, W[2], y0);
                    s1 = tw2(y0, s0);
                    YLD(YF2, 3);
                    s2 = jb < 2 ? cfma2<false>(x3, W[3], y1) : cfma2<true>(x3, W[3], y1);
                    s3 = tw2(y1, s2);
                    YLD(YF2, 2);
                    bfly2(s0, s2, z[0], x2);
                    z[2] = cmul2<true>(x2, both(be2));
                    pack(jb, 0);
                    YLD(YF2, 1);
                    bflyi2(s1, s3, x3, x1);
                    pack(jb, 2);
                    z[1] = cmul2<true>(x1, both(be1));
                    YLD(YF2, 3);
                    z[3] = cmul2<true>(x3, both(be3));
                    YLD(YF2, 1);
                }
                pack(3, 1);
                pack(3, 3);
                pinu(af);
                wg_fence();
                mma64_rs<1, 0>(ya, af, dF); mma64_rs<1, 1>(ya, af + 4, dF + 128); mma64_rs<1, 1>(ya, af + 8, dF + 256); mma64_rs<1, 1>(ya, af + 12, dF + 384);
                wg_commit();
                mma64_rs<1, 0>(yb, af + 16, dF); mma64_rs<1, 1>(yb, af + 20, dF + 128); mma64_rs<1, 1>(yb, af + 24, dF + 256); mma64_rs<1, 1>(yb, af + 28, dF + 384);
                wg_commit();
                STAMP3(33);
                if (w == 2) fence_async_sm();
                __syncwarp();
                if (lane == 0) mbar_arrive(bars + B_WFREE);
                {
                    const uint32_t a0 = buf + (mi & 1) * 4096 + (16 * w + 8 * (mi >> 1) + gl) * 64;
#pragma unroll
                    for (int u = 0; u < 2; u++)
#pragma unroll
                        for (int c = 0; c < 4; c++) {
                            if (c == 0) {
                                if (u == 0) { wg_wait<1>(); pin(ya); STAMP3(34); }
                                else { wg_wait<0>(); pin(yb); pinu(af); }
                            }
                            const int i = 8 * c;
                            const float(&yy)[32] = u ? yb : ya;
                            const cf x0 = cmulc({yy[i], yy[i + 1]}, T[2 * c]), x1 = cmulc({yy[i + 4], yy[i + 5]}, T[2 * c + 1]);
                            const uint32_t o0 = pk(x0.x, x1.x), o2 = pk(x0.y, x1.y);
                            YLD(YF2, 3);
                            const cf y0 = cmulc({yy[i + 2], yy[i + 3]}, T[2 * c]), y1 = cmulc({yy[i + 6], yy[i + 7]}, T[2 * c + 1]);
                            stsm4(a0 + u * 8192 + ((c ^ (gl >> 1)) << 4), o0, pk(y0.x, y1.x), o2, pk(y0.y, y1.y));
                            YLD(YF2, 2 - (c & 1));
                        }
                }
                STAMP3(38);
                const uint32_t flip = ((g & 1) && !(un >> 24)) ? 0x80008000u : 0u, flipt = flip | (tag & ~tmask);
                const int rw = 8 * w + (gl & 4) + 2 * (mi & 1) + ((gl >> 1) & 1);
                const uint32_t a0 = (extra ? ((gl & 1) == gi ? sb + 32768 : sb + 65536) : buf) + rw * 128 +
                                    (((((gl & 1) << 1) | ((mi >> 1) ^ ((un >> 17) & 1))) ^ (rw & 7)) << 4);
                auto put = [&](const float (&v)[32], uint32_t a) {
#pragma unroll
                    for (int i = 0; i < 32; i += 8)
                        stsm4((a ^ ((i & 8) * 8)) + (i >> 4) * 4096, (pk(v[i], v[i + 1]) & tmask) ^ flipt, (pk(v[i + 2], v[i + 3]) & tmask) ^ flipt,
                              pk(v[i + 4], v[i + 5]) ^ flip, pk(v[i + 6], v[i + 7]) ^ flip);
                };
                fence_async_sm();
                bar_sync(3, 128);
                float va[32], vb[32];
                wg_fence();
                mma64_ss<1, 0>(va, dF, dB); mma64_ss<1, 0>(vb, dF, dB + 512);
                mma64_ss<1, 1>(va, dF + 128, dB + 64); mma64_ss<1, 1>(vb, dF + 128, dB + 576);
                mma64_ss<1, 1>(va, dF + 256, dB + 128); mma64_ss<1, 1>(vb, dF + 256, dB + 640);
                mma64_ss<1, 1>(va, dF + 384, dB + 192); mma64_ss<1, 1>(vb, dF + 384, dB + 704);
                wg_commit();
                STAMP3(35);
                uint32_t bad = 0;
                if (!gi) {
                    mbar_wait(bars + B_UIN + 8, 0);
                    bad = tag_bad(tga + 16384, tag);
                }
                wg_wait<0>();
                pin(va);
                pin(vb);
                STAMP3(36);
                ok = wg_all_ok(bad, 3);
                put(va, a0);
                if (gi) {
                    put(vb, a0 + 8192);
                    fence_async_sm();
                    __syncwarp();
                    if (lane == 0) mbar_arrive(bars + B_STG);
                    break;
                }
                constexpr uint64_t dN = mkdesc(OFF_P + 16384, 4096, 512, 2);
                wg_fence();
                mma128_first(acc, dF, dN);
                mma128_ss<0, 0, 1, 1>(acc, dF + 2, dN + 64);
                mma128_ss<0, 0, 1, 1>(acc, dF + 4, dN + 128);
                mma128_ss<0, 0, 1, 1>(acc, dF + 6, dN + 192);
                wg_commit();
                put(vb, a0 + 8192);
                wg_wait<0>();
                pin(acc);
            }
            if (extra) return;
        }
        uint2 xd[16], dd;
        auto skip = [&]() {
            const int lane = (threadIdx.x + p.zero[2]) & 31;
            const uint2* xp = (const uint2*)(p.xb + (uint32_t)((tc * 128 + 64 * (w & 1) + 32 * hf + 8 * (w >> 1)) * 1024 + cb * 128)) + lane;
            dd = __ldg((const uint2*)(p.dsk + cb * 128) + lane);
#pragma unroll
            for (int j = 0; j < (XT ? 8 : 16); j++) {
                asm volatile("ld.global.nc.L1::no_allocate.v2.b32 {%0,%1}, [%2];" : "=r"(xd[j].x), "=r"(xd[j].y) : "l"(xp + ((j >> 3) * 16 + (j & 7)) * 256));
            }
        };
        auto skip2 = [&]() {
            if (XT) {
                const uint32_t xa = sb + OFF_W + (2 * (w & 1) + hf) * 4096 + (w >> 1) * 2048 + ((threadIdx.x + p.zero[3]) & 31) * 8;
                mbar_wait(bars + B_WIN, 0);
#pragma unroll
                for (int j = 0; j < 8; j++) asm volatile("ld.shared.v2.b32 {%0,%1}, [%2];" : "=r"(xd[8 + j].x), "=r"(xd[8 + j].y) : "r"(xa + j * 256) : "memory");
            }
#pragma unroll
            for (int j = 0; j < 16; j++) {
                if (j % 4 == 0) YIELD();
                asm volatile("fma.rn.bf16x2 %0, %0, %1, %2;" : "+r"(xd[j].x) : "r"(dd.x), "r"(0x80008000u));
                asm volatile("fma.rn.bf16x2 %0, %0, %1, %2;" : "+r"(xd[j].y) : "r"(dd.y), "r"(0x80008000u));
            }
            YIELD();
        };
        {
            INDICES(5)
            uint32_t sp[8];
#pragma unroll
            for (int j = 0; j < 2; j++) { const uint4 v = ldtab(TAB_SP + j * 512 + t7 * 4); sp[4 * j] = v.x; sp[4 * j + 1] = v.y; sp[4 * j + 2] = v.z; sp[4 * j + 3] = v.w; }
            cf tw[8];
            load_tw(tw, k1);
            tw[4].x *= 2.f; tw[4].y *= 2.f;
            const uint32_t tag = get_epoch(bars) & 1;
            const uint32_t in = sb + OFF_P + hf * 8192;
            constexpr uint64_t dF = mkdesc(OFF_F, 16, 1024, 1);
            const uint64_t dB = mkdesc(OFF_P, 2048, 256, 3) + hf * 512;
            float ae[32], ao[32];
            c2 ev[2][4];
            auto blk = [&](const float (&a)[32], int i) { return c2{{a[i], a[i + 1]}, {a[i + 2], a[i + 3]}}; };
            auto unfold = [&](c2 a, c2 u, int n, c2& zn, c2& zm, int yl) {
                const float wc = n == 1 ? 0.92387953251128674f : (n == 2 ? 0.70710678118654752f : 0.38268343236508977f);
                const float ws = n == 3 ? 0.92387953251128674f : (n == 2 ? 0.70710678118654752f : 0.38268343236508977f);
                const v2 c = {wc, wc}, s = {ws, ws}, two = {2.f, 2.f};
                const c2 y = cmul2<false>(a, both(tw[n])), t = both(tw[8 - n]);
                c2 E;
                E.x = fnm2(u.y, t.y, y.x); E.y = fnm2(u.x, t.y, y.y); E.x = fma2(u.x, t.x, E.x); E.y = fnm2(u.y, t.x, E.y);
                YLD(yl, 2);
                const c2 D = tw2(y, E);
                zn.x = fnm2(D.y, c, E.x); zn.y = fma2(D.y, s, E.y); zn.x = fma2(D.x, s, zn.x); zn.y = fma2(D.x, c, zn.y);
                zm.x = tw2(E.x, zn.x); zm.y = fnm2(E.y, two, zn.y);
                YLD(yl, 1);
            };
#pragma unroll
            for (int rgn = 0; rgn < 2; rgn++) {
#pragma unroll 1
                for (int n = 0; n < 4096; n++) {
                    mbar_wait(bars + B_VIN + rgn * 16 + hf * 8, n & 1);
                    if (rgn) STAMP(25);
                    if (rgn == 0) {
                        pinu(sp);
                        wg_fence();
                        mma48_ss<0>(ae, dF, dB + 128); mma16_rs<0>(ae, sp[0], 0u, sp[1], 0u, dB);
                        mma48_ss<1>(ae, dF + 2, dB + 160); mma16_rs<1>(ae, sp[2], 0u, sp[3], 0u, dB + 32);
                        mma48_ss<1>(ae, dF + 4, dB + 192); mma16_rs<1>(ae, 0u, sp[4], 0u, sp[5], dB + 64);
                        mma48_ss<1>(ae, dF + 6, dB + 224); mma16_rs<1>(ae, 0u, sp[6], 0u, sp[7], dB + 96);
                    } else {
                        wg_fence();
                        mma64_ss<0, 0>(ao, dF, dB + 1024);
                        mma64_ss<0, 1>(ao, dF + 2, dB + 1056);
                        mma64_ss<0, 1>(ao, dF + 4, dB + 1088);
                        mma64_ss<0, 1>(ao, dF + 6, dB + 1120);
                    }
                    wg_commit();
                    const bool ok = wg_all_ok(tag_bad(in + rgn * 16384 + t7 * 64 + (t7 & 6) * 8, tag), hf ? 3 : 8);
                    wg_wait<0>();
                    if (rgn) pin(ao);
                    else { pin(ae); pinu(sp); }
                    if (ok) break;
                    wg_all_ok(0, hf ? 3 : 8);
                    if (w == 0 && elect_one()) {
                        mbar_expect_tx(bars + B_VIN + rgn * 16 + hf * 8, 8192);
                        tma2d(in + rgn * 16384, &tmVld, hf * 32, vrow + rgn * 128, bars + B_VIN + rgn * 16 + hf * 8);
                    }
                }
                if (rgn == 0) {
#pragma unroll
                    for (int cl = 0; cl < 2; cl++) {
                        const c2 b = blk(ae, 4 * cl), z0 = {add2(b.x, b.y), sub2(b.x, b.y)};
                        const c2 a0 = cfma2<false>(blk(ae, 16 + 4 * cl), both(tw[4]), z0), a1 = tw2(z0, a0);
                        YIELD();
                        c2 z2, z6, a2, a3;
                        unfold(blk(ae, 8 + 4 * cl), blk(ae, 24 + 4 * cl), 2, z2, z6, 2);
                        bfly2(z2, z6, a2, a3);
                        bfly2(a0, a2, ev[cl][0], ev[cl][2]);
                        YIELD();
                        bflyi2(a1, a3, ev[cl][1], ev[cl][3]);
                    }
                    YIELD();
                }
            }
            skip();
            const uint32_t a0 = in + (8 * w + (gl ^ (2 * hf)) + 32 * (mi & 1)) * 32 + (mi >> 1) * 16384 + (gl & 4) * 4;
#pragma unroll
            for (int cl = 0; cl < 2; cl++) {
                c2 z1, z3, z5, z7, a4, a5, a6, a7;
                unfold(blk(ao, 4 * cl), blk(ao, 24 + 4 * cl), 1, z1, z7, YF3);
                if (cl == 0) wg_all_ok(0, hf ? 3 : 8);
                unfold(blk(ao, 8 + 4 * cl), blk(ao, 16 + 4 * cl), 3, z3, z5, YF3);
                bfly2(z1, z5, a4, a5);
                bfly2(z3, z7, a6, a7);
                YLD(YF3, 2);
                dft8_end<YF3>(ev[cl], a4, a5, a6, a7, [&](int r, c2 u, c2 v) { stsm4((a0 ^ (cl * 16)) + r * 2048, pkv(u.x), pkv(u.y), pkv(v.x), pkv(v.y)); });
            }
            bar_sync(7, 256);
            STAMP(26);
        }
        INDICES(6)
        const int t0 = tc * 128 + 64 * (w & 1) + 32 * hf + 8 * (w >> 1);
        {
            const int n0 = 16 * hf + 4 * w + mi;
            uint32_t la = sb + OFF_P + (((gl >> 2) * 8256) ^ (n0 * 32)) + ((((gl >> 1) & 1) ^ (w & 1)) << 4) + (gl & 1) * 8;
            const float* op = p.out + (uint32_t)((4 * n0 + fb) * 2048 + fcb * 32 + gl * 4);
#pragma unroll 1
            for (int it = 0; it < 4; it++) {
                uint32_t u[8];
#pragma unroll
                for (int i = 0; i < 4; i++) asm volatile("ld.shared.v2.b32 {%0,%1}, [%2];" : "=r"(u[2 * i]), "=r"(u[2 * i + 1]) : "r"(la + i * 1024) : "memory");
#pragma unroll
                for (int i = 0; i < 4; i++) {
                    stg128(op + i * 128 * 2048, u[2 * i] << 16, u[2 * i] & 0xffff0000u, u[2 * i + 1] << 16, u[2 * i + 1] & 0xffff0000u);
                    if (TRYP >> i & 1) asm volatile("{.reg .pred p; mbarrier.try_wait.parity.shared::cta.b64 p, [%0], 0, %1; @p pmevent 0;}" ::"r"(bars + B_LDONE), "r"(PACE_O) : "memory");
                }
                la += it == 1 ? 12288 : 4096;
                op += 4 * 128 * 2048;
            }
            STAMP(27);
        }
        skip2();
        const uint32_t ra = sb + hf * 16384 + w * 4096;
        float* ob = p.out + (size_t)t0 * 2048 + 1024 + cb * 128 + lane * 4;
#pragma unroll
        for (int mb = 0; mb < 2; mb++) {
            if (hf == 0) { if (mb == 0) bar_sync(9, 256); else bar_sync(11, 256); }
            else { if (mb == 0) bar_sync(10, 256); else bar_sync(12, 256); }
            if (mb == 0) STAMP(17);
            float v[8][4];
#pragma unroll
            for (int j = 0; j < 8; j++) lds128f(ra + (mb ? 0 : (NST - 1) * 32768) + j * 512 + ((lane * 16) ^ ((j & 3) * 32)), v[j][0], v[j][1], v[j][2], v[j][3]);
#pragma unroll
            for (int j = 0; j < 8; j++) {
                const uint2 s = xd[8 * mb + j];
                stg128(ob + (16 * mb + j) * 2048, __float_as_uint(v[j][0] + up(s.x)), __float_as_uint(v[j][1] + __uint_as_float(s.x & 0xffff0000u)),
                       __float_as_uint(v[j][2] + up(s.y)), __float_as_uint(v[j][3] + __uint_as_float(s.y & 0xffff0000u)));
            }
        }
        STAMP(9);
        if (threadIdx.x == 480) RECL(2);
    }
}

typedef CUresult (*EncodeFn)(CUtensorMap*, CUtensorMapDataType, cuuint32_t, void*, const cuuint64_t*, const cuuint64_t*, const cuuint32_t*,
                             const cuuint32_t*, CUtensorMapInterleave, CUtensorMapSwizzle, CUtensorMapL2promotion, CUtensorMapFloatOOBfill);

static CUtensorMap make_map(EncodeFn enc, const void* ptr, int rank, const cuuint64_t* dims, const cuuint64_t* strides, const cuuint32_t* box,
                            CUtensorMapSwizzle swz, CUtensorMapL2promotion promo, CUtensorMapDataType dt = CU_TENSOR_MAP_DATA_TYPE_BFLOAT16) {
    CUtensorMap m;
    const cuuint32_t es[5] = {1, 1, 1, 1, 1};
    enc(&m, dt, rank, const_cast<void*>(ptr), dims, strides, box, es, CU_TENSOR_MAP_INTERLEAVE_NONE, swz, promo,
        CU_TENSOR_MAP_FLOAT_OOB_FILL_NONE);
    return m;
}

extern "C" void kernel_launch(void* const* d_in, const int* in_sizes, int n_in, void* d_out, int out_size) {
    void* fn = nullptr;
    cudaDriverEntryPointQueryResult qr;
    cudaGetDriverEntryPoint("cuTensorMapEncodeTiled", &fn, cudaEnableDefault, &qr);
    EncodeFn enc = (EncodeFn)fn;
    void *pU, *pV;
    cudaGetSymbolAddress(&pU, g_U);
    cudaGetSymbolAddress(&pV, g_V);
    const CUtensorMapL2promotion P256 = CU_TENSOR_MAP_L2_PROMOTION_L2_256B, P0 = CU_TENSOR_MAP_L2_PROMOTION_NONE;

    const cuuint64_t dX[5] = {1024, 2, 4, 16, 16}, sX[4] = {2048, 32 * 2048, 2 * 2048, 128 * 2048};
    const cuuint32_t bX[5] = {64, 2, 4, 16, 1};
    CUtensorMap tmX = make_map(enc, d_in[3], 5, dX, sX, bX, CU_TENSOR_MAP_SWIZZLE_128B, CU_TENSOR_MAP_L2_PROMOTION_L2_128B);
    const cuuint64_t dB[4] = {1024, 8, 2, 96}, sB[3] = {2048, 256 * 2048, 8 * 2048}, dC[4] = {1024, 8, 2, 64}, sC[3] = {2048, 8 * 2048, 16 * 2048};
    const cuuint32_t bB[4] = {64, 8, 2, 4};
    CUtensorMap tmBre = make_map(enc, d_in[6], 4, dB, sB, bB, CU_TENSOR_MAP_SWIZZLE_128B, P256);
    CUtensorMap tmBim = make_map(enc, d_in[7], 4, dB, sB, bB, CU_TENSOR_MAP_SWIZZLE_128B, P256);
    CUtensorMap tmCre = make_map(enc, d_in[8], 4, dC, sC, bB, CU_TENSOR_MAP_SWIZZLE_128B, P256);
    CUtensorMap tmCim = make_map(enc, d_in[9], 4, dC, sC, bB, CU_TENSOR_MAP_SWIZZLE_128B, P256);

    const cuuint64_t dU[2] = {8192, 256}, sU[1] = {16384};
    const cuuint32_t bS[2] = {64, UBOX};
    CUtensorMap tmUst = make_map(enc, pU, 2, dU, sU, bS, CU_TENSOR_MAP_SWIZZLE_128B, P0);
    const cuuint64_t dV[2] = {16384, 128}, sV[1] = {32768}, dL[2] = {64, 32768}, sL[1] = {128};
    const cuuint32_t bL[2] = {32, 128};
    CUtensorMap tmVst = make_map(enc, pV, 2, dV, sV, bS, CU_TENSOR_MAP_SWIZZLE_128B, P0);
    CUtensorMap tmVld = make_map(enc, pV, 2, dL, sL, bL, CU_TENSOR_MAP_SWIZZLE_NONE, P0);
    const cuuint64_t dR[2] = {1024, 2048}, sR[1] = {2048};
    const cuuint32_t bR[2] = {128, 16};
    CUtensorMap tmXR = make_map(enc, d_in[3], 2, dR, sR, bR, CU_TENSOR_MAP_SWIZZLE_NONE, P0);
    const cuuint64_t dA[4] = {1024, 64, 8, 4}, sA[3] = {32 * 2048, 4 * 2048, 2048};
    const cuuint32_t bA[4] = {16, 64, 1, 1};
    CUtensorMap tmXA = make_map(enc, d_in[0], 4, dA, sA, bA, CU_TENSOR_MAP_SWIZZLE_32B, CU_TENSOR_MAP_L2_PROMOTION_L2_128B);
    const cuuint64_t dF[2] = {512 * 1026 / 8, 4}, sF[1] = {512 * 1026};
    const cuuint32_t bF[2] = {WPITCH / 8, 4};
    CUtensorMap tmWr = make_map(enc, d_in[1], 2, dF, sF, bF, CU_TENSOR_MAP_SWIZZLE_NONE, P0, CU_TENSOR_MAP_DATA_TYPE_UINT64);
    CUtensorMap tmWi = make_map(enc, d_in[2], 2, dF, sF, bF, CU_TENSOR_MAP_SWIZZLE_NONE, P0, CU_TENSOR_MAP_DATA_TYPE_UINT64);

    Params p = {};
    p.xb = (const __nv_bfloat16*)d_in[3];
    p.lre = (const __nv_bfloat16*)d_in[4];
    p.lim = (const __nv_bfloat16*)d_in[5];
    p.ldt = (const __nv_bfloat16*)d_in[10];
    p.dsk = (const __nv_bfloat16*)d_in[11];
    p.out = (float*)d_out;
    p.da[0] = p.da[1] = mkdesc(0, 16, 1024, 1) - 1;
    p.da[2] = p.da[3] = mkdesc(0, 512, 2048, 2) - 1;
    for (int i = 0; i < 258; i++) {
        int cj;
        const int kap = kappa_of(i >> 1, i & 1), s3 = slot3_of(kap, cj);
        p.unit[i] = kap | s3 << 16 | cj << 24;
    }
    cudaFuncSetAttribute(fused_kernel, cudaFuncAttributeMaxDynamicSharedMemorySize, SMEM_BYTES);
    fused_kernel<<<130, 512, SMEM_BYTES>>>(Maps{{tmX, tmBre, tmBim, tmCre, tmCim, tmXA, tmUst, tmVst, tmWr, tmWi, tmVld, tmXR}}, p);
}
```

```cpp
#include <cuda_runtime.h>
#include <cuda.h>
#include <cuda_bf16.h>
#include <stdint.h>

#define NST 5
#define SB0 1024
#define WPITCH 1056
#define OFF_P (NST * 32768)
#define OFF_F (OFF_P + 32768)
#define OFF_W (OFF_F + 8192)
#define OFF_TL (OFF_W + 16 * WPITCH)
#define OFF_TM (OFF_TL + 4096)
#define OFF_T1 (OFF_TM + 4096)
#define OFF_BAR (OFF_T1 + 2048)
#define OFF_STAMP (OFF_BAR + 384)
#define SMEM_BYTES (OFF_BAR + 512)
#define B_FULL 0
#define B_EMPTY 40
#define B_STGU 80
#define B_HGO 88
#define B_LAM 120
#define B_STG 128
#define B_WFREE 136
#define B_EP 144
#define B_LDONE 152
#define B_UIN 160
#define B_WIN 176
#define B_XIN 184
#define B_VIN 200
#define B_HRTY 232
#define B_HLD 240
#define B_END 280
#define B_EPOCH 280

#define PACE_U 250
#define PACE_V 120
#define PACE_O 250
#define HAND 3
#define POLL_AT 24
#define XA_FIRST 3
#define XA_AT 0
#define YS 3
#define UDELAY 250
#define PACE_W 120
#define HINT_U 0
#define HINT_V 2
#define GRP 0x8a
#define EARLY_U 36
#define EARLY_V 36
#define EARLY_H 4
#define KMC 3
#define GRP2 GRP
#define YS2 1
#define HP0 0x22222220
#define HP1 0x44444440
#define YFE 4
#define TRYP 15
#define XT 1
#define UBOX 32
#define SKEW 4
#define SPIN_LIMIT 32768

#define YIELD() asm volatile("pmevent 0;")
#define YF1 3
#define YF2 2
#define YF3 4
#define YLD(level, n) do { if ((level) >= (n)) YIELD(); } while (0)

__device__ __align__(1024) uint8_t g_U[4 << 20];
__device__ __align__(1024) uint8_t g_V[4 << 20];
__device__ __align__(1024) uint8_t g_H[8 << 20];
__device__ __align__(1024) uint4 g_carry[16 * 512];
__device__ __align__(1024) unsigned g_hcnt[16 * 64];
__device__ __align__(128) unsigned g_cnt[128];
__device__ __align__(128) unsigned g_epoch[129 * 8];

#define RECL(i) do { } while (0)
#define STAMP(i) do { } while (0)
#define STAMPR(i) do { } while (0)
#define STAMPW(a, b) do { } while (0)
#define STAMPX(a, b) do { } while (0)
#define STAMP5(i) do { } while (0)
#define STAMP3(i) do { } while (0)

#define TAB_FG 0
#define TAB_F1 2048
#define TAB_T 4096
#define TAB_SP 6144
#define TAB_TW 7168
#define TAB_FX 7680
__device__ __align__(1024) const uint32_t g_tab[7808] = {
0x80003d80,0x80003d80,0x80003d80,0x80003d80,0x80003d80,0x80003d80,0x80003d80,0x80003d80,0x80003d80,0x80003d80,0x80003d80,0x80003d80,0x80003d80,0x80003d80,0x80003d80,0x80003d80,
0x80003d80,0x80003d80,0x80003d80,0x80003d80,0x80003d80,0x80003d80,0x80003d80,0x80003d80,0x80003d80,0x80003d80,0x80003d80,0x80003d80,0x80003d80,0x80003d80,0x80003d80,0x80003d80,
0x3c483d7b,0x3d0e3d55,0x3d553d0e,0x3d7b3c48,0x80003d80,0x3cc43d6d,0x3d353d35,0x3d6d3cc4,0x3d7bbc48,0x3d55bd0e,0x3d0ebd55,0x3c48bd7b,0x3d800000,0x3d6dbcc4,0x3d35bd35,0x3cc4bd6d,
0xbc48bd7b,0xbd0ebd55,0xbd55bd0e,0xbd7bbc48,0x8000bd80,0xbcc4bd6d,0xbd35bd35,0xbd6dbcc4,0xbd7b3c48,0xbd553d0e,0xbd0e3d55,0xbc483d7b,0xbd800000,0xbd6d3cc4,0xbd353d35,0xbcc43d6d,
0x8000bd80,0xbd35bd35,0xbd800000,0xbd353d35,0xbcc4bd6d,0xbd6dbcc4,0xbd6d3cc4,0xbcc43d6d,0x80003d80,0x3d353d35,0x3d800000,0x3d35bd35,0x3cc43d6d,0x3d6d3cc4,0x3d6dbcc4,0x3cc4bd6d,
0x8000bd80,0xbd35bd35,0xbd800000,0xbd353d35,0xbcc4bd6d,0xbd6dbcc4,0xbd6d3cc4,0xbcc43d6d,0x80003d80,0x3d353d35,0x3d800000,0x3d35bd35,0x3cc43d6d,0x3d6d3cc4,0x3d6dbcc4,0x3cc4bd6d,
0xbd553d0e,0x3c483d7b,0x3d7b3c48,0x3d0ebd55,0xbd800000,0xbcc43d6d,0x3d353d35,0x3d6dbcc4,0x3d0e3d55,0x3d7bbc48,0x3c48bd7b,0xbd55bd0e,0x80003d80,0x3d6d3cc4,0x3d35bd35,0xbcc4bd6d,
0x3d55bd0e,0xbc48bd7b,0xbd7bbc48,0xbd0e3d55,0x3d800000,0x3cc4bd6d,0xbd35bd35,0xbd6d3cc4,0xbd0ebd55,0xbd7b3c48,0xbc483d7b,0x3d553d0e,0x8000bd80,0xbd6dbcc4,0xbd353d35,0x3cc43d6d,
0x80003d80,0x3d800000,0x8000bd80,0xbd800000,0x3d353d35,0x3d35bd35,0xbd35bd35,0xbd353d35,0x80003d80,0x3d800000,0x8000bd80,0xbd800000,0x3d353d35,0x3d35bd35,0xbd35bd35,0xbd353d35,
0x80003d80,0x3d800000,0x8000bd80,0xbd800000,0x3d353d35,0x3d35bd35,0xbd35bd35,0xbd353d35,0x80003d80,0x3d800000,0x8000bd80,0xbd800000,0x3d353d35,0x3d35bd35,0xbd35bd35,0xbd353d35,
0xbd55bd0e,0xbc483d7b,0x3d7bbc48,0xbd0ebd55,0x8000bd80,0xbd6d3cc4,0x3d353d35,0x3cc4bd6d,0xbd0e3d55,0x3d7b3c48,0xbc48bd7b,0xbd553d0e,0xbd800000,0x3cc43d6d,0x3d35bd35,0xbd6dbcc4,
0x3d553d0e,0x3c48bd7b,0xbd7b3c48,0x3d0e3d55,0x80003d80,0x3d6dbcc4,0xbd35bd35,0xbcc43d6d,0x3d0ebd55,0xbd7bbc48,0x3c483d7b,0x3d55bd0e,0x3d800000,0xbcc4bd6d,0xbd353d35,0x3d6d3cc4,
0x8000bd80,0xbd353d35,0x3d800000,0xbd35bd35,0xbd6dbcc4,0x3cc43d6d,0x3cc4bd6d,0xbd6d3cc4,0x80003d80,0x3d35bd35,0xbd800000,0x3d353d35,0x3d6d3cc4,0xbcc4bd6d,0xbcc43d6d,0x3d6dbcc4,
0x8000bd80,0xbd353d35,0x3d800000,0xbd35bd35,0xbd6dbcc4,0x3cc43d6d,0x3cc4bd6d,0xbd6d3cc4,0x80003d80,0x3d35bd35,0xbd800000,0x3d353d35,0x3d6d3cc4,0xbcc4bd6d,0xbcc43d6d,0x3d6dbcc4,
0x3c48bd7b,0xbd0e3d55,0x3d55bd0e,0xbd7b3c48,0x3d800000,0xbd6dbcc4,0x3d353d35,0xbcc4bd6d,0xbd7bbc48,0x3d553d0e,0xbd0ebd55,0x3c483d7b,0x8000bd80,0xbcc43d6d,0x3d35bd35,0xbd6d3cc4,
0xbc483d7b,0x3d0ebd55,0xbd553d0e,0x3d7bbc48,0xbd800000,0x3d6d3cc4,0xbd35bd35,0x3cc43d6d,0x3d7b3c48,0xbd55bd0e,0x3d0e3d55,0xbc48bd7b,0x80003d80,0x3cc4bd6d,0xbd353d35,0x3d6dbcc4,
0x3d800000,0x3d800000,0x3d800000,0x3d800000,0x3d800000,0x3d800000,0x3d800000,0x3d800000,0x3d800000,0x3d800000,0x3d800000,0x3d800000,0x3d800000,0x3d800000,0x3d800000,0x3d800000,
0x3d800000,0x3d800000,0x3d800000,0x3d800000,0x3d800000,0x3d800000,0x3d800000,0x3d800000,0x3d800000,0x3d800000,0x3d800000,0x3d800000,0x3d800000,0x3d800000,0x3d800000,0x3d800000,
0x3d7bbc48,0x3d55bd0e,0x3d0ebd55,0x3c48bd7b,0x3d800000,0x3d6dbcc4,0x3d35bd35,0x3cc4bd6d,0xbc48bd7b,0xbd0ebd55,0xbd55bd0e,0xbd7bbc48,0xbd80,0xbcc4bd6d,0xbd35bd35,0xbd6dbcc4,
0xbd7b3c48,0xbd553d0e,0xbd0e3d55,0xbc483d7b,0xbd800000,0xbd6d3cc4,0xbd353d35,0xbcc43d6d,0x3c483d7b,0x3d0e3d55,0x3d553d0e,0x3d7b3c48,0x3d80,0x3cc43d6d,0x3d353d35,0x3d6d3cc4,
0xbd800000,0xbd353d35,0x3d80,0x3d353d35,0xbd6d3cc4,0xbcc43d6d,0x3cc43d6d,0x3d6d3cc4,0x3d800000,0x3d35bd35,0xbd80,0xbd35bd35,0x3d6dbcc4,0x3cc4bd6d,0xbcc4bd6d,0xbd6dbcc4,
0xbd800000,0xbd353d35,0x3d80,0x3d353d35,0xbd6d3cc4,0xbcc43d6d,0x3cc43d6d,0x3d6d3cc4,0x3d800000,0x3d35bd35,0xbd80,0xbd35bd35,0x3d6dbcc4,0x3cc4bd6d,0xbcc4bd6d,0xbd6dbcc4,
0x3d0e3d55,0x3d7bbc48,0x3c48bd7b,0xbd55bd0e,0x3d80,0x3d6d3cc4,0x3d35bd35,0xbcc4bd6d,0x3d55bd0e,0xbc48bd7b,0xbd7bbc48,0xbd0e3d55,0x3d800000,0x3cc4bd6d,0xbd35bd35,0xbd6d3cc4,
0xbd0ebd55,0xbd7b3c48,0xbc483d7b,0x3d553d0e,0xbd80,0xbd6dbcc4,0xbd353d35,0x3cc43d6d,0xbd553d0e,0x3c483d7b,0x3d7b3c48,0x3d0ebd55,0xbd800000,0xbcc43d6d,0x3d353d35,0x3d6dbcc4,
0x3d800000,0xbd80,0xbd800000,0x3d80,0x3d35bd35,0xbd35bd35,0xbd353d35,0x3d353d35,0x3d800000,0xbd80,0xbd800000,0x3d80,0x3d35bd35,0xbd35bd35,0xbd353d35,0x3d353d35,
0x3d800000,0xbd80,0xbd800000,0x3d80,0x3d35bd35,0xbd35bd35,0xbd353d35,0x3d353d35,0x3d800000,0xbd80,0xbd800000,0x3d80,0x3d35bd35,0xbd35bd35,0xbd353d35,0x3d353d35,
0xbd0e3d55,0x3d7b3c48,0xbc48bd7b,0xbd553d0e,0xbd800000,0x3cc43d6d,0x3d35bd35,0xbd6dbcc4,0x3d553d0e,0x3c48bd7b,0xbd7b3c48,0x3d0e3d55,0x3d80,0x3d6dbcc4,0xbd35bd35,0xbcc43d6d,
0x3d0ebd55,0xbd7bbc48,0x3c483d7b,0x3d55bd0e,0x3d800000,0xbcc4bd6d,0xbd353d35,0x3d6d3cc4,0xbd55bd0e,0xbc483d7b,0x3d7bbc48,0xbd0ebd55,0xbd80,0xbd6d3cc4,0x3d353d35,0x3cc4bd6d,
0xbd800000,0x3d353d35,0xbd80,0xbd353d35,0xbcc43d6d,0x3d6dbcc4,0xbd6dbcc4,0x3cc43d6d,0x3d800000,0xbd35bd35,0x3d80,0x3d35bd35,0x3cc4bd6d,0xbd6d3cc4,0x3d6d3cc4,0xbcc4bd6d,
0xbd800000,0x3d353d35,0xbd80,0xbd353d35,0xbcc43d6d,0x3d6dbcc4,0xbd6dbcc4,0x3cc43d6d,0x3d800000,0xbd35bd35,0x3d80,0x3d35bd35,0x3cc4bd6d,0xbd6d3cc4,0x3d6d3cc4,0xbcc4bd6d,
0xbd7bbc48,0x3d553d0e,0xbd0ebd55,0x3c483d7b,0xbd80,0xbcc43d6d,0x3d35bd35,0xbd6d3cc4,0xbc483d7b,0x3d0ebd55,0xbd553d0e,0x3d7bbc48,0xbd800000,0x3d6d3cc4,0xbd35bd35,0x3cc43d6d,
0x3d7b3c48,0xbd55bd0e,0x3d0e3d55,0xbc48bd7b,0x3d80,0x3cc4bd6d,0xbd353d35,0x3d6dbcc4,0x3c48bd7b,0xbd0e3d55,0x3d55bd0e,0xbd7b3c48,0x3d800000,0xbd6dbcc4,0x3d353d35,0xbcc4bd6d,
0x80003d80,0x8000bd80,0x80003d80,0x8000bd80,0x3d800000,0xbd800000,0x3d800000,0xbd800000,0x80003d80,0x8000bd80,0x80003d80,0x8000bd80,0x3d800000,0xbd800000,0x3d800000,0xbd800000,
0x80003d80,0x8000bd80,0x80003d80,0x8000bd80,0x3d800000,0xbd800000,0x3d800000,0xbd800000,0x80003d80,0x8000bd80,0x80003d80,0x8000bd80,0x3d800000,0xbd800000,0x3d800000,0xbd800000,
0x3d7bbc48,0xbd553d0e,0x3d0ebd55,0xbc483d7b,0x80003d80,0xbcc4bd6d,0x3d353d35,0xbd6dbcc4,0xbc48bd7b,0x3d0e3d55,0xbd55bd0e,0x3d7b3c48,0x3d800000,0xbd6d3cc4,0x3d35bd35,0xbcc43d6d,
0xbd7b3c48,0x3d55bd0e,0xbd0e3d55,0x3c48bd7b,0x8000bd80,0x3cc43d6d,0xbd35bd35,0x3d6d3cc4,0x3c483d7b,0xbd0ebd55,0x3d553d0e,0xbd7bbc48,0xbd800000,0x3d6dbcc4,0xbd353d35,0x3cc4bd6d,
0x8000bd80,0x3d353d35,0xbd800000,0x3d35bd35,0xbd6d3cc4,0x3cc4bd6d,0x3cc43d6d,0xbd6dbcc4,0x80003d80,0xbd35bd35,0x3d800000,0xbd353d35,0x3d6dbcc4,0xbcc43d6d,0xbcc4bd6d,0x3d6d3cc4,
0x8000bd80,0x3d353d35,0xbd800000,0x3d35bd35,0xbd6d3cc4,0x3cc4bd6d,0x3cc43d6d,0xbd6dbcc4,0x80003d80,0xbd35bd35,0x3d800000,0xbd353d35,0x3d6dbcc4,0xbcc43d6d,0xbcc4bd6d,0x3d6d3cc4,
0x3d0e3d55,0xbd7b3c48,0x3c48bd7b,0x3d553d0e,0xbd800000,0x3cc4bd6d,0x3d353d35,0xbd6d3cc4,0x3d55bd0e,0x3c483d7b,0xbd7bbc48,0x3d0ebd55,0x80003d80,0xbd6dbcc4,0x3d35bd35,0x3cc43d6d,
0xbd0ebd55,0x3d7bbc48,0xbc483d7b,0xbd55bd0e,0x3d800000,0xbcc43d6d,0xbd35bd35,0x3d6dbcc4,0xbd553d0e,0xbc48bd7b,0x3d7b3c48,0xbd0e3d55,0x8000bd80,0x3d6d3cc4,0xbd353d35,0xbcc4bd6d,
0x80003d80,0xbd800000,0x8000bd80,0x3d800000,0x3d35bd35,0x3d353d35,0xbd353d35,0xbd35bd35,0x80003d80,0xbd800000,0x8000bd80,0x3d800000,0x3d35bd35,0x3d353d35,0xbd353d35,0xbd35bd35,
0x80003d80,0xbd800000,0x8000bd80,0x3d800000,0x3d35bd35,0x3d353d35,0xbd353d35,0xbd35bd35,0x80003d80,0xbd800000,0x8000bd80,0x3d800000,0x3d35bd35,0x3d353d35,0xbd353d35,0xbd35bd35,
0xbd0e3d55,0xbd7bbc48,0xbc48bd7b,0x3d55bd0e,0x8000bd80,0x3d6dbcc4,0x3d353d35,0xbcc43d6d,0x3d553d0e,0xbc483d7b,0xbd7b3c48,0xbd0ebd55,0xbd800000,0xbcc4bd6d,0x3d35bd35,0x3d6d3cc4,
0x3d0ebd55,0x3d7b3c48,0x3c483d7b,0xbd553d0e,0x80003d80,0xbd6d3cc4,0xbd35bd35,0x3cc4bd6d,0xbd55bd0e,0x3c48bd7b,0x3d7bbc48,0x3d0e3d55,0x3d800000,0x3cc43d6d,0xbd353d35,0xbd6dbcc4,
0x8000bd80,0x3d35bd35,0x3d800000,0x3d353d35,0xbcc43d6d,0xbd6d3cc4,0xbd6dbcc4,0xbcc4bd6d,0x80003d80,0xbd353d35,0xbd800000,0xbd35bd35,0x3cc4bd6d,0x3d6dbcc4,0x3d6d3cc4,0x3cc43d6d,
0x8000bd80,0x3d35bd35,0x3d800000,0x3d353d35,0xbcc43d6d,0xbd6d3cc4,0xbd6dbcc4,0xbcc4bd6d,0x80003d80,0xbd353d35,0xbd800000,0xbd35bd35,0x3cc4bd6d,0x3d6dbcc4,0x3d6d3cc4,0x3cc43d6d,
0xbd7bbc48,0xbd55bd0e,0xbd0ebd55,0xbc48bd7b,0x3d800000,0x3d6d3cc4,0x3d353d35,0x3cc43d6d,0xbc483d7b,0xbd0e3d55,0xbd553d0e,0xbd7b3c48,0x8000bd80,0x3cc4bd6d,0x3d35bd35,0x3d6dbcc4,
0x3d7b3c48,0x3d553d0e,0x3d0e3d55,0x3c483d7b,0xbd800000,0xbd6dbcc4,0xbd35bd35,0xbcc4bd6d,0x3c48bd7b,0x3d0ebd55,0x3d55bd0e,0x3d7bbc48,0x80003d80,0xbcc43d6d,0xbd353d35,0xbd6d3cc4,
0x3d800000,0xbd800000,0x3d800000,0xbd800000,0xbd80,0x3d80,0xbd80,0x3d80,0x3d800000,0xbd800000,0x3d800000,0xbd800000,0xbd80,0x3d80,0xbd80,0x3d80,
0x3d800000,0xbd800000,0x3d800000,0xbd800000,0xbd80,0x3d80,0xbd80,0x3d80,0x3d800000,0xbd800000,0x3d800000,0xbd800000,0xbd80,0x3d80,0xbd80,0x3d80,
0xbc48bd7b,0x3d0e3d55,0xbd55bd0e,0x3d7b3c48,0x3d800000,0xbd6d3cc4,0x3d35bd35,0xbcc43d6d,0xbd7b3c48,0x3d55bd0e,0xbd0e3d55,0x3c48bd7b,0xbd80,0x3cc43d6d,0xbd35bd35,0x3d6d3cc4,
0x3c483d7b,0xbd0ebd55,0x3d553d0e,0xbd7bbc48,0xbd800000,0x3d6dbcc4,0xbd353d35,0x3cc4bd6d,0x3d7bbc48,0xbd553d0e,0x3d0ebd55,0xbc483d7b,0x3d80,0xbcc4bd6d,0x3d353d35,0xbd6dbcc4,
0xbd800000,0x3d35bd35,0x3d80,0xbd35bd35,0x3cc43d6d,0xbd6dbcc4,0x3d6dbcc4,0xbcc43d6d,0x3d800000,0xbd353d35,0xbd80,0x3d353d35,0xbcc4bd6d,0x3d6d3cc4,0xbd6d3cc4,0x3cc4bd6d,
0xbd800000,0x3d35bd35,0x3d80,0xbd35bd35,0x3cc43d6d,0xbd6dbcc4,0x3d6dbcc4,0xbcc43d6d,0x3d800000,0xbd353d35,0xbd80,0x3d353d35,0xbcc4bd6d,0x3d6d3cc4,0xbd6d3cc4,0x3cc4bd6d,
0x3d55bd0e,0x3c483d7b,0xbd7bbc48,0x3d0ebd55,0x3d80,0xbd6dbcc4,0x3d35bd35,0x3cc43d6d,0xbd0ebd55,0x3d7bbc48,0xbc483d7b,0xbd55bd0e,0x3d800000,0xbcc43d6d,0xbd35bd35,0x3d6dbcc4,
0xbd553d0e,0xbc48bd7b,0x3d7b3c48,0xbd0e3d55,0xbd80,0x3d6d3cc4,0xbd353d35,0xbcc4bd6d,0x3d0e3d55,0xbd7b3c48,0x3c48bd7b,0x3d553d0e,0xbd800000,0x3cc4bd6d,0x3d353d35,0xbd6d3cc4,
0x3d800000,0x3d80,0xbd800000,0xbd80,0xbd35bd35,0x3d35bd35,0x3d353d35,0xbd353d35,0x3d800000,0x3d80,0xbd800000,0xbd80,0xbd35bd35,0x3d35bd35,0x3d353d35,0xbd353d35,
0x3d800000,0x3d80,0xbd800000,0xbd80,0xbd35bd35,0x3d35bd35,0x3d353d35,0xbd353d35,0x3d800000,0x3d80,0xbd800000,0xbd80,0xbd35bd35,0x3d35bd35,0x3d353d35,0xbd353d35,
0x3d553d0e,0xbc483d7b,0xbd7b3c48,0xbd0ebd55,0xbd800000,0xbcc4bd6d,0x3d35bd35,0x3d6d3cc4,0x3d0ebd55,0x3d7b3c48,0x3c483d7b,0xbd553d0e,0x3d80,0xbd6d3cc4,0xbd35bd35,0x3cc4bd6d,
0xbd55bd0e,0x3c48bd7b,0x3d7bbc48,0x3d0e3d55,0x3d800000,0x3cc43d6d,0xbd353d35,0xbd6dbcc4,0xbd0e3d55,0xbd7bbc48,0xbc48bd7b,0x3d55bd0e,0xbd80,0x3d6dbcc4,0x3d353d35,0xbcc43d6d,
0xbd800000,0xbd35bd35,0xbd80,0x3d35bd35,0x3d6d3cc4,0x3cc43d6d,0xbcc43d6d,0xbd6d3cc4,0x3d800000,0x3d353d35,0x3d80,0xbd353d35,0xbd6dbcc4,0xbcc4bd6d,0x3cc4bd6d,0x3d6dbcc4,
0xbd800000,0xbd35bd35,0xbd80,0x3d35bd35,0x3d6d3cc4,0x3cc43d6d,0xbcc43d6d,0xbd6d3cc4,0x3d800000,0x3d353d35,0x3d80,0xbd353d35,0xbd6dbcc4,0xbcc4bd6d,0x3cc4bd6d,0x3d6dbcc4,
0xbc483d7b,0xbd0e3d55,0xbd553d0e,0xbd7b3c48,0xbd80,0x3cc4bd6d,0x3d35bd35,0x3d6dbcc4,0x3d7b3c48,0x3d553d0e,0x3d0e3d55,0x3c483d7b,0xbd800000,0xbd6dbcc4,0xbd35bd35,0xbcc4bd6d,
0x3c48bd7b,0x3d0ebd55,0x3d55bd0e,0x3d7bbc48,0x3d80,0xbcc43d6d,0xbd353d35,0xbd6d3cc4,0xbd7bbc48,0xbd55bd0e,0xbd0ebd55,0xbc48bd7b,0x3d800000,0x3d6d3cc4,0x3d353d35,0x3cc43d6d,
0x80003d80,0x80003d80,0x80003d80,0x80003d80,0x8000bd80,0x8000bd80,0x8000bd80,0x8000bd80,0x80003d80,0x80003d80,0x80003d80,0x80003d80,0x8000bd80,0x8000bd80,0x8000bd80,0x8000bd80,
0x80003d80,0x80003d80,0x80003d80,0x80003d80,0x8000bd80,0x8000bd80,0x8000bd80,0x8000bd80,0x80003d80,0x80003d80,0x80003d80,0x80003d80,0x8000bd80,0x8000bd80,0x8000bd80,0x8000bd80,
0xbc48bd7b,0xbd0ebd55,0xbd55bd0e,0xbd7bbc48,0x80003d80,0x3cc43d6d,0x3d353d35,0x3d6d3cc4,0xbd7b3c48,0xbd553d0e,0xbd0e3d55,0xbc483d7b,0x3d800000,0x3d6dbcc4,0x3d35bd35,0x3cc4bd6d,
0x3c483d7b,0x3d0e3d55,0x3d553d0e,0x3d7b3c48,0x8000bd80,0xbcc4bd6d,0xbd35bd35,0xbd6dbcc4,0x3d7bbc48,0x3d55bd0e,0x3d0ebd55,0x3c48bd7b,0xbd800000,0xbd6d3cc4,0xbd353d35,0xbcc43d6d,
0x8000bd80,0xbd35bd35,0xbd800000,0xbd353d35,0x3cc43d6d,0x3d6d3cc4,0x3d6dbcc4,0x3cc4bd6d,0x80003d80,0x3d353d35,0x3d800000,0x3d35bd35,0xbcc4bd6d,0xbd6dbcc4,0xbd6d3cc4,0xbcc43d6d,
0x8000bd80,0xbd35bd35,0xbd800000,0xbd353d35,0x3cc43d6d,0x3d6d3cc4,0x3d6dbcc4,0x3cc4bd6d,0x80003d80,0x3d353d35,0x3d800000,0x3d35bd35,0xbcc4bd6d,0xbd6dbcc4,0xbd6d3cc4,0xbcc43d6d,
0x3d55bd0e,0xbc48bd7b,0xbd7bbc48,0xbd0e3d55,0xbd800000,0xbcc43d6d,0x3d353d35,0x3d6dbcc4,0xbd0ebd55,0xbd7b3c48,0xbc483d7b,0x3d553d0e,0x80003d80,0x3d6d3cc4,0x3d35bd35,0xbcc4bd6d,
0xbd553d0e,0x3c483d7b,0x3d7b3c48,0x3d0ebd55,0x3d800000,0x3cc4bd6d,0xbd35bd35,0xbd6d3cc4,0x3d0e3d55,0x3d7bbc48,0x3c48bd7b,0xbd55bd0e,0x8000bd80,0xbd6dbcc4,0xbd353d35,0x3cc43d6d,
0x80003d80,0x3d800000,0x8000bd80,0xbd800000,0xbd35bd35,0xbd353d35,0x3d353d35,0x3d35bd35,0x80003d80,0x3d800000,0x8000bd80,0xbd800000,0xbd35bd35,0xbd353d35,0x3d353d35,0x3d35bd35,
0x80003d80,0x3d800000,0x8000bd80,0xbd800000,0xbd35bd35,0xbd353d35,0x3d353d35,0x3d35bd35,0x80003d80,0x3d800000,0x8000bd80,0xbd800000,0xbd35bd35,0xbd353d35,0x3d353d35,0x3d35bd35,
0x3d553d0e,0x3c48bd7b,0xbd7b3c48,0x3d0e3d55,0x8000bd80,0xbd6d3cc4,0x3d353d35,0x3cc4bd6d,0x3d0ebd55,0xbd7bbc48,0x3c483d7b,0x3d55bd0e,0xbd800000,0x3cc43d6d,0x3d35bd35,0xbd6dbcc4,
0xbd55bd0e,0xbc483d7b,0x3d7bbc48,0xbd0ebd55,0x80003d80,0x3d6dbcc4,0xbd35bd35,0xbcc43d6d,0xbd0e3d55,0x3d7b3c48,0xbc48bd7b,0xbd553d0e,0x3d800000,0xbcc4bd6d,0xbd353d35,0x3d6d3cc4,
0x8000bd80,0xbd353d35,0x3d800000,0xbd35bd35,0x3d6d3cc4,0xbcc4bd6d,0xbcc43d6d,0x3d6dbcc4,0x80003d80,0x3d35bd35,0xbd800000,0x3d353d35,0xbd6dbcc4,0x3cc43d6d,0x3cc4bd6d,0xbd6d3cc4,
0x8000bd80,0xbd353d35,0x3d800000,0xbd35bd35,0x3d6d3cc4,0xbcc4bd6d,0xbcc43d6d,0x3d6dbcc4,0x80003d80,0x3d35bd35,0xbd800000,0x3d353d35,0xbd6dbcc4,0x3cc43d6d,0x3cc4bd6d,0xbd6d3cc4,
0xbc483d7b,0x3d0ebd55,0xbd553d0e,0x3d7bbc48,0x3d800000,0xbd6dbcc4,0x3d353d35,0xbcc4bd6d,0x3d7b3c48,0xbd55bd0e,0x3d0e3d55,0xbc48bd7b,0x8000bd80,0xbcc43d6d,0x3d35bd35,0xbd6d3cc4,
0x3c48bd7b,0xbd0e3d55,0x3d55bd0e,0xbd7b3c48,0xbd800000,0x3d6d3cc4,0xbd35bd35,0x3cc43d6d,0xbd7bbc48,0x3d553d0e,0xbd0ebd55,0x3c483d7b,0x80003d80,0x3cc4bd6d,0xbd353d35,0x3d6dbcc4,
0x3d800000,0x3d800000,0x3d800000,0x3d800000,0xbd800000,0xbd800000,0xbd800000,0xbd800000,0x3d800000,0x3d800000,0x3d800000,0x3d800000,0xbd800000,0xbd800000,0xbd800000,0xbd800000,
0x3d800000,0x3d800000,0x3d800000,0x3d800000,0xbd800000,0xbd800000,0xbd800000,0xbd800000,0x3d800000,0x3d800000,0x3d800000,0x3d800000,0xbd800000,0xbd800000,0xbd800000,0xbd800000,
0xbd7b3c48,0xbd553d0e,0xbd0e3d55,0xbc483d7b,0x3d800000,0x3d6dbcc4,0x3d35bd35,0x3cc4bd6d,0x3c483d7b,0x3d0e3d55,0x3d553d0e,0x3d7b3c48,0xbd80,0xbcc4bd6d,0xbd35bd35,0xbd6dbcc4,
0x3d7bbc48,0x3d55bd0e,0x3d0ebd55,0x3c48bd7b,0xbd800000,0xbd6d3cc4,0xbd353d35,0xbcc43d6d,0xbc48bd7b,0xbd0ebd55,0xbd55bd0e,0xbd7bbc48,0x3d80,0x3cc43d6d,0x3d353d35,0x3d6d3cc4,
0xbd800000,0xbd353d35,0x3d80,0x3d353d35,0x3d6dbcc4,0x3cc4bd6d,0xbcc4bd6d,0xbd6dbcc4,0x3d800000,0x3d35bd35,0xbd80,0xbd35bd35,0xbd6d3cc4,0xbcc43d6d,0x3cc43d6d,0x3d6d3cc4,
0xbd800000,0xbd353d35,0x3d80,0x3d353d35,0x3d6dbcc4,0x3cc4bd6d,0xbcc4bd6d,0xbd6dbcc4,0x3d800000,0x3d35bd35,0xbd80,0xbd35bd35,0xbd6d3cc4,0xbcc43d6d,0x3cc43d6d,0x3d6d3cc4,
0xbd0ebd55,0xbd7b3c48,0xbc483d7b,0x3d553d0e,0x3d80,0x3d6d3cc4,0x3d35bd35,0xbcc4bd6d,0xbd553d0e,0x3c483d7b,0x3d7b3c48,0x3d0ebd55,0x3d800000,0x3cc4bd6d,0xbd35bd35,0xbd6d3cc4,
0x3d0e3d55,0x3d7bbc48,0x3c48bd7b,0xbd55bd0e,0xbd80,0xbd6dbcc4,0xbd353d35,0x3cc43d6d,0x3d55bd0e,0xbc48bd7b,0xbd7bbc48,0xbd0e3d55,0xbd800000,0xbcc43d6d,0x3d353d35,0x3d6dbcc4,
0x3d800000,0xbd80,0xbd800000,0x3d80,0xbd353d35,0x3d353d35,0x3d35bd35,0xbd35bd35,0x3d800000,0xbd80,0xbd800000,0x3d80,0xbd353d35,0x3d353d35,0x3d35bd35,0xbd35bd35,
0x3d800000,0xbd80,0xbd800000,0x3d80,0xbd353d35,0x3d353d35,0x3d35bd35,0xbd35bd35,0x3d800000,0xbd80,0xbd800000,0x3d80,0xbd353d35,0x3d353d35,0x3d35bd35,0xbd35bd35,
0x3d0ebd55,0xbd7bbc48,0x3c483d7b,0x3d55bd0e,0xbd800000,0x3cc43d6d,0x3d35bd35,0xbd6dbcc4,0xbd55bd0e,0xbc483d7b,0x3d7bbc48,0xbd0ebd55,0x3d80,0x3d6dbcc4,0xbd35bd35,0xbcc43d6d,
0xbd0e3d55,0x3d7b3c48,0xbc48bd7b,0xbd553d0e,0x3d800000,0xbcc4bd6d,0xbd353d35,0x3d6d3cc4,0x3d553d0e,0x3c48bd7b,0xbd7b3c48,0x3d0e3d55,0xbd80,0xbd6d3cc4,0x3d353d35,0x3cc4bd6d,
0xbd800000,0x3d353d35,0xbd80,0xbd353d35,0x3cc4bd6d,0xbd6d3cc4,0x3d6d3cc4,0xbcc4bd6d,0x3d800000,0xbd35bd35,0x3d80,0x3d35bd35,0xbcc43d6d,0x3d6dbcc4,0xbd6dbcc4,0x3cc43d6d,
0xbd800000,0x3d353d35,0xbd80,0xbd353d35,0x3cc4bd6d,0xbd6d3cc4,0x3d6d3cc4,0xbcc4bd6d,0x3d800000,0xbd35bd35,0x3d80,0x3d35bd35,0xbcc43d6d,0x3d6dbcc4,0xbd6dbcc4,0x3cc43d6d,
0x3d7b3c48,0xbd55bd0e,0x3d0e3d55,0xbc48bd7b,0xbd80,0xbcc43d6d,0x3d35bd35,0xbd6d3cc4,0x3c48bd7b,0xbd0e3d55,0x3d55bd0e,0xbd7b3c48,0xbd800000,0x3d6d3cc4,0xbd35bd35,0x3cc43d6d,
0xbd7bbc48,0x3d553d0e,0xbd0ebd55,0x3c483d7b,0x3d80,0x3cc4bd6d,0xbd353d35,0x3d6dbcc4,0xbc483d7b,0x3d0ebd55,0xbd553d0e,0x3d7bbc48,0x3d800000,0xbd6dbcc4,0x3d353d35,0xbcc4bd6d,
0x80003d80,0x8000bd80,0x80003d80,0x8000bd80,0xbd800000,0x3d800000,0xbd800000,0x3d800000,0x80003d80,0x8000bd80,0x80003d80,0x8000bd80,0xbd800000,0x3d800000,0xbd800000,0x3d800000,
0x80003d80,0x8000bd80,0x80003d80,0x8000bd80,0xbd800000,0x3d800000,0xbd800000,0x3d800000,0x80003d80,0x8000bd80,0x80003d80,0x8000bd80,0xbd800000,0x3d800000,0xbd800000,0x3d800000,
0xbd7b3c48,0x3d55bd0e,0xbd0e3d55,0x3c48bd7b,0x80003d80,0xbcc4bd6d,0x3d353d35,0xbd6dbcc4,0x3c483d7b,0xbd0ebd55,0x3d553d0e,0xbd7bbc48,0x3d800000,0xbd6d3cc4,0x3d35bd35,0xbcc43d6d,
0x3d7bbc48,0xbd553d0e,0x3d0ebd55,0xbc483d7b,0x8000bd80,0x3cc43d6d,0xbd35bd35,0x3d6d3cc4,0xbc48bd7b,0x3d0e3d55,0xbd55bd0e,0x3d7b3c48,0xbd800000,0x3d6dbcc4,0xbd353d35,0x3cc4bd6d,
0x8000bd80,0x3d353d35,0xbd800000,0x3d35bd35,0x3d6dbcc4,0xbcc43d6d,0xbcc4bd6d,0x3d6d3cc4,0x80003d80,0xbd35bd35,0x3d800000,0xbd353d35,0xbd6d3cc4,0x3cc4bd6d,0x3cc43d6d,0xbd6dbcc4,
0x8000bd80,0x3d353d35,0xbd800000,0x3d35bd35,0x3d6dbcc4,0xbcc43d6d,0xbcc4bd6d,0x3d6d3cc4,0x80003d80,0xbd35bd35,0x3d800000,0xbd353d35,0xbd6d3cc4,0x3cc4bd6d,0x3cc43d6d,0xbd6dbcc4,
0xbd0ebd55,0x3d7bbc48,0xbc483d7b,0xbd55bd0e,0xbd800000,0x3cc4bd6d,0x3d353d35,0xbd6d3cc4,0xbd553d0e,0xbc48bd7b,0x3d7b3c48,0xbd0e3d55,0x80003d80,0xbd6dbcc4,0x3d35bd35,0x3cc43d6d,
0x3d0e3d55,0xbd7b3c48,0x3c48bd7b,0x3d553d0e,0x3d800000,0xbcc43d6d,0xbd35bd35,0x3d6dbcc4,0x3d55bd0e,0x3c483d7b,0xbd7bbc48,0x3d0ebd55,0x8000bd80,0x3d6d3cc4,0xbd353d35,0xbcc4bd6d,
0x80003d80,0xbd800000,0x8000bd80,0x3d800000,0xbd353d35,0xbd35bd35,0x3d35bd35,0x3d353d35,0x80003d80,0xbd800000,0x8000bd80,0x3d800000,0xbd353d35,0xbd35bd35,0x3d35bd35,0x3d353d35,
0x80003d80,0xbd800000,0x8000bd80,0x3d800000,0xbd353d35,0xbd35bd35,0x3d35bd35,0x3d353d35,0x80003d80,0xbd800000,0x8000bd80,0x3d800000,0xbd353d35,0xbd35bd35,0x3d35bd35,0x3d353d35,
0x3d0ebd55,0x3d7b3c48,0x3c483d7b,0xbd553d0e,0x8000bd80,0x3d6dbcc4,0x3d353d35,0xbcc43d6d,0xbd55bd0e,0x3c48bd7b,0x3d7bbc48,0x3d0e3d55,0xbd800000,0xbcc4bd6d,0x3d35bd35,0x3d6d3cc4,
0xbd0e3d55,0xbd7bbc48,0xbc48bd7b,0x3d55bd0e,0x80003d80,0xbd6d3cc4,0xbd35bd35,0x3cc4bd6d,0x3d553d0e,0xbc483d7b,0xbd7b3c48,0xbd0ebd55,0x3d800000,0x3cc43d6d,0xbd353d35,0xbd6dbcc4,
0x8000bd80,0x3d35bd35,0x3d800000,0x3d353d35,0x3cc4bd6d,0x3d6dbcc4,0x3d6d3cc4,0x3cc43d6d,0x80003d80,0xbd353d35,0xbd800000,0xbd35bd35,0xbcc43d6d,0xbd6d3cc4,0xbd6dbcc4,0xbcc4bd6d,
0x8000bd80,0x3d35bd35,0x3d800000,0x3d353d35,0x3cc4bd6d,0x3d6dbcc4,0x3d6d3cc4,0x3cc43d6d,0x80003d80,0xbd353d35,0xbd800000,0xbd35bd35,0xbcc43d6d,0xbd6d3cc4,0xbd6dbcc4,0xbcc4bd6d,
0x3d7b3c48,0x3d553d0e,0x3d0e3d55,0x3c483d7b,0x3d800000,0x3d6d3cc4,0x3d353d35,0x3cc43d6d,0x3c48bd7b,0x3d0ebd55,0x3d55bd0e,0x3d7bbc48,0x8000bd80,0x3cc4bd6d,0x3d35bd35,0x3d6dbcc4,
0xbd7bbc48,0xbd55bd0e,0xbd0ebd55,0xbc48bd7b,0xbd800000,0xbd6dbcc4,0xbd35bd35,0xbcc4bd6d,0xbc483d7b,0xbd0e3d55,0xbd553d0e,0xbd7b3c48,0x80003d80,0xbcc43d6d,0xbd353d35,0xbd6d3cc4,
0x3d800000,0xbd800000,0x3d800000,0xbd800000,0x3d80,0xbd80,0x3d80,0xbd80,0x3d800000,0xbd800000,0x3d800000,0xbd800000,0x3d80,0xbd80,0x3d80,0xbd80,
0x3d800000,0xbd800000,0x3d800000,0xbd800000,0x3d80,0xbd80,0x3d80,0xbd80,0x3d800000,0xbd800000,0x3d800000,0xbd800000,0x3d80,0xbd80,0x3d80,0xbd80,
0x3c483d7b,0xbd0ebd55,0x3d553d0e,0xbd7bbc48,0x3d800000,0xbd6d3cc4,0x3d35bd35,0xbcc43d6d,0x3d7bbc48,0xbd553d0e,0x3d0ebd55,0xbc483d7b,0xbd80,0x3cc43d6d,0xbd35bd35,0x3d6d3cc4,
0xbc48bd7b,0x3d0e3d55,0xbd55bd0e,0x3d7b3c48,0xbd800000,0x3d6dbcc4,0xbd353d35,0x3cc4bd6d,0xbd7b3c48,0x3d55bd0e,0xbd0e3d55,0x3c48bd7b,0x3d80,0xbcc4bd6d,0x3d353d35,0xbd6dbcc4,
0xbd800000,0x3d35bd35,0x3d80,0xbd35bd35,0xbcc4bd6d,0x3d6d3cc4,0xbd6d3cc4,0x3cc4bd6d,0x3d800000,0xbd353d35,0xbd80,0x3d353d35,0x3cc43d6d,0xbd6dbcc4,0x3d6dbcc4,0xbcc43d6d,
0xbd800000,0x3d35bd35,0x3d80,0xbd35bd35,0xbcc4bd6d,0x3d6d3cc4,0xbd6d3cc4,0x3cc4bd6d,0x3d800000,0xbd353d35,0xbd80,0x3d353d35,0x3cc43d6d,0xbd6dbcc4,0x3d6dbcc4,0xbcc43d6d,
0xbd553d0e,0xbc48bd7b,0x3d7b3c48,0xbd0e3d55,0x3d80,0xbd6dbcc4,0x3d35bd35,0x3cc43d6d,0x3d0e3d55,0xbd7b3c48,0x3c48bd7b,0x3d553d0e,0x3d800000,0xbcc43d6d,0xbd35bd35,0x3d6dbcc4,
0x3d55bd0e,0x3c483d7b,0xbd7bbc48,0x3d0ebd55,0xbd80,0x3d6d3cc4,0xbd353d35,0xbcc4bd6d,0xbd0ebd55,0x3d7bbc48,0xbc483d7b,0xbd55bd0e,0xbd800000,0x3cc4bd6d,0x3d353d35,0xbd6d3cc4,
0x3d800000,0x3d80,0xbd800000,0xbd80,0x3d353d35,0xbd353d35,0xbd35bd35,0x3d35bd35,0x3d800000,0x3d80,0xbd800000,0xbd80,0x3d353d35,0xbd353d35,0xbd35bd35,0x3d35bd35,
0x3d800000,0x3d80,0xbd800000,0xbd80,0x3d353d35,0xbd353d35,0xbd35bd35,0x3d35bd35,0x3d800000,0x3d80,0xbd800000,0xbd80,0x3d353d35,0xbd353d35,0xbd35bd35,0x3d35bd35,
0xbd55bd0e,0x3c48bd7b,0x3d7bbc48,0x3d0e3d55,0xbd800000,0xbcc4bd6d,0x3d35bd35,0x3d6d3cc4,0xbd0e3d55,0xbd7bbc48,0xbc48bd7b,0x3d55bd0e,0x3d80,0xbd6d3cc4,0xbd35bd35,0x3cc4bd6d,
0x3d553d0e,0xbc483d7b,0xbd7b3c48,0xbd0ebd55,0x3d800000,0x3cc43d6d,0xbd353d35,0xbd6dbcc4,0x3d0ebd55,0x3d7b3c48,0x3c483d7b,0xbd553d0e,0xbd80,0x3d6dbcc4,0x3d353d35,0xbcc43d6d,
0xbd800000,0xbd35bd35,0xbd80,0x3d35bd35,0xbd6dbcc4,0xbcc4bd6d,0x3cc4bd6d,0x3d6dbcc4,0x3d800000,0x3d353d35,0x3d80,0xbd353d35,0x3d6d3cc4,0x3cc43d6d,0xbcc43d6d,0xbd6d3cc4,
0xbd800000,0xbd35bd35,0xbd80,0x3d35bd35,0xbd6dbcc4,0xbcc4bd6d,0x3cc4bd6d,0x3d6dbcc4,0x3d800000,0x3d353d35,0x3d80,0xbd353d35,0x3d6d3cc4,0x3cc43d6d,0xbcc43d6d,0xbd6d3cc4,
0x3c48bd7b,0x3d0ebd55,0x3d55bd0e,0x3d7bbc48,0xbd80,0x3cc4bd6d,0x3d35bd35,0x3d6dbcc4,0xbd7bbc48,0xbd55bd0e,0xbd0ebd55,0xbc48bd7b,0xbd800000,0xbd6dbcc4,0xbd35bd35,0xbcc4bd6d,
0xbc483d7b,0xbd0e3d55,0xbd553d0e,0xbd7b3c48,0x3d80,0xbcc43d6d,0xbd353d35,0xbd6d3cc4,0x3d7b3c48,0x3d553d0e,0x3d0e3d55,0x3c483d7b,0x3d800000,0x3d6d3cc4,0x3d353d35,0x3cc43d6d,
0x3f003f00,0xbf003f00,0x3f003f00,0xbf003f00,0x3f003f00,0xbf003f00,0x3f003f00,0xbf003f00,0x3f003f00,0xbf003f00,0x3f003f00,0xbf003f00,0x3f003f00,0xbf003f00,0x3f003f00,0xbf003f00,
0x3eff3f00,0xbd490000,0x3ea23eb5,0xbec6beb5,0x3ef53efb,0xbe15bdc8,0x3e713e8e,0xbee2bed5,0x3ee23eed,0xbe71be44,0x3e153e44,0xbef5beed,0x3ec63ed5,0xbea2be8e,0x3d493dc8,0xbeffbefb,
0x3efb3f00,0xbdc80000,0xbdc80000,0xbefbbf00,0x3ed53eed,0xbe8ebe44,0xbe8ebe44,0xbed5beed,0x3e8e3eb5,0xbed5beb5,0xbed5beb5,0xbe8ebeb5,0x3dc83e44,0xbefbbeed,0xbefbbeed,0xbdc8be44,
0x3ef53f00,0xbe150000,0xbee2beb5,0xbe71beb5,0x3ea23ed5,0xbec6be8e,0xbeffbefb,0x3d49bdc8,0x3d493e44,0xbeffbeed,0xbec6beed,0x3ea23e44,0xbe71bdc8,0xbee2befb,0xbe15be8e,0x3ef53ed5,
0x3eed3f00,0xbe440000,0xbeedbf00,0x3e440000,0x3e443eb5,0xbeedbeb5,0xbe44beb5,0x3eed3eb5,0xbe440000,0xbeedbf00,0x3e440000,0x3eed3f00,0xbeedbeb5,0xbe44beb5,0x3eed3eb5,0x3e443eb5,
0x3ee23f00,0xbe710000,0xbe15beb5,0x3ef53eb5,0x3d493e8e,0xbeffbed5,0x3ea23dc8,0x3ec63efb,0xbec6be44,0xbea2beed,0x3eff3eed,0xbd493e44,0xbef5befb,0x3e15bdc8,0x3e713ed5,0xbee2be8e,
0x3ed53f00,0xbe8e0000,0x3e8e0000,0x3ed53f00,0xbdc83e44,0xbefbbeed,0x3efb3eed,0xbdc83e44,0xbefbbeb5,0xbdc8beb5,0x3dc83eb5,0xbefbbeb5,0xbe8ebeed,0x3ed53e44,0xbed5be44,0xbe8ebeed,
0x3ec63f00,0xbea20000,0x3eff3eb5,0x3d493eb5,0xbe713dc8,0xbee2befb,0x3e153ed5,0xbef5be8e,0xbef5beed,0x3e15be44,0xbee2be44,0xbe71beed,0x3d49be8e,0x3eff3ed5,0xbea2befb,0x3ec63dc8,
0x3eb53f00,0xbeb50000,0x3eb53f00,0xbeb50000,0xbeb50000,0xbeb5bf00,0xbeb50000,0xbeb5bf00,0xbeb5bf00,0x3eb50000,0xbeb5bf00,0x3eb50000,0x3eb50000,0x3eb53f00,0x3eb50000,0x3eb53f00,
0x3ea23f00,0xbec60000,0xbd493eb5,0xbeffbeb5,0xbee2bdc8,0xbe71befb,0xbef5bed5,0x3e15be8e,0xbe15beed,0x3ef53e44,0x3e71be44,0x3ee23eed,0x3eff3e8e,0x3d493ed5,0x3ec63efb,0xbea23dc8,
0x3e8e3f00,0xbed50000,0xbed50000,0xbe8ebf00,0xbefbbe44,0xbdc8beed,0xbdc8beed,0x3efb3e44,0x3dc8beb5,0x3efb3eb5,0x3efb3eb5,0xbdc83eb5,0x3ed53eed,0xbe8e3e44,0xbe8e3e44,0xbed5beed,
0x3e713f00,0xbee20000,0xbef5beb5,0x3e15beb5,0xbeffbe8e,0x3d49bed5,0x3ec6bdc8,0x3ea23efb,0x3ea2be44,0x3ec63eed,0x3d493eed,0xbeffbe44,0x3e153efb,0xbef5bdc8,0xbee2bed5,0x3e71be8e,
0x3e443f00,0xbeed0000,0xbe44bf00,0x3eed0000,0xbeedbeb5,0x3e44beb5,0x3eed3eb5,0xbe443eb5,0x3eed0000,0x3e443f00,0xbeed0000,0xbe44bf00,0xbe443eb5,0xbeedbeb5,0x3e44beb5,0x3eed3eb5,
0x3e153f00,0xbef50000,0x3e71beb5,0x3ee23eb5,0xbec6bed5,0x3ea2be8e,0x3d493efb,0xbeffbdc8,0x3eff3e44,0xbd493eed,0xbea2beed,0x3ec6be44,0xbee23dc8,0xbe71befb,0x3ef53e8e,0xbe153ed5,
0x3dc83f00,0xbefb0000,0x3efb0000,0x3dc83f00,0xbe8ebeed,0x3ed5be44,0xbed53e44,0xbe8ebeed,0x3ed53eb5,0xbe8e3eb5,0x3e8ebeb5,0x3ed53eb5,0xbefbbe44,0x3dc8beed,0xbdc83eed,0xbefbbe44,
0x3d493f00,0xbeff0000,0x3ec63eb5,0xbea23eb5,0xbe15befb,0x3ef5bdc8,0xbee2be8e,0x3e71bed5,0x3e713eed,0xbee23e44,0x3ef53e44,0xbe153eed,0xbea2bed5,0x3ec6be8e,0xbeffbdc8,0x3d49befb,
0x3f00,0xbf000000,0x3f00,0xbf000000,0xbf00,0x3f000000,0xbf00,0x3f000000,0x3f00,0xbf000000,0x3f00,0xbf000000,0xbf00,0x3f000000,0xbf00,0x3f000000,
0xbd493f00,0xbeff0000,0xbec63eb5,0xbea2beb5,0x3e15befb,0x3ef53dc8,0x3ee2be8e,0x3e713ed5,0xbe713eed,0xbee2be44,0xbef53e44,0xbe15beed,0x3ea2bed5,0x3ec63e8e,0x3effbdc8,0x3d493efb,
0xbdc83f00,0xbefb0000,0xbefb0000,0x3dc8bf00,0x3e8ebeed,0x3ed53e44,0x3ed53e44,0xbe8e3eed,0xbed53eb5,0xbe8ebeb5,0xbe8ebeb5,0x3ed5beb5,0x3efbbe44,0x3dc83eed,0x3dc83eed,0xbefb3e44,
0xbe153f00,0xbef50000,0xbe71beb5,0x3ee2beb5,0x3ec6bed5,0x3ea23e8e,0xbd493efb,0xbeff3dc8,0xbeff3e44,0xbd49beed,0x3ea2beed,0x3ec63e44,0x3ee23dc8,0xbe713efb,0xbef53e8e,0xbe15bed5,
0xbe443f00,0xbeed0000,0x3e44bf00,0x3eed0000,0x3eedbeb5,0x3e443eb5,0xbeed3eb5,0xbe44beb5,0xbeed0000,0x3e44bf00,0x3eed0000,0xbe443f00,0x3e443eb5,0xbeed3eb5,0xbe44beb5,0x3eedbeb5,
0xbe713f00,0xbee20000,0x3ef5beb5,0x3e153eb5,0x3effbe8e,0x3d493ed5,0xbec6bdc8,0x3ea2befb,0xbea2be44,0x3ec6beed,0xbd493eed,0xbeff3e44,0xbe153efb,0xbef53dc8,0x3ee2bed5,0x3e713e8e,
0xbe8e3f00,0xbed50000,0x3ed50000,0xbe8e3f00,0x3efbbe44,0xbdc83eed,0x3dc8beed,0x3efbbe44,0xbdc8beb5,0x3efbbeb5,0xbefb3eb5,0xbdc8beb5,0xbed53eed,0xbe8ebe44,0x3e8e3e44,0xbed53eed,
0xbea23f00,0xbec60000,0x3d493eb5,0xbeff3eb5,0x3ee2bdc8,0xbe713efb,0x3ef5bed5,0x3e153e8e,0x3e15beed,0x3ef5be44,0xbe71be44,0x3ee2beed,0xbeff3e8e,0x3d49bed5,0xbec63efb,0xbea2bdc8,
0xbeb53f00,0xbeb50000,0xbeb53f00,0xbeb50000,0x3eb50000,0xbeb53f00,0x3eb50000,0xbeb53f00,0x3eb5bf00,0x3eb50000,0x3eb5bf00,0x3eb50000,0xbeb50000,0x3eb5bf00,0xbeb50000,0x3eb5bf00,
0xbec63f00,0xbea20000,0xbeff3eb5,0x3d49beb5,0x3e713dc8,0xbee23efb,0xbe153ed5,0xbef53e8e,0x3ef5beed,0x3e153e44,0x3ee2be44,0xbe713eed,0xbd49be8e,0x3effbed5,0x3ea2befb,0x3ec6bdc8,
0xbed53f00,0xbe8e0000,0xbe8e0000,0x3ed5bf00,0x3dc83e44,0xbefb3eed,0xbefb3eed,0xbdc8be44,0x3efbbeb5,0xbdc83eb5,0xbdc83eb5,0xbefb3eb5,0x3e8ebeed,0x3ed5be44,0x3ed5be44,0xbe8e3eed,
0xbee23f00,0xbe710000,0x3e15beb5,0x3ef5beb5,0xbd493e8e,0xbeff3ed5,0xbea23dc8,0x3ec6befb,0x3ec6be44,0xbea23eed,0xbeff3eed,0xbd49be44,0x3ef5befb,0x3e153dc8,0xbe713ed5,0xbee23e8e,
0xbeed3f00,0xbe440000,0x3eedbf00,0x3e440000,0xbe443eb5,0xbeed3eb5,0x3e44beb5,0x3eedbeb5,0x3e440000,0xbeed3f00,0xbe440000,0x3eedbf00,0x3eedbeb5,0xbe443eb5,0xbeed3eb5,0x3e44beb5,
0xbef53f00,0xbe150000,0x3ee2beb5,0xbe713eb5,0xbea23ed5,0xbec63e8e,0x3effbefb,0x3d493dc8,0xbd493e44,0xbeff3eed,0x3ec6beed,0x3ea2be44,0x3e71bdc8,0xbee23efb,0x3e15be8e,0x3ef5bed5,
0xbefb3f00,0xbdc80000,0x3dc80000,0xbefb3f00,0xbed53eed,0xbe8e3e44,0x3e8ebe44,0xbed53eed,0xbe8e3eb5,0xbed53eb5,0x3ed5beb5,0xbe8e3eb5,0xbdc83e44,0xbefb3eed,0x3efbbeed,0xbdc83e44,
0xbeff3f00,0xbd490000,0xbea23eb5,0xbec63eb5,0xbef53efb,0xbe153dc8,0xbe713e8e,0xbee23ed5,0xbee23eed,0xbe713e44,0xbe153e44,0xbef53eed,0xbec63ed5,0xbea23e8e,0xbd493dc8,0xbeff3efb,
0x3f003f00,0xbf003f00,0x3f003f00,0xbf003f00,0x3f003f00,0xbf003f00,0x3f003f00,0xbf003f00,0x3f003f00,0xbf003f00,0x3f003f00,0xbf003f00,0x3f003f00,0xbf003f00,0x3f003f00,0xbf003f00,
0xbd490000,0xbeffbf00,0xbec6beb5,0xbea2beb5,0xbe15bdc8,0xbef5befb,0xbee2bed5,0xbe71be8e,0xbe71be44,0xbee2beed,0xbef5beed,0xbe15be44,0xbea2be8e,0xbec6bed5,0xbeffbefb,0xbd49bdc8,
0xbefbbf00,0x3dc80000,0x3dc80000,0x3efb3f00,0xbed5beed,0x3e8e3e44,0x3e8e3e44,0x3ed53eed,0xbe8ebeb5,0x3ed53eb5,0x3ed53eb5,0x3e8e3eb5,0xbdc8be44,0x3efb3eed,0x3efb3eed,0x3dc83e44,
0x3e150000,0x3ef53f00,0x3e713eb5,0xbee2beb5,0x3ec63e8e,0x3ea23ed5,0xbd493dc8,0xbeffbefb,0x3eff3eed,0x3d493e44,0xbea2be44,0xbec6beed,0x3ee23efb,0xbe71bdc8,0xbef5bed5,0xbe15be8e,
0x3eed3f00,0xbe440000,0xbeedbf00,0x3e440000,0x3e443eb5,0xbeedbeb5,0xbe44beb5,0x3eed3eb5,0xbe440000,0xbeedbf00,0x3e440000,0x3eed3f00,0xbeedbeb5,0xbe44beb5,0x3eed3eb5,0x3e443eb5,
0xbe710000,0xbee2bf00,0x3ef53eb5,0x3e153eb5,0xbeffbed5,0xbd49be8e,0x3ec63efb,0xbea2bdc8,0xbea2beed,0x3ec63e44,0xbd493e44,0xbeffbeed,0x3e15bdc8,0x3ef53efb,0xbee2be8e,0xbe71bed5,
0xbed5bf00,0x3e8e0000,0xbe8e0000,0xbed5bf00,0x3dc8be44,0x3efb3eed,0xbefbbeed,0x3dc8be44,0x3efb3eb5,0x3dc83eb5,0xbdc8beb5,0x3efb3eb5,0x3e8e3eed,0xbed5be44,0x3ed53e44,0x3e8e3eed,
0x3ea20000,0x3ec63f00,0xbd49beb5,0x3eff3eb5,0x3ee23efb,0xbe713dc8,0x3ef53e8e,0x3e153ed5,0xbe153e44,0xbef5beed,0x3e713eed,0xbee2be44,0xbeffbed5,0x3d49be8e,0xbec6bdc8,0xbea2befb,
0x3eb53f00,0xbeb50000,0x3eb53f00,0xbeb50000,0xbeb50000,0xbeb5bf00,0xbeb50000,0xbeb5bf00,0xbeb5bf00,0x3eb50000,0xbeb5bf00,0x3eb50000,0x3eb50000,0x3eb53f00,0x3eb50000,0x3eb53f00,
0xbec60000,0xbea2bf00,0xbeffbeb5,0x3d49beb5,0xbe71befb,0x3ee23dc8,0x3e15be8e,0x3ef53ed5,0x3ef53e44,0x3e153eed,0x3ee23eed,0xbe713e44,0x3d493ed5,0xbeffbe8e,0xbea23dc8,0xbec6befb,
0xbe8ebf00,0x3ed50000,0x3ed50000,0x3e8e3f00,0x3efb3e44,0x3dc83eed,0x3dc83eed,0xbefbbe44,0xbdc83eb5,0xbefbbeb5,0xbefbbeb5,0x3dc8beb5,0xbed5beed,0x3e8ebe44,0x3e8ebe44,0x3ed53eed,
0x3ee20000,0x3e713f00,0xbe153eb5,0xbef5beb5,0xbd493ed5,0xbeffbe8e,0xbea2befb,0x3ec6bdc8,0xbec6beed,0x3ea2be44,0x3eff3e44,0x3d493eed,0x3ef53dc8,0x3e153efb,0xbe713e8e,0xbee2bed5,
0x3e443f00,0xbeed0000,0xbe44bf00,0x3eed0000,0xbeedbeb5,0x3e44beb5,0x3eed3eb5,0xbe443eb5,0x3eed0000,0x3e443f00,0xbeed0000,0xbe44bf00,0xbe443eb5,0xbeedbeb5,0x3e44beb5,0x3eed3eb5,
0xbef50000,0xbe15bf00,0x3ee23eb5,0xbe713eb5,0x3ea2be8e,0x3ec63ed5,0xbeffbdc8,0xbd49befb,0xbd493eed,0xbeffbe44,0x3ec6be44,0x3ea23eed,0xbe71befb,0x3ee2bdc8,0xbe153ed5,0xbef5be8e,
0xbdc8bf00,0x3efb0000,0xbefb0000,0xbdc8bf00,0x3e8e3eed,0xbed53e44,0x3ed5be44,0x3e8e3eed,0xbed5beb5,0x3e8ebeb5,0xbe8e3eb5,0xbed5beb5,0x3efb3e44,0xbdc83eed,0x3dc8beed,0x3efb3e44,
0x3eff0000,0x3d493f00,0x3ea2beb5,0x3ec63eb5,0xbef53dc8,0xbe15befb,0xbe713ed5,0xbee2be8e,0x3ee2be44,0x3e713eed,0x3e15beed,0x3ef53e44,0xbec63e8e,0xbea2bed5,0xbd493efb,0xbeffbdc8,
0x3f00,0xbf000000,0x3f00,0xbf000000,0xbf00,0x3f000000,0xbf00,0x3f000000,0x3f00,0xbf000000,0x3f00,0xbf000000,0xbf00,0x3f000000,0xbf00,0x3f000000,
0xbeff0000,0x3d49bf00,0xbea2beb5,0x3ec6beb5,0x3ef53dc8,0xbe153efb,0x3e713ed5,0xbee23e8e,0xbee2be44,0x3e71beed,0xbe15beed,0x3ef5be44,0x3ec63e8e,0xbea23ed5,0x3d493efb,0xbeff3dc8,
0x3dc8bf00,0x3efb0000,0x3efb0000,0xbdc83f00,0xbe8e3eed,0xbed5be44,0xbed5be44,0x3e8ebeed,0x3ed5beb5,0x3e8e3eb5,0x3e8e3eb5,0xbed53eb5,0xbefb3e44,0xbdc8beed,0xbdc8beed,0x3efbbe44,
0x3ef50000,0xbe153f00,0xbee23eb5,0xbe71beb5,0xbea2be8e,0x3ec6bed5,0x3effbdc8,0xbd493efb,0x3d493eed,0xbeff3e44,0xbec6be44,0x3ea2beed,0x3e71befb,0x3ee23dc8,0x3e153ed5,0xbef53e8e,
0xbe443f00,0xbeed0000,0x3e44bf00,0x3eed0000,0x3eedbeb5,0x3e443eb5,0xbeed3eb5,0xbe44beb5,0xbeed0000,0x3e44bf00,0x3eed0000,0xbe443f00,0x3e443eb5,0xbeed3eb5,0xbe44beb5,0x3eedbeb5,
0xbee20000,0x3e71bf00,0x3e153eb5,0xbef53eb5,0x3d493ed5,0xbeff3e8e,0x3ea2befb,0x3ec63dc8,0x3ec6beed,0x3ea23e44,0xbeff3e44,0x3d49beed,0xbef53dc8,0x3e15befb,0x3e713e8e,0xbee23ed5,
0x3e8ebf00,0x3ed50000,0xbed50000,0x3e8ebf00,0xbefb3e44,0x3dc8beed,0xbdc83eed,0xbefb3e44,0x3dc83eb5,0xbefb3eb5,0x3efbbeb5,0x3dc83eb5,0x3ed5beed,0x3e8e3e44,0xbe8ebe44,0x3ed5beed,
0x3ec60000,0xbea23f00,0x3effbeb5,0x3d493eb5,0x3e71befb,0x3ee2bdc8,0xbe15be8e,0x3ef5bed5,0xbef53e44,0x3e15beed,0xbee23eed,0xbe71be44,0xbd493ed5,0xbeff3e8e,0x3ea23dc8,0xbec63efb,
0xbeb53f00,0xbeb50000,0xbeb53f00,0xbeb50000,0x3eb50000,0xbeb53f00,0x3eb50000,0xbeb53f00,0x3eb5bf00,0x3eb50000,0x3eb5bf00,0x3eb50000,0xbeb50000,0x3eb5bf00,0xbeb50000,0x3eb5bf00,
0xbea20000,0x3ec6bf00,0x3d49beb5,0x3effbeb5,0xbee23efb,0xbe71bdc8,0xbef53e8e,0x3e15bed5,0x3e153e44,0xbef53eed,0xbe713eed,0xbee23e44,0x3effbed5,0x3d493e8e,0x3ec6bdc8,0xbea23efb,
0x3ed5bf00,0x3e8e0000,0x3e8e0000,0xbed53f00,0xbdc8be44,0x3efbbeed,0x3efbbeed,0x3dc83e44,0xbefb3eb5,0x3dc8beb5,0x3dc8beb5,0x3efbbeb5,0xbe8e3eed,0xbed53e44,0xbed53e44,0x3e8ebeed,
0x3e710000,0xbee23f00,0xbef53eb5,0x3e15beb5,0x3effbed5,0xbd493e8e,0xbec63efb,0xbea23dc8,0x3ea2beed,0x3ec6be44,0x3d493e44,0xbeff3eed,0xbe15bdc8,0x3ef5befb,0x3ee2be8e,0xbe713ed5,
0xbeed3f00,0xbe440000,0x3eedbf00,0x3e440000,0xbe443eb5,0xbeed3eb5,0x3e44beb5,0x3eedbeb5,0x3e440000,0xbeed3f00,0xbe440000,0x3eedbf00,0x3eedbeb5,0xbe443eb5,0xbeed3eb5,0x3e44beb5,
0xbe150000,0x3ef5bf00,0xbe713eb5,0xbee23eb5,0xbec63e8e,0x3ea2bed5,0x3d493dc8,0xbeff3efb,0xbeff3eed,0x3d49be44,0x3ea2be44,0xbec63eed,0xbee23efb,0xbe713dc8,0x3ef5bed5,0xbe153e8e,
0x3efbbf00,0x3dc80000,0xbdc80000,0x3efbbf00,0x3ed5beed,0x3e8ebe44,0xbe8e3e44,0x3ed5beed,0x3e8ebeb5,0x3ed5beb5,0xbed53eb5,0x3e8ebeb5,0x3dc8be44,0x3efbbeed,0xbefb3eed,0x3dc8be44,
0x3d490000,0xbeff3f00,0x3ec6beb5,0xbea23eb5,0x3e15bdc8,0xbef53efb,0x3ee2bed5,0xbe713e8e,0x3e71be44,0xbee23eed,0x3ef5beed,0xbe153e44,0x3ea2be8e,0xbec63ed5,0x3effbefb,0xbd493dc8,
0x3f003f00,0xbf003f00,0x3f003f00,0xbf003f00,0x3f003f00,0xbf003f00,0x3f003f00,0xbf003f00,0x3f003f00,0xbf003f00,0x3f003f00,0xbf003f00,0x3f003f00,0xbf003f00,0x3f003f00,0xbf003f00,
0xbeffbf00,0x3d490000,0xbea2beb5,0x3ec63eb5,0xbef5befb,0x3e153dc8,0xbe71be8e,0x3ee23ed5,0xbee2beed,0x3e713e44,0xbe15be44,0x3ef53eed,0xbec6bed5,0x3ea23e8e,0xbd49bdc8,0x3eff3efb,
0x3efb3f00,0xbdc80000,0xbdc80000,0xbefbbf00,0x3ed53eed,0xbe8ebe44,0xbe8ebe44,0xbed5beed,0x3e8e3eb5,0xbed5beb5,0xbed5beb5,0xbe8ebeb5,0x3dc83e44,0xbefbbeed,0xbefbbeed,0xbdc8be44,
0xbef5bf00,0x3e150000,0x3ee23eb5,0x3e713eb5,0xbea2bed5,0x3ec63e8e,0x3eff3efb,0xbd493dc8,0xbd49be44,0x3eff3eed,0x3ec63eed,0xbea2be44,0x3e713dc8,0x3ee23efb,0x3e153e8e,0xbef5bed5,
0x3eed3f00,0xbe440000,0xbeedbf00,0x3e440000,0x3e443eb5,0xbeedbeb5,0xbe44beb5,0x3eed3eb5,0xbe440000,0xbeedbf00,0x3e440000,0x3eed3f00,0xbeedbeb5,0xbe44beb5,0x3eed3eb5,0x3e443eb5,
0xbee2bf00,0x3e710000,0x3e153eb5,0xbef5beb5,0xbd49be8e,0x3eff3ed5,0xbea2bdc8,0xbec6befb,0x3ec63e44,0x3ea23eed,0xbeffbeed,0x3d49be44,0x3ef53efb,0xbe153dc8,0xbe71bed5,0x3ee23e8e,
0x3ed53f00,0xbe8e0000,0x3e8e0000,0x3ed53f00,0xbdc83e44,0xbefbbeed,0x3efb3eed,0xbdc83e44,0xbefbbeb5,0xbdc8beb5,0x3dc83eb5,0xbefbbeb5,0xbe8ebeed,0x3ed53e44,0xbed5be44,0xbe8ebeed,
0xbec6bf00,0x3ea20000,0xbeffbeb5,0xbd49beb5,0x3e71bdc8,0x3ee23efb,0xbe15bed5,0x3ef53e8e,0x3ef53eed,0xbe153e44,0x3ee23e44,0x3e713eed,0xbd493e8e,0xbeffbed5,0x3ea23efb,0xbec6bdc8,
0x3eb53f00,0xbeb50000,0x3eb53f00,0xbeb50000,0xbeb50000,0xbeb5bf00,0xbeb50000,0xbeb5bf00,0xbeb5bf00,0x3eb50000,0xbeb5bf00,0x3eb50000,0x3eb50000,0x3eb53f00,0x3eb50000,0x3eb53f00,
0xbea2bf00,0x3ec60000,0x3d49beb5,0x3eff3eb5,0x3ee23dc8,0x3e713efb,0x3ef53ed5,0xbe153e8e,0x3e153eed,0xbef5be44,0xbe713e44,0xbee2beed,0xbeffbe8e,0xbd49bed5,0xbec6befb,0x3ea2bdc8,
0x3e8e3f00,0xbed50000,0xbed50000,0xbe8ebf00,0xbefbbe44,0xbdc8beed,0xbdc8beed,0x3efb3e44,0x3dc8beb5,0x3efb3eb5,0x3efb3eb5,0xbdc83eb5,0x3ed53eed,0xbe8e3e44,0xbe8e3e44,0xbed5beed,
0xbe71bf00,0x3ee20000,0x3ef53eb5,0xbe153eb5,0x3eff3e8e,0xbd493ed5,0xbec63dc8,0xbea2befb,0xbea23e44,0xbec6beed,0xbd49beed,0x3eff3e44,0xbe15befb,0x3ef53dc8,0x3ee23ed5,0xbe713e8e,
0x3e443f00,0xbeed0000,0xbe44bf00,0x3eed0000,0xbeedbeb5,0x3e44beb5,0x3eed3eb5,0xbe443eb5,0x3eed0000,0x3e443f00,0xbeed0000,0xbe44bf00,0xbe443eb5,0xbeedbeb5,0x3e44beb5,0x3eed3eb5,
0xbe15bf00,0x3ef50000,0xbe713eb5,0xbee2beb5,0x3ec63ed5,0xbea23e8e,0xbd49befb,0x3eff3dc8,0xbeffbe44,0x3d49beed,0x3ea23eed,0xbec63e44,0x3ee2bdc8,0x3e713efb,0xbef5be8e,0x3e15bed5,
0x3dc83f00,0xbefb0000,0x3efb0000,0x3dc83f00,0xbe8ebeed,0x3ed5be44,0xbed53e44,0xbe8ebeed,0x3ed53eb5,0xbe8e3eb5,0x3e8ebeb5,0x3ed53eb5,0xbefbbe44,0x3dc8beed,0xbdc83eed,0xbefbbe44,
0xbd49bf00,0x3eff0000,0xbec6beb5,0x3ea2beb5,0x3e153efb,0xbef53dc8,0x3ee23e8e,0xbe713ed5,0xbe71beed,0x3ee2be44,0xbef5be44,0x3e15beed,0x3ea23ed5,0xbec63e8e,0x3eff3dc8,0xbd493efb,
0x3f00,0xbf000000,0x3f00,0xbf000000,0xbf00,0x3f000000,0xbf00,0x3f000000,0x3f00,0xbf000000,0x3f00,0xbf000000,0xbf00,0x3f000000,0xbf00,0x3f000000,
0x3d49bf00,0x3eff0000,0x3ec6beb5,0x3ea23eb5,0xbe153efb,0xbef5bdc8,0xbee23e8e,0xbe71bed5,0x3e71beed,0x3ee23e44,0x3ef5be44,0x3e153eed,0xbea23ed5,0xbec6be8e,0xbeff3dc8,0xbd49befb,
0xbdc83f00,0xbefb0000,0xbefb0000,0x3dc8bf00,0x3e8ebeed,0x3ed53e44,0x3ed53e44,0xbe8e3eed,0xbed53eb5,0xbe8ebeb5,0xbe8ebeb5,0x3ed5beb5,0x3efbbe44,0x3dc83eed,0x3dc83eed,0xbefb3e44,
0x3e15bf00,0x3ef50000,0x3e713eb5,0xbee23eb5,0xbec63ed5,0xbea2be8e,0x3d49befb,0x3effbdc8,0x3effbe44,0x3d493eed,0xbea23eed,0xbec6be44,0xbee2bdc8,0x3e71befb,0x3ef5be8e,0x3e153ed5,
0xbe443f00,0xbeed0000,0x3e44bf00,0x3eed0000,0x3eedbeb5,0x3e443eb5,0xbeed3eb5,0xbe44beb5,0xbeed0000,0x3e44bf00,0x3eed0000,0xbe443f00,0x3e443eb5,0xbeed3eb5,0xbe44beb5,0x3eedbeb5,
0x3e71bf00,0x3ee20000,0xbef53eb5,0xbe15beb5,0xbeff3e8e,0xbd49bed5,0x3ec63dc8,0xbea23efb,0x3ea23e44,0xbec63eed,0x3d49beed,0x3effbe44,0x3e15befb,0x3ef5bdc8,0xbee23ed5,0xbe71be8e,
0xbe8e3f00,0xbed50000,0x3ed50000,0xbe8e3f00,0x3efbbe44,0xbdc83eed,0x3dc8beed,0x3efbbe44,0xbdc8beb5,0x3efbbeb5,0xbefb3eb5,0xbdc8beb5,0xbed53eed,0xbe8ebe44,0x3e8e3e44,0xbed53eed,
0x3ea2bf00,0x3ec60000,0xbd49beb5,0x3effbeb5,0xbee23dc8,0x3e71befb,0xbef53ed5,0xbe15be8e,0xbe153eed,0xbef53e44,0x3e713e44,0xbee23eed,0x3effbe8e,0xbd493ed5,0x3ec6befb,0x3ea23dc8,
0xbeb53f00,0xbeb50000,0xbeb53f00,0xbeb50000,0x3eb50000,0xbeb53f00,0x3eb50000,0xbeb53f00,0x3eb5bf00,0x3eb50000,0x3eb5bf00,0x3eb50000,0xbeb50000,0x3eb5bf00,0xbeb50000,0x3eb5bf00,
0x3ec6bf00,0x3ea20000,0x3effbeb5,0xbd493eb5,0xbe71bdc8,0x3ee2befb,0x3e15bed5,0x3ef5be8e,0xbef53eed,0xbe15be44,0xbee23e44,0x3e71beed,0x3d493e8e,0xbeff3ed5,0xbea23efb,0xbec63dc8,
0xbed53f00,0xbe8e0000,0xbe8e0000,0x3ed5bf00,0x3dc83e44,0xbefb3eed,0xbefb3eed,0xbdc8be44,0x3efbbeb5,0xbdc83eb5,0xbdc83eb5,0xbefb3eb5,0x3e8ebeed,0x3ed5be44,0x3ed5be44,0xbe8e3eed,
0x3ee2bf00,0x3e710000,0xbe153eb5,0xbef53eb5,0x3d49be8e,0x3effbed5,0x3ea2bdc8,0xbec63efb,0xbec63e44,0x3ea2beed,0x3effbeed,0x3d493e44,0xbef53efb,0xbe15bdc8,0x3e71bed5,0x3ee2be8e,
0xbeed3f00,0xbe440000,0x3eedbf00,0x3e440000,0xbe443eb5,0xbeed3eb5,0x3e44beb5,0x3eedbeb5,0x3e440000,0xbeed3f00,0xbe440000,0x3eedbf00,0x3eedbeb5,0xbe443eb5,0xbeed3eb5,0x3e44beb5,
0x3ef5bf00,0x3e150000,0xbee23eb5,0x3e71beb5,0x3ea2bed5,0x3ec6be8e,0xbeff3efb,0xbd49bdc8,0x3d49be44,0x3effbeed,0xbec63eed,0xbea23e44,0xbe713dc8,0x3ee2befb,0xbe153e8e,0xbef53ed5,
0xbefb3f00,0xbdc80000,0x3dc80000,0xbefb3f00,0xbed53eed,0xbe8e3e44,0x3e8ebe44,0xbed53eed,0xbe8e3eb5,0xbed53eb5,0x3ed5beb5,0xbe8e3eb5,0xbdc83e44,0xbefb3eed,0x3efbbeed,0xbdc83e44,
0x3effbf00,0x3d490000,0x3ea2beb5,0x3ec6beb5,0x3ef5befb,0x3e15bdc8,0x3e71be8e,0x3ee2bed5,0x3ee2beed,0x3e71be44,0x3e15be44,0x3ef5beed,0x3ec6bed5,0x3ea2be8e,0x3d49bdc8,0x3effbefb,
0x3f003f00,0xbf003f00,0x3f003f00,0xbf003f00,0x3f003f00,0xbf003f00,0x3f003f00,0xbf003f00,0x3f003f00,0xbf003f00,0x3f003f00,0xbf003f00,0x3f003f00,0xbf003f00,0x3f003f00,0xbf003f00,
0x3d490000,0x3eff3f00,0x3ec63eb5,0x3ea23eb5,0x3e153dc8,0x3ef53efb,0x3ee23ed5,0x3e713e8e,0x3e713e44,0x3ee23eed,0x3ef53eed,0x3e153e44,0x3ea23e8e,0x3ec63ed5,0x3eff3efb,0x3d493dc8,
0xbefbbf00,0x3dc80000,0x3dc80000,0x3efb3f00,0xbed5beed,0x3e8e3e44,0x3e8e3e44,0x3ed53eed,0xbe8ebeb5,0x3ed53eb5,0x3ed53eb5,0x3e8e3eb5,0xbdc8be44,0x3efb3eed,0x3efb3eed,0x3dc83e44,
0xbe150000,0xbef5bf00,0xbe71beb5,0x3ee23eb5,0xbec6be8e,0xbea2bed5,0x3d49bdc8,0x3eff3efb,0xbeffbeed,0xbd49be44,0x3ea23e44,0x3ec63eed,0xbee2befb,0x3e713dc8,0x3ef53ed5,0x3e153e8e,
0x3eed3f00,0xbe440000,0xbeedbf00,0x3e440000,0x3e443eb5,0xbeedbeb5,0xbe44beb5,0x3eed3eb5,0xbe440000,0xbeedbf00,0x3e440000,0x3eed3f00,0xbeedbeb5,0xbe44beb5,0x3eed3eb5,0x3e443eb5,
0x3e710000,0x3ee23f00,0xbef5beb5,0xbe15beb5,0x3eff3ed5,0x3d493e8e,0xbec6befb,0x3ea23dc8,0x3ea23eed,0xbec6be44,0x3d49be44,0x3eff3eed,0xbe153dc8,0xbef5befb,0x3ee23e8e,0x3e713ed5,
0xbed5bf00,0x3e8e0000,0xbe8e0000,0xbed5bf00,0x3dc8be44,0x3efb3eed,0xbefbbeed,0x3dc8be44,0x3efb3eb5,0x3dc83eb5,0xbdc8beb5,0x3efb3eb5,0x3e8e3eed,0xbed5be44,0x3ed53e44,0x3e8e3eed,
0xbea20000,0xbec6bf00,0x3d493eb5,0xbeffbeb5,0xbee2befb,0x3e71bdc8,0xbef5be8e,0xbe15bed5,0x3e15be44,0x3ef53eed,0xbe71beed,0x3ee23e44,0x3eff3ed5,0xbd493e8e,0x3ec63dc8,0x3ea23efb,
0x3eb53f00,0xbeb50000,0x3eb53f00,0xbeb50000,0xbeb50000,0xbeb5bf00,0xbeb50000,0xbeb5bf00,0xbeb5bf00,0x3eb50000,0xbeb5bf00,0x3eb50000,0x3eb50000,0x3eb53f00,0x3eb50000,0x3eb53f00,
0x3ec60000,0x3ea23f00,0x3eff3eb5,0xbd493eb5,0x3e713efb,0xbee2bdc8,0xbe153e8e,0xbef5bed5,0xbef5be44,0xbe15beed,0xbee2beed,0x3e71be44,0xbd49bed5,0x3eff3e8e,0x3ea2bdc8,0x3ec63efb,
0xbe8ebf00,0x3ed50000,0x3ed50000,0x3e8e3f00,0x3efb3e44,0x3dc83eed,0x3dc83eed,0xbefbbe44,0xbdc83eb5,0xbefbbeb5,0xbefbbeb5,0x3dc8beb5,0xbed5beed,0x3e8ebe44,0x3e8ebe44,0x3ed53eed,
0xbee20000,0xbe71bf00,0x3e15beb5,0x3ef53eb5,0x3d49bed5,0x3eff3e8e,0x3ea23efb,0xbec63dc8,0x3ec63eed,0xbea23e44,0xbeffbe44,0xbd49beed,0xbef5bdc8,0xbe15befb,0x3e71be8e,0x3ee23ed5,
0x3e443f00,0xbeed0000,0xbe44bf00,0x3eed0000,0xbeedbeb5,0x3e44beb5,0x3eed3eb5,0xbe443eb5,0x3eed0000,0x3e443f00,0xbeed0000,0xbe44bf00,0xbe443eb5,0xbeedbeb5,0x3e44beb5,0x3eed3eb5,
0x3ef50000,0x3e153f00,0xbee2beb5,0x3e71beb5,0xbea23e8e,0xbec6bed5,0x3eff3dc8,0x3d493efb,0x3d49beed,0x3eff3e44,0xbec63e44,0xbea2beed,0x3e713efb,0xbee23dc8,0x3e15bed5,0x3ef53e8e,
0xbdc8bf00,0x3efb0000,0xbefb0000,0xbdc8bf00,0x3e8e3eed,0xbed53e44,0x3ed5be44,0x3e8e3eed,0xbed5beb5,0x3e8ebeb5,0xbe8e3eb5,0xbed5beb5,0x3efb3e44,0xbdc83eed,0x3dc8beed,0x3efb3e44,
0xbeff0000,0xbd49bf00,0xbea23eb5,0xbec6beb5,0x3ef5bdc8,0x3e153efb,0x3e71bed5,0x3ee23e8e,0xbee23e44,0xbe71beed,0xbe153eed,0xbef5be44,0x3ec6be8e,0x3ea23ed5,0x3d49befb,0x3eff3dc8,
0x3f00,0xbf000000,0x3f00,0xbf000000,0xbf00,0x3f000000,0xbf00,0x3f000000,0x3f00,0xbf000000,0x3f00,0xbf000000,0xbf00,0x3f000000,0xbf00,0x3f000000,
0x3eff0000,0xbd493f00,0x3ea23eb5,0xbec63eb5,0xbef5bdc8,0x3e15befb,0xbe71bed5,0x3ee2be8e,0x3ee23e44,0xbe713eed,0x3e153eed,0xbef53e44,0xbec6be8e,0x3ea2bed5,0xbd49befb,0x3effbdc8,
0x3dc8bf00,0x3efb0000,0x3efb0000,0xbdc83f00,0xbe8e3eed,0xbed5be44,0xbed5be44,0x3e8ebeed,0x3ed5beb5,0x3e8e3eb5,0x3e8e3eb5,0xbed53eb5,0xbefb3e44,0xbdc8beed,0xbdc8beed,0x3efbbe44,
0xbef50000,0x3e15bf00,0x3ee2beb5,0x3e713eb5,0x3ea23e8e,0xbec63ed5,0xbeff3dc8,0x3d49befb,0xbd49beed,0x3effbe44,0x3ec63e44,0xbea23eed,0xbe713efb,0xbee2bdc8,0xbe15bed5,0x3ef5be8e,
0xbe443f00,0xbeed0000,0x3e44bf00,0x3eed0000,0x3eedbeb5,0x3e443eb5,0xbeed3eb5,0xbe44beb5,0xbeed0000,0x3e44bf00,0x3eed0000,0xbe443f00,0x3e443eb5,0xbeed3eb5,0xbe44beb5,0x3eedbeb5,
0x3ee20000,0xbe713f00,0xbe15beb5,0x3ef5beb5,0xbd49bed5,0x3effbe8e,0xbea23efb,0xbec6bdc8,0xbec63eed,0xbea2be44,0x3effbe44,0xbd493eed,0x3ef5bdc8,0xbe153efb,0xbe71be8e,0x3ee2bed5,
0x3e8ebf00,0x3ed50000,0xbed50000,0x3e8ebf00,0xbefb3e44,0x3dc8beed,0xbdc83eed,0xbefb3e44,0x3dc83eb5,0xbefb3eb5,0x3efbbeb5,0x3dc83eb5,0x3ed5beed,0x3e8e3e44,0xbe8ebe44,0x3ed5beed,
0xbec60000,0x3ea2bf00,0xbeff3eb5,0xbd49beb5,0xbe713efb,0xbee23dc8,0x3e153e8e,0xbef53ed5,0x3ef5be44,0xbe153eed,0x3ee2beed,0x3e713e44,0x3d49bed5,0x3effbe8e,0xbea2bdc8,0x3ec6befb,
0xbeb53f00,0xbeb50000,0xbeb53f00,0xbeb50000,0x3eb50000,0xbeb53f00,0x3eb50000,0xbeb53f00,0x3eb5bf00,0x3eb50000,0x3eb5bf00,0x3eb50000,0xbeb50000,0x3eb5bf00,0xbeb50000,0x3eb5bf00,
0x3ea20000,0xbec63f00,0xbd493eb5,0xbeff3eb5,0x3ee2befb,0x3e713dc8,0x3ef5be8e,0xbe153ed5,0xbe15be44,0x3ef5beed,0x3e71beed,0x3ee2be44,0xbeff3ed5,0xbd49be8e,0xbec63dc8,0x3ea2befb,
0x3ed5bf00,0x3e8e0000,0x3e8e0000,0xbed53f00,0xbdc8be44,0x3efbbeed,0x3efbbeed,0x3dc83e44,0xbefb3eb5,0x3dc8beb5,0x3dc8beb5,0x3efbbeb5,0xbe8e3eed,0xbed53e44,0xbed53e44,0x3e8ebeed,
0xbe710000,0x3ee2bf00,0x3ef5beb5,0xbe153eb5,0xbeff3ed5,0x3d49be8e,0x3ec6befb,0x3ea2bdc8,0xbea23eed,0xbec63e44,0xbd49be44,0x3effbeed,0x3e153dc8,0xbef53efb,0xbee23e8e,0x3e71bed5,
0xbeed3f00,0xbe440000,0x3eedbf00,0x3e440000,0xbe443eb5,0xbeed3eb5,0x3e44beb5,0x3eedbeb5,0x3e440000,0xbeed3f00,0xbe440000,0x3eedbf00,0x3eedbeb5,0xbe443eb5,0xbeed3eb5,0x3e44beb5,
0x3e150000,0xbef53f00,0x3e71beb5,0x3ee2beb5,0x3ec6be8e,0xbea23ed5,0xbd49bdc8,0x3effbefb,0x3effbeed,0xbd493e44,0xbea23e44,0x3ec6beed,0x3ee2befb,0x3e71bdc8,0xbef53ed5,0x3e15be8e,
0x3efbbf00,0x3dc80000,0xbdc80000,0x3efbbf00,0x3ed5beed,0x3e8ebe44,0xbe8e3e44,0x3ed5beed,0x3e8ebeb5,0x3ed5beb5,0xbed53eb5,0x3e8ebeb5,0x3dc8be44,0x3efbbeed,0xbefb3eed,0x3dc8be44,
0xbd490000,0x3effbf00,0xbec63eb5,0x3ea2beb5,0xbe153dc8,0x3ef5befb,0xbee23ed5,0x3e71be8e,0xbe713e44,0x3ee2beed,0xbef53eed,0x3e15be44,0xbea23e8e,0x3ec6bed5,0xbeff3efb,0x3d49bdc8,
0x3f800000,0x0,0x3f800000,0x0,0x3f800000,0x0,0x3f800000,0x0,0x3f800000,0x0,0x3f800000,0x0,0x3f800000,0x0,0x3f800000,0x0,
0x3f800000,0x0,0x3f7ffec4,0xbbc90f88,0x3f7ffb11,0xbc490e90,0x3f7ff4e6,0xbc96c9b6,0x3f7fec43,0xbcc90ab0,0x3f7fe129,0xbcfb49ba,0x3f7fd397,0xbd16c32c,0x3f7fc38f,0xbd2fe007,
0x3f800000,0x0,0x3f7ffb11,0xbc490e90,0x3f7fec43,0xbcc90ab0,0x3f7fd397,0xbd16c32c,0x3f7fb10f,0xbd48fb30,0x3f7f84ab,0xbd7b2b74,0x3f7f4e6d,0xbd96a905,0x3f7f0e58,0xbdafb680,
0x3f800000,0x0,0x3f7ff4e6,0xbc96c9b6,0x3f7fd397,0xbd16c32c,0x3f7f9c18,0xbd621469,0x3f7f4e6d,0xbd96a905,0x3f7eea9d,0xbdbc3ac3,0x3f7e70b0,0xbde1bc2e,0x3f7de0b1,0xbe039502,
0x3f800000,0x0,0x3f7fec43,0xbcc90ab0,0x3f7fb10f,0xbd48fb30,0x3f7f4e6d,0xbd96a905,0x3f7ec46d,0xbdc8bd36,0x3f7e1324,0xbdfab273,0x3f7d3aac,0xbe164083,0x3f7c3b28,0xbe2f10a2,
0x3f800000,0x0,0x3f7fe129,0xbcfb49ba,0x3f7f84ab,0xbd7b2b74,0x3f7eea9d,0xbdbc3ac3,0x3f7e1324,0xbdfab273,0x3f7cfe73,0xbe1c76de,0x3f7baccd,0xbe3b6ecf,0x3f7a1e84,0xbe5a3997,
0x3f800000,0x0,0x3f7fd397,0xbd16c32c,0x3f7f4e6d,0xbd96a905,0x3f7e70b0,0xbde1bc2e,0x3f7d3aac,0xbe164083,0x3f7baccd,0xbe3b6ecf,0x3f79c79d,0xbe605c13,0x3f778bc5,0xbe827dc0,
0x3f800000,0x0,0x3f7fc38f,0xbd2fe007,0x3f7f0e58,0xbdafb680,0x3f7de0b1,0xbe039502,0x3f7c3b28,0xbe2f10a2,0x3f7a1e84,0xbe5a3997,0x3f778bc5,0xbe827dc0,0x3f748422,0xbe97a117,
0x3f800000,0x0,0x3f7fb10f,0xbd48fb30,0x3f7ec46d,0xbdc8bd36,0x3f7d3aac,0xbe164083,0x3f7b14be,0xbe47c5c2,0x3f7853f8,0xbe78cfcc,0x3f74fa0b,0xbe94a031,0x3f710908,0xbeac7cd4,
0x3f800000,0x0,0x3f7f9c18,0xbd621469,0x3f7e70b0,0xbde1bc2e,0x3f7c7eb0,0xbe28defc,0x3f79c79d,0xbe605c13,0x3f764d97,0xbe8b9507,0x3f721352,0xbea68f12,0x3f6d1c1d,0xbec1071e,
0x3f800000,0x0,0x3f7f84ab,0xbd7b2b74,0x3f7e1324,0xbdfab273,0x3f7baccd,0xbe3b6ecf,0x3f7853f8,0xbe78cfcc,0x3f740bdd,0xbe9aa086,0x3f6ed89e,0xbeb8442a,0x3f68bf3c,0xbed53641,
0x3f800000,0x0,0x3f7f6ac7,0xbd8a200a,0x3f7dabcc,0xbe09cf86,0x3f7ac516,0xbe4dee60,0x3f76ba07,0xbe888e93,0x3f718f57,0xbea986c4,0x3f6b4b0c,0xbec9b953,0x3f63f473,0xbee900b7,
0x3f800000,0x0,0x3f7f4e6d,0xbd96a905,0x3f7d3aac,0xbe164083,0x3f79c79d,0xbe605c13,0x3f74fa0b,0xbe94a031,0x3f6ed89e,0xbeb8442a,0x3f676bd8,0xbedae880,0x3f5ebe05,0xbefc5d27,
0x3f800000,0x0,0x3f7f2f9d,0xbda3308c,0x3f7cbfc9,0xbe22abb6,0x3f78b47b,0xbe72b651,0x3f731447,0xbea09ae5,0x3f6be858,0xbec6d529,0x3f633c5a,0xbeebcbbb,0x3f591e6a,0xbf07a136,
0x3f800000,0x0,0x3f7f0e58,0xbdafb680,0x3f7c3b28,0xbe2f10a2,0x3f778bc5,0xbe827dc0,0x3f710908,0xbeac7cd4,0x3f68bf3c,0xbed53641,0x3f5ebe05,0xbefc5d27,0x3f531849,0xbf10d3cd,
0x3f800000,0x0,0x3f7eea9d,0xbdbc3ac3,0x3f7baccd,0xbe3b6ecf,0x3f764d97,0xbe8b9507,0x3f6ed89e,0xbeb8442a,0x3f655e0b,0xbee363fa,0x3f59f26a,0xbf064b82,0x3f4cae79,0xbf19c200,
0x3f800000,0x0,0x3f7ec46d,0xbdc8bd36,0x3f7b14be,0xbe47c5c2,0x3f74fa0b,0xbe94a031,0x3f6c835e,0xbec3ef15,0x3f61c598,0xbef15aea,0x3f54db31,0xbf0e39da,0x3f45e403,0xbf226799,
0x3f800000,0x0,0x3f7e9bc9,0xbdd53db9,0x3f7a7302,0xbe541501,0x3f73913f,0xbe9d9e78,0x3f6a09a7,0xbecf7bca,0x3f5df6be,0xbeff17b2,0x3f4f7a1f,0xbf15f6d9,0x3f3ebc1b,0xbf2ac082,
0x3f800000,0x0,0x3f7e70b0,0xbde1bc2e,0x3f79c79d,0xbe605c13,0x3f721352,0xbea68f12,0x3f676bd8,0xbedae880,0x3f59f26a,0xbf064b82,0x3f49d112,0xbf1d7fd1,0x3f373a23,0xbf32c8c9,
0x3f800000,0x0,0x3f7e4323,0xbdee3876,0x3f791298,0xbe6c9a7f,0x3f708066,0xbeaf713a,0x3f64aa59,0xbee63375,0x3f55b993,0xbf0cead0,0x3f43e200,0xbf24d225,0x3f2f61a5,0xbf3a7ca4,
0x3f800000,0x0,0x3f7e1324,0xbdfab273,0x3f7853f8,0xbe78cfcc,0x3f6ed89e,0xbeb8442a,0x3f61c598,0xbef15aea,0x3f514d3d,0xbf13682a,0x3f3daef9,0xbf2beb4a,0x3f273656,0xbf41d870,
0x3f800000,0x0,0x3f7de0b1,0xbe039502,0x3f778bc5,0xbe827dc0,0x3f6d1c1d,0xbec1071e,0x3f5ebe05,0xbefc5d27,0x3f4cae79,0xbf19c200,0x3f373a23,0xbf32c8c9,0x3f1ebc12,0xbf48d8b3,
0x3f800000,0x0,0x3f7dabcc,0xbe09cf86,0x3f76ba07,0xbe888e93,0x3f6b4b0c,0xbec9b953,0x3f5b941a,0xbf039c3d,0x3f47de65,0xbf1ff6cb,0x3f3085bb,0xbf396842,0x3f15f6d9,0xbf4f7a1f,
0x3f800000,0x0,0x3f7d7474,0xbe1008b7,0x3f75dec6,0xbe8e9a22,0x3f696591,0xbed25a09,0x3f584853,0xbf08f59b,0x3f42de29,0xbf26050a,0x3f299415,0xbf3fc767,0x3f0cead0,0xbf55b993,
0x3f800000,0x0,0x3f7d3aac,0xbe164083,0x3f74fa0b,0xbe94a031,0x3f676bd8,0xbedae880,0x3f54db31,0xbf0e39da,0x3f3daef9,0xbf2beb4a,0x3f226799,0xbf45e403,0x3f039c3d,0xbf5b941a,
0x3f800000,0x0,0x3f7cfe73,0xbe1c76de,0x3f740bdd,0xbe9aa086,0x3f655e0b,0xbee363fa,0x3f514d3d,0xbf13682a,0x3f385216,0xbf31a81d,0x3f1b02c6,0xbf4bbbf8,0x3ef41f07,0xbf6106f2,
0x3f800000,0x0,0x3f7cbfc9,0xbe22abb6,0x3f731447,0xbea09ae5,0x3f633c5a,0xbeebcbbb,0x3f4d9f02,0xbf187fc0,0x3f32c8c9,0xbf373a23,0x3f13682a,0xbf514d3d,0x3ee0924f,0xbf660f88,
0x3f800000,0x0,0x3f7c7eb0,0xbe28defc,0x3f721352,0xbea68f12,0x3f6106f2,0xbef41f07,0x3f49d112,0xbf1d7fd1,0x3f2d1469,0xbf3ca003,0x3f0b9a6b,0xbf5695e5,0x3ecc9b8b,0xbf6aab7b,
0x3f800000,0x0,0x3f7c3b28,0xbe2f10a2,0x3f710908,0xbeac7cd4,0x3f5ebe05,0xbefc5d27,0x3f45e403,0xbf226799,0x3f273656,0xbf41d870,0x3f039c3d,0xbf5b941a,0x3eb8442a,0xbf6ed89e,
0x3f800000,0x0,0x3f7bf531,0xbe354098,0x3f6ff573,0xbeb263ef,0x3f5c61c7,0xbf0242b1,0x3f41d870,0xbf273656,0x3f212ff9,0xbf46e22a,0x3ef6e0cb,0xbf604621,0x3ea395c5,0xbf7294f8,
0x3f800000,0x0,0x3f7baccd,0xbe3b6ecf,0x3f6ed89e,0xbeb8442a,0x3f59f26a,0xbf064b82,0x3f3daef9,0xbf2beb4a,0x3f1b02c6,0xbf4bbbf8,0x3ee63375,0xbf64aa59,0x3e8e9a22,0xbf75dec6,
0x3f800000,0x0,0x3f7b61fc,0xbe419b37,0x3f6db293,0xbebe1d4a,0x3f577026,0xbf0a48ad,0x3f396842,0xbf3085bb,0x3f14b039,0xbf5064af,0x3ed53641,0xbf68bf3c,0x3e72b651,0xbf78b47b,
0x3f800000,0x0,0x3f800000,0x0,0x3f800000,0x0,0x3f800000,0x0,0x3f800000,0x0,0x3f800000,0x0,0x3f800000,0x0,0x3f800000,0x0,
0x3f7fb10f,0xbd48fb30,0x3f7f9c18,0xbd621469,0x3f7f84ab,0xbd7b2b74,0x3f7f6ac7,0xbd8a200a,0x3f7f4e6d,0xbd96a905,0x3f7f2f9d,0xbda3308c,0x3f7f0e58,0xbdafb680,0x3f7eea9d,0xbdbc3ac3,
0x3f7ec46d,0xbdc8bd36,0x3f7e70b0,0xbde1bc2e,0x3f7e1324,0xbdfab273,0x3f7dabcc,0xbe09cf86,0x3f7d3aac,0xbe164083,0x3f7cbfc9,0xbe22abb6,0x3f7c3b28,0xbe2f10a2,0x3f7baccd,0xbe3b6ecf,
0x3f7d3aac,0xbe164083,0x3f7c7eb0,0xbe28defc,0x3f7baccd,0xbe3b6ecf,0x3f7ac516,0xbe4dee60,0x3f79c79d,0xbe605c13,0x3f78b47b,0xbe72b651,0x3f778bc5,0xbe827dc0,0x3f764d97,0xbe8b9507,
0x3f7b14be,0xbe47c5c2,0x3f79c79d,0xbe605c13,0x3f7853f8,0xbe78cfcc,0x3f76ba07,0xbe888e93,0x3f74fa0b,0xbe94a031,0x3f731447,0xbea09ae5,0x3f710908,0xbeac7cd4,0x3f6ed89e,0xbeb8442a,
0x3f7853f8,0xbe78cfcc,0x3f764d97,0xbe8b9507,0x3f740bdd,0xbe9aa086,0x3f718f57,0xbea986c4,0x3f6ed89e,0xbeb8442a,0x3f6be858,0xbec6d529,0x3f68bf3c,0xbed53641,0x3f655e0b,0xbee363fa,
0x3f74fa0b,0xbe94a031,0x3f721352,0xbea68f12,0x3f6ed89e,0xbeb8442a,0x3f6b4b0c,0xbec9b953,0x3f676bd8,0xbedae880,0x3f633c5a,0xbeebcbbb,0x3f5ebe05,0xbefc5d27,0x3f59f26a,0xbf064b82,
0x3f710908,0xbeac7cd4,0x3f6d1c1d,0xbec1071e,0x3f68bf3c,0xbed53641,0x3f63f473,0xbee900b7,0x3f5ebe05,0xbefc5d27,0x3f591e6a,0xbf07a136,0x3f531849,0xbf10d3cd,0x3f4cae79,0xbf19c200,
0x3f6c835e,0xbec3ef15,0x3f676bd8,0xbedae880,0x3f61c598,0xbef15aea,0x3f5b941a,0xbf039c3d,0x3f54db31,0xbf0e39da,0x3f4d9f02,0xbf187fc0,0x3f45e403,0xbf226799,0x3f3daef9,0xbf2beb4a,
0x3f676bd8,0xbedae880,0x3f6106f2,0xbef41f07,0x3f59f26a,0xbf064b82,0x3f5233c6,0xbf121eb0,0x3f49d112,0xbf1d7fd1,0x3f40d0da,0xbf286605,0x3f373a23,0xbf32c8c9,0x3f2d1469,0xbf3ca003,
0x3f61c598,0xbef15aea,0x3f59f26a,0xbf064b82,0x3f514d3d,0xbf13682a,0x3f47de65,0xbf1ff6cb,0x3f3daef9,0xbf2beb4a,0x3f32c8c9,0xbf373a23,0x3f273656,0xbf41d870,0x3f1b02c6,0xbf4bbbf8,
0x3f5b941a,0xbf039c3d,0x3f5233c6,0xbf121eb0,0x3f47de65,0xbf1ff6cb,0x3f3ca003,0xbf2d1469,0x3f3085bb,0xbf396842,0x3f239da9,0xbf44e3f5,0x3f15f6d9,0xbf4f7a1f,0x3f07a136,0xbf591e6a,
0x3f54db31,0xbf0e39da,0x3f49d112,0xbf1d7fd1,0x3f3daef9,0xbf2beb4a,0x3f3085bb,0xbf396842,0x3f226799,0xbf45e403,0x3f13682a,0xbf514d3d,0x3f039c3d,0xbf5b941a,0x3ee63375,0xbf64aa59,
0x3f4d9f02,0xbf187fc0,0x3f40d0da,0xbf286605,0x3f32c8c9,0xbf373a23,0x3f239da9,0xbf44e3f5,0x3f13682a,0xbf514d3d,0x3f0242b1,0xbf5c61c7,0x3ee0924f,0xbf660f88,0x3ebb31a0,0xbf6e46be,
0x3f45e403,0xbf226799,0x3f373a23,0xbf32c8c9,0x3f273656,0xbf41d870,0x3f15f6d9,0xbf4f7a1f,0x3f039c3d,0xbf5b941a,0x3ee0924f,0xbf660f88,0x3eb8442a,0xbf6ed89e,0x3e8e9a22,0xbf75dec6,
0x3f3daef9,0xbf2beb4a,0x3f2d1469,0xbf3ca003,0x3f1b02c6,0xbf4bbbf8,0x3f07a136,0xbf591e6a,0x3ee63375,0xbf64aa59,0x3ebb31a0,0xbf6e46be,0x3e8e9a22,0xbf75dec6,0x3e419b37,0xbf7b61fc,
0x3f3504f3,0xbf3504f3,0x3f226799,0xbf45e403,0x3f0e39da,0xbf54db31,0x3ef15aea,0xbf61c598,0x3ec3ef15,0xbf6c835e,0x3e94a031,0xbf74fa0b,0x3e47c5c2,0xbf7b14be,0x3dc8bd36,0xbf7ec46d,
0x3f2beb4a,0xbf3daef9,0x3f173c07,0xbf4e8d90,0x3f00e7e4,0xbf5d2d53,0x3ed25a09,0xbf696591,0x3ea09ae5,0xbf731447,0x3e5a3997,0xbf7a1e84,0x3de1bc2e,0xbf7e70b0,0x3bc90f88,0xbf7ffec4,
0x3f226799,0xbf45e403,0x3f0b9a6b,0xbf5695e5,0x3ee63375,0xbf64aa59,0x3eb263ef,0xbf6ff573,0x3e78cfcc,0xbf7853f8,0x3e09cf86,0xbf7dabcc,0x3cc90ab0,0xbf7fec43,0xbdafb680,0xbf7f0e58,
0x3f187fc0,0xbf4d9f02,0x3eff17b2,0xbf5df6be,0x3ec9b953,0xbf6b4b0c,0x3e919ddd,0xbf756d97,0x3e2f10a2,0xbf7c3b28,0x3d621469,0xbf7f9c18,0xbd7b2b74,0xbf7f84ab,0xbe354098,0xbf7bf531,
0x3f0e39da,0xbf54db31,0x3ee63375,0xbf64aa59,0x3eac7cd4,0xbf710908,0x3e605c13,0xbf79c79d,0x3dc8bd36,0xbf7ec46d,0xbcc90ab0,0xbf7fec43,0xbe164083,0xbf7d3aac,0xbe888e93,0xbf76ba07,
0x3f039c3d,0xbf5b941a,0x3ecc9b8b,0xbf6aab7b,0x3e8e9a22,0xbf75dec6,0x3e1c76de,0xbf7cfe73,0x3cc90ab0,0xbf7fec43,0xbdd53db9,0xbf7e9bc9,0xbe6c9a7f,0xbf791298,0xbeb554ec,0xbf6f6830,
0x3ef15aea,0xbf61c598,0x3eb263ef,0xbf6ff573,0x3e605c13,0xbf79c79d,0x3dafb680,0xbf7f0e58,0xbd48fb30,0xbf7fb10f,0xbe3b6ecf,0xbf7baccd,0xbea09ae5,0xbf731447,0xbee0924f,0xbf660f88,
0x3edae880,0xbf676bd8,0x3e97a117,0xbf748422,0x3e22abb6,0xbf7cbfc9,0x3c96c9b6,0xbf7ff4e6,0xbdfab273,0xbf7e1324,0xbe8586ce,0xbf772417,0xbec9b953,0xbf6b4b0c,0xbf04f484,0xbf5ac450,
0x3ec3ef15,0xbf6c835e,0x3e78cfcc,0xbf7853f8,0x3dc8bd36,0xbf7ec46d,0xbd48fb30,0xbf7fb10f,0xbe47c5c2,0xbf7b14be,0xbeac7cd4,0xbf710908,0xbef15aea,0xbf61c598,0xbf187fc0,0xbf4d9f02,
0x3eac7cd4,0xbf710908,0x3e419b37,0xbf7b61fc,0x3d16c32c,0xbf7fd397,0xbdee3876,0xbf7e4323,0xbe888e93,0xbf76ba07,0xbed25a09,0xbf696591,0xbf0b9a6b,0xbf5695e5,0xbf2ac082,0xbf3ebc1b,
0x3e94a031,0xbf74fa0b,0x3e09cf86,0xbf7dabcc,0xbcc90ab0,0xbf7fec43,0xbe3b6ecf,0xbf7baccd,0xbeac7cd4,0xbf710908,0xbef6e0cb,0xbf604621,0xbf1d7fd1,0xbf49d112,0xbf3b8f3b,0xbf2e3bde,
0x3e78cfcc,0xbf7853f8,0x3da3308c,0xbf7f2f9d,0xbdafb680,0xbf7f0e58,0xbe7ee6e1,0xbf77f110,0xbecf7bca,0xbf6a09a7,0xbf0cead0,0xbf55b993,0xbf2e3bde,0xbf3b8f3b,0xbf4ac77f,0xbf1c420c,
0x3e47c5c2,0xbf7b14be,0x3cc90ab0,0xbf7fec43,0xbe164083,0xbf7d3aac,0xbea09ae5,0xbf731447,0xbef15aea,0xbf61c598,0xbf1d7fd1,0xbf49d112,0xbf3daef9,0xbf2beb4a,0xbf584853,0xbf08f59b,
0x3e164083,0xbf7d3aac,0xbcfb49ba,0xbf7fe129,0xbe541501,0xbf7a7302,0xbec1071e,0xbf6d1c1d,0xbf08f59b,0xbf584853,0xbf2d1469,0xbf3ca003,0xbf4bbbf8,0xbf1b02c6,0xbf63f473,0xbee900b7,
0x3dc8bd36,0xbf7ec46d,0xbdafb680,0xbf7f0e58,0xbe888e93,0xbf76ba07,0xbee0924f,0xbf660f88,0xbf187fc0,0xbf4d9f02,0xbf3b8f3b,0xbf2e3bde,0xbf584853,0xbf08f59b,0xbf6db293,0xbebe1d4a,
0x3d48fb30,0xbf7fb10f,0xbe1008b7,0xbf7d7474,0xbea68f12,0xbf721352,0xbeff17b2,0xbf5df6be,0xbf273656,0xbf41d870,0xbf48d8b3,0xbf1ebc12,0xbf633c5a,0xbeebcbbb,0xbf756d97,0xbe919ddd,
0x3f800000,0x0,0x3f800000,0x0,0x3f800000,0x0,0x3f800000,0x0,0x3f800000,0x0,0x3f800000,0x0,0x3f800000,0x0,0x3f800000,0x0,
0x3f7ec46d,0xbdc8bd36,0x3f7e9bc9,0xbdd53db9,0x3f7e70b0,0xbde1bc2e,0x3f7e4323,0xbdee3876,0x3f7e1324,0xbdfab273,0x3f7de0b1,0xbe039502,0x3f7dabcc,0xbe09cf86,0x3f7d7474,0xbe1008b7,
0x3f7b14be,0xbe47c5c2,0x3f7a7302,0xbe541501,0x3f79c79d,0xbe605c13,0x3f791298,0xbe6c9a7f,0x3f7853f8,0xbe78cfcc,0x3f778bc5,0xbe827dc0,0x3f76ba07,0xbe888e93,0x3f75dec6,0xbe8e9a22,
0x3f74fa0b,0xbe94a031,0x3f73913f,0xbe9d9e78,0x3f721352,0xbea68f12,0x3f708066,0xbeaf713a,0x3f6ed89e,0xbeb8442a,0x3f6d1c1d,0xbec1071e,0x3f6b4b0c,0xbec9b953,0x3f696591,0xbed25a09,
0x3f6c835e,0xbec3ef15,0x3f6a09a7,0xbecf7bca,0x3f676bd8,0xbedae880,0x3f64aa59,0xbee63375,0x3f61c598,0xbef15aea,0x3f5ebe05,0xbefc5d27,0x3f5b941a,0xbf039c3d,0x3f584853,0xbf08f59b,
0x3f61c598,0xbef15aea,0x3f5df6be,0xbeff17b2,0x3f59f26a,0xbf064b82,0x3f55b993,0xbf0cead0,0x3f514d3d,0xbf13682a,0x3f4cae79,0xbf19c200,0x3f47de65,0xbf1ff6cb,0x3f42de29,0xbf26050a,
0x3f54db31,0xbf0e39da,0x3f4f7a1f,0xbf15f6d9,0x3f49d112,0xbf1d7fd1,0x3f43e200,0xbf24d225,0x3f3daef9,0xbf2beb4a,0x3f373a23,0xbf32c8c9,0x3f3085bb,0xbf396842,0x3f299415,0xbf3fc767,
0x3f45e403,0xbf226799,0x3f3ebc1b,0xbf2ac082,0x3f373a23,0xbf32c8c9,0x3f2f61a5,0xbf3a7ca4,0x3f273656,0xbf41d870,0x3f1ebc12,0xbf48d8b3,0x3f15f6d9,0xbf4f7a1f,0x3f0cead0,0xbf55b993,
0x3f3504f3,0xbf3504f3,0x3f2beb4a,0xbf3daef9,0x3f226799,0xbf45e403,0x3f187fc0,0xbf4d9f02,0x3f0e39da,0xbf54db31,0x3f039c3d,0xbf5b941a,0x3ef15aea,0xbf61c598,0x3edae880,0xbf676bd8,
0x3f226799,0xbf45e403,0x3f173c07,0xbf4e8d90,0x3f0b9a6b,0xbf5695e5,0x3eff17b2,0xbf5df6be,0x3ee63375,0xbf64aa59,0x3ecc9b8b,0xbf6aab7b,0x3eb263ef,0xbf6ff573,0x3e97a117,0xbf748422,
0x3f0e39da,0xbf54db31,0x3f00e7e4,0xbf5d2d53,0x3ee63375,0xbf64aa59,0x3ec9b953,0xbf6b4b0c,0x3eac7cd4,0xbf710908,0x3e8e9a22,0xbf75dec6,0x3e605c13,0xbf79c79d,0x3e22abb6,0xbf7cbfc9,
0x3ef15aea,0xbf61c598,0x3ed25a09,0xbf696591,0x3eb263ef,0xbf6ff573,0x3e919ddd,0xbf756d97,0x3e605c13,0xbf79c79d,0x3e1c76de,0xbf7cfe73,0x3dafb680,0xbf7f0e58,0x3c96c9b6,0xbf7ff4e6,
0x3ec3ef15,0xbf6c835e,0x3ea09ae5,0xbf731447,0x3e78cfcc,0xbf7853f8,0x3e2f10a2,0xbf7c3b28,0x3dc8bd36,0xbf7ec46d,0x3cc90ab0,0xbf7fec43,0xbd48fb30,0xbf7fb10f,0xbdfab273,0xbf7e1324,
0x3e94a031,0xbf74fa0b,0x3e5a3997,0xbf7a1e84,0x3e09cf86,0xbf7dabcc,0x3d621469,0xbf7f9c18,0xbcc90ab0,0xbf7fec43,0xbdd53db9,0xbf7e9bc9,0xbe3b6ecf,0xbf7baccd,0xbe8586ce,0xbf772417,
0x3e47c5c2,0xbf7b14be,0x3de1bc2e,0xbf7e70b0,0x3cc90ab0,0xbf7fec43,0xbd7b2b74,0xbf7f84ab,0xbe164083,0xbf7d3aac,0xbe6c9a7f,0xbf791298,0xbea09ae5,0xbf731447,0xbec9b953,0xbf6b4b0c,
0x3dc8bd36,0xbf7ec46d,0x3bc90f88,0xbf7ffec4,0xbdafb680,0xbf7f0e58,0xbe354098,0xbf7bf531,0xbe888e93,0xbf76ba07,0xbeb554ec,0xbf6f6830,0xbee0924f,0xbf660f88,0xbf04f484,0xbf5ac450,
0x0,0xbf800000,0xbdc8bd36,0xbf7ec46d,0xbe47c5c2,0xbf7b14be,0xbe94a031,0xbf74fa0b,0xbec3ef15,0xbf6c835e,0xbef15aea,0xbf61c598,0xbf0e39da,0xbf54db31,0xbf226799,0xbf45e403,
0xbdc8bd36,0xbf7ec46d,0xbe4dee60,0xbf7ac516,0xbe9aa086,0xbf740bdd,0xbecc9b8b,0xbf6aab7b,0xbefc5d27,0xbf5ebe05,0xbf14b039,0xbf5064af,0xbf299415,0xbf3fc767,0xbf3ca003,0xbf2d1469,
0xbe47c5c2,0xbf7b14be,0xbe9aa086,0xbf740bdd,0xbecf7bca,0xbf6a09a7,0xbf00e7e4,0xbf5d2d53,0xbf187fc0,0xbf4d9f02,0xbf2e3bde,0xbf3b8f3b,0xbf41d870,0xbf273656,0xbf531849,0xbf10d3cd,
0xbe94a031,0xbf74fa0b,0xbecc9b8b,0xbf6aab7b,0xbf00e7e4,0xbf5d2d53,0xbf19c200,0xbf4cae79,0xbf3085bb,0xbf396842,0xbf44e3f5,0xbf239da9,0xbf5695e5,0xbf0b9a6b,0xbf655e0b,0xbee363fa,
0xbec3ef15,0xbf6c835e,0xbefc5d27,0xbf5ebe05,0xbf187fc0,0xbf4d9f02,0xbf3085bb,0xbf396842,0xbf45e403,0xbf226799,0xbf584853,0xbf08f59b,0xbf676bd8,0xbedae880,0xbf731447,0xbea09ae5,
0xbef15aea,0xbf61c598,0xbf14b039,0xbf5064af,0xbf2e3bde,0xbf3b8f3b,0xbf44e3f5,0xbf239da9,0xbf584853,0xbf08f59b,0xbf6816a8,0xbed8106b,0xbf740bdd,0xbe9aa086,0xbf7bf531,0xbe354098,
0xbf0e39da,0xbf54db31,0xbf299415,0xbf3fc767,0xbf41d870,0xbf273656,0xbf5695e5,0xbf0b9a6b,0xbf676bd8,0xbedae880,0xbf740bdd,0xbe9aa086,0xbf7c3b28,0xbe2f10a2,0xbf7fd397,0xbd16c32c,
0xbf226799,0xbf45e403,0xbf3ca003,0xbf2d1469,0xbf531849,0xbf10d3cd,0xbf655e0b,0xbee363fa,0xbf731447,0xbea09ae5,0xbf7bf531,0xbe354098,0xbf7fd397,0xbd16c32c,0xbf7e9bc9,0x3dd53db9,
0xbf3504f3,0xbf3504f3,0xbf4d9f02,0xbf187fc0,0xbf61c598,0xbef15aea,0xbf710908,0xbeac7cd4,0xbf7b14be,0xbe47c5c2,0xbf7fb10f,0xbd48fb30,0xbf7ec46d,0x3dc8bd36,0xbf7853f8,0x3e78cfcc,
0xbf45e403,0xbf226799,0xbf5c61c7,0xbf0242b1,0xbf6db293,0xbebe1d4a,0xbf796e4e,0xbe667c66,0xbf7f4e6d,0xbd96a905,0xbf7f2f9d,0x3da3308c,0xbf791298,0x3e6c9a7f,0xbf6d1c1d,0x3ec1071e,
0xbf54db31,0xbf0e39da,0xbf68bf3c,0xbed53641,0xbf76ba07,0xbe888e93,0xbf7e70b0,0xbde1bc2e,0xbf7fb10f,0x3d48fb30,0xbf7a7302,0x3e541501,0xbf6ed89e,0x3eb8442a,0xbf5d2d53,0x3f00e7e4,
0xbf61c598,0xbef15aea,0xbf7294f8,0xbea395c5,0xbf7cbfc9,0xbe22abb6,0xbf7ffec4,0x3bc90f88,0xbf7c3b28,0x3e2f10a2,0xbf718f57,0x3ea986c4,0xbf604621,0x3ef6e0cb,0xbf48d8b3,0x3f1ebc12,
0xbf6c835e,0xbec3ef15,0xbf79c79d,0xbe605c13,0xbf7fb10f,0xbd48fb30,0xbf7e1324,0x3dfab273,0xbf74fa0b,0x3e94a031,0xbf64aa59,0x3ee63375,0xbf4d9f02,0x3f187fc0,0xbf3085bb,0x3f396842,
0xbf74fa0b,0xbe94a031,0xbf7e4323,0xbdee3876,0xbf7f84ab,0x3d7b2b74,0xbf78b47b,0x3e72b651,0xbf6a09a7,0x3ecf7bca,0xbf53fac3,0x3f0f8784,0xbf373a23,0x3f32c8c9,0xbf14b039,0x3f5064af,
0xbf7b14be,0xbe47c5c2,0xbf7ffb11,0xbc490e90,0xbf7c3b28,0x3e2f10a2,0xbf6ff573,0x3eb263ef,0xbf5b941a,0x3f039c3d,0xbf3fc767,0x3f299415,0xbf1d7fd1,0x3f49d112,0xbeebcbbb,0x3f633c5a,
0xbf7ec46d,0xbdc8bd36,0xbf7eea9d,0x3dbc3ac3,0xbf75dec6,0x3e8e9a22,0xbf63f473,0x3ee900b7,0xbf49d112,0x3f1d7fd1,0xbf286605,0x3f40d0da,0xbf00e7e4,0x3f5d2d53,0xbea986c4,0x3f718f57,
0x3f800000,0x0,0x3f800000,0x0,0x3f800000,0x0,0x3f800000,0x0,0x3f800000,0x0,0x3f800000,0x0,0x3f800000,0x0,0x3f800000,0x0,
0x3f7d3aac,0xbe164083,0x3f7cfe73,0xbe1c76de,0x3f7cbfc9,0xbe22abb6,0x3f7c7eb0,0xbe28defc,0x3f7c3b28,0xbe2f10a2,0x3f7bf531,0xbe354098,0x3f7baccd,0xbe3b6ecf,0x3f7b61fc,0xbe419b37,
0x3f74fa0b,0xbe94a031,0x3f740bdd,0xbe9aa086,0x3f731447,0xbea09ae5,0x3f721352,0xbea68f12,0x3f710908,0xbeac7cd4,0x3f6ff573,0xbeb263ef,0x3f6ed89e,0xbeb8442a,0x3f6db293,0xbebe1d4a,
0x3f676bd8,0xbedae880,0x3f655e0b,0xbee363fa,0x3f633c5a,0xbeebcbbb,0x3f6106f2,0xbef41f07,0x3f5ebe05,0xbefc5d27,0x3f5c61c7,0xbf0242b1,0x3f59f26a,0xbf064b82,0x3f577026,0xbf0a48ad,
0x3f54db31,0xbf0e39da,0x3f514d3d,0xbf13682a,0x3f4d9f02,0xbf187fc0,0x3f49d112,0xbf1d7fd1,0x3f45e403,0xbf226799,0x3f41d870,0xbf273656,0x3f3daef9,0xbf2beb4a,0x3f396842,0xbf3085bb,
0x3f3daef9,0xbf2beb4a,0x3f385216,0xbf31a81d,0x3f32c8c9,0xbf373a23,0x3f2d1469,0xbf3ca003,0x3f273656,0xbf41d870,0x3f212ff9,0xbf46e22a,0x3f1b02c6,0xbf4bbbf8,0x3f14b039,0xbf5064af,
0x3f226799,0xbf45e403,0x3f1b02c6,0xbf4bbbf8,0x3f13682a,0xbf514d3d,0x3f0b9a6b,0xbf5695e5,0x3f039c3d,0xbf5b941a,0x3ef6e0cb,0xbf604621,0x3ee63375,0xbf64aa59,0x3ed53641,0xbf68bf3c,
0x3f039c3d,0xbf5b941a,0x3ef41f07,0xbf6106f2,0x3ee0924f,0xbf660f88,0x3ecc9b8b,0xbf6aab7b,0x3eb8442a,0xbf6ed89e,0x3ea395c5,0xbf7294f8,0x3e8e9a22,0xbf75dec6,0x3e72b651,0xbf78b47b,
0x3ec3ef15,0xbf6c835e,0x3eac7cd4,0xbf710908,0x3e94a031,0xbf74fa0b,0x3e78cfcc,0xbf7853f8,0x3e47c5c2,0xbf7b14be,0x3e164083,0xbf7d3aac,0x3dc8bd36,0xbf7ec46d,0x3d48fb30,0xbf7fb10f,
0x3e78cfcc,0xbf7853f8,0x3e419b37,0xbf7b61fc,0x3e09cf86,0xbf7dabcc,0x3da3308c,0xbf7f2f9d,0x3cc90ab0,0xbf7fec43,0xbcfb49ba,0xbf7fe129,0xbdafb680,0xbf7f0e58,0xbe1008b7,0xbf7d7474,
0x3dc8bd36,0xbf7ec46d,0x3d16c32c,0xbf7fd397,0xbcc90ab0,0xbf7fec43,0xbdafb680,0xbf7f0e58,0xbe164083,0xbf7d3aac,0xbe541501,0xbf7a7302,0xbe888e93,0xbf76ba07,0xbea68f12,0xbf721352,
0xbd48fb30,0xbf7fb10f,0xbdee3876,0xbf7e4323,0xbe3b6ecf,0xbf7baccd,0xbe7ee6e1,0xbf77f110,0xbea09ae5,0xbf731447,0xbec1071e,0xbf6d1c1d,0xbee0924f,0xbf660f88,0xbeff17b2,0xbf5df6be,
0xbe47c5c2,0xbf7b14be,0xbe888e93,0xbf76ba07,0xbeac7cd4,0xbf710908,0xbecf7bca,0xbf6a09a7,0xbef15aea,0xbf61c598,0xbf08f59b,0xbf584853,0xbf187fc0,0xbf4d9f02,0xbf273656,0xbf41d870,
0xbeac7cd4,0xbf710908,0xbed25a09,0xbf696591,0xbef6e0cb,0xbf604621,0xbf0cead0,0xbf55b993,0xbf1d7fd1,0xbf49d112,0xbf2d1469,0xbf3ca003,0xbf3b8f3b,0xbf2e3bde,0xbf48d8b3,0xbf1ebc12,
0xbef15aea,0xbf61c598,0xbf0b9a6b,0xbf5695e5,0xbf1d7fd1,0xbf49d112,0xbf2e3bde,0xbf3b8f3b,0xbf3daef9,0xbf2beb4a,0xbf4bbbf8,0xbf1b02c6,0xbf584853,0xbf08f59b,0xbf633c5a,0xbeebcbbb,
0xbf187fc0,0xbf4d9f02,0xbf2ac082,0xbf3ebc1b,0xbf3b8f3b,0xbf2e3bde,0xbf4ac77f,0xbf1c420c,0xbf584853,0xbf08f59b,0xbf63f473,0xbee900b7,0xbf6db293,0xbebe1d4a,0xbf756d97,0xbe919ddd,
0xbf3504f3,0xbf3504f3,0xbf45e403,0xbf226799,0xbf54db31,0xbf0e39da,0xbf61c598,0xbef15aea,0xbf6c835e,0xbec3ef15,0xbf74fa0b,0xbe94a031,0xbf7b14be,0xbe47c5c2,0xbf7ec46d,0xbdc8bd36,
0xbf4d9f02,0xbf187fc0,0xbf5c61c7,0xbf0242b1,0xbf68bf3c,0xbed53641,0xbf7294f8,0xbea395c5,0xbf79c79d,0xbe605c13,0xbf7e4323,0xbdee3876,0xbf7ffb11,0xbc490e90,0xbf7eea9d,0x3dbc3ac3,
0xbf61c598,0xbef15aea,0xbf6db293,0xbebe1d4a,0xbf76ba07,0xbe888e93,0xbf7cbfc9,0xbe22abb6,0xbf7fb10f,0xbd48fb30,0xbf7f84ab,0x3d7b2b74,0xbf7c3b28,0x3e2f10a2,0xbf75dec6,0x3e8e9a22,
0xbf710908,0xbeac7cd4,0xbf796e4e,0xbe667c66,0xbf7e70b0,0xbde1bc2e,0xbf7ffec4,0x3bc90f88,0xbf7e1324,0x3dfab273,0xbf78b47b,0x3e72b651,0xbf6ff573,0x3eb263ef,0xbf63f473,0x3ee900b7,
0xbf7b14be,0xbe47c5c2,0xbf7f4e6d,0xbd96a905,0xbf7fb10f,0x3d48fb30,0xbf7c3b28,0x3e2f10a2,0xbf74fa0b,0x3e94a031,0xbf6a09a7,0x3ecf7bca,0xbf5b941a,0x3f039c3d,0xbf49d112,0x3f1d7fd1,
0xbf7fb10f,0xbd48fb30,0xbf7f2f9d,0x3da3308c,0xbf7a7302,0x3e541501,0xbf718f57,0x3ea986c4,0xbf64aa59,0x3ee63375,0xbf53fac3,0x3f0f8784,0xbf3fc767,0x3f299415,0xbf286605,0x3f40d0da,
0xbf7ec46d,0x3dc8bd36,0xbf791298,0x3e6c9a7f,0xbf6ed89e,0x3eb8442a,0xbf604621,0x3ef6e0cb,0xbf4d9f02,0x3f187fc0,0xbf373a23,0x3f32c8c9,0xbf1d7fd1,0x3f49d112,0xbf00e7e4,0x3f5d2d53,
0xbf7853f8,0x3e78cfcc,0xbf6d1c1d,0x3ec1071e,0xbf5d2d53,0x3f00e7e4,0xbf48d8b3,0x3f1ebc12,0xbf3085bb,0x3f396842,0xbf14b039,0x3f5064af,0xbeebcbbb,0x3f633c5a,0xbea986c4,0x3f718f57,
0xbf6c835e,0x3ec3ef15,0xbf5b941a,0x3f039c3d,0xbf45e403,0x3f226799,0xbf2beb4a,0x3f3daef9,0xbf0e39da,0x3f54db31,0xbedae880,0x3f676bd8,0xbe94a031,0x3f74fa0b,0xbe164083,0x3f7d3aac,
0xbf5b941a,0x3f039c3d,0xbf44e3f5,0x3f239da9,0xbf299415,0x3f3fc767,0xbf0a48ad,0x3f577026,0xbecf7bca,0x3f6a09a7,0xbe8586ce,0x3f772417,0xbde1bc2e,0x3f7e70b0,0x3d2fe007,0x3f7fc38f,
0xbf45e403,0x3f226799,0xbf299415,0x3f3fc767,0xbf08f59b,0x3f584853,0xbec9b953,0x3f6b4b0c,0xbe78cfcc,0x3f7853f8,0xbdafb680,0x3f7f0e58,0x3d96a905,0x3f7f4e6d,0x3e6c9a7f,0x3f791298,
0xbf2beb4a,0x3f3daef9,0xbf0a48ad,0x3f577026,0xbec9b953,0x3f6b4b0c,0xbe72b651,0x3f78b47b,0xbd96a905,0x3f7f4e6d,0x3dbc3ac3,0x3f7eea9d,0x3e827dc0,0x3f778bc5,0x3ed25a09,0x3f696591,
0xbf0e39da,0x3f54db31,0xbecf7bca,0x3f6a09a7,0xbe78cfcc,0x3f7853f8,0xbd96a905,0x3f7f4e6d,0x3dc8bd36,0x3f7ec46d,0x3e888e93,0x3f76ba07,0x3edae880,0x3f676bd8,0x3f13682a,0x3f514d3d,
0xbedae880,0x3f676bd8,0xbe8586ce,0x3f772417,0xbdafb680,0x3f7f0e58,0x3dbc3ac3,0x3f7eea9d,0x3e888e93,0x3f76ba07,0x3eddbe79,0x3f66becc,0x3f15f6d9,0x3f4f7a1f,0x3f385216,0x3f31a81d,
0xbe94a031,0x3f74fa0b,0xbde1bc2e,0x3f7e70b0,0x3d96a905,0x3f7f4e6d,0x3e827dc0,0x3f778bc5,0x3edae880,0x3f676bd8,0x3f15f6d9,0x3f4f7a1f,0x3f396842,0x3f3085bb,0x3f5695e5,0x3f0b9a6b,
0xbe164083,0x3f7d3aac,0x3d2fe007,0x3f7fc38f,0x3e6c9a7f,0x3f791298,0x3ed25a09,0x3f696591,0x3f13682a,0x3f514d3d,0x3f385216,0x3f31a81d,0x3f5695e5,0x3f0b9a6b,0x3f6d1c1d,0x3ec1071e,
0xbd803d80,0x80003e00,0x80003e00,0x80003e00,0x80003e00,0x80003e00,0x80003e00,0x80003e00,0x80003e00,0x80003e00,0x80003e00,0x80003e00,0x80003e00,0x80003e00,0x80003e00,0x80003e00,
0x3d803d80,0x3cc83dfb,0x3e000000,0x3dfbbcc8,0x3d443ded,0x3d8e3dd5,0x3dedbd44,0x3dd5bd8e,0x3db53db5,0x3dd53d8e,0x3db5bdb5,0x3d8ebdd5,0x3ded3d44,0x3dfb3cc8,0x3d44bded,0x3cc8bdfb,
0xbd803d80,0x3d443ded,0x8000be00,0xbd44bded,0x3db53db5,0x3ded3d44,0xbdb5bdb5,0xbdedbd44,0x3e000000,0x3dedbd44,0xbe000000,0xbded3d44,0x3db5bdb5,0x3d44bded,0xbdb53db5,0xbd443ded,
0x3d803d80,0x3d8e3dd5,0xbe000000,0xbdd53d8e,0x3ded3d44,0x3dfbbcc8,0xbd443ded,0x3cc83dfb,0x3db5bdb5,0x3cc8bdfb,0x3db53db5,0x3dfb3cc8,0xbd44bded,0xbdd5bd8e,0x3dedbd44,0x3d8ebdd5,
0xbd803d80,0x3db53db5,0x80003e00,0x3db53db5,0x3e000000,0x3db5bdb5,0x3e000000,0x3db5bdb5,0x8000be00,0xbdb5bdb5,0x8000be00,0xbdb5bdb5,0xbe000000,0xbdb53db5,0xbe000000,0xbdb53db5,
0x3d803d80,0x3dd53d8e,0x3e000000,0x3d8ebdd5,0x3dedbd44,0x3cc8bdfb,0xbd44bded,0xbdfbbcc8,0xbdb5bdb5,0xbdfb3cc8,0xbdb53db5,0x3cc83dfb,0xbd443ded,0x3d8e3dd5,0x3ded3d44,0x3dd5bd8e,
0xbd803d80,0x3ded3d44,0x8000be00,0xbdedbd44,0x3db5bdb5,0xbd44bded,0xbdb53db5,0x3d443ded,0xbe000000,0xbd443ded,0x3e000000,0x3d44bded,0x3db53db5,0x3dedbd44,0xbdb5bdb5,0xbded3d44,
0x3d803d80,0x3dfb3cc8,0xbe000000,0xbcc83dfb,0x3d44bded,0xbdd5bd8e,0x3ded3d44,0x3d8ebdd5,0xbdb53db5,0x3d8e3dd5,0xbdb5bdb5,0xbdd53d8e,0x3dedbd44,0xbcc8bdfb,0x3d443ded,0x3dfbbcc8,
0xbd803d80,0x3e000000,0x80003e00,0x3e000000,0x8000be00,0xbe000000,0x8000be00,0xbe000000,0x80003e00,0x3e000000,0x80003e00,0x3e000000,0x8000be00,0xbe000000,0x8000be00,0xbe000000,
0x3d803d80,0x3dfbbcc8,0x3e000000,0xbcc8bdfb,0xbd44bded,0xbdd53d8e,0xbded3d44,0x3d8e3dd5,0x3db53db5,0x3d8ebdd5,0x3db5bdb5,0xbdd5bd8e,0xbdedbd44,0xbcc83dfb,0xbd443ded,0x3dfb3cc8,
0xbd803d80,0x3dedbd44,0x8000be00,0xbded3d44,0xbdb5bdb5,0xbd443ded,0x3db53db5,0x3d44bded,0x3e000000,0xbd44bded,0xbe000000,0x3d443ded,0xbdb53db5,0x3ded3d44,0x3db5bdb5,0xbdedbd44,
0x3d803d80,0x3dd5bd8e,0xbe000000,0x3d8e3dd5,0xbdedbd44,0x3cc83dfb,0x3d44bded,0xbdfb3cc8,0x3db5bdb5,0xbdfbbcc8,0x3db53db5,0x3cc8bdfb,0x3d443ded,0x3d8ebdd5,0xbded3d44,0x3dd53d8e,
0xbd803d80,0x3db5bdb5,0x80003e00,0x3db5bdb5,0xbe000000,0x3db53db5,0xbe000000,0x3db53db5,0x8000be00,0xbdb53db5,0x8000be00,0xbdb53db5,0x3e000000,0xbdb5bdb5,0x3e000000,0xbdb5bdb5,
0x3d803d80,0x3d8ebdd5,0x3e000000,0xbdd5bd8e,0xbded3d44,0x3dfb3cc8,0x3d443ded,0x3cc8bdfb,0xbdb5bdb5,0x3cc83dfb,0xbdb53db5,0x3dfbbcc8,0x3d44bded,0xbdd53d8e,0xbdedbd44,0x3d8e3dd5,
0xbd803d80,0x3d44bded,0x8000be00,0xbd443ded,0xbdb53db5,0x3dedbd44,0x3db5bdb5,0xbded3d44,0xbe000000,0x3ded3d44,0x3e000000,0xbdedbd44,0xbdb5bdb5,0x3d443ded,0x3db53db5,0xbd44bded,
0x3d803d80,0x3cc8bdfb,0xbe000000,0x3dfb3cc8,0xbd443ded,0x3d8ebdd5,0xbdedbd44,0x3dd53d8e,0xbdb53db5,0x3dd5bd8e,0xbdb5bdb5,0x3d8e3dd5,0xbded3d44,0x3dfbbcc8,0xbd44bded,0x3cc83dfb,
0xbd803d80,0x8000be00,0x80003e00,0x8000be00,0x80003e00,0x8000be00,0x80003e00,0x8000be00,0x80003e00,0x8000be00,0x80003e00,0x8000be00,0x80003e00,0x8000be00,0x80003e00,0x8000be00,
0x3d803d80,0xbcc8bdfb,0x3e000000,0xbdfb3cc8,0x3d443ded,0xbd8ebdd5,0x3dedbd44,0xbdd53d8e,0x3db53db5,0xbdd5bd8e,0x3db5bdb5,0xbd8e3dd5,0x3ded3d44,0xbdfbbcc8,0x3d44bded,0xbcc83dfb,
0xbd803d80,0xbd44bded,0x8000be00,0x3d443ded,0x3db53db5,0xbdedbd44,0xbdb5bdb5,0x3ded3d44,0x3e000000,0xbded3d44,0xbe000000,0x3dedbd44,0x3db5bdb5,0xbd443ded,0xbdb53db5,0x3d44bded,
0x3d803d80,0xbd8ebdd5,0xbe000000,0x3dd5bd8e,0x3ded3d44,0xbdfb3cc8,0xbd443ded,0xbcc8bdfb,0x3db5bdb5,0xbcc83dfb,0x3db53db5,0xbdfbbcc8,0xbd44bded,0x3dd53d8e,0x3dedbd44,0xbd8e3dd5,
0xbd803d80,0xbdb5bdb5,0x80003e00,0xbdb5bdb5,0x3e000000,0xbdb53db5,0x3e000000,0xbdb53db5,0x8000be00,0x3db53db5,0x8000be00,0x3db53db5,0xbe000000,0x3db5bdb5,0xbe000000,0x3db5bdb5,
0x3d803d80,0xbdd5bd8e,0x3e000000,0xbd8e3dd5,0x3dedbd44,0xbcc83dfb,0xbd44bded,0x3dfb3cc8,0xbdb5bdb5,0x3dfbbcc8,0xbdb53db5,0xbcc8bdfb,0xbd443ded,0xbd8ebdd5,0x3ded3d44,0xbdd53d8e,
0xbd803d80,0xbdedbd44,0x8000be00,0x3ded3d44,0x3db5bdb5,0x3d443ded,0xbdb53db5,0xbd44bded,0xbe000000,0x3d44bded,0x3e000000,0xbd443ded,0x3db53db5,0xbded3d44,0xbdb5bdb5,0x3dedbd44,
0x3d803d80,0xbdfbbcc8,0xbe000000,0x3cc8bdfb,0x3d44bded,0x3dd53d8e,0x3ded3d44,0xbd8e3dd5,0xbdb53db5,0xbd8ebdd5,0xbdb5bdb5,0x3dd5bd8e,0x3dedbd44,0x3cc83dfb,0x3d443ded,0xbdfb3cc8,
0xbd803d80,0xbe000000,0x80003e00,0xbe000000,0x8000be00,0x3e000000,0x8000be00,0x3e000000,0x80003e00,0xbe000000,0x80003e00,0xbe000000,0x8000be00,0x3e000000,0x8000be00,0x3e000000,
0x3d803d80,0xbdfb3cc8,0x3e000000,0x3cc83dfb,0xbd44bded,0x3dd5bd8e,0xbded3d44,0xbd8ebdd5,0x3db53db5,0xbd8e3dd5,0x3db5bdb5,0x3dd53d8e,0xbdedbd44,0x3cc8bdfb,0xbd443ded,0xbdfbbcc8,
0xbd803d80,0xbded3d44,0x8000be00,0x3dedbd44,0xbdb5bdb5,0x3d44bded,0x3db53db5,0xbd443ded,0x3e000000,0x3d443ded,0xbe000000,0xbd44bded,0xbdb53db5,0xbdedbd44,0x3db5bdb5,0x3ded3d44,
0x3d803d80,0xbdd53d8e,0xbe000000,0xbd8ebdd5,0xbdedbd44,0xbcc8bdfb,0x3d44bded,0x3dfbbcc8,0x3db5bdb5,0x3dfb3cc8,0x3db53db5,0xbcc83dfb,0x3d443ded,0xbd8e3dd5,0xbded3d44,0xbdd5bd8e,
0xbd803d80,0xbdb53db5,0x80003e00,0xbdb53db5,0xbe000000,0xbdb5bdb5,0xbe000000,0xbdb5bdb5,0x8000be00,0x3db5bdb5,0x8000be00,0x3db5bdb5,0x3e000000,0x3db53db5,0x3e000000,0x3db53db5,
0x3d803d80,0xbd8e3dd5,0x3e000000,0x3dd53d8e,0xbded3d44,0xbdfbbcc8,0x3d443ded,0xbcc83dfb,0xbdb5bdb5,0xbcc8bdfb,0xbdb53db5,0xbdfb3cc8,0x3d44bded,0x3dd5bd8e,0xbdedbd44,0xbd8ebdd5,
0xbd803d80,0xbd443ded,0x8000be00,0x3d44bded,0xbdb53db5,0xbded3d44,0x3db5bdb5,0x3dedbd44,0xbe000000,0xbdedbd44,0x3e000000,0x3ded3d44,0xbdb5bdb5,0xbd44bded,0x3db53db5,0x3d443ded,
0x3d803d80,0xbcc83dfb,0xbe000000,0xbdfbbcc8,0xbd443ded,0xbd8e3dd5,0xbdedbd44,0xbdd5bd8e,0xbdb53db5,0xbdd53d8e,0xbdb5bdb5,0xbd8ebdd5,0xbded3d44,0xbdfb3cc8,0xbd44bded,0xbcc8bdfb,
0x80003e00,0x80003e00,0x80003e00,0x80003e00,0x80003e00,0x80003e00,0x80003e00,0x80003e00,0x80003e00,0x80003e00,0x80003e00,0x80003e00,0x80003e00,0x80003e00,0x80003e00,0x80003e00,
0x3c493dff,0x3d153df5,0x3dffbc49,0x3df5bd15,0x3d713de2,0x3da23dc6,0x3de2bd71,0x3dc6bda2,0x3dc63da2,0x3de23d71,0x3da2bdc6,0x3d71bde2,0x3df53d15,0x3dff3c49,0x3d15bdf5,0x3c49bdff,
0x3cc83dfb,0x3d8e3dd5,0xbcc8bdfb,0xbd8ebdd5,0x3dd53d8e,0x3dfb3cc8,0xbdd5bd8e,0xbdfbbcc8,0x3dfbbcc8,0x3dd5bd8e,0xbdfb3cc8,0xbdd53d8e,0x3d8ebdd5,0x3cc8bdfb,0xbd8e3dd5,0xbcc83dfb,
0x3d153df5,0x3dc63da2,0xbdf53d15,0xbda23dc6,0x3dff3c49,0x3de2bd71,0xbc493dff,0x3d713de2,0x3d71bde2,0xbc49bdff,0x3de23d71,0x3dffbc49,0xbda2bdc6,0xbdf5bd15,0x3dc6bda2,0x3d15bdf5,
0x3d443ded,0x3ded3d44,0x3d443ded,0x3ded3d44,0x3dedbd44,0x3d44bded,0x3dedbd44,0x3d44bded,0xbd44bded,0xbdedbd44,0xbd44bded,0xbdedbd44,0xbded3d44,0xbd443ded,0xbded3d44,0xbd443ded,
0x3d713de2,0x3dff3c49,0x3de2bd71,0x3c49bdff,0x3da2bdc6,0xbd15bdf5,0xbdc6bda2,0xbdf53d15,0xbdf5bd15,0xbdc63da2,0xbd153df5,0x3da23dc6,0x3c493dff,0x3de23d71,0x3dffbc49,0x3d71bde2,
0x3d8e3dd5,0x3dfbbcc8,0xbd8ebdd5,0xbdfb3cc8,0x3cc8bdfb,0xbdd5bd8e,0xbcc83dfb,0x3dd53d8e,0xbdd53d8e,0x3cc83dfb,0x3dd5bd8e,0xbcc8bdfb,0x3dfb3cc8,0x3d8ebdd5,0xbdfbbcc8,0xbd8e3dd5,
0x3da23dc6,0x3de2bd71,0xbdc63da2,0x3d713de2,0xbd15bdf5,0xbdff3c49,0x3df5bd15,0xbc49bdff,0xbc493dff,0x3df53d15,0xbdffbc49,0xbd153df5,0x3d71bde2,0xbdc6bda2,0x3de23d71,0x3da2bdc6,
0x3db53db5,0x3db5bdb5,0x3db53db5,0x3db5bdb5,0xbdb5bdb5,0xbdb53db5,0xbdb5bdb5,0xbdb53db5,0x3db53db5,0x3db5bdb5,0x3db53db5,0x3db5bdb5,0xbdb5bdb5,0xbdb53db5,0xbdb5bdb5,0xbdb53db5,
0x3dc63da2,0x3d71bde2,0x3da2bdc6,0xbde2bd71,0xbdf5bd15,0xbc493dff,0xbd153df5,0x3dff3c49,0x3dffbc49,0xbd15bdf5,0xbc49bdff,0xbdf53d15,0xbde23d71,0x3da23dc6,0x3d713de2,0x3dc6bda2,
0x3dd53d8e,0x3cc8bdfb,0xbdd5bd8e,0xbcc83dfb,0xbdfb3cc8,0x3d8e3dd5,0x3dfbbcc8,0xbd8ebdd5,0x3d8ebdd5,0xbdfbbcc8,0xbd8e3dd5,0x3dfb3cc8,0x3cc83dfb,0x3dd5bd8e,0xbcc8bdfb,0xbdd53d8e,
0x3de23d71,0xbc49bdff,0xbd713de2,0x3dffbc49,0xbdc63da2,0x3df53d15,0xbda2bdc6,0xbd153df5,0xbd15bdf5,0xbda23dc6,0x3df5bd15,0xbdc6bda2,0x3dff3c49,0xbd71bde2,0xbc493dff,0x3de2bd71,
0x3ded3d44,0xbd44bded,0x3ded3d44,0xbd44bded,0xbd443ded,0x3dedbd44,0xbd443ded,0x3dedbd44,0xbdedbd44,0x3d443ded,0xbdedbd44,0x3d443ded,0x3d44bded,0xbded3d44,0x3d44bded,0xbded3d44,
0x3df53d15,0xbda2bdc6,0x3d15bdf5,0xbdc63da2,0x3c493dff,0x3d71bde2,0x3dffbc49,0xbde2bd71,0xbde23d71,0x3dff3c49,0x3d713de2,0x3c49bdff,0xbdc6bda2,0x3d153df5,0xbda23dc6,0x3df5bd15,
0x3dfb3cc8,0xbdd5bd8e,0xbdfbbcc8,0x3dd53d8e,0x3d8e3dd5,0xbcc8bdfb,0xbd8ebdd5,0x3cc83dfb,0xbcc83dfb,0x3d8ebdd5,0x3cc8bdfb,0xbd8e3dd5,0xbdd53d8e,0x3dfbbcc8,0x3dd5bd8e,0xbdfb3cc8,
0x3dff3c49,0xbdf5bd15,0xbc493dff,0x3d15bdf5,0x3de23d71,0xbdc6bda2,0xbd713de2,0x3da2bdc6,0x3da23dc6,0xbd71bde2,0xbdc63da2,0x3de2bd71,0x3d153df5,0xbc49bdff,0xbdf53d15,0x3dffbc49,
0x3e000000,0xbe000000,0x3e000000,0xbe000000,0x3e000000,0xbe000000,0x3e000000,0xbe000000,0x3e000000,0xbe000000,0x3e000000,0xbe000000,0x3e000000,0xbe000000,0x3e000000,0xbe000000,
0x3dffbc49,0xbdf53d15,0xbc49bdff,0x3d153df5,0x3de2bd71,0xbdc63da2,0xbd71bde2,0x3da23dc6,0x3da2bdc6,0xbd713de2,0xbdc6bda2,0x3de23d71,0x3d15bdf5,0xbc493dff,0xbdf5bd15,0x3dff3c49,
0x3dfbbcc8,0xbdd53d8e,0xbdfb3cc8,0x3dd5bd8e,0x3d8ebdd5,0xbcc83dfb,0xbd8e3dd5,0x3cc8bdfb,0xbcc8bdfb,0x3d8e3dd5,0x3cc83dfb,0xbd8ebdd5,0xbdd5bd8e,0x3dfb3cc8,0x3dd53d8e,0xbdfbbcc8,
0x3df5bd15,0xbda23dc6,0x3d153df5,0xbdc6bda2,0x3c49bdff,0x3d713de2,0x3dff3c49,0xbde23d71,0xbde2bd71,0x3dffbc49,0x3d71bde2,0x3c493dff,0xbdc63da2,0x3d15bdf5,0xbda2bdc6,0x3df53d15,
0x3dedbd44,0xbd443ded,0x3dedbd44,0xbd443ded,0xbd44bded,0x3ded3d44,0xbd44bded,0x3ded3d44,0xbded3d44,0x3d44bded,0xbded3d44,0x3d44bded,0x3d443ded,0xbdedbd44,0x3d443ded,0xbdedbd44,
0x3de2bd71,0xbc493dff,0xbd71bde2,0x3dff3c49,0xbdc6bda2,0x3df5bd15,0xbda23dc6,0xbd15bdf5,0xbd153df5,0xbda2bdc6,0x3df53d15,0xbdc63da2,0x3dffbc49,0xbd713de2,0xbc49bdff,0x3de23d71,
0x3dd5bd8e,0x3cc83dfb,0xbdd53d8e,0xbcc8bdfb,0xbdfbbcc8,0x3d8ebdd5,0x3dfb3cc8,0xbd8e3dd5,0x3d8e3dd5,0xbdfb3cc8,0xbd8ebdd5,0x3dfbbcc8,0x3cc8bdfb,0x3dd53d8e,0xbcc83dfb,0xbdd5bd8e,
0x3dc6bda2,0x3d713de2,0x3da23dc6,0xbde23d71,0xbdf53d15,0xbc49bdff,0xbd15bdf5,0x3dffbc49,0x3dff3c49,0xbd153df5,0xbc493dff,0xbdf5bd15,0xbde2bd71,0x3da2bdc6,0x3d71bde2,0x3dc63da2,
0x3db5bdb5,0x3db53db5,0x3db5bdb5,0x3db53db5,0xbdb53db5,0xbdb5bdb5,0xbdb53db5,0xbdb5bdb5,0x3db5bdb5,0x3db53db5,0x3db5bdb5,0x3db53db5,0xbdb53db5,0xbdb5bdb5,0xbdb53db5,0xbdb5bdb5,
0x3da2bdc6,0x3de23d71,0xbdc6bda2,0x3d71bde2,0xbd153df5,0xbdffbc49,0x3df53d15,0xbc493dff,0xbc49bdff,0x3df5bd15,0xbdff3c49,0xbd15bdf5,0x3d713de2,0xbdc63da2,0x3de2bd71,0x3da23dc6,
0x3d8ebdd5,0x3dfb3cc8,0xbd8e3dd5,0xbdfbbcc8,0x3cc83dfb,0xbdd53d8e,0xbcc8bdfb,0x3dd5bd8e,0xbdd5bd8e,0x3cc8bdfb,0x3dd53d8e,0xbcc83dfb,0x3dfbbcc8,0x3d8e3dd5,0xbdfb3cc8,0xbd8ebdd5,
0x3d71bde2,0x3dffbc49,0x3de23d71,0x3c493dff,0x3da23dc6,0xbd153df5,0xbdc63da2,0xbdf5bd15,0xbdf53d15,0xbdc6bda2,0xbd15bdf5,0x3da2bdc6,0x3c49bdff,0x3de2bd71,0x3dff3c49,0x3d713de2,
0x3d44bded,0x3dedbd44,0x3d44bded,0x3dedbd44,0x3ded3d44,0x3d443ded,0x3ded3d44,0x3d443ded,0xbd443ded,0xbded3d44,0xbd443ded,0xbded3d44,0xbdedbd44,0xbd44bded,0xbdedbd44,0xbd44bded,
0x3d15bdf5,0x3dc6bda2,0xbdf5bd15,0xbda2bdc6,0x3dffbc49,0x3de23d71,0xbc49bdff,0x3d71bde2,0x3d713de2,0xbc493dff,0x3de2bd71,0x3dff3c49,0xbda23dc6,0xbdf53d15,0x3dc63da2,0x3d153df5,
0x3cc8bdfb,0x3d8ebdd5,0xbcc83dfb,0xbd8e3dd5,0x3dd5bd8e,0x3dfbbcc8,0xbdd53d8e,0xbdfb3cc8,0x3dfb3cc8,0x3dd53d8e,0xbdfbbcc8,0xbdd5bd8e,0x3d8e3dd5,0x3cc83dfb,0xbd8ebdd5,0xbcc8bdfb,
0x3c49bdff,0x3d15bdf5,0x3dff3c49,0x3df53d15,0x3d71bde2,0x3da2bdc6,0x3de23d71,0x3dc63da2,0x3dc6bda2,0x3de2bd71,0x3da23dc6,0x3d713de2,0x3df5bd15,0x3dffbc49,0x3d153df5,0x3c493dff,
0x3f800000,0x0,0x3f800000,0x0,0x3f800000,0x0,0x3f800000,0x0,0x3f800000,0x0,0x3f800000,0x0,0x3f800000,0x0,0x3f800000,0x0,
0x3f800000,0x0,0x3f7ffb11,0xbc490e90,0x3f7fec43,0xbcc90ab0,0x3f7fd397,0xbd16c32c,0x3f7fb10f,0xbd48fb30,0x3f7f84ab,0xbd7b2b74,0x3f7f4e6d,0xbd96a905,0x3f7f0e58,0xbdafb680,
0x3f800000,0x0,0x3f7fec43,0xbcc90ab0,0x3f7fb10f,0xbd48fb30,0x3f7f4e6d,0xbd96a905,0x3f7ec46d,0xbdc8bd36,0x3f7e1324,0xbdfab273,0x3f7d3aac,0xbe164083,0x3f7c3b28,0xbe2f10a2,
0x3f800000,0x0,0x3f7fd397,0xbd16c32c,0x3f7f4e6d,0xbd96a905,0x3f7e70b0,0xbde1bc2e,0x3f7d3aac,0xbe164083,0x3f7baccd,0xbe3b6ecf,0x3f79c79d,0xbe605c13,0x3f778bc5,0xbe827dc0,
0x3f800000,0x0,0x3f7fb10f,0xbd48fb30,0x3f7ec46d,0xbdc8bd36,0x3f7d3aac,0xbe164083,0x3f7b14be,0xbe47c5c2,0x3f7853f8,0xbe78cfcc,0x3f74fa0b,0xbe94a031,0x3f710908,0xbeac7cd4,
0x3f800000,0x0,0x3f7f84ab,0xbd7b2b74,0x3f7e1324,0xbdfab273,0x3f7baccd,0xbe3b6ecf,0x3f7853f8,0xbe78cfcc,0x3f740bdd,0xbe9aa086,0x3f6ed89e,0xbeb8442a,0x3f68bf3c,0xbed53641,
0x3f800000,0x0,0x3f7f4e6d,0xbd96a905,0x3f7d3aac,0xbe164083,0x3f79c79d,0xbe605c13,0x3f74fa0b,0xbe94a031,0x3f6ed89e,0xbeb8442a,0x3f676bd8,0xbedae880,0x3f5ebe05,0xbefc5d27,
0x3f800000,0x0,0x3f7f0e58,0xbdafb680,0x3f7c3b28,0xbe2f10a2,0x3f778bc5,0xbe827dc0,0x3f710908,0xbeac7cd4,0x3f68bf3c,0xbed53641,0x3f5ebe05,0xbefc5d27,0x3f531849,0xbf10d3cd,
0x3f800000,0x0,0x3f7ec46d,0xbdc8bd36,0x3f7b14be,0xbe47c5c2,0x3f74fa0b,0xbe94a031,0x3f6c835e,0xbec3ef15,0x3f61c598,0xbef15aea,0x3f54db31,0xbf0e39da,0x3f45e403,0xbf226799,
0x3f800000,0x0,0x3f7e70b0,0xbde1bc2e,0x3f79c79d,0xbe605c13,0x3f721352,0xbea68f12,0x3f676bd8,0xbedae880,0x3f59f26a,0xbf064b82,0x3f49d112,0xbf1d7fd1,0x3f373a23,0xbf32c8c9,
0x3f800000,0x0,0x3f7e1324,0xbdfab273,0x3f7853f8,0xbe78cfcc,0x3f6ed89e,0xbeb8442a,0x3f61c598,0xbef15aea,0x3f514d3d,0xbf13682a,0x3f3daef9,0xbf2beb4a,0x3f273656,0xbf41d870,
0x3f800000,0x0,0x3f7dabcc,0xbe09cf86,0x3f76ba07,0xbe888e93,0x3f6b4b0c,0xbec9b953,0x3f5b941a,0xbf039c3d,0x3f47de65,0xbf1ff6cb,0x3f3085bb,0xbf396842,0x3f15f6d9,0xbf4f7a1f,
0x3f800000,0x0,0x3f7d3aac,0xbe164083,0x3f74fa0b,0xbe94a031,0x3f676bd8,0xbedae880,0x3f54db31,0xbf0e39da,0x3f3daef9,0xbf2beb4a,0x3f226799,0xbf45e403,0x3f039c3d,0xbf5b941a,
0x3f800000,0x0,0x3f7cbfc9,0xbe22abb6,0x3f731447,0xbea09ae5,0x3f633c5a,0xbeebcbbb,0x3f4d9f02,0xbf187fc0,0x3f32c8c9,0xbf373a23,0x3f13682a,0xbf514d3d,0x3ee0924f,0xbf660f88,
0x3f800000,0x0,0x3f7c3b28,0xbe2f10a2,0x3f710908,0xbeac7cd4,0x3f5ebe05,0xbefc5d27,0x3f45e403,0xbf226799,0x3f273656,0xbf41d870,0x3f039c3d,0xbf5b941a,0x3eb8442a,0xbf6ed89e,
0x3f800000,0x0,0x3f7baccd,0xbe3b6ecf,0x3f6ed89e,0xbeb8442a,0x3f59f26a,0xbf064b82,0x3f3daef9,0xbf2beb4a,0x3f1b02c6,0xbf4bbbf8,0x3ee63375,0xbf64aa59,0x3e8e9a22,0xbf75dec6,
0x3f800000,0x0,0x3f7b14be,0xbe47c5c2,0x3f6c835e,0xbec3ef15,0x3f54db31,0xbf0e39da,0x3f3504f3,0xbf3504f3,0x3f0e39da,0xbf54db31,0x3ec3ef15,0xbf6c835e,0x3e47c5c2,0xbf7b14be,
0x3f800000,0x0,0x3f7a7302,0xbe541501,0x3f6a09a7,0xbecf7bca,0x3f4f7a1f,0xbf15f6d9,0x3f2beb4a,0xbf3daef9,0x3f00e7e4,0xbf5d2d53,0x3ea09ae5,0xbf731447,0x3de1bc2e,0xbf7e70b0,
0x3f800000,0x0,0x3f79c79d,0xbe605c13,0x3f676bd8,0xbedae880,0x3f49d112,0xbf1d7fd1,0x3f226799,0xbf45e403,0x3ee63375,0xbf64aa59,0x3e78cfcc,0xbf7853f8,0x3cc90ab0,0xbf7fec43,
0x3f800000,0x0,0x3f791298,0xbe6c9a7f,0x3f64aa59,0xbee63375,0x3f43e200,0xbf24d225,0x3f187fc0,0xbf4d9f02,0x3ec9b953,0xbf6b4b0c,0x3e2f10a2,0xbf7c3b28,0xbd7b2b74,0xbf7f84ab,
0x3f800000,0x0,0x3f7853f8,0xbe78cfcc,0x3f61c598,0xbef15aea,0x3f3daef9,0xbf2beb4a,0x3f0e39da,0xbf54db31,0x3eac7cd4,0xbf710908,0x3dc8bd36,0xbf7ec46d,0xbe164083,0xbf7d3aac,
0x3f800000,0x0,0x3f778bc5,0xbe827dc0,0x3f5ebe05,0xbefc5d27,0x3f373a23,0xbf32c8c9,0x3f039c3d,0xbf5b941a,0x3e8e9a22,0xbf75dec6,0x3cc90ab0,0xbf7fec43,0xbe6c9a7f,0xbf791298,
0x3f800000,0x0,0x3f76ba07,0xbe888e93,0x3f5b941a,0xbf039c3d,0x3f3085bb,0xbf396842,0x3ef15aea,0xbf61c598,0x3e605c13,0xbf79c79d,0xbd48fb30,0xbf7fb10f,0xbea09ae5,0xbf731447,
0x3f800000,0x0,0x3f75dec6,0xbe8e9a22,0x3f584853,0xbf08f59b,0x3f299415,0xbf3fc767,0x3edae880,0xbf676bd8,0x3e22abb6,0xbf7cbfc9,0xbdfab273,0xbf7e1324,0xbec9b953,0xbf6b4b0c,
0x3f800000,0x0,0x3f74fa0b,0xbe94a031,0x3f54db31,0xbf0e39da,0x3f226799,0xbf45e403,0x3ec3ef15,0xbf6c835e,0x3dc8bd36,0xbf7ec46d,0xbe47c5c2,0xbf7b14be,0xbef15aea,0xbf61c598,
0x3f800000,0x0,0x3f740bdd,0xbe9aa086,0x3f514d3d,0xbf13682a,0x3f1b02c6,0xbf4bbbf8,0x3eac7cd4,0xbf710908,0x3d16c32c,0xbf7fd397,0xbe888e93,0xbf76ba07,0xbf0b9a6b,0xbf5695e5,
0x3f800000,0x0,0x3f731447,0xbea09ae5,0x3f4d9f02,0xbf187fc0,0x3f13682a,0xbf514d3d,0x3e94a031,0xbf74fa0b,0xbcc90ab0,0xbf7fec43,0xbeac7cd4,0xbf710908,0xbf1d7fd1,0xbf49d112,
0x3f800000,0x0,0x3f721352,0xbea68f12,0x3f49d112,0xbf1d7fd1,0x3f0b9a6b,0xbf5695e5,0x3e78cfcc,0xbf7853f8,0xbdafb680,0xbf7f0e58,0xbecf7bca,0xbf6a09a7,0xbf2e3bde,0xbf3b8f3b,
0x3f800000,0x0,0x3f710908,0xbeac7cd4,0x3f45e403,0xbf226799,0x3f039c3d,0xbf5b941a,0x3e47c5c2,0xbf7b14be,0xbe164083,0xbf7d3aac,0xbef15aea,0xbf61c598,0xbf3daef9,0xbf2beb4a,
0x3f800000,0x0,0x3f6ff573,0xbeb263ef,0x3f41d870,0xbf273656,0x3ef6e0cb,0xbf604621,0x3e164083,0xbf7d3aac,0xbe541501,0xbf7a7302,0xbf08f59b,0xbf584853,0xbf4bbbf8,0xbf1b02c6,
0x3f800000,0x0,0x3f6ed89e,0xbeb8442a,0x3f3daef9,0xbf2beb4a,0x3ee63375,0xbf64aa59,0x3dc8bd36,0xbf7ec46d,0xbe888e93,0xbf76ba07,0xbf187fc0,0xbf4d9f02,0xbf584853,0xbf08f59b,
0x3f800000,0x0,0x3f6db293,0xbebe1d4a,0x3f396842,0xbf3085bb,0x3ed53641,0xbf68bf3c,0x3d48fb30,0xbf7fb10f,0xbea68f12,0xbf721352,0xbf273656,0xbf41d870,0xbf633c5a,0xbeebcbbb,
0x3f800000,0x3f800000,0x3f800000,0x3f800000,0x3f800000,0x3f800000,0x3f800000,0x3f800000,0x3f800000,0xbf800000,0x3f800000,0xbf800000,0x3f800000,0xbf800000,0x3f800000,0xbf800000,
0x3f800000,0x3f3504f3,0x0,0xbf3504f3,0xbf800000,0xbf3504f3,0x0,0x3f3504f3,0x0,0xbf3504f3,0xbf800000,0xbf3504f3,0x0,0x3f3504f3,0x3f800000,0x3f3504f3,
0x3f800000,0x0,0xbf800000,0x0,0x3f800000,0x0,0xbf800000,0x0,0x0,0xbf800000,0x0,0x3f800000,0x0,0xbf800000,0x0,0x3f800000,
0x3f800000,0xbf3504f3,0x0,0x3f3504f3,0xbf800000,0x3f3504f3,0x0,0xbf3504f3,0x0,0xbf3504f3,0x3f800000,0xbf3504f3,0x0,0x3f3504f3,0xbf800000,0x3f3504f3,
0x3f800000,0x3f6c835e,0x3f3504f3,0x3ec3ef15,0x0,0xbec3ef15,0xbf3504f3,0xbf6c835e,0x0,0xbec3ef15,0xbf3504f3,0xbf6c835e,0xbf800000,0xbf6c835e,0xbf3504f3,0xbec3ef15,
0x3f800000,0x3ec3ef15,0xbf3504f3,0xbf6c835e,0x0,0x3f6c835e,0x3f3504f3,0xbec3ef15,0x0,0xbf6c835e,0xbf3504f3,0x3ec3ef15,0x3f800000,0x3ec3ef15,0xbf3504f3,0xbf6c835e,
0x3f800000,0xbec3ef15,0xbf3504f3,0x3f6c835e,0x0,0xbf6c835e,0x3f3504f3,0x3ec3ef15,0x0,0xbf6c835e,0x3f3504f3,0x3ec3ef15,0xbf800000,0x3ec3ef15,0x3f3504f3,0xbf6c835e,
0x3f800000,0xbf6c835e,0x3f3504f3,0xbec3ef15,0x0,0x3ec3ef15,0xbf3504f3,0x3f6c835e,0x0,0xbec3ef15,0x3f3504f3,0xbf6c835e,0x3f800000,0xbf6c835e,0x3f3504f3,0xbec3ef15,
};

struct Params {
    const __nv_bfloat16 *xb, *lre, *lim, *ldt, *dsk;
    float* out;
    int zero[8];
    uint64_t da[4];
    uint32_t unit[258];
};

struct Maps { CUtensorMap m[12]; };

struct cf { float x, y; };
__device__ __forceinline__ uint32_t smem_u32(const void* p) { return (uint32_t)__cvta_generic_to_shared(p); }
__device__ __forceinline__ void mbar_init(uint32_t a, uint32_t c) { asm volatile("mbarrier.init.shared::cta.b64 [%0], %1;" ::"r"(a), "r"(c) : "memory"); }
__device__ __forceinline__ void mbar_expect_tx(uint32_t a, uint32_t b) { asm volatile("mbarrier.arrive.expect_tx.shared::cta.b64 _, [%0], %1;" ::"r"(a), "r"(b) : "memory"); }
__device__ __forceinline__ void mbar_arrive(uint32_t a) { asm volatile("mbarrier.arrive.shared::cta.b64 _, [%0];" ::"r"(a) : "memory"); }
__device__ __forceinline__ void mbar_wait(uint32_t a, uint32_t ph) {
    asm volatile("{.reg .pred p; .reg .u32 n;\n"
                 "mov.u32 n, 0;\n"
                 "LOOP: mbarrier.try_wait.parity.shared::cta.b64 p, [%0], %1;\n"
                 "@p bra DONE;\n"
                 "add.u32 n, n, 1;\n"
                 "setp.lt.u32 p, n, %2;\n"
                 "@p bra LOOP;\n"
                 "DONE: }" ::"r"(a), "r"(ph), "n"(SPIN_LIMIT) : "memory");
}
__device__ __forceinline__ unsigned ld_rlx(const unsigned* p) { unsigned v; asm volatile("ld.relaxed.gpu.global.u32 %0, [%1];" : "=r"(v) : "l"(p) : "memory"); return v; }
__device__ __forceinline__ void wait_cnt(const unsigned* p, unsigned target) {
    unsigned n = 0;
    while ((int)(ld_rlx(p) - target) < 0 && ++n < SPIN_LIMIT) __nanosleep(20);
}
__device__ __forceinline__ void red_hint(unsigned* p) { asm volatile("red.relaxed.gpu.global.add.u32 [%0], 1;" ::"l"(p) : "memory"); }
__device__ __forceinline__ void fence_async() { asm volatile("fence.proxy.async.global;" ::: "memory"); }
__device__ __forceinline__ void fence_async_sm() { asm volatile("fence.proxy.async.shared::cta;" ::: "memory"); }
#define bar_sync(id, n) asm volatile("bar.sync %0, %1;" ::"n"(id), "n"(n) : "memory")
#define bar_arrive(id, n) asm volatile("bar.arrive %0, %1;" ::"n"(id), "n"(n) : "memory")
__device__ __forceinline__ bool elect_one() {
    uint32_t r;
    asm volatile("{.reg .pred p; elect.sync _|p, 0xffffffff; selp.u32 %0, 1, 0, p;}" : "=r"(r));
    return r != 0;
}

__device__ __forceinline__ void tma2d(uint32_t dst, const CUtensorMap* m, int c0, int c1, uint32_t bar) {
    asm volatile("cp.async.bulk.tensor.2d.shared::cluster.global.mbarrier::complete_tx::bytes [%0], [%1, {%3,%4}], [%2];" ::"r"(dst), "l"(m), "r"(bar), "r"(c0), "r"(c1) : "memory");
}
__device__ __forceinline__ void tma4d(uint32_t dst, const CUtensorMap* m, int c0, int c1, int c2, int c3, uint32_t bar) {
    asm volatile("cp.async.bulk.tensor.4d.shared::cluster.global.mbarrier::complete_tx::bytes [%0], [%1, {%3,%4,%5,%6}], [%2];" ::"r"(dst), "l"(m), "r"(bar), "r"(c0), "r"(c1), "r"(c2), "r"(c3) : "memory");
}
__device__ __forceinline__ void tma4d_mc(uint32_t dst, const CUtensorMap* m, int c0, int c3, uint32_t bar) {
    asm volatile("cp.async.bulk.tensor.4d.shared::cluster.global.mbarrier::complete_tx::bytes.multicast::cluster [%0], [%1, {%3,%6,%6,%4}], [%2], %5;" ::"r"(dst), "l"(m), "r"(bar), "r"(c0), "r"(c3), "h"((uint16_t)3), "r"(0) : "memory");
}
__device__ __forceinline__ void tma2d_st(const CUtensorMap* m, int c0, int c1, uint32_t src) {
    asm volatile("cp.async.bulk.tensor.2d.global.shared::cta.bulk_group [%0, {%2,%3}], [%1];" ::"l"(m), "r"(src), "r"(c0), "r"(c1) : "memory");
}
__device__ __forceinline__ void tma5d(uint32_t dst, const CUtensorMap* m, int c0, int c1, int c2, int c3, int c4, uint32_t bar) {
    asm volatile("cp.async.bulk.tensor.5d.shared::cluster.global.mbarrier::complete_tx::bytes [%0], [%1, {%3,%4,%5,%6,%7}], [%2];" ::"r"(dst), "l"(m), "r"(bar), "r"(c0), "r"(c1), "r"(c2), "r"(c3), "r"(c4) : "memory");
}
__device__ __forceinline__ void bulk_ld(uint32_t dst, const void* src, uint32_t n, uint32_t bar) {
    asm volatile("cp.async.bulk.shared::cluster.global.mbarrier::complete_tx::bytes [%0], [%1], %2, [%3];" ::"r"(dst), "l"(src), "r"(n), "r"(bar) : "memory");
}
__device__ __forceinline__ void pf_map(const CUtensorMap* m) { asm volatile("prefetch.tensormap [%0];" ::"l"(m) : "memory"); }
__device__ __forceinline__ void bulk_commit() { asm volatile("cp.async.bulk.commit_group;" ::: "memory"); }
template <int N> __device__ __forceinline__ void bulk_wait_read() { asm volatile("cp.async.bulk.wait_group.read %0;" ::"n"(N) : "memory"); }
__device__ __forceinline__ void stsm4(uint32_t a, uint32_t r0, uint32_t r1, uint32_t r2, uint32_t r3) {
    asm volatile("stmatrix.sync.aligned.m8n8.x4.shared.b16 [%0], {%1,%2,%3,%4};" ::"r"(a), "r"(r0), "r"(r1), "r"(r2), "r"(r3) : "memory");
}
__device__ __forceinline__ void sts128f(uint32_t a, cf u, cf v) {
    asm volatile("st.shared.v4.f32 [%0], {%1,%2,%3,%4};" ::"r"(a), "f"(u.x), "f"(u.y), "f"(v.x), "f"(v.y) : "memory");
}
__device__ __forceinline__ void stg128(const void* a, uint32_t r0, uint32_t r1, uint32_t r2, uint32_t r3) {
    asm volatile("st.global.v4.b32 [%0], {%1,%2,%3,%4};" ::"l"(a), "r"(r0), "r"(r1), "r"(r2), "r"(r3) : "memory");
}
__device__ __forceinline__ void lds128f(uint32_t a, float& x, float& y, float& z, float& u) { asm volatile("ld.shared.v4.f32 {%0,%1,%2,%3}, [%4];" : "=f"(x), "=f"(y), "=f"(z), "=f"(u) : "r"(a) : "memory"); }
__device__ __forceinline__ cf lds_cf(uint32_t a) { cf v; asm volatile("ld.shared.v2.f32 {%0,%1}, [%2];" : "=f"(v.x), "=f"(v.y) : "r"(a) : "memory"); return v; }
__device__ __forceinline__ uint4 ldtab(int word) { return __ldg((const uint4*)(g_tab + word)); }
__device__ __forceinline__ void load_tw(cf (&tw)[8], int k1) {
#pragma unroll
    for (int i = 0; i < 4; i++) {
        const uint4 v = ldtab(TAB_TW + k1 * 16 + i * 4);
        tw[2 * i] = {__uint_as_float(v.x), __uint_as_float(v.y)};
        tw[2 * i + 1] = {__uint_as_float(v.z), __uint_as_float(v.w)};
    }
}
__device__ __forceinline__ void load_T(cf (&T)[8], int t7) {
#pragma unroll
    for (int i = 0; i < 4; i++)
        asm volatile("ld.global.nc.v4.f32 {%0,%1,%2,%3}, [%4];" : "=f"(T[2 * i].x), "=f"(T[2 * i].y), "=f"(T[2 * i + 1].x), "=f"(T[2 * i + 1].y) : "l"(g_tab + TAB_T + i * 512 + t7 * 4));
}
__device__ __forceinline__ uint32_t lds_u16(uint32_t a) { uint32_t v; asm volatile("ld.shared.u16 %0, [%1];" : "=r"(v) : "r"(a)); return v; }
__device__ __forceinline__ float up(uint32_t v) { return __uint_as_float(v << 16); }
__device__ __forceinline__ unsigned get_epoch(uint32_t bars) {
    mbar_wait(bars + B_EP, 0);
    unsigned e;
    asm volatile("ld.shared.u32 %0, [%1];" : "=r"(e) : "r"(bars + B_EPOCH) : "memory");
    return e;
}
__device__ __forceinline__ void sts64f(uint32_t a, float x, float y) { asm volatile("st.shared.v2.f32 [%0], {%1,%2};" ::"r"(a), "f"(x), "f"(y) : "memory"); }
__device__ __forceinline__ uint32_t pk(float lo, float hi) { uint32_t r; asm("cvt.rn.bf16x2.f32 %0, %1, %2;" : "=r"(r) : "f"(hi), "f"(lo)); return r; }
__device__ __forceinline__ uint32_t bitsel(uint32_t a, uint32_t m, uint32_t b) {
    uint32_t r;
    asm("lop3.b32 %0, %1, %2, %3, 0xea;" : "=r"(r) : "r"(a), "r"(m), "r"(b));
    return r;
}

__host__ __device__ constexpr uint64_t mkdesc(uint32_t off, uint32_t lbo, uint32_t sbo, uint32_t swz) {
    return (uint64_t)((SB0 + off) >> 4) | ((uint64_t)(lbo >> 4) << 16) | ((uint64_t)(sbo >> 4) << 32) | ((uint64_t)swz << 62);
}
__device__ __forceinline__ void wg_fence() { asm volatile("wgmma.fence.sync.aligned;" ::: "memory"); }
__device__ __forceinline__ void wg_commit() { asm volatile("wgmma.commit_group.sync.aligned;" ::: "memory"); }
template <int N> __device__ __forceinline__ void wg_wait() { asm volatile("wgmma.wait_group.sync.aligned %0;" ::"n"(N) : "memory"); }
template <int N> __device__ __forceinline__ void pin(float (&d)[N]) {
#pragma unroll
    for (int i = 0; i < N; i++) asm volatile("" : "+f"(d[i])::"memory");
}
template <int N> __device__ __forceinline__ void pinu(uint32_t (&d)[N]) {
#pragma unroll
    for (int i = 0; i < N; i++) asm volatile("" : "+r"(d[i])::"memory");
}

#define R8(d, o) "+f"(d[o]), "+f"(d[o + 1]), "+f"(d[o + 2]), "+f"(d[o + 3]), "+f"(d[o + 4]), "+f"(d[o + 5]), "+f"(d[o + 6]), "+f"(d[o + 7])
#define L8 "%0,%1,%2,%3,%4,%5,%6,%7"
#define L24 L8 ",%8,%9,%10,%11,%12,%13,%14,%15,%16,%17,%18,%19,%20,%21,%22,%23"
#define L32 L24 ",%24,%25,%26,%27,%28,%29,%30,%31"
#define L64 L32 ",%32,%33,%34,%35,%36,%37,%38,%39,%40,%41,%42,%43,%44,%45,%46,%47,%48,%49,%50,%51,%52,%53,%54,%55,%56,%57,%58,%59,%60,%61,%62,%63"

template <int O, int TA, int TB, int SC, int N> __device__ __forceinline__ void mma128_ss(float (&d)[N], uint64_t da, uint64_t db) {
    asm volatile("wgmma.mma_async.sync.aligned.m64n128k16.f32.bf16.bf16 {" L64 "}, %64, %65, %66, 1, 1, %67, %68;"
                 : R8(d, O), R8(d, O + 8), R8(d, O + 16), R8(d, O + 24), R8(d, O + 32), R8(d, O + 40), R8(d, O + 48), R8(d, O + 56)
                 : "l"(da), "l"(db), "n"(SC), "n"(TA), "n"(TB));
}
#define W8(d, o) "=f"(d[o]), "=f"(d[o + 1]), "=f"(d[o + 2]), "=f"(d[o + 3]), "=f"(d[o + 4]), "=f"(d[o + 5]), "=f"(d[o + 6]), "=f"(d[o + 7])
__device__ __forceinline__ void mma128_first(float (&d)[64], uint64_t da, uint64_t db) {
    asm volatile("wgmma.mma_async.sync.aligned.m64n128k16.f32.bf16.bf16 {" L64 "}, %64, %65, 0, 1, 1, 0, 1;"
                 : W8(d, 0), W8(d, 8), W8(d, 16), W8(d, 24), W8(d, 32), W8(d, 40), W8(d, 48), W8(d, 56) : "l"(da), "l"(db));
}
template <int TB, int SC> __device__ __forceinline__ void mma128_rs(float (&d)[64], const uint32_t* a, uint64_t db) {
    asm volatile("wgmma.mma_async.sync.aligned.m64n128k16.f32.bf16.bf16 {" L64 "}, {%64,%65,%66,%67}, %68, %69, 1, 1, %70;"
                 : R8(d, 0), R8(d, 8), R8(d, 16), R8(d, 24), R8(d, 32), R8(d, 40), R8(d, 48), R8(d, 56)
                 : "r"(a[0]), "r"(a[1]), "r"(a[2]), "r"(a[3]), "l"(db), "n"(SC), "n"(TB));
}
template <int TB, int SC> __device__ __forceinline__ void mma64_rs(float (&d)[32], const uint32_t* a, uint64_t db) {
    asm volatile("wgmma.mma_async.sync.aligned.m64n64k16.f32.bf16.bf16 {" L32 "}, {%32,%33,%34,%35}, %36, %37, 1, 1, %38;"
                 : R8(d, 0), R8(d, 8), R8(d, 16), R8(d, 24)
                 : "r"(a[0]), "r"(a[1]), "r"(a[2]), "r"(a[3]), "l"(db), "n"(SC), "n"(TB));
}
template <int TA, int SC> __device__ __forceinline__ void mma64_ss(float (&d)[32], uint64_t da, uint64_t db) {
    asm volatile("wgmma.mma_async.sync.aligned.m64n64k16.f32.bf16.bf16 {" L32 "}, %32, %33, %34, 1, 1, %35, 1;"
                 : R8(d, 0), R8(d, 8), R8(d, 16), R8(d, 24)
                 : "l"(da), "l"(db), "n"(SC), "n"(TA));
}
template <int SC> __device__ __forceinline__ void mma48_ss(float (&d)[32], uint64_t da, uint64_t db) {
    asm volatile("wgmma.mma_async.sync.aligned.m64n48k16.f32.bf16.bf16 {" L24 "}, %24, %25, %26, 1, 1, 0, 1;"
                 : R8(d, 8), R8(d, 16), R8(d, 24)
                 : "l"(da), "l"(db), "n"(SC));
}
template <int SC> __device__ __forceinline__ void mma16_rs(float (&d)[32], uint32_t a0, uint32_t a1, uint32_t a2, uint32_t a3, uint64_t db) {
    asm volatile("wgmma.mma_async.sync.aligned.m64n16k16.f32.bf16.bf16 {" L8 "}, {%8,%9,%10,%11}, %12, %13, 1, 1, 1;"
                 : R8(d, 0)
                 : "r"(a0), "r"(a1), "r"(a2), "r"(a3), "l"(db), "n"(SC));
}

__device__ __forceinline__ cf cmul(cf a, cf b) { return {fmaf(a.x, b.x, -a.y * b.y), fmaf(a.x, b.y, a.y * b.x)}; }
__device__ __forceinline__ cf csq(cf a) { return {fmaf(a.x, a.x, -a.y * a.y), (a.x + a.x) * a.y}; }
__device__ __forceinline__ cf cmulc(cf a, cf b) { return {fmaf(a.x, b.x, a.y * b.y), fmaf(a.y, b.x, -a.x * b.y)}; }
__device__ __forceinline__ cf cfma(cf a, cf b, cf c) { return {fmaf(a.x, b.x, fmaf(-a.y, b.y, c.x)), fmaf(a.x, b.y, fmaf(a.y, b.x, c.y))}; }
__device__ __forceinline__ cf csel(int c, cf a, cf b) {
    cf r;
    asm("{.reg .pred p; setp.ne.s32 p, %6, 0; selp.f32 %0, %2, %4, p; selp.f32 %1, %3, %5, p;}" : "=f"(r.x), "=f"(r.y) : "f"(a.x), "f"(a.y), "f"(b.x), "f"(b.y), "r"(c));
    return r;
}
__device__ __forceinline__ cf cadd(cf a, cf b) { return {a.x + b.x, a.y + b.y}; }
__device__ __forceinline__ cf csub(cf a, cf b) { return {a.x - b.x, a.y - b.y}; }
__device__ __forceinline__ cf twice_minus(cf a, cf s) { return {fmaf(2.f, a.x, -s.x), fmaf(2.f, a.y, -s.y)}; }
struct v2 { float a, b; };
struct c2 { v2 x, y; };
#define OP2(name, args, txt, ...) \
    __device__ __forceinline__ v2 name args { v2 r; asm volatile(txt : "=f"(r.a) : __VA_ARGS__(a)); asm volatile(txt : "=f"(r.b) : __VA_ARGS__(b)); return r; }
#define A_XY(e) "f"(x.e), "f"(y.e)
#define A_XYZ(e) "f"(x.e), "f"(y.e), "f"(z.e)
OP2(add2, (v2 x, v2 y), "add.rn.f32 %0, %1, %2;", A_XY)
OP2(sub2, (v2 x, v2 y), "sub.rn.f32 %0, %1, %2;", A_XY)
OP2(mul2, (v2 x, v2 y), "mul.rn.f32 %0, %1, %2;", A_XY)
OP2(tw2, (v2 x, v2 y), "{.reg .f32 n; neg.f32 n, %2; fma.rn.f32 %0, %1, 0f40000000, n;}", A_XY)
OP2(fma2, (v2 x, v2 y, v2 z), "fma.rn.f32 %0, %1, %2, %3;", A_XYZ)
OP2(fms2, (v2 x, v2 y, v2 z), "{.reg .f32 n; neg.f32 n, %3; fma.rn.f32 %0, %1, %2, n;}", A_XYZ)
OP2(fnm2, (v2 x, v2 y, v2 z), "{.reg .f32 n; neg.f32 n, %1; fma.rn.f32 %0, n, %2, %3;}", A_XYZ)
__device__ __forceinline__ c2 both(cf a) { return {{a.x, a.x}, {a.y, a.y}}; }
__device__ __forceinline__ c2 tw2(c2 a, c2 s) { c2 r; r.x = tw2(a.x, s.x); r.y = tw2(a.y, s.y); return r; }
template <bool CJ> __device__ __forceinline__ c2 cmul2(c2 a, c2 t) {
    const v2 p = mul2(a.y, t.y), q = mul2(a.x, t.y);
    c2 r;
    r.x = CJ ? fma2(a.x, t.x, p) : fms2(a.x, t.x, p);
    r.y = CJ ? fms2(a.y, t.x, q) : fma2(a.y, t.x, q);
    return r;
}
template <bool CJ> __device__ __forceinline__ c2 cfma2(c2 a, c2 t, c2 c) {
    const v2 p = CJ ? fma2(a.y, t.y, c.x) : fnm2(a.y, t.y, c.x), q = CJ ? fnm2(a.x, t.y, c.y) : fma2(a.x, t.y, c.y);
    c2 r;
    r.x = fma2(a.x, t.x, p);
    r.y = fma2(a.y, t.x, q);
    return r;
}
__device__ __forceinline__ void bfly2(c2 a, c2 b, c2& s, c2& d) { s.x = add2(a.x, b.x); d.x = sub2(a.x, b.x); s.y = add2(a.y, b.y); d.y = sub2(a.y, b.y); }
__device__ __forceinline__ void bflyi2(c2 a, c2 b, c2& s, c2& d) { s.x = add2(a.x, b.y); d.x = sub2(a.x, b.y); s.y = sub2(a.y, b.x); d.y = add2(a.y, b.x); }
__device__ __forceinline__ uint32_t pkv(float lo, float hi) { uint32_t r; asm volatile("cvt.rn.bf16x2.f32 %0, %1, %2;" : "=r"(r) : "f"(hi), "f"(lo)); return r; }
__device__ __forceinline__ uint32_t pkv(v2 v) { return pkv(v.a, v.b); }
__device__ __forceinline__ float upv(uint32_t v) { float r; asm volatile("shl.b32 %0, %1, 16;" : "=f"(r) : "r"(v)); return r; }
__device__ __forceinline__ cf twid(int m, int M) {
    int r = ((m + M / 2) & (M - 1)) - M / 2;
    float s, c;
    __sincosf((float)r * (-6.283185307179586f / (float)M), &s, &c);
    return {c, s};
}
template <int YL, class F> __device__ __forceinline__ void dft8_end(const c2 (&e)[4], c2 a4, c2 a5, c2 a6, c2 a7, F out) {
    const v2 s = {0.70710678118654752f, 0.70710678118654752f};
    c2 o0, o1, o2, o3, u, v;
    bfly2(a4, a6, o0, o2);
    YLD(YL, 4);
    bfly2(e[0], o0, u, v);
    out(0, u, v);
    YLD(YL, 2);
    bflyi2(e[2], o2, u, v);
    out(2, u, v);
    YLD(YL, 4);
    bflyi2(a5, a7, o1, o3);
    YLD(YL, 1);
    o0.x = add2(o1.y, o1.x); o0.y = sub2(o1.y, o1.x);
    u.x = fma2(o0.x, s, e[1].x); v.x = fnm2(o0.x, s, e[1].x); u.y = fma2(o0.y, s, e[1].y); v.y = fnm2(o0.y, s, e[1].y);
    out(1, u, v);
    YLD(YL, 2);
    o2.x = sub2(o3.y, o3.x); o2.y = add2(o3.y, o3.x);
    u.x = fma2(o2.x, s, e[3].x); v.x = fnm2(o2.x, s, e[3].x); u.y = fnm2(o2.y, s, e[3].y); v.y = fma2(o2.y, s, e[3].y);
    out(3, u, v);
    YLD(YL, 1);
}

__device__ __forceinline__ void bid2tile(int b, int& tc, int& cb) {
    const int c = b >> 1, e = c - 36, t7 = (e * 37) >> 8;
    int g;
    asm("{.reg .pred p, q; setp.lt.s32 p, %2, 4; setp.lt.s32 q, %2, 36; selp.s32 %0, %3, %4, q; selp.s32 %1, %5, %6, q; selp.s32 %0, 0, %0, p; selp.s32 %1, %7, %1, p;}"
        : "=&r"(g), "=&r"(cb) : "r"(c), "r"((c + 4) & 7), "r"(1 + e - 7 * t7), "r"((c - 4) >> 3), "r"(4 + t7), "r"(4 + c));
    tc = 2 * g + (b & 1);
}
__host__ __device__ __forceinline__ int pos_of(int n) { return (n & 24) + 4 * (n & 1) + ((n >> 1) & 3); }
static int kappa_of(int b, int gi) {
    const int r = b >> 4, k1 = 2 * ((b & 15) ^ (4 * gi)) + gi;
    return b >= 128 ? gi * 256 : (k1 || r < 4 ? k1 + 64 * r : 64 * r - 224);
}
static int slot3_of(int kap, int& cj) {
    int m = kap & 15;
    cj = (m > 8) || ((m & 7) == 0 && kap > 256);
    const int kk = cj ? 512 - kap : kap;
    m = kk & 15;
    return kk == 256 ? 0 : (m & 1) * 128 + (m & 6) * 16 + pos_of((kk >> 4) + 2 * (m & 8));
}

__device__ __forceinline__ uint32_t tag_bad(uint32_t a, uint32_t tag) {
    uint32_t v;
    asm volatile("ld.shared.u32 %0, [%1];" : "=r"(v) : "r"(a) : "memory");
    return (v ^ tag) & 1;
}
__device__ __forceinline__ bool wg_all_ok(uint32_t bad, int id) {
    uint32_t ok;
    asm volatile("{.reg .pred p, q; setp.eq.u32 q, %1, 0; barrier.red.and.aligned.pred p, %2, 128, q; selp.u32 %0, 1, 0, p;}" : "=r"(ok) : "r"(bad), "r"(id) : "memory");
    return __all_sync(~0u, ok);
}

__device__ __forceinline__ uint32_t lines_bad(uint32_t va, uint32_t tag, uint32_t bit) {
    uint32_t bad;
    asm volatile("{.reg .b32 a, b, c, d;\n"
                 "ld.shared.u32 a, [%1]; ld.shared.u32 b, [%1+4096]; ld.shared.u32 c, [%1+8192]; ld.shared.u32 d, [%1+12288];\n"
                 "lop3.b32 a, a, b, %2, 0x7e; lop3.b32 c, c, d, %2, 0x7e; lop3.b32 %0, a, c, %3, 0xa8;}"
                 : "=r"(bad) : "r"(va), "r"(tag), "r"(bit) : "memory");
    return bad;
}
__device__ __forceinline__ void load_w(uint32_t sb, const CUtensorMap* m, int kap, uint32_t more) {
    mbar_expect_tx(sb + OFF_BAR + B_WIN, 16 * WPITCH + more);
#pragma unroll 1
    for (int i = 0; i < 4; i++) {
        if (i) __nanosleep(PACE_W);
        tma2d(sb + OFF_W + i * (4 * WPITCH), m + (i & 1), ((i & 2 ? (512 - kap) & 511 : kap) * 1026 >> 4) * 2, 0, sb + OFF_BAR + B_WIN);
    }
}
__device__ __forceinline__ void carry_poll(unsigned __int128 (&f)[4], const uint4* a, int n, uint32_t tag) {
    f[0] = f[1] = f[2] = f[3] = tag;
    asm volatile("{.reg .pred p<4>;\n"
                 "setp.ge.s32 p0, %5, 0; setp.ge.s32 p1, %5, 4; setp.ge.s32 p2, %5, 8; setp.ge.s32 p3, %5, 12;\n"
                 "@p0 ld.relaxed.gpu.global.b128 %0, [%4];\n"
                 "@p1 ld.relaxed.gpu.global.b128 %1, [%4+-32768];\n"
                 "@p2 ld.relaxed.gpu.global.b128 %2, [%4+-65536];\n"
                 "@p3 ld.relaxed.gpu.global.b128 %3, [%4+-98304];}"
                 : "+q"(f[0]), "+q"(f[1]), "+q"(f[2]), "+q"(f[3]) : "l"(a), "r"(n) : "memory");
}
__device__ __forceinline__ uint32_t carry_sum(const unsigned __int128 (&f)[4], const cf (&m4)[2], uint32_t tag, cf (&P)[2]) {
#pragma unroll
    for (int h = 0; h < 2; h++)
#pragma unroll
        for (int a = 3; a >= 0; a--) {
            const cf v = {__uint_as_float((uint32_t)(f[a] >> (64 * h))), __uint_as_float((uint32_t)(f[a] >> (64 * h + 32)))};
            P[h] = a == 3 ? v : cfma(m4[h], P[h], v);
        }
    return (((uint32_t)f[0] ^ tag) | ((uint32_t)f[1] ^ tag) | ((uint32_t)f[2] ^ tag) | ((uint32_t)f[3] ^ tag)) & 15u;
}

struct Ring {
    uint32_t full, rel;
    uint32_t ph, bh;
    uint64_t da;
    bool sig;
    uint32_t k;
};
__device__ __forceinline__ void ring_release(const Ring& r, int slot) {
    if (r.sig) asm volatile("mbarrier.arrive.shared::cluster.b64 _, [%0];" ::"r"(r.rel + 8 * slot) : "memory");
}
__device__ __forceinline__ void ring_wait(Ring& r, int slot) {
    if (slot == 0) r.ph ^= 1;
    mbar_wait(r.full + 8 * slot, r.ph);
}
template <int SLOT, int TA, int HF, int J> __device__ __forceinline__ void mma_g(float (&d)[128], const Ring& r, int sc) {
    constexpr int O = 64 * HF;
    asm volatile("{.reg .b64 da, db; .reg .b32 l; .reg .pred p; setp.ne.s32 p, %67, 0; add.u64 da, %64, %69; mov.b32 l, %65; mov.b64 db, {l,%66};\n"
                 "wgmma.mma_async.sync.aligned.m64n128k16.f32.bf16.bf16 {" L64 "}, da, db, p, 1, 1, %68, 0;}"
                 : R8(d, O), R8(d, O + 8), R8(d, O + 16), R8(d, O + 24), R8(d, O + 32), R8(d, O + 40), R8(d, O + 48), R8(d, O + 56)
                 : "l"(r.da), "n"((uint32_t)mkdesc(SLOT * 32768 + 16384 + J * 32, 16, 0, 0)), "r"(r.bh), "r"(sc), "n"(TA),
                   "n"(1 + SLOT * 2048 + (TA ? HF * 64 + J * 256 : HF * 512 + J * 2)));
}
static_assert((GRP >> HAND & 1) && (GRP >> 7 & 1), "hand-over at the end of a group");
template <int SLOT, int TA, int I, int BAR> __device__ __forceinline__ void gemm_mmas(float (&d)[128], Ring& r, int sc, bool last) {
    mma_g<SLOT, TA, I & 1, I / 2>(d, r, I < 2 ? sc : 1);
    constexpr int G = TA ? GRP2 : GRP;
    if (G >> I & 1) {
        wg_commit();
        if (BAR && I == HAND) asm volatile("{.reg .pred p; setp.ne.s32 p, %1, 0; @p bar.arrive %0, 256;}" ::"n"(BAR), "r"((int)last) : "memory");
        wg_wait<1>();
        if ((G & (1 << I) - 1) == 0 && sc) ring_release(r, (SLOT + NST - 1) % NST);
    }
    if constexpr (I < 7) gemm_mmas<SLOT, TA, I + 1, BAR>(d, r, sc, last);
}
template <int SLOT, int TA, int BAR = 0> __device__ __forceinline__ void gemm_step(float (&d)[128], Ring& r, int sc, bool last = false) {
    ring_wait(r, SLOT);
    wg_fence();
    gemm_mmas<SLOT, TA, 0, BAR>(d, r, sc, last);
}
template <int K, int HF> __device__ __forceinline__ void gemm_half(float (&d)[128], Ring& r) {
    if (HF == 0) { ring_wait(r, K % NST); wg_fence(); }
    mma_g<K % NST, 1, HF, 0>(d, r, 1); mma_g<K % NST, 1, HF, 1>(d, r, 1); mma_g<K % NST, 1, HF, 2>(d, r, 1); mma_g<K % NST, 1, HF, 3>(d, r, 1);
    if constexpr (HF == 0 && K < 64 - SKEW) { mma_g<K % NST, 1, 1, 0>(d, r, 1); mma_g<K % NST, 1, 1, 1>(d, r, 1); mma_g<K % NST, 1, 1, 2>(d, r, 1); mma_g<K % NST, 1, 1, 3>(d, r, 1); }
    if constexpr (K < 63) gemm_half<K + 1, HF>(d, r);
}
struct Prod {
    uint32_t b0, b1, b2, b3, b4, dbase;
    unsigned* prof;
    __device__ __forceinline__ Prod(uint32_t sb, int slot, uint32_t off) {
        const uint32_t bars = sb + OFF_BAR;
        b0 = bars + slot % NST * 8; b1 = bars + (slot + 1) % NST * 8; b2 = bars + (slot + 2) % NST * 8; b3 = bars + (slot + 3) % NST * 8; b4 = bars + (slot + 4) % NST * 8;
        dbase = sb + off - bars * 4096;
    }
    __device__ __forceinline__ uint32_t dst() const { return b0 * 4096 + dbase; }
    __device__ __forceinline__ void next() { const uint32_t t = b0; b0 = b1; b1 = b2; b2 = b3; b3 = b4; b4 = t; }
};
__device__ __forceinline__ void load_shared(Prod& r, uint32_t ph, const CUtensorMap* m, int c0, int c3) {
    uint32_t dst = r.dst();
    asm volatile("pmevent 0;" : "+r"(dst), "+r"(c0), "+r"(c3), "+l"(m));
    mbar_wait(r.b0 + B_EMPTY, ph);
    tma4d_mc(dst, m, c0, c3, r.b0);
    YIELD();
    r.next();
}
__host__ __device__ constexpr uint64_t phases_from(int k) {
    uint64_t v = 0;
    for (int i = 0; i < 64; i++) v |= (uint64_t)((k + i) / NST & 1) << i;
    return v;
}
__device__ __forceinline__ uint32_t phases(int k, int n) { return ((uint32_t)(phases_from(0) >> k) & ((1u << n) - 1)) | 1u << n; }

__global__ void __cluster_dims__(2, 1, 1) __launch_bounds__(512, 1)
fused_kernel(const __grid_constant__ Maps tm, const __grid_constant__ Params p) {
    const CUtensorMap &tmX = tm.m[0], &tmBre = tm.m[1], &tmBim = tm.m[2], &tmXA = tm.m[5], &tmUst = tm.m[6], &tmVst = tm.m[7], &tmWr = tm.m[8], &tmVld = tm.m[10];
    extern __shared__ __align__(1024) uint8_t smraw[];
    const uint32_t sb = smem_u32(smraw);
    const uint32_t bars = sb + OFF_BAR;
    const int bid = blockIdx.x;
    const bool extra = bid >= 128;
    if (threadIdx.x == 480) RECL(0);
    int tc, cb;
    if (threadIdx.x < 32) {
        if (elect_one()) {
            pf_map(&tmX);
            pf_map(&tmBre);
            pf_map(&tmBim);
#pragma unroll
            for (int s = 0; s < NST; s++) mbar_init(bars + B_FULL + s * 8, 33);
            asm volatile("fence.mbarrier_init.release.cluster;" ::: "memory");
            bid2tile(bid, tc, cb);
            mbar_expect_tx(bars + B_FULL, 32768);
            tma5d(sb + 16384, &tmX, 0, 0, 0, 0, tc, bars + B_FULL);
            tma4d(sb, &tmBre, 0, 0, 0, cb * 4, bars + B_FULL);
            tma4d(sb + 8192, &tmBim, 0, 0, 0, cb * 4, bars + B_FULL);
            asm volatile("mbarrier.arrive.shared::cta.b64 _, [%0], 32;" ::"r"(bars + B_FULL) : "memory");
            STAMP(56);
        }
        __syncwarp();
    }
    const int wid = __shfl_sync(~0u, threadIdx.x >> 5, 0);
    if (wid == 1) {
        if (elect_one()) {
#pragma unroll
            for (int o = B_EMPTY; o < B_END; o += 8) mbar_init(bars + o, o < B_STGU ? 2 : (o == B_STGU ? 8 : (o < B_EP ? 4 : 1)));
            asm volatile("fence.mbarrier_init.release.cluster;" ::: "memory");
        }
        __syncwarp();
    }
    const int wg = ((wid >> 2) + 3) & 3, w = wid & 3;
    const int fb = bid >> 5, fcb = bid & 31, fpos = pos_of(fcb);
    const int vrow = ((bid & ~3) | (bid & 1) << 1 | (bid >> 1 & 1)) * 256;
    bid2tile(bid, tc, cb);
    asm volatile("barrier.cluster.arrive.relaxed.aligned;" ::: "memory");

    if (wg == 3) {
        asm volatile("setmaxnreg.dec.sync.aligned.u32 24;");
        if (w == 0) {
            if (extra) mbar_wait(bars + B_FULL, 0);
            else if (KMC > 1 && elect_one()) {
#pragma unroll 1
                for (int k = 1 + (bid >> 8); k < KMC; k++) {
                    mbar_expect_tx(bars + B_FULL + k * 8, 32768);
                    tma5d(sb + k * 32768 + 16384, &tmX, k * 64, 0, 0, 0, tc, bars + B_FULL + k * 8);
                    tma4d(sb + k * 32768, &tmBre, k * 64, 0, 0, cb * 4, bars + B_FULL + k * 8);
                    tma4d(sb + k * 32768 + 8192, &tmBim, k * 64, 0, 0, cb * 4, bars + B_FULL + k * 8);
                    asm volatile("mbarrier.arrive.shared::cta.b64 _, [%0], 32;" ::"r"(bars + B_FULL + k * 8) : "memory");
                }
                STAMP(28);
            }
            __syncwarp();
        }
        asm volatile("barrier.cluster.wait.aligned;" ::: "memory");
        if (bid == 129 || (sb & 0x3FFFF) != SB0) return;
        if (w < 2) {
            if (extra || !elect_one()) return;
            const int rank = bid & 1;
            if (w == 0) {
                Prod r(sb, KMC, 16384);
                int c0 = 64 * KMC;
#pragma unroll 1
                for (uint32_t pat = phases(NST + KMC, 32 - KMC); pat != 1; pat >>= 1) {
                    uint32_t dst = r.dst();
                    asm volatile("pmevent 0;" : "+r"(dst));
                    mbar_wait(r.b0 + B_EMPTY, pat);
                    if (c0 >= 0) tma5d(dst, &tmX, c0, 0, 0, 0, tc, r.b0);
                    mbar_expect_tx(r.b0, c0 >= 0 ? 32768 : 16384);
                    asm volatile("mbarrier.arrive.shared::cta.b64 _, [%0], 32;" ::"r"(r.b0) : "memory");
                    c0 = c0 == 960 ? -64 * NST : c0 + 64;
                    r.next();
                }
                r.dbase -= 16384;
                const uint8_t* src = g_H + (size_t)tc * (32 * 16384);
                uint32_t all = (uint32_t)phases_from(32 - NST);
#pragma unroll 1
                for (int hh = 0; hh < 4; hh++) {
                    uint32_t pat = (all & 255) | 256;
                    all >>= 8;
                    if (!(hh & 1)) wait_cnt(g_hcnt + tc * 64 + hh * 16, 32 * get_epoch(bars) - EARLY_H);
                    else mbar_wait(bars + B_HGO + 8 * hh, 0);
                    STAMPR(45 + hh);
#pragma unroll 1
                    do {
                        uint32_t dst = r.dst(), hb = r.b0 + B_HLD;
                        asm volatile("pmevent 0;" : "+r"(dst), "+r"(hb));
                        mbar_wait(r.b0 + B_EMPTY, pat);
                        bulk_ld(dst, src, 16384, hb);
                        YIELD();
                        mbar_expect_tx(r.b0 + B_HLD, 16384);
                        mbar_expect_tx(r.b0, 16384);
                        src += 16384;
                        r.next();
                        pat >>= 1;
                    } while (pat != 1);
                }
            } else {
                Prod r(sb, KMC, rank * 8192);
                int c = 64 * KMC;
#pragma unroll 1
                for (uint32_t pat = phases(NST + KMC, 32 - KMC); pat != 1; pat >>= 1) {
                    load_shared(r, pat, &tmBre + rank, c & 1023, cb * 4 + ((c >> 5) & 64));
                    c += c == 960 ? 2112 - 64 * NST : 64;
                }
                r.dbase += 16384;
                uint32_t pat = (uint32_t)phases_from(32 - NST);
#pragma unroll 1
                for (c = 0; c != 1024; c += 64) {
                    load_shared(r, pat, &tmBre + 2, c, cb * 8 + rank * 4);
                    load_shared(r, pat >> 1, &tmBre + 3, c, cb * 8 + rank * 4);
                    pat >>= 2;
                }
                mbar_arrive(bars + B_LDONE);
            }
        } else if (w == 2) {
            if (!elect_one()) return;
            STAMP5(39);
            if (!extra) {
                mbar_expect_tx(bars + B_XIN, 16384);
                mbar_expect_tx(bars + B_XIN + 8, 16384);
#pragma unroll 1
                for (int i = 0; i < 8; i++) {
                    const int k = i - XA_FIRST + XA_AT;
                    if (i >= XA_FIRST) mbar_wait(bars + B_EMPTY + (k < NST ? k : k - NST) * 8, k >= NST);
                    tma4d(sb + OFF_P + i * 2048, &tmXA, fcb * 32, 0, ((2 * i) & 7) + (i >> 2), fb, bars + B_XIN + (i & 4) * 2);
                    tma4d(sb + OFF_P + 16384 + i * 2048, &tmXA, fcb * 32 + 16, 0, ((2 * i) & 7) + (i >> 2), fb, bars + B_XIN + (i & 4) * 2);
                    if (!i) STAMP5(30);
                    STAMP5(31);
                }
            }
            pf_map(&tmWr);
            pf_map(&tmWr + 1);
            const unsigned ep = get_epoch(bars);
            if (!extra) mbar_wait(bars + B_XIN + 8, 0);
            STAMP5(32);
            load_w(sb, &tmWr, p.unit[2 * bid] & 0xffff, 8192);
            pf_map(&tmUst);
            if (!extra) mbar_wait(bars + B_STGU, 0);
            STAMP(21);
#pragma unroll 1
            for (int gi = 0; gi < 2; gi++) {
                if (!extra) {
#pragma unroll 1
                    for (int r = 128 * gi; r < 128 * gi + 128; r += UBOX) {
                        if (gi) __nanosleep(PACE_U);
                        tma2d_st(&tmUst, fb * 2048 + fpos * 64, r, sb + OFF_P + r * 128);
                        bulk_commit();
                    }
                    bulk_wait_read<HINT_U>();
                    red_hint(g_cnt + gi * 32);
                }
                if (!gi) bulk_ld(sb + OFF_F, g_tab + TAB_FG, 8192, bars + B_WIN);
                bulk_wait_read<0>();
                STAMPR(40 + gi);
                wait_cnt(g_cnt + 32 * gi, 128 * ep - (gi ? 0 : EARLY_U));
                {
                    if (gi) __nanosleep(UDELAY);
                    else STAMP(42);
                    mbar_expect_tx(bars + B_UIN + 8 * gi, 16384);
                    bulk_ld(sb + OFF_P + gi * 16384, g_U + (size_t)(extra ? 0 : bid + 128 * gi) * 16384, 16384, bars + B_UIN + 8 * gi);
                }
            }
            pf_map(&tmBre + 2); pf_map(&tmBre + 3); pf_map(&tmVst); pf_map(&tmVld);
            mbar_wait(bars + B_WFREE, 0);
            load_w(sb, &tmWr, p.unit[2 * bid + 1] & 0xffff, 0);
#pragma unroll 1
            for (int gi = 0; gi < 2; gi++) {
                const int vc = ((p.unit[2 * bid + gi] >> 16) & 255) * 64, go = vc >> 13;
                const uint32_t src = extra ? sb + 32768 : sb + OFF_P + gi * 16384;
                mbar_wait(bars + B_STG, gi);
                STAMPR(23 + gi);
                if (extra && !gi) continue;
                if (bid + gi != 0) {
#pragma unroll 1
                    for (int r = 0; r < 128; r += 32) {
                        if (r && !gi) __nanosleep(PACE_V);
                        tma2d_st(&tmVst, vc, r, src + r * 128);
                        bulk_commit();
                    }
                }
                bulk_wait_read<HINT_V>();
                red_hint(g_cnt + 64 + 32 * go);
                bulk_wait_read<0>();
                STAMP(49);
                if (extra) break;
                wait_cnt(g_cnt + 64 + 32 * gi, (129 - gi) * ep - gi * EARLY_V);
                {
                    STAMPR(43 + gi);
#pragma unroll
                    for (int h = 0; h < 2; h++) {
                        mbar_expect_tx(bars + B_VIN + gi * 16 + h * 8, 8192);
                        tma2d(src + h * 8192, &tmVld, h * 32, vrow + gi * 128, bars + B_VIN + gi * 16 + h * 8);
                    }
                }
                if (XT && !gi) {
                    mbar_wait(bars + B_WFREE, 1);
                    mbar_expect_tx(bars + B_WIN, 16384);
#pragma unroll 1
                    for (int i = 0; i < 4; i++) {
                        tma2d(sb + OFF_W + i * 4096, tm.m + 11, cb * 128, tc * 128 + 32 * i + 16, bars + B_WIN);
                    }
                }
            }
        } else {
            const uint32_t tag = ld_rlx(g_epoch + bid * 8) + 1;
            __syncwarp();
            if (elect_one()) {
                asm volatile("st.shared.u32 [%0], %1;" ::"r"(bars + B_EPOCH), "r"(tag) : "memory");
                mbar_arrive(bars + B_EP);
                asm volatile("st.relaxed.gpu.global.u32 [%0], %1;" ::"l"(g_epoch + bid * 8), "r"(tag) : "memory");
            }
            __syncwarp();
            if (extra) return;
            const int lane = (threadIdx.x + p.zero[0]) & 31;
            Prod r(sb, 32, 0);
            uint32_t va = (lane & 3) * 516 + (lane >> 4) * 2048 + (lane & 12) * 32 + (lane >> 2) * 16 + r.dbase;
            asm volatile("" : "+r"(va));
            uint32_t n = 0;
#pragma unroll 1
            for (int half = 0; half < 2; half++) {
#pragma unroll 1
                for (uint32_t pat = phases(16 * half, 16); pat != 1; pat >>= 1) {
                    uint32_t la = r.b0 * 4096 + va;
                    asm volatile("pmevent 0;" : "+r"(la));
                    mbar_wait(r.b0 + B_HLD, pat);
                    uint32_t bad = lines_bad(la, tag, 1);
                    if (!bad) mbar_arrive(r.b0);
                    asm volatile("pmevent 0;" : "+r"(bad));
#pragma unroll 1
                    while (__any_sync(~0u, bad)) {
                        const int kk = __shfl_sync(~0u, pat, 0);
                        if (elect_one()) {
                            mbar_expect_tx(bars + B_HRTY, 16384);
                            bulk_ld(r.dst(), g_H + (uint32_t)(tc * 32 + half * 16 + __clz(kk) - 15) * 16384, 16384, bars + B_HRTY);
                        }
                        __syncwarp();
                        mbar_wait(bars + B_HRTY, n++);
                        if (bad && !lines_bad(la, tag, n < SPIN_LIMIT)) { bad = 0; mbar_arrive(r.b0); }
                        __syncwarp();
                    }
                    if (pat >> 16) STAMPR(6 + 23 * half);
                    r.next();
                }
            }
        }
    } else {
        asm volatile("setmaxnreg.inc.sync.aligned.u32 152;");
        asm volatile("barrier.cluster.wait.aligned;" ::: "memory");
        STAMP(55);
        if ((extra && (wg != 2 || bid == 129)) || (sb & 0x3FFFF) != SB0) return;
        const int hf = wg - 1;
#define INDICES(i) const int t7 = (threadIdx.x + p.zero[i]) & 127, lane = t7 & 31, g = lane >> 2, q = lane & 3, k1 = t7 >> 2, mi = lane >> 3, gl = lane & 7; \
                   const uint32_t tmask = q == 0 ? ~1u : ~0u;
        if (wg == 1) {
            INDICES(1)
            const int ch = (t7 >> 6) * 512 + (t7 & 8) * 32 + cb * 32 + ((t7 >> 1) & 24) + (t7 & 7);
            const float lr = __bfloat162float(p.lre[ch]), li = __bfloat162float(p.lim[ch]);
            const float dt = __bfloat162float(__float2bfloat16(expf(__bfloat162float(p.ldt[ch]))));
            float sn, cs;
            sincospif(dt * li * 0.31830988618379067f, &sn, &cs);
            const float ex = expf(dt * lr), br = ex * cs, bi = ex * sn;
            const float inv = __fdividef(2.0f, lr * lr + li * li);
            const cf lam = {br, -bi}, gam = {((br - 1.f) * lr + bi * li) * inv, -(bi * lr - (br - 1.f) * li) * inv};
            const cf l32 = csq(csq(csq(csq(csq(lam))))), l64 = csq(l32), m1 = csq(l64), m2 = csq(m1), g2 = cmul(gam, l64);
            sts128f(sb + OFF_T1 + t7 * 16, lam, l32);
            sts128f(sb + OFF_TL + t7 * 32, gam, cmul(gam, l32));
            sts128f(sb + OFF_TL + t7 * 32 + 16, g2, cmul(g2, l32));
            sts128f(sb + OFF_TM + t7 * 32, csq(m2), m1);
            sts128f(sb + OFF_TM + t7 * 32 + 16, m2, cmul(m2, m1));
            __syncwarp();
            if (lane == 0) mbar_arrive(bars + B_LAM);
        }
        if (wg != 0 && !extra) {
            INDICES(2)
            uint32_t f1[16];
#pragma unroll
            for (int j = 0; j < 4; j++) { const uint4 v = ldtab(TAB_F1 + j * 512 + t7 * 4); f1[4 * j] = v.x; f1[4 * j + 1] = v.y; f1[4 * j + 2] = v.z; f1[4 * j + 3] = v.w; }
            cf tw[8];
            load_tw(tw, k1);
            const uint32_t tbit = get_epoch(bars) & ~tmask;
            const uint64_t dx = mkdesc(OFF_P, 2048, 256, 3) + hf * 1024;
            const int gr = gl & 1, jr = (gl >> 1) + 4 * ((w ^ gl) & 1);
            const uint32_t a0 = w + gl ? sb + OFF_P + (gr * 128 + 8 * (w >> 1) + jr + 64 * (mi >> 1)) * 128 : sb + OFF_F + 2048;
            const uint32_t rs = w + gl ? 2048 : 0;
            const uint32_t scr = sb + OFF_F + hf * 1024;
            float acc[32];
            c2 ev[2][4];
            uint4 fx0, fx1;
            float s0, s1;
#pragma unroll 1
            for (int od = 0;; od++) {
                if (od) STAMP5(33 + hf);
                mbar_wait(bars + B_XIN + od * 8, 0);
                if (od) STAMP(20);
                pinu(f1);
                wg_fence();
                mma64_rs<1, 0>(acc, f1, dx + od * 512);
                mma64_rs<1, 1>(acc, f1 + 4, dx + od * 512 + 32);
                mma64_rs<1, 1>(acc, f1 + 8, dx + od * 512 + 64);
                mma64_rs<1, 1>(acc, f1 + 12, dx + od * 512 + 96);
                wg_commit();
                wg_wait<0>();
                pin(acc);
                pinu(f1);
                if (od) STAMP5(35);
                if (k1 == 0) {
#pragma unroll
                    for (int i = 0; i < 8; i++) sts128f(scr + (i >> 1) * 256 + od * 128 + (i & 1) * 64 + q * 16, {acc[4 * i], acc[4 * i + 1]}, {acc[4 * i + 2], acc[4 * i + 3]});
                }
                if (od) break;
                asm volatile("ld.global.nc.v4.b32 {%0,%1,%2,%3}, [%4];" : "=r"(fx0.x), "=r"(fx0.y), "=r"(fx0.z), "=r"(fx0.w) : "l"(g_tab + TAB_FX + (t7 & 120)));
                asm volatile("ld.global.nc.v4.b32 {%0,%1,%2,%3}, [%4];" : "=r"(fx1.x), "=r"(fx1.y), "=r"(fx1.z), "=r"(fx1.w) : "l"(g_tab + TAB_FX + (t7 & 120) + 4));
#pragma unroll
                for (int cl = 0; cl < 2; cl++) {
                    auto in = [&](int n) { const int i = 4 * (n + cl); return c2{{acc[i], acc[i + 1]}, {acc[i + 2], acc[i + 3]}}; };
                    const c2 a0 = cfma2<false>(in(4), both(tw[4]), in(0)), a1 = tw2(in(0), a0);
                    YIELD();
                    const c2 t2 = cmul2<false>(in(2), both(tw[2]));
                    YIELD();
                    const c2 a2 = cfma2<false>(in(6), both(tw[6]), t2), a3 = tw2(t2, a2);
                    YIELD();
                    bfly2(a0, a2, ev[cl][0], ev[cl][2]);
                    YIELD();
                    bflyi2(a1, a3, ev[cl][1], ev[cl][3]);
                    YIELD();
                }
                wg_all_ok(0, hf ? 3 : 8);
                const uint32_t sa = scr + gl * 16 + (w >> 1) * 8;
                const cf x0 = lds_cf(sa), x2 = lds_cf(sa + 256), x4 = lds_cf(sa + 512), x6 = lds_cf(sa + 768);
                const float c0 = __uint_as_float(fx0.x), c2 = __uint_as_float(fx0.z), c4 = __uint_as_float(fx1.x), c6 = __uint_as_float(fx1.z);
                s0 = fmaf(c6, x6.x, fmaf(c4, x4.x, fmaf(c2, x2.x, c0 * x0.x)));
                s1 = fmaf(c6, x6.y, fmaf(c4, x4.y, fmaf(c2, x2.y, c0 * x0.y)));
            }
#pragma unroll
            for (int cl = 0; cl < 2; cl++) {
                auto in = [&](int n) { const int i = 4 * (n - 1 + cl); return c2{{acc[i], acc[i + 1]}, {acc[i + 2], acc[i + 3]}}; };
                const c2 t1 = cmul2<false>(in(1), both(tw[1]));
                YLD(YF1, 2);
                const c2 a4 = cfma2<false>(in(5), both(tw[5]), t1), a5 = tw2(t1, a4);
                YLD(YF1, 3);
                cf sx[8];
                if (cl == 0) {
                    bar_sync(6, 256);
                    STAMP5(36);
#pragma unroll
                    for (int n = 1; n < 8; n += 2) sx[n] = lds_cf(scr + n * 128 + gl * 16 + (w >> 1) * 8);
                }
                const c2 t3 = cmul2<false>(in(3), both(tw[3]));
                YLD(YF1, 1);
                const c2 a6 = cfma2<false>(in(7), both(tw[7]), t3), a7 = tw2(t3, a6);
                YLD(YF1, 2);
                const uint32_t a1 = a0 + (((((mi & 1) << 2) | ((2 * hf + cl) ^ (fpos & 3))) ^ jr) << 4);
                dft8_end<YF1>(ev[cl], a4, a5, a6, a7, [&](int r, c2 u, c2 v) {
                    uint32_t o0 = pkv(u.x), o1 = pkv(u.y), o2 = pkv(v.x), o3 = pkv(v.y);
                    if (cl == 0) { o0 = bitsel(o0, tmask, tbit); o2 = bitsel(o2, tmask, tbit); }
                    stsm4(a1 + r * rs, o0, o1, o2, o3);
                });
                if (cl == 0) {
                    YLD(YF1, 2);
#pragma unroll
                    for (int n = 1; n < 8; n += 2) {
                        const float c = __uint_as_float(n < 4 ? (n == 0 ? fx0.x : n == 1 ? fx0.y : n == 2 ? fx0.z : fx0.w) : (n == 4 ? fx1.x : n == 5 ? fx1.y : n == 6 ? fx1.z : fx1.w));
                        s0 = fmaf(c, sx[n].x, s0); s1 = fmaf(c, sx[n].y, s1);
                    }
                    asm volatile("st.shared.b32 [%0], %1;" ::"r"(sb + OFF_P + (t7 >> 4) * 2048 + (((mi & 1) * 4 + ((2 * hf + (g & 1)) ^ (fpos & 3))) << 4) + q * 4), "r"(bitsel(pk(s0, s1), tmask, tbit)) : "memory");
                    YLD(YF1, 1);
                }
            }
            fence_async_sm();
            __syncwarp();
            if (lane == 0) mbar_arrive(bars + B_STGU);
        }
        if (wg != 2) {
        if (wg == 0) bar_sync(4, 128);
        asm volatile("setmaxnreg.inc.sync.aligned.u32 168;");
        float d[128];
        Ring rg;
        rg.full = bars + B_FULL;
        asm("mapa.shared::cluster.u32 %0, %1, %2;" : "=r"(rg.rel) : "r"(bars + B_EMPTY), "r"(w & 1));
        rg.sig = ((threadIdx.x + p.zero[7]) & 95) == 0;
        rg.bh = (uint32_t)(mkdesc(0, 0, 1024, 1) >> 32) + p.zero[0];
        rg.da = p.da[0];
        rg.ph = 1;
        rg.k = 130 * 66 + bid * 66 + 16 * wg;
        if (wg == 0) {
            STAMP(0);
            gemm_step<0, 0>(d, rg, 0);
        } else {
            bar_sync(1, 256);
            STAMP(10);
        }
        rg.da = p.da[1];
#pragma unroll 1
        for (int i = 0; i < 3; i++) {
            gemm_step<1, 0>(d, rg, i >= wg);
            gemm_step<2, 0>(d, rg, 1);
            gemm_step<3, 0>(d, rg, 1);
            gemm_step<4, 0>(d, rg, 1);
            gemm_step<0, 0, 1>(d, rg, 1, i - wg == 2);
        }
        if (wg != p.zero[1]) {
            rg.da = p.da[0];
            gemm_step<1, 0, 2>(d, rg, 1, true);
        }
        {
            INDICES(3)
            cf lam[2], l32[2], l2[2];
            const uint32_t ta = sb + (wg * 64 + 16 * w + g) * 16;
            mbar_wait(bars + B_LAM, 0);
            const unsigned ep = get_epoch(bars), tag = ep & 15u;
            lds128f(ta + OFF_T1, lam[0].x, lam[0].y, l32[0].x, l32[0].y);
            lds128f(ta + OFF_T1 + 128, lam[1].x, lam[1].y, l32[1].x, l32[1].y);
            const uint4* cpub = g_carry + (uint32_t)(wg * 256 + cb * 32 + 8 * w + tc * 512 + g);
            l2[0] = csq(lam[0]);
            l2[1] = csq(lam[1]);
            asm volatile("pmevent 0;" : "+l"(cpub), "+f"(l2[0].x), "+f"(l2[0].y), "+f"(l2[1].x), "+f"(l2[1].y));
            wg_wait<0>();
            ring_release(rg, wg);
            pin(d);
            STAMPW(1, 11);
            cf f[2];
#pragma unroll
            for (int h = 0; h < 2; h++) {
                c2 c = {{d[2 * h], d[2 * h + 1]}, {d[64 + 2 * h], d[65 + 2 * h]}};
#pragma unroll
                for (int i = 1; i < 16; i++) {
                    const int r = 4 * i + 2 * h;
#define P1A "fma.rn.f32 a0, %2, %9, %4; fma.rn.f32 a1, %3, %9, %5;\n"
#define P1B "fma.rn.f32 b0, %0, n, %6; fma.rn.f32 b1, %1, n, %7;\n"
#define P1X "fma.rn.f32 %0, %0, %8, a0; fma.rn.f32 %1, %1, %8, a1;\n"
#define P1Y "fma.rn.f32 %2, %2, %8, b0; fma.rn.f32 %3, %3, %8, b1;\n"
#define P1ARG : "+f"(c.x.a), "+f"(c.x.b), "+f"(c.y.a), "+f"(c.y.b) : "f"(d[r]), "f"(d[r + 1]), "f"(d[64 + r]), "f"(d[65 + r]), "f"(l2[h].x), "f"(l2[h].y)
                    if (i & 1) asm volatile("{.reg .f32 a0, a1, b0, b1, n; neg.f32 n, %9;\n" P1A P1B P1X P1Y "}" P1ARG);
                    else asm volatile("{.reg .f32 a0, a1, b0, b1, n; neg.f32 n, %9;\n" P1B P1A P1Y P1X "}" P1ARG);
                    if (i % YS == 0) YIELD();
                    if (i == 12) lds128f(ta + OFF_T1 + 128 * h, lam[h].x, lam[h].y, l32[h].x, l32[h].y);
                }
                f[h] = cfma(lam[h], {c.x.a, -c.y.a}, {c.x.b, -c.y.b});
            }
            cf st[2], gam[2];
            gam[0] = lds_cf(2 * ta - sb + OFF_TL);
            gam[1] = lds_cf(2 * ta - sb + OFF_TL + 256);
            cf v0[2], v1[2], v2[2];
#pragma unroll
            for (int h = 0; h < 2; h++) {
                v0[h] = {__shfl_sync(~0u, f[h].x, 0, 4), __shfl_sync(~0u, f[h].y, 0, 4)};
                v1[h] = {__shfl_sync(~0u, f[h].x, 1, 4), __shfl_sync(~0u, f[h].y, 1, 4)};
                v2[h] = {__shfl_sync(~0u, f[h].x, 2, 4), __shfl_sync(~0u, f[h].y, 2, 4)};
            }
#pragma unroll
            for (int h = 0; h < 2; h++) {
                v1[h] = cfma(l32[h], v0[h], v1[h]);
                v2[h] = cfma(l32[h], v1[h], v2[h]);
                f[h] = cfma(l32[h], v2[h], f[h]);
            }
            asm volatile("{.reg .pred p; .reg .b64 a, b; .reg .b128 v; setp.eq.u32 p, %5, 3; mov.b64 a, {%1,%2}; mov.b64 b, {%3,%4}; mov.b128 v, {a, b};\n"
                         "@p st.relaxed.gpu.global.b128 [%0], v;}" ::"l"(cpub),
                         "r"(bitsel(__float_as_uint(f[0].x), ~15u, tag)), "r"(__float_as_uint(f[0].y)), "r"(__float_as_uint(f[1].x)), "r"(__float_as_uint(f[1].y)), "r"(q) : "memory");
            STAMPX(2, 12);
            YIELD();
#pragma unroll
            for (int h = 0; h < 2; h++) st[h] = cmul(gam[h], csel(q & 2, csel(q & 1, v2[h], v1[h]), csel(q & 1, v0[h], cf{0.f, 0.f})));
            const uint4* cget = cpub + (gl - g) - (1 + mi) * 512;
            const int nget = tc - 1 - mi;
            unsigned __int128 fq[4];
            auto prescale = [&](int i) {
                const int h = i >> 4, r = 4 * (i & 15) + 2 * h;
                asm volatile("{.reg .f32 s0, s1, n; neg.f32 n, %4; mul.f32 s0, %5, %1; mul.f32 s1, %5, %3; mul.f32 %1, n, %1; mul.f32 %3, n, %3;\n"
                             "fma.rn.f32 %1, %5, %0, %1; fma.rn.f32 %3, %5, %2, %3; fma.rn.f32 %0, %4, %0, s0; fma.rn.f32 %2, %4, %2, s1;}"
                             : "+f"(d[r]), "+f"(d[64 + r]), "+f"(d[r + 1]), "+f"(d[65 + r]) : "f"(gam[h].x), "f"(gam[h].y));
            };
#pragma unroll
            for (int i = 0; i < 32; i++) {
                if (i == POLL_AT) carry_poll(fq, cget, nget, tag);
                if (i % YS2 == 0) YIELD();
                prescale(i);
            }
            YIELD();
            const uint32_t tm = sb + OFF_TM + (wg * 64 + 16 * w) * 32;
            cf m4[2], mj[2], P[2], lq[2];
#pragma unroll
            for (int h = 0; h < 2; h++) {
                m4[h] = lds_cf(tm + gl * 32 + h * 256);
                mj[h] = lds_cf(tm + gl * 32 + h * 256 + mi * 8);
            }
            uint32_t bad = carry_sum(fq, m4, tag, P);
            unsigned n = 0;
            while (__any_sync(~0u, bad) && ++n < SPIN_LIMIT) {
                unsigned __int128 fr[4];
                carry_poll(fr, cget, nget, tag);
                bad = carry_sum(fr, m4, tag, P);
                YIELD();
                mj[0] = lds_cf(tm + gl * 32 + mi * 8);
                mj[1] = lds_cf(tm + gl * 32 + 256 + mi * 8);
            }
            STAMPX(53, 54);
            P[0] = csel(mi, cmul(P[0], mj[0]), P[0]);
            P[1] = csel(mi, cmul(P[1], mj[1]), P[1]);
            __syncwarp();
            sts128f(tm + lane * 16, P[0], P[1]);
#pragma unroll
            for (int h = 0; h < 2; h++) {
                lq[h] = lds_cf(2 * ta - sb + OFF_TL + h * 256 + q * 8);
                lam[h] = lds_cf(ta + OFF_T1 + h * 128);
            }
            __syncwarp();
            float ps[4][4];
#pragma unroll
            for (int j = 0; j < 4; j++) lds128f(tm + g * 16 + j * 128, ps[j][0], ps[j][1], ps[j][2], ps[j][3]);
            const uint8_t* hp = g_H + (uint32_t)((tc * 32 + wg * 16 + (cb & 6)) * 16384 + ((cb & 1) * 4 + w) * 2048 + g * 64 + ((q ^ (g >> 1)) << 4));
#pragma unroll
            for (int h = 0; h < 2; h++)
                st[h] = cfma(lq[h], {(ps[0][2 * h] + ps[1][2 * h]) + (ps[2][2 * h] + ps[3][2 * h]), (ps[0][2 * h + 1] + ps[1][2 * h + 1]) + (ps[2][2 * h + 1] + ps[3][2 * h + 1])}, st[h]);
            STAMPX(3, 13);
            uint32_t hv[32];
#pragma unroll
            for (int h = 0; h < 2; h++) {
                YIELD();
                cf c = st[h];
#pragma unroll
                for (int i = 0; i < 16; i++) {
                    const int r = 4 * i + 2 * h;
                    const cf a = cfma(lam[h], c, {d[r], d[64 + r]});
                    c = cfma(lam[h], a, {d[r + 1], d[65 + r]});
                    hv[i] = pk(a.x, c.x);
                    hv[16 + i] = pk(a.y, c.y);
                    if ((i & 3) == (i >> 2)) { hv[i] = bitsel(hv[i], ~1u, ep & 1); hv[16 + i] = bitsel(hv[16 + i], ~1u, ep & 1); }
                    if (h == 0 && (i & 3) == 3) {
                        stg128(hp + (i >> 2) * 512, hv[i - 3], hv[i - 2], hv[i - 1], hv[i]);
                        stg128(hp + 16384 + (i >> 2) * 512, hv[13 + i], hv[14 + i], hv[15 + i], hv[16 + i]);
                    }
                }
                if (h == 0) {
                    STAMPW(4, 14);
                    if (lane == 0) red_hint(g_hcnt + tc * 64 + wg * 32);
                }
            }
            YIELD();
#pragma unroll
            for (int j = 0; j < 8; j++) {
                const int n0 = (HP0 >> (4 * j) & 15) * 60, n1 = (HP1 >> (4 * j) & 15) * 60;
                if (n0 | n1) __nanosleep(n0 + wg * (n1 - n0));
                stg128(hp + (8 + (j >> 2)) * 16384 + (j & 3) * 512, hv[4 * j], hv[4 * j + 1], hv[4 * j + 2], hv[4 * j + 3]);
            }
            __syncwarp();
            if (lane == 0) mbar_arrive(bars + B_HGO + 16 * wg + 8);
            STAMPW(5, 15);
        }
        if (wg == p.zero[2]) {
            INDICES(1)
            float y[128];
            const uint32_t sa = sb + w * 4096 + g * 512 + q * 8;
            bar_sync(2, 256);
            STAMP(7);
            rg.da = p.da[2];
            rg.ph = 0;
            rg.k = 130 * 66 + bid * 66 + 32;
#pragma unroll 1
            for (int i = 0;; i++) {
                gemm_step<2, 1>(y, rg, i);
                gemm_step<3, 1>(y, rg, 1);
                gemm_step<4, 1>(y, rg, 1);
                if (i == 5) break;
                gemm_step<0, 1>(y, rg, 1);
                gemm_step<1, 1>(y, rg, 1);
            }
            rg.da = p.da[3];
            gemm_half<60, 0>(y, rg);
            wg_commit();
            gemm_half<64 - SKEW, 1>(y, rg);
            wg_commit();
#pragma unroll
            for (int r = 0; r < 4; r++) {
                if (r == 0) {
                    wg_wait<1>();
#pragma unroll
                    for (int i = 0; i < 64; i++) asm volatile("" : "+f"(y[i])::"memory");
                    STAMP(16);
                    bar_sync(4, 128);
                }
                if (r == 2) {
                    STAMP(18);
                    wg_wait<0>();
#pragma unroll
                    for (int i = 64; i < 128; i++) asm volatile("" : "+f"(y[i])::"memory");
                    STAMP(8);
                    bar_sync(4, 128);
                }
#pragma unroll
                for (int c = 0; c < 16; c++) {
                    const int yi = 64 * (r >> 1) + 4 * c + 2 * (r & 1);
                    sts64f(sa + (r < 2 ? (NST - 1) * 32768 : 0) + (r & 1) * 16384 + (c >> 2) * 128 + (((c ^ g) & 3) << 5), y[yi], y[yi + 1]);
                }
                if (r == 0) bar_arrive(9, 256);
                if (r == 1) bar_arrive(10, 256);
                if (r == 2) bar_arrive(11, 256);
                if (r == 3) bar_arrive(12, 256);
            }
            STAMP(19);
            return;
        }
        bar_sync(8, 128);
        asm volatile("setmaxnreg.dec.sync.aligned.u32 152;");
        } else {
            INDICES(4)
            cf T[8];
            load_T(T, t7);
            const uint32_t tag = get_epoch(bars) & 1;
            float acc[64];
            constexpr uint64_t dF = mkdesc(OFF_F, 16, 1024, 1);
            const uint32_t tga = sb + OFF_P + t7 * 128 + (((t7 & 1) ^ (g & 2)) << 4);
            bool ok = false;
            mbar_wait(bars + B_WIN, 0);
#pragma unroll 1
            for (int gi = 0;; gi++) {
                const uint32_t un = p.unit[2 * bid + gi];
                const int kap = un & 0xffff;
                const uint32_t buf = sb + OFF_P + gi * 16384;
                STAMP3(39);
                float za[32], zb[32], ya[32], yb[32];
                const uint64_t dB = mkdesc(OFF_P, 4096, 512, 2) + gi * 1024;
                uint32_t ad, am, pa, pb;
                if (w == 2) {
                    ad = sb + OFF_W + (lane & 8) * 128;
                    am = ad + ((lane & 4) | (((kap ? 3 : 4) - lane) & 3)) * WPITCH + (8 * WPITCH + ((-2 * kap) & 15));
                    ad += gl * WPITCH + ((2 * kap) & 15);
                    asm volatile("" : "+r"(ad), "+r"(am));
                    mbar_wait(bars + B_WIN, gi);
                    pa = lds_u16(ad);
                    pb = lds_u16(am);
                }
#pragma unroll 1
                for (int n = gi; !ok && n < 4096; n++) {
                    if (n) bar_sync(3, 128);
                    if (n && w == 0 && elect_one()) { mbar_expect_tx(bars + B_UIN + gi * 8, 16384); bulk_ld(buf, g_U + (size_t)(extra ? 0 : bid + gi * 128) * 16384, 16384, bars + B_UIN + gi * 8); }
                    mbar_wait(bars + B_UIN + gi * 8, n & 1);
                    STAMP3(22);
                    wg_fence();
                    mma128_first(acc, dF, dB);
                    mma128_ss<0, 0, 1, 1>(acc, dF + 2, dB + 64);
                    mma128_ss<0, 0, 1, 1>(acc, dF + 4, dB + 128);
                    mma128_ss<0, 0, 1, 1>(acc, dF + 6, dB + 192);
                    wg_commit();
                    YIELD();
                    ok = wg_all_ok(tag_bad(tga + gi * 16384, tag), 3);
                    wg_wait<0>();
                    pin(acc);
                }
                STAMP3(30);
                uint32_t af[32];
#pragma unroll
                for (int b = 0; b < 4; b++) {
#pragma unroll
                    for (int c = 0; c < 4; c++) {
                        const int i = 4 * (4 * b + c);
                        cf x0 = cmul({acc[i], acc[i + 2]}, T[2 * c]), x1 = cmul({acc[i + 1], acc[i + 3]}, T[2 * c + 1]);
                        af[16 * (b >> 1) + 4 * c + (b & 1)] = pk(x0.x, x0.y);
                        af[16 * (b >> 1) + 4 * c + 2 + (b & 1)] = pk(x1.x, x1.y);
                        YLD(YF2, c == 3 ? 1 : (c == 1 ? 2 : 3));
                    }
                    if (b == 0 && w == 2) {
                        const uint32_t sg = (lane & 4) << 13, v = pk(0.5f * (up(pa) + up(pb ^ sg)), 0.f);
                        asm volatile("st.shared.u16 [%0], %1;" ::"r"(ad), "r"(v) : "memory");
                        asm volatile("st.shared.u16 [%0], %1;" ::"r"(am), "r"(v ^ sg) : "memory");
                    }
                    if (b == 1) {
                        wg_fence();
                        mma64_rs<0, 0>(za, af, dF); mma64_rs<0, 1>(za, af + 4, dF + 2); mma64_rs<0, 1>(za, af + 8, dF + 4); mma64_rs<0, 1>(za, af + 12, dF + 6);
                        wg_commit();
                    }
                }
                wg_fence();
                mma64_rs<0, 0>(zb, af + 16, dF); mma64_rs<0, 1>(zb, af + 20, dF + 2); mma64_rs<0, 1>(zb, af + 24, dF + 4); mma64_rs<0, 1>(zb, af + 28, dF + 6);
                wg_commit();
                STAMP3(31);
                int kq;
                asm volatile("mad.lo.s32 %0, %1, 512, %2;" : "=r"(kq) : "r"(q), "r"(kap));
                uint32_t wad[4];
#pragma unroll
                for (int j = 0; j < 4; j++) wad[j] = sb + OFF_W + ((j + (kq >> 9)) & 3) * WPITCH + ((2 * kap) & 15) + 2 * k1 + 128 * q;
                if (gi) fence_async_sm();
                bar_sync(3, 128);
                if (lane < gi) mbar_arrive(bars + B_STG);
                uint32_t wn[16];
#pragma unroll
                for (int j = 0; j < 16; j++) wn[j] = lds_u16(wad[j >> 2] + (j & 1) * 64 + (j & 2) * (2 * WPITCH));
                const cf be1 = twid(kq, 2048), be2 = cmul(be1, be1), be3 = cmul(be1, be2);
                YLD(YF2, 1);
                wg_wait<0>();
                pin(za);
                pin(zb);
                pinu(af);
                STAMP3(32);
                c2 z[4];
                auto pack = [&](int jb, int b) {
                    af[16 * (b >> 1) + 4 * jb + (b & 1)] = pkv(z[b].x);
                    af[16 * (b >> 1) + 4 * jb + 2 + (b & 1)] = pkv(z[b].y);
                };
#pragma unroll
                for (int jb = 0; jb < 4; jb++) {
                    if (jb == 2) STAMP3(37);
                    if (jb == 1) {
#pragma unroll
                        for (int j = 0; j < 4; j++)
                            wad[j] = sb + OFF_W + (8 + (((kap ? 3 : 4) - j - q) & 3)) * WPITCH + ((-2 * kap) & 15) + 1024 - 2 * k1 - 128 * q;
                    }
                    c2 W[4];
                    auto next = [&](int j) {
                        W[j] = {{upv(wn[4 * j]), upv(wn[4 * j + 1])}, {upv(wn[4 * j + 2]), upv(wn[4 * j + 3])}};
                        if (jb < 3) {
#pragma unroll
                            for (int n = 0; n < 4; n++) wn[4 * j + n] = lds_u16(wad[j] + (jb ? 512 - 512 * jb - (n & 1) * 64 : 512 + (n & 1) * 64) + (n & 2) * (2 * WPITCH));
                        }
                    };
                    const int i = 8 * jb;
                    const c2 z0 = {{za[i], za[i + 1]}, {za[i + 4], za[i + 5]}};
                    if (jb) pack(jb - 1, 1);
                    next(0);
                    c2 s0 = cfma2<false>({{zb[i], zb[i + 1]}, {zb[i + 4], zb[i + 5]}}, both(be2), z0), s1 = tw2(z0, s0);
                    YLD(YF2, 2);
                    if (jb) pack(jb - 1, 3);
                    if (jb == 3) load_T(T, t7);
                    next(1);
                    const c2 z1 = cmul2<false>({{za[i + 2], za[i + 3]}, {za[i + 6], za[i + 7]}}, both(be1));
                    YLD(YF2, 3);
                    c2 s2 = cfma2<false>({{zb[i + 2], zb[i + 3]}, {zb[i + 6], zb[i + 7]}}, both(be3), z1), s3 = tw2(z1, s2);
                    YLD(YF2, 1);
                    c2 x0, x1, x2, x3;
                    next(2);
                    bfly2(s0, s2, x0, x2);
                    const c2 y0 = jb < 2 ? cmul2<false>(x0, W[0]) : cmul2<true>(x0, W[0]);
                    YLD(YF2, 2);
                    next(3);
                    bflyi2(s1, s3, x1, x3);
                    const c2 y1 = jb < 2 ? cmul2<false>(x1, W[1]) : cmul2<true>(x1, W[1]);
                    YLD(YF2, 1);
                    s0 = jb < 2 ? cfma2<false>(x2, W[2], y0) : cfma2<true>(x2, W[2], y0);
                    s1 = tw2(y0, s0);
                    YLD(YF2, 3);
                    s2 = jb < 2 ? cfma2<false>(x3, W[3], y1) : cfma2<true>(x3, W[3], y1);
                    s3 = tw2(y1, s2);
                    YLD(YF2, 2);
                    bfly2(s0, s2, z[0], x2);
                    z[2] = cmul2<true>(x2, both(be2));
                    pack(jb, 0);
                    YLD(YF2, 1);
                    bflyi2(s1, s3, x3, x1);
                    pack(jb, 2);
                    z[1] = cmul2<true>(x1, both(be1));
                    YLD(YF2, 3);
                    z[3] = cmul2<true>(x3, both(be3));
                    YLD(YF2, 1);
                }
                pack(3, 1);
                pack(3, 3);
                pinu(af);
                wg_fence();
                mma64_rs<1, 0>(ya, af, dF); mma64_rs<1, 1>(ya, af + 4, dF + 128); mma64_rs<1, 1>(ya, af + 8, dF + 256); mma64_rs<1, 1>(ya, af + 12, dF + 384);
                wg_commit();
                mma64_rs<1, 0>(yb, af + 16, dF); mma64_rs<1, 1>(yb, af + 20, dF + 128); mma64_rs<1, 1>(yb, af + 24, dF + 256); mma64_rs<1, 1>(yb, af + 28, dF + 384);
                wg_commit();
                STAMP3(33);
                if (w == 2) fence_async_sm();
                __syncwarp();
                if (lane == 0) mbar_arrive(bars + B_WFREE);
                {
                    const uint32_t a0 = buf + (mi & 1) * 4096 + (16 * w + 8 * (mi >> 1) + gl) * 64;
#pragma unroll
                    for (int u = 0; u < 2; u++)
#pragma unroll
                        for (int c = 0; c < 4; c++) {
                            if (c == 0) {
                                if (u == 0) { wg_wait<1>(); pin(ya); STAMP3(34); }
                                else { wg_wait<0>(); pin(yb); pinu(af); }
                            }
                            const int i = 8 * c;
                            const float(&yy)[32] = u ? yb : ya;
                            const cf x0 = cmulc({yy[i], yy[i + 1]}, T[2 * c]), x1 = cmulc({yy[i + 4], yy[i + 5]}, T[2 * c + 1]);
                            const uint32_t o0 = pk(x0.x, x1.x), o2 = pk(x0.y, x1.y);
                            YLD(YF2, 3);
                            const cf y0 = cmulc({yy[i + 2], yy[i + 3]}, T[2 * c]), y1 = cmulc({yy[i + 6], yy[i + 7]}, T[2 * c + 1]);
                            stsm4(a0 + u * 8192 + ((c ^ (gl >> 1)) << 4), o0, pk(y0.x, y1.x), o2, pk(y0.y, y1.y));
                            YLD(YF2, 2 - (c & 1));
                        }
                }
                STAMP3(38);
                const uint32_t flip = ((g & 1) && !(un >> 24)) ? 0x80008000u : 0u, flipt = flip | (tag & ~tmask);
                const int rw = 8 * w + (gl & 4) + 2 * (mi & 1) + ((gl >> 1) & 1);
                const uint32_t a0 = (extra ? ((gl & 1) == gi ? sb + 32768 : sb + 65536) : buf) + rw * 128 +
                                    (((((gl & 1) << 1) | ((mi >> 1) ^ ((un >> 17) & 1))) ^ (rw & 7)) << 4);
                auto put = [&](const float (&v)[32], uint32_t a) {
#pragma unroll
                    for (int i = 0; i < 32; i += 8)
                        stsm4((a ^ ((i & 8) * 8)) + (i >> 4) * 4096, (pk(v[i], v[i + 1]) & tmask) ^ flipt, (pk(v[i + 2], v[i + 3]) & tmask) ^ flipt,
                              pk(v[i + 4], v[i + 5]) ^ flip, pk(v[i + 6], v[i + 7]) ^ flip);
                };
                fence_async_sm();
                bar_sync(3, 128);
                float va[32], vb[32];
                wg_fence();
                mma64_ss<1, 0>(va, dF, dB); mma64_ss<1, 0>(vb, dF, dB + 512);
                mma64_ss<1, 1>(va, dF + 128, dB + 64); mma64_ss<1, 1>(vb, dF + 128, dB + 576);
                mma64_ss<1, 1>(va, dF + 256, dB + 128); mma64_ss<1, 1>(vb, dF + 256, dB + 640);
                mma64_ss<1, 1>(va, dF + 384, dB + 192); mma64_ss<1, 1>(vb, dF + 384, dB + 704);
                wg_commit();
                STAMP3(35);
                uint32_t bad = 0;
                if (!gi) {
                    mbar_wait(bars + B_UIN + 8, 0);
                    bad = tag_bad(tga + 16384, tag);
                }
                wg_wait<0>();
                pin(va);
                pin(vb);
                STAMP3(36);
                ok = wg_all_ok(bad, 3);
                put(va, a0);
                if (gi) {
                    put(vb, a0 + 8192);
                    fence_async_sm();
                    __syncwarp();
                    if (lane == 0) mbar_arrive(bars + B_STG);
                    break;
                }
                constexpr uint64_t dN = mkdesc(OFF_P + 16384, 4096, 512, 2);
                wg_fence();
                mma128_first(acc, dF, dN);
                mma128_ss<0, 0, 1, 1>(acc, dF + 2, dN + 64);
                mma128_ss<0, 0, 1, 1>(acc, dF + 4, dN + 128);
                mma128_ss<0, 0, 1, 1>(acc, dF + 6, dN + 192);
                wg_commit();
                put(vb, a0 + 8192);
                wg_wait<0>();
                pin(acc);
            }
            if (extra) return;
        }
        uint2 xd[16], dd;
        auto skip = [&]() {
            const int lane = (threadIdx.x + p.zero[2]) & 31;
            const uint2* xp = (const uint2*)(p.xb + (uint32_t)((tc * 128 + 64 * (w & 1) + 32 * hf + 8 * (w >> 1)) * 1024 + cb * 128)) + lane;
            dd = __ldg((const uint2*)(p.dsk + cb * 128) + lane);
#pragma unroll
            for (int j = 0; j < (XT ? 8 : 16); j++) {
                asm volatile("ld.global.nc.L1::no_allocate.v2.b32 {%0,%1}, [%2];" : "=r"(xd[j].x), "=r"(xd[j].y) : "l"(xp + ((j >> 3) * 16 + (j & 7)) * 256));
            }
        };
        auto skip2 = [&]() {
            if (XT) {
                const uint32_t xa = sb + OFF_W + (2 * (w & 1) + hf) * 4096 + (w >> 1) * 2048 + ((threadIdx.x + p.zero[3]) & 31) * 8;
                mbar_wait(bars + B_WIN, 0);
#pragma unroll
                for (int j = 0; j < 8; j++) asm volatile("ld.shared.v2.b32 {%0,%1}, [%2];" : "=r"(xd[8 + j].x), "=r"(xd[8 + j].y) : "r"(xa + j * 256) : "memory");
            }
#pragma unroll
            for (int j = 0; j < 16; j++) {
                if (j % 4 == 0) YIELD();
                asm volatile("fma.rn.bf16x2 %0, %0, %1, %2;" : "+r"(xd[j].x) : "r"(dd.x), "r"(0x80008000u));
                asm volatile("fma.rn.bf16x2 %0, %0, %1, %2;" : "+r"(xd[j].y) : "r"(dd.y), "r"(0x80008000u));
            }
            YIELD();
        };
        {
            INDICES(5)
            uint32_t sp[8];
#pragma unroll
            for (int j = 0; j < 2; j++) { const uint4 v = ldtab(TAB_SP + j * 512 + t7 * 4); sp[4 * j] = v.x; sp[4 * j + 1] = v.y; sp[4 * j + 2] = v.z; sp[4 * j + 3] = v.w; }
            cf tw[8];
            load_tw(tw, k1);
            tw[4].x *= 2.f; tw[4].y *= 2.f;
            const uint32_t tag = get_epoch(bars) & 1;
            const uint32_t in = sb + OFF_P + hf * 8192;
            constexpr uint64_t dF = mkdesc(OFF_F, 16, 1024, 1);
            const uint64_t dB = mkdesc(OFF_P, 2048, 256, 3) + hf * 512;
            float ae[32], ao[32];
            c2 ev[2][4];
            auto blk = [&](const float (&a)[32], int i) { return c2{{a[i], a[i + 1]}, {a[i + 2], a[i + 3]}}; };
            auto unfold = [&](c2 a, c2 u, int n, c2& zn, c2& zm, int yl) {
                const float wc = n == 1 ? 0.92387953251128674f : (n == 2 ? 0.70710678118654752f : 0.38268343236508977f);
                const float ws = n == 3 ? 0.92387953251128674f : (n == 2 ? 0.70710678118654752f : 0.38268343236508977f);
                const v2 c = {wc, wc}, s = {ws, ws}, two = {2.f, 2.f};
                const c2 y = cmul2<false>(a, both(tw[n])), t = both(tw[8 - n]);
                YLD(yl, 3);
                c2 E;
                E.x = fnm2(u.y, t.y, y.x); E.y = fnm2(u.x, t.y, y.y); E.x = fma2(u.x, t.x, E.x); E.y = fnm2(u.y, t.x, E.y);
                YLD(yl, 2);
                const c2 D = tw2(y, E);
                zn.x = fnm2(D.y, c, E.x); zn.y = fma2(D.y, s, E.y); zn.x = fma2(D.x, s, zn.x); zn.y = fma2(D.x, c, zn.y);
                YLD(yl, 4);
                zm.x = tw2(E.x, zn.x); zm.y = fnm2(E.y, two, zn.y);
                YLD(yl, 1);
            };
#pragma unroll
            for (int rgn = 0; rgn < 2; rgn++) {
#pragma unroll 1
                for (int n = 0; n < 4096; n++) {
                    mbar_wait(bars + B_VIN + rgn * 16 + hf * 8, n & 1);
                    if (rgn) STAMP(25);
                    if (rgn == 0) {
                        pinu(sp);
                        wg_fence();
                        mma48_ss<0>(ae, dF, dB + 128); mma16_rs<0>(ae, sp[0], 0u, sp[1], 0u, dB);
                        mma48_ss<1>(ae, dF + 2, dB + 160); mma16_rs<1>(ae, sp[2], 0u, sp[3], 0u, dB + 32);
                        mma48_ss<1>(ae, dF + 4, dB + 192); mma16_rs<1>(ae, 0u, sp[4], 0u, sp[5], dB + 64);
                        mma48_ss<1>(ae, dF + 6, dB + 224); mma16_rs<1>(ae, 0u, sp[6], 0u, sp[7], dB + 96);
                    } else {
                        wg_fence();
                        mma64_ss<0, 0>(ao, dF, dB + 1024);
                        mma64_ss<0, 1>(ao, dF + 2, dB + 1056);
                        mma64_ss<0, 1>(ao, dF + 4, dB + 1088);
                        mma64_ss<0, 1>(ao, dF + 6, dB + 1120);
                    }
                    wg_commit();
                    const bool ok = wg_all_ok(tag_bad(in + rgn * 16384 + t7 * 64 + (t7 & 6) * 8, tag), hf ? 3 : 8);
                    wg_wait<0>();
                    if (rgn) pin(ao);
                    else { pin(ae); pinu(sp); }
                    if (ok) break;
                    wg_all_ok(0, hf ? 3 : 8);
                    if (w == 0 && elect_one()) {
                        mbar_expect_tx(bars + B_VIN + rgn * 16 + hf * 8, 8192);
                        tma2d(in + rgn * 16384, &tmVld, hf * 32, vrow + rgn * 128, bars + B_VIN + rgn * 16 + hf * 8);
                    }
                }
                if (rgn == 0) {
#pragma unroll
                    for (int cl = 0; cl < 2; cl++) {
                        const c2 b = blk(ae, 4 * cl), z0 = {add2(b.x, b.y), sub2(b.x, b.y)};
                        const c2 a0 = cfma2<false>(blk(ae, 16 + 4 * cl), both(tw[4]), z0), a1 = tw2(z0, a0);
                        YIELD();
                        c2 z2, z6, a2, a3;
                        unfold(blk(ae, 8 + 4 * cl), blk(ae, 24 + 4 * cl), 2, z2, z6, YFE);
                        bfly2(z2, z6, a2, a3);
                        bfly2(a0, a2, ev[cl][0], ev[cl][2]);
                        YIELD();
                        bflyi2(a1, a3, ev[cl][1], ev[cl][3]);
                    }
                    YIELD();
                }
            }
            skip();
            const uint32_t a0 = in + (8 * w + (gl ^ (2 * hf)) + 32 * (mi & 1)) * 32 + (mi >> 1) * 16384 + (gl & 4) * 4;
#pragma unroll
            for (int cl = 0; cl < 2; cl++) {
                c2 z1, z3, z5, z7, a4, a5, a6, a7;
                unfold(blk(ao, 4 * cl), blk(ao, 24 + 4 * cl), 1, z1, z7, YF3);
                if (cl == 0) wg_all_ok(0, hf ? 3 : 8);
                unfold(blk(ao, 8 + 4 * cl), blk(ao, 16 + 4 * cl), 3, z3, z5, YF3);
                bfly2(z1, z5, a4, a5);
                YLD(YF3, 3);
                bfly2(z3, z7, a6, a7);
                YLD(YF3, 2);
                dft8_end<YF3>(ev[cl], a4, a5, a6, a7, [&](int r, c2 u, c2 v) { stsm4((a0 ^ (cl * 16)) + r * 2048, pkv(u.x), pkv(u.y), pkv(v.x), pkv(v.y)); });
            }
            bar_sync(7, 256);
            STAMP(26);
        }
        INDICES(6)
        const int t0 = tc * 128 + 64 * (w & 1) + 32 * hf + 8 * (w >> 1);
        {
            const int n0 = 16 * hf + 4 * w + mi;
            uint32_t la = sb + OFF_P + (((gl >> 2) * 8256) ^ (n0 * 32)) + ((((gl >> 1) & 1) ^ (w & 1)) << 4) + (gl & 1) * 8;
            const float* op = p.out + (uint32_t)((4 * n0 + fb) * 2048 + fcb * 32 + gl * 4);
#pragma unroll 1
            for (int it = 0; it < 4; it++) {
                uint32_t u[8];
#pragma unroll
                for (int i = 0; i < 4; i++) asm volatile("ld.shared.v2.b32 {%0,%1}, [%2];" : "=r"(u[2 * i]), "=r"(u[2 * i + 1]) : "r"(la + i * 1024) : "memory");
#pragma unroll
                for (int i = 0; i < 4; i++) {
                    stg128(op + i * 128 * 2048, u[2 * i] << 16, u[2 * i] & 0xffff0000u, u[2 * i + 1] << 16, u[2 * i + 1] & 0xffff0000u);
                    if (TRYP >> i & 1) asm volatile("{.reg .pred p; mbarrier.try_wait.parity.shared::cta.b64 p, [%0], 0, %1; @p pmevent 0;}" ::"r"(bars + B_LDONE), "r"(PACE_O) : "memory");
                }
                la += it == 1 ? 12288 : 4096;
                op += 4 * 128 * 2048;
            }
            STAMP(27);
        }
        skip2();
        const uint32_t ra = sb + hf * 16384 + w * 4096;
        float* ob = p.out + (size_t)t0 * 2048 + 1024 + cb * 128 + lane * 4;
#pragma unroll
        for (int mb = 0; mb < 2; mb++) {
            if (hf == 0) { if (mb == 0) bar_sync(9, 256); else bar_sync(11, 256); }
            else { if (mb == 0) bar_sync(10, 256); else bar_sync(12, 256); }
            if (mb == 0) STAMP(17);
            float v[8][4];
#pragma unroll
            for (int j = 0; j < 8; j++) lds128f(ra + (mb ? 0 : (NST - 1) * 32768) + j * 512 + ((lane * 16) ^ ((j & 3) * 32)), v[j][0], v[j][1], v[j][2], v[j][3]);
#pragma unroll
            for (int j = 0; j < 8; j++) {
                const uint2 s = xd[8 * mb + j];
                stg128(ob + (16 * mb + j) * 2048, __float_as_uint(v[j][0] + up(s.x)), __float_as_uint(v[j][1] + __uint_as_float(s.x & 0xffff0000u)),
                       __float_as_uint(v[j][2] + up(s.y)), __float_as_uint(v[j][3] + __uint_as_float(s.y & 0xffff0000u)));
            }
        }
        STAMP(9);
        if (threadIdx.x == 480) RECL(2);
    }
}

typedef CUresult (*EncodeFn)(CUtensorMap*, CUtensorMapDataType, cuuint32_t, void*, const cuuint64_t*, const cuuint64_t*, const cuuint32_t*,
                             const cuuint32_t*, CUtensorMapInterleave, CUtensorMapSwizzle, CUtensorMapL2promotion, CUtensorMapFloatOOBfill);

static CUtensorMap make_map(EncodeFn enc, const void* ptr, int rank, const cuuint64_t* dims, const cuuint64_t* strides, const cuuint32_t* box,
                            CUtensorMapSwizzle swz, CUtensorMapL2promotion promo, CUtensorMapDataType dt = CU_TENSOR_MAP_DATA_TYPE_BFLOAT16) {
    CUtensorMap m;
    const cuuint32_t es[5] = {1, 1, 1, 1, 1};
    enc(&m, dt, rank, const_cast<void*>(ptr), dims, strides, box, es, CU_TENSOR_MAP_INTERLEAVE_NONE, swz, promo,
        CU_TENSOR_MAP_FLOAT_OOB_FILL_NONE);
    return m;
}

extern "C" void kernel_launch(void* const* d_in, const int* in_sizes, int n_in, void* d_out, int out_size) {
    void* fn = nullptr;
    cudaDriverEntryPointQueryResult qr;
    cudaGetDriverEntryPoint("cuTensorMapEncodeTiled", &fn, cudaEnableDefault, &qr);
    EncodeFn enc = (EncodeFn)fn;
    void *pU, *pV;
    cudaGetSymbolAddress(&pU, g_U);
    cudaGetSymbolAddress(&pV, g_V);
    const CUtensorMapL2promotion P256 = CU_TENSOR_MAP_L2_PROMOTION_L2_256B, P0 = CU_TENSOR_MAP_L2_PROMOTION_NONE;

    const cuuint64_t dX[5] = {1024, 2, 4, 16, 16}, sX[4] = {2048, 32 * 2048, 2 * 2048, 128 * 2048};
    const cuuint32_t bX[5] = {64, 2, 4, 16, 1};
    CUtensorMap tmX = make_map(enc, d_in[3], 5, dX, sX, bX, CU_TENSOR_MAP_SWIZZLE_128B, CU_TENSOR_MAP_L2_PROMOTION_L2_128B);
    const cuuint64_t dB[4] = {1024, 8, 2, 96}, sB[3] = {2048, 256 * 2048, 8 * 2048}, dC[4] = {1024, 8, 2, 64}, sC[3] = {2048, 8 * 2048, 16 * 2048};
    const cuuint32_t bB[4] = {64, 8, 2, 4};
    CUtensorMap tmBre = make_map(enc, d_in[6], 4, dB, sB, bB, CU_TENSOR_MAP_SWIZZLE_128B, P256);
    CUtensorMap tmBim = make_map(enc, d_in[7], 4, dB, sB, bB, CU_TENSOR_MAP_SWIZZLE_128B, P256);
    CUtensorMap tmCre = make_map(enc, d_in[8], 4, dC, sC, bB, CU_TENSOR_MAP_SWIZZLE_128B, P256);
    CUtensorMap tmCim = make_map(enc, d_in[9], 4, dC, sC, bB, CU_TENSOR_MAP_SWIZZLE_128B, P256);

    const cuuint64_t dU[2] = {8192, 256}, sU[1] = {16384};
    const cuuint32_t bS[2] = {64, UBOX};
    CUtensorMap tmUst = make_map(enc, pU, 2, dU, sU, bS, CU_TENSOR_MAP_SWIZZLE_128B, P0);
    const cuuint64_t dV[2] = {16384, 128}, sV[1] = {32768}, dL[2] = {64, 32768}, sL[1] = {128};
    const cuuint32_t bL[2] = {32, 128};
    CUtensorMap tmVst = make_map(enc, pV, 2, dV, sV, bS, CU_TENSOR_MAP_SWIZZLE_128B, P0);
    CUtensorMap tmVld = make_map(enc, pV, 2, dL, sL, bL, CU_TENSOR_MAP_SWIZZLE_NONE, P0);
    const cuuint64_t dR[2] = {1024, 2048}, sR[1] = {2048};
    const cuuint32_t bR[2] = {128, 16};
    CUtensorMap tmXR = make_map(enc, d_in[3], 2, dR, sR, bR, CU_TENSOR_MAP_SWIZZLE_NONE, P0);
    const cuuint64_t dA[4] = {1024, 64, 8, 4}, sA[3] = {32 * 2048, 4 * 2048, 2048};
    const cuuint32_t bA[4] = {16, 64, 1, 1};
    CUtensorMap tmXA = make_map(enc, d_in[0], 4, dA, sA, bA, CU_TENSOR_MAP_SWIZZLE_32B, CU_TENSOR_MAP_L2_PROMOTION_L2_128B);
    const cuuint64_t dF[2] = {512 * 1026 / 8, 4}, sF[1] = {512 * 1026};
    const cuuint32_t bF[2] = {WPITCH / 8, 4};
    CUtensorMap tmWr = make_map(enc, d_in[1], 2, dF, sF, bF, CU_TENSOR_MAP_SWIZZLE_NONE, P0, CU_TENSOR_MAP_DATA_TYPE_UINT64);
    CUtensorMap tmWi = make_map(enc, d_in[2], 2, dF, sF, bF, CU_TENSOR_MAP_SWIZZLE_NONE, P0, CU_TENSOR_MAP_DATA_TYPE_UINT64);

    Params p = {};
    p.xb = (const __nv_bfloat16*)d_in[3];
    p.lre = (const __nv_bfloat16*)d_in[4];
    p.lim = (const __nv_bfloat16*)d_in[5];
    p.ldt = (const __nv_bfloat16*)d_in[10];
    p.dsk = (const __nv_bfloat16*)d_in[11];
    p.out = (float*)d_out;
    p.da[0] = p.da[1] = mkdesc(0, 16, 1024, 1) - 1;
    p.da[2] = p.da[3] = mkdesc(0, 512, 2048, 2) - 1;
    for (int i = 0; i < 258; i++) {
        int cj;
        const int kap = kappa_of(i >> 1, i & 1), s3 = slot3_of(kap, cj);
        p.unit[i] = kap | s3 << 16 | cj << 24;
    }
    cudaFuncSetAttribute(fused_kernel, cudaFuncAttributeMaxDynamicSharedMemorySize, SMEM_BYTES);
    fused_kernel<<<130, 512, SMEM_BYTES>>>(Maps{{tmX, tmBre, tmBim, tmCre, tmCim, tmXA, tmUst, tmVst, tmWr, tmWi, tmVld, tmXR}}, p);
}
```

```cpp
#include <cuda_runtime.h>
#include <cuda.h>
#include <cuda_bf16.h>
#include <stdint.h>

#define NST 5
#define SB0 1024
#define WPITCH 1056
#define OFF_P (NST * 32768)
#define OFF_F (OFF_P + 32768)
#define OFF_W (OFF_F + 8192)
#define OFF_TL (OFF_W + 16 * WPITCH)
#define OFF_TM (OFF_TL + 4096)
#define OFF_T1 (OFF_TM + 4096)
#define OFF_BAR (OFF_T1 + 2048)
#define OFF_STAMP (OFF_BAR + 384)
#define SMEM_BYTES (OFF_BAR + 512)
#define B_FULL 0
#define B_EMPTY 40
#define B_STGU 80
#define B_HGO 88
#define B_LAM 120
#define B_STG 128
#define B_WFREE 136
#define B_EP 144
#define B_LDONE 152
#define B_UIN 160
#define B_WIN 176
#define B_XIN 184
#define B_VIN 200
#define B_HRTY 232
#define B_HLD 240
#define B_END 280
#define B_EPOCH 280

#define PACE_U 250
#define PACE_V 120
#define PACE_O 250
#define HAND 3
#define POLL_AT 24
#define XA_FIRST 3
#define XA_AT 0
#define YS 3
#define UDELAY 250
#define PACE_W 120
#define HINT_U 0
#define HINT_V 2
#define GRP 0x8a
#define EARLY_U 36
#define EARLY_V 36
#define EARLY_H 4
#define KMC 3
#define GRP2 GRP
#define YS2 1
#define PPOLL 5
#define HP0 0x22222220
#define HP1 0x44444440
#define TRYP 15
#define XT 1
#define UBOX 32
#define SKEW 4
#define SPIN_LIMIT 32768

#define YIELD() asm volatile("pmevent 0;")
#define YF1 3
#define YF2 2
#define YF3 4
#define YLD(level, n) do { if ((level) >= (n)) YIELD(); } while (0)

__device__ __align__(1024) uint8_t g_U[4 << 20];
__device__ __align__(1024) uint8_t g_V[4 << 20];
__device__ __align__(1024) uint8_t g_H[8 << 20];
__device__ __align__(1024) uint4 g_carry[16 * 512];
__device__ __align__(1024) unsigned g_hcnt[16 * 64];
__device__ __align__(128) unsigned g_cnt[128];
__device__ __align__(128) unsigned g_epoch[129 * 8];

#define RECL(i) do { } while (0)
#define STAMP(i) do { } while (0)
#define STAMPR(i) do { } while (0)
#define STAMPW(a, b) do { } while (0)
#define STAMPX(a, b) do { } while (0)
#define STAMP5(i) do { } while (0)
#define STAMP3(i) do { } while (0)

#define TAB_FG 0
#define TAB_F1 2048
#define TAB_T 4096
#define TAB_SP 6144
#define TAB_TW 7168
#define TAB_FX 7680
__device__ __align__(1024) const uint32_t g_tab[7808] = {
0x80003d80,0x80003d80,0x80003d80,0x80003d80,0x80003d80,0x80003d80,0x80003d80,0x80003d80,0x80003d80,0x80003d80,0x80003d80,0x80003d80,0x80003d80,0x80003d80,0x80003d80,0x80003d80,
0x80003d80,0x80003d80,0x80003d80,0x80003d80,0x80003d80,0x80003d80,0x80003d80,0x80003d80,0x80003d80,0x80003d80,0x80003d80,0x80003d80,0x80003d80,0x80003d80,0x80003d80,0x80003d80,
0x3c483d7b,0x3d0e3d55,0x3d553d0e,0x3d7b3c48,0x80003d80,0x3cc43d6d,0x3d353d35,0x3d6d3cc4,0x3d7bbc48,0x3d55bd0e,0x3d0ebd55,0x3c48bd7b,0x3d800000,0x3d6dbcc4,0x3d35bd35,0x3cc4bd6d,
0xbc48bd7b,0xbd0ebd55,0xbd55bd0e,0xbd7bbc48,0x8000bd80,0xbcc4bd6d,0xbd35bd35,0xbd6dbcc4,0xbd7b3c48,0xbd553d0e,0xbd0e3d55,0xbc483d7b,0xbd800000,0xbd6d3cc4,0xbd353d35,0xbcc43d6d,
0x8000bd80,0xbd35bd35,0xbd800000,0xbd353d35,0xbcc4bd6d,0xbd6dbcc4,0xbd6d3cc4,0xbcc43d6d,0x80003d80,0x3d353d35,0x3d800000,0x3d35bd35,0x3cc43d6d,0x3d6d3cc4,0x3d6dbcc4,0x3cc4bd6d,
0x8000bd80,0xbd35bd35,0xbd800000,0xbd353d35,0xbcc4bd6d,0xbd6dbcc4,0xbd6d3cc4,0xbcc43d6d,0x80003d80,0x3d353d35,0x3d800000,0x3d35bd35,0x3cc43d6d,0x3d6d3cc4,0x3d6dbcc4,0x3cc4bd6d,
0xbd553d0e,0x3c483d7b,0x3d7b3c48,0x3d0ebd55,0xbd800000,0xbcc43d6d,0x3d353d35,0x3d6dbcc4,0x3d0e3d55,0x3d7bbc48,0x3c48bd7b,0xbd55bd0e,0x80003d80,0x3d6d3cc4,0x3d35bd35,0xbcc4bd6d,
0x3d55bd0e,0xbc48bd7b,0xbd7bbc48,0xbd0e3d55,0x3d800000,0x3cc4bd6d,0xbd35bd35,0xbd6d3cc4,0xbd0ebd55,0xbd7b3c48,0xbc483d7b,0x3d553d0e,0x8000bd80,0xbd6dbcc4,0xbd353d35,0x3cc43d6d,
0x80003d80,0x3d800000,0x8000bd80,0xbd800000,0x3d353d35,0x3d35bd35,0xbd35bd35,0xbd353d35,0x80003d80,0x3d800000,0x8000bd80,0xbd800000,0x3d353d35,0x3d35bd35,0xbd35bd35,0xbd353d35,
0x80003d80,0x3d800000,0x8000bd80,0xbd800000,0x3d353d35,0x3d35bd35,0xbd35bd35,0xbd353d35,0x80003d80,0x3d800000,0x8000bd80,0xbd800000,0x3d353d35,0x3d35bd35,0xbd35bd35,0xbd353d35,
0xbd55bd0e,0xbc483d7b,0x3d7bbc48,0xbd0ebd55,0x8000bd80,0xbd6d3cc4,0x3d353d35,0x3cc4bd6d,0xbd0e3d55,0x3d7b3c48,0xbc48bd7b,0xbd553d0e,0xbd800000,0x3cc43d6d,0x3d35bd35,0xbd6dbcc4,
0x3d553d0e,0x3c48bd7b,0xbd7b3c48,0x3d0e3d55,0x80003d80,0x3d6dbcc4,0xbd35bd35,0xbcc43d6d,0x3d0ebd55,0xbd7bbc48,0x3c483d7b,0x3d55bd0e,0x3d800000,0xbcc4bd6d,0xbd353d35,0x3d6d3cc4,
0x8000bd80,0xbd353d35,0x3d800000,0xbd35bd35,0xbd6dbcc4,0x3cc43d6d,0x3cc4bd6d,0xbd6d3cc4,0x80003d80,0x3d35bd35,0xbd800000,0x3d353d35,0x3d6d3cc4,0xbcc4bd6d,0xbcc43d6d,0x3d6dbcc4,
0x8000bd80,0xbd353d35,0x3d800000,0xbd35bd35,0xbd6dbcc4,0x3cc43d6d,0x3cc4bd6d,0xbd6d3cc4,0x80003d80,0x3d35bd35,0xbd800000,0x3d353d35,0x3d6d3cc4,0xbcc4bd6d,0xbcc43d6d,0x3d6dbcc4,
0x3c48bd7b,0xbd0e3d55,0x3d55bd0e,0xbd7b3c48,0x3d800000,0xbd6dbcc4,0x3d353d35,0xbcc4bd6d,0xbd7bbc48,0x3d553d0e,0xbd0ebd55,0x3c483d7b,0x8000bd80,0xbcc43d6d,0x3d35bd35,0xbd6d3cc4,
0xbc483d7b,0x3d0ebd55,0xbd553d0e,0x3d7bbc48,0xbd800000,0x3d6d3cc4,0xbd35bd35,0x3cc43d6d,0x3d7b3c48,0xbd55bd0e,0x3d0e3d55,0xbc48bd7b,0x80003d80,0x3cc4bd6d,0xbd353d35,0x3d6dbcc4,
0x3d800000,0x3d800000,0x3d800000,0x3d800000,0x3d800000,0x3d800000,0x3d800000,0x3d800000,0x3d800000,0x3d800000,0x3d800000,0x3d800000,0x3d800000,0x3d800000,0x3d800000,0x3d800000,
0x3d800000,0x3d800000,0x3d800000,0x3d800000,0x3d800000,0x3d800000,0x3d800000,0x3d800000,0x3d800000,0x3d800000,0x3d800000,0x3d800000,0x3d800000,0x3d800000,0x3d800000,0x3d800000,
0x3d7bbc48,0x3d55bd0e,0x3d0ebd55,0x3c48bd7b,0x3d800000,0x3d6dbcc4,0x3d35bd35,0x3cc4bd6d,0xbc48bd7b,0xbd0ebd55,0xbd55bd0e,0xbd7bbc48,0xbd80,0xbcc4bd6d,0xbd35bd35,0xbd6dbcc4,
0xbd7b3c48,0xbd553d0e,0xbd0e3d55,0xbc483d7b,0xbd800000,0xbd6d3cc4,0xbd353d35,0xbcc43d6d,0x3c483d7b,0x3d0e3d55,0x3d553d0e,0x3d7b3c48,0x3d80,0x3cc43d6d,0x3d353d35,0x3d6d3cc4,
0xbd800000,0xbd353d35,0x3d80,0x3d353d35,0xbd6d3cc4,0xbcc43d6d,0x3cc43d6d,0x3d6d3cc4,0x3d800000,0x3d35bd35,0xbd80,0xbd35bd35,0x3d6dbcc4,0x3cc4bd6d,0xbcc4bd6d,0xbd6dbcc4,
0xbd800000,0xbd353d35,0x3d80,0x3d353d35,0xbd6d3cc4,0xbcc43d6d,0x3cc43d6d,0x3d6d3cc4,0x3d800000,0x3d35bd35,0xbd80,0xbd35bd35,0x3d6dbcc4,0x3cc4bd6d,0xbcc4bd6d,0xbd6dbcc4,
0x3d0e3d55,0x3d7bbc48,0x3c48bd7b,0xbd55bd0e,0x3d80,0x3d6d3cc4,0x3d35bd35,0xbcc4bd6d,0x3d55bd0e,0xbc48bd7b,0xbd7bbc48,0xbd0e3d55,0x3d800000,0x3cc4bd6d,0xbd35bd35,0xbd6d3cc4,
0xbd0ebd55,0xbd7b3c48,0xbc483d7b,0x3d553d0e,0xbd80,0xbd6dbcc4,0xbd353d35,0x3cc43d6d,0xbd553d0e,0x3c483d7b,0x3d7b3c48,0x3d0ebd55,0xbd800000,0xbcc43d6d,0x3d353d35,0x3d6dbcc4,
0x3d800000,0xbd80,0xbd800000,0x3d80,0x3d35bd35,0xbd35bd35,0xbd353d35,0x3d353d35,0x3d800000,0xbd80,0xbd800000,0x3d80,0x3d35bd35,0xbd35bd35,0xbd353d35,0x3d353d35,
0x3d800000,0xbd80,0xbd800000,0x3d80,0x3d35bd35,0xbd35bd35,0xbd353d35,0x3d353d35,0x3d800000,0xbd80,0xbd800000,0x3d80,0x3d35bd35,0xbd35bd35,0xbd353d35,0x3d353d35,
0xbd0e3d55,0x3d7b3c48,0xbc48bd7b,0xbd553d0e,0xbd800000,0x3cc43d6d,0x3d35bd35,0xbd6dbcc4,0x3d553d0e,0x3c48bd7b,0xbd7b3c48,0x3d0e3d55,0x3d80,0x3d6dbcc4,0xbd35bd35,0xbcc43d6d,
0x3d0ebd55,0xbd7bbc48,0x3c483d7b,0x3d55bd0e,0x3d800000,0xbcc4bd6d,0xbd353d35,0x3d6d3cc4,0xbd55bd0e,0xbc483d7b,0x3d7bbc48,0xbd0ebd55,0xbd80,0xbd6d3cc4,0x3d353d35,0x3cc4bd6d,
0xbd800000,0x3d353d35,0xbd80,0xbd353d35,0xbcc43d6d,0x3d6dbcc4,0xbd6dbcc4,0x3cc43d6d,0x3d800000,0xbd35bd35,0x3d80,0x3d35bd35,0x3cc4bd6d,0xbd6d3cc4,0x3d6d3cc4,0xbcc4bd6d,
0xbd800000,0x3d353d35,0xbd80,0xbd353d35,0xbcc43d6d,0x3d6dbcc4,0xbd6dbcc4,0x3cc43d6d,0x3d800000,0xbd35bd35,0x3d80,0x3d35bd35,0x3cc4bd6d,0xbd6d3cc4,0x3d6d3cc4,0xbcc4bd6d,
0xbd7bbc48,0x3d553d0e,0xbd0ebd55,0x3c483d7b,0xbd80,0xbcc43d6d,0x3d35bd35,0xbd6d3cc4,0xbc483d7b,0x3d0ebd55,0xbd553d0e,0x3d7bbc48,0xbd800000,0x3d6d3cc4,0xbd35bd35,0x3cc43d6d,
0x3d7b3c48,0xbd55bd0e,0x3d0e3d55,0xbc48bd7b,0x3d80,0x3cc4bd6d,0xbd353d35,0x3d6dbcc4,0x3c48bd7b,0xbd0e3d55,0x3d55bd0e,0xbd7b3c48,0x3d800000,0xbd6dbcc4,0x3d353d35,0xbcc4bd6d,
0x80003d80,0x8000bd80,0x80003d80,0x8000bd80,0x3d800000,0xbd800000,0x3d800000,0xbd800000,0x80003d80,0x8000bd80,0x80003d80,0x8000bd80,0x3d800000,0xbd800000,0x3d800000,0xbd800000,
0x80003d80,0x8000bd80,0x80003d80,0x8000bd80,0x3d800000,0xbd800000,0x3d800000,0xbd800000,0x80003d80,0x8000bd80,0x80003d80,0x8000bd80,0x3d800000,0xbd800000,0x3d800000,0xbd800000,
0x3d7bbc48,0xbd553d0e,0x3d0ebd55,0xbc483d7b,0x80003d80,0xbcc4bd6d,0x3d353d35,0xbd6dbcc4,0xbc48bd7b,0x3d0e3d55,0xbd55bd0e,0x3d7b3c48,0x3d800000,0xbd6d3cc4,0x3d35bd35,0xbcc43d6d,
0xbd7b3c48,0x3d55bd0e,0xbd0e3d55,0x3c48bd7b,0x8000bd80,0x3cc43d6d,0xbd35bd35,0x3d6d3cc4,0x3c483d7b,0xbd0ebd55,0x3d553d0e,0xbd7bbc48,0xbd800000,0x3d6dbcc4,0xbd353d35,0x3cc4bd6d,
0x8000bd80,0x3d353d35,0xbd800000,0x3d35bd35,0xbd6d3cc4,0x3cc4bd6d,0x3cc43d6d,0xbd6dbcc4,0x80003d80,0xbd35bd35,0x3d800000,0xbd353d35,0x3d6dbcc4,0xbcc43d6d,0xbcc4bd6d,0x3d6d3cc4,
0x8000bd80,0x3d353d35,0xbd800000,0x3d35bd35,0xbd6d3cc4,0x3cc4bd6d,0x3cc43d6d,0xbd6dbcc4,0x80003d80,0xbd35bd35,0x3d800000,0xbd353d35,0x3d6dbcc4,0xbcc43d6d,0xbcc4bd6d,0x3d6d3cc4,
0x3d0e3d55,0xbd7b3c48,0x3c48bd7b,0x3d553d0e,0xbd800000,0x3cc4bd6d,0x3d353d35,0xbd6d3cc4,0x3d55bd0e,0x3c483d7b,0xbd7bbc48,0x3d0ebd55,0x80003d80,0xbd6dbcc4,0x3d35bd35,0x3cc43d6d,
0xbd0ebd55,0x3d7bbc48,0xbc483d7b,0xbd55bd0e,0x3d800000,0xbcc43d6d,0xbd35bd35,0x3d6dbcc4,0xbd553d0e,0xbc48bd7b,0x3d7b3c48,0xbd0e3d55,0x8000bd80,0x3d6d3cc4,0xbd353d35,0xbcc4bd6d,
0x80003d80,0xbd800000,0x8000bd80,0x3d800000,0x3d35bd35,0x3d353d35,0xbd353d35,0xbd35bd35,0x80003d80,0xbd800000,0x8000bd80,0x3d800000,0x3d35bd35,0x3d353d35,0xbd353d35,0xbd35bd35,
0x80003d80,0xbd800000,0x8000bd80,0x3d800000,0x3d35bd35,0x3d353d35,0xbd353d35,0xbd35bd35,0x80003d80,0xbd800000,0x8000bd80,0x3d800000,0x3d35bd35,0x3d353d35,0xbd353d35,0xbd35bd35,
0xbd0e3d55,0xbd7bbc48,0xbc48bd7b,0x3d55bd0e,0x8000bd80,0x3d6dbcc4,0x3d353d35,0xbcc43d6d,0x3d553d0e,0xbc483d7b,0xbd7b3c48,0xbd0ebd55,0xbd800000,0xbcc4bd6d,0x3d35bd35,0x3d6d3cc4,
0x3d0ebd55,0x3d7b3c48,0x3c483d7b,0xbd553d0e,0x80003d80,0xbd6d3cc4,0xbd35bd35,0x3cc4bd6d,0xbd55bd0e,0x3c48bd7b,0x3d7bbc48,0x3d0e3d55,0x3d800000,0x3cc43d6d,0xbd353d35,0xbd6dbcc4,
0x8000bd80,0x3d35bd35,0x3d800000,0x3d353d35,0xbcc43d6d,0xbd6d3cc4,0xbd6dbcc4,0xbcc4bd6d,0x80003d80,0xbd353d35,0xbd800000,0xbd35bd35,0x3cc4bd6d,0x3d6dbcc4,0x3d6d3cc4,0x3cc43d6d,
0x8000bd80,0x3d35bd35,0x3d800000,0x3d353d35,0xbcc43d6d,0xbd6d3cc4,0xbd6dbcc4,0xbcc4bd6d,0x80003d80,0xbd353d35,0xbd800000,0xbd35bd35,0x3cc4bd6d,0x3d6dbcc4,0x3d6d3cc4,0x3cc43d6d,
0xbd7bbc48,0xbd55bd0e,0xbd0ebd55,0xbc48bd7b,0x3d800000,0x3d6d3cc4,0x3d353d35,0x3cc43d6d,0xbc483d7b,0xbd0e3d55,0xbd553d0e,0xbd7b3c48,0x8000bd80,0x3cc4bd6d,0x3d35bd35,0x3d6dbcc4,
0x3d7b3c48,0x3d553d0e,0x3d0e3d55,0x3c483d7b,0xbd800000,0xbd6dbcc4,0xbd35bd35,0xbcc4bd6d,0x3c48bd7b,0x3d0ebd55,0x3d55bd0e,0x3d7bbc48,0x80003d80,0xbcc43d6d,0xbd353d35,0xbd6d3cc4,
0x3d800000,0xbd800000,0x3d800000,0xbd800000,0xbd80,0x3d80,0xbd80,0x3d80,0x3d800000,0xbd800000,0x3d800000,0xbd800000,0xbd80,0x3d80,0xbd80,0x3d80,
0x3d800000,0xbd800000,0x3d800000,0xbd800000,0xbd80,0x3d80,0xbd80,0x3d80,0x3d800000,0xbd800000,0x3d800000,0xbd800000,0xbd80,0x3d80,0xbd80,0x3d80,
0xbc48bd7b,0x3d0e3d55,0xbd55bd0e,0x3d7b3c48,0x3d800000,0xbd6d3cc4,0x3d35bd35,0xbcc43d6d,0xbd7b3c48,0x3d55bd0e,0xbd0e3d55,0x3c48bd7b,0xbd80,0x3cc43d6d,0xbd35bd35,0x3d6d3cc4,
0x3c483d7b,0xbd0ebd55,0x3d553d0e,0xbd7bbc48,0xbd800000,0x3d6dbcc4,0xbd353d35,0x3cc4bd6d,0x3d7bbc48,0xbd553d0e,0x3d0ebd55,0xbc483d7b,0x3d80,0xbcc4bd6d,0x3d353d35,0xbd6dbcc4,
0xbd800000,0x3d35bd35,0x3d80,0xbd35bd35,0x3cc43d6d,0xbd6dbcc4,0x3d6dbcc4,0xbcc43d6d,0x3d800000,0xbd353d35,0xbd80,0x3d353d35,0xbcc4bd6d,0x3d6d3cc4,0xbd6d3cc4,0x3cc4bd6d,
0xbd800000,0x3d35bd35,0x3d80,0xbd35bd35,0x3cc43d6d,0xbd6dbcc4,0x3d6dbcc4,0xbcc43d6d,0x3d800000,0xbd353d35,0xbd80,0x3d353d35,0xbcc4bd6d,0x3d6d3cc4,0xbd6d3cc4,0x3cc4bd6d,
0x3d55bd0e,0x3c483d7b,0xbd7bbc48,0x3d0ebd55,0x3d80,0xbd6dbcc4,0x3d35bd35,0x3cc43d6d,0xbd0ebd55,0x3d7bbc48,0xbc483d7b,0xbd55bd0e,0x3d800000,0xbcc43d6d,0xbd35bd35,0x3d6dbcc4,
0xbd553d0e,0xbc48bd7b,0x3d7b3c48,0xbd0e3d55,0xbd80,0x3d6d3cc4,0xbd353d35,0xbcc4bd6d,0x3d0e3d55,0xbd7b3c48,0x3c48bd7b,0x3d553d0e,0xbd800000,0x3cc4bd6d,0x3d353d35,0xbd6d3cc4,
0x3d800000,0x3d80,0xbd800000,0xbd80,0xbd35bd35,0x3d35bd35,0x3d353d35,0xbd353d35,0x3d800000,0x3d80,0xbd800000,0xbd80,0xbd35bd35,0x3d35bd35,0x3d353d35,0xbd353d35,
0x3d800000,0x3d80,0xbd800000,0xbd80,0xbd35bd35,0x3d35bd35,0x3d353d35,0xbd353d35,0x3d800000,0x3d80,0xbd800000,0xbd80,0xbd35bd35,0x3d35bd35,0x3d353d35,0xbd353d35,
0x3d553d0e,0xbc483d7b,0xbd7b3c48,0xbd0ebd55,0xbd800000,0xbcc4bd6d,0x3d35bd35,0x3d6d3cc4,0x3d0ebd55,0x3d7b3c48,0x3c483d7b,0xbd553d0e,0x3d80,0xbd6d3cc4,0xbd35bd35,0x3cc4bd6d,
0xbd55bd0e,0x3c48bd7b,0x3d7bbc48,0x3d0e3d55,0x3d800000,0x3cc43d6d,0xbd353d35,0xbd6dbcc4,0xbd0e3d55,0xbd7bbc48,0xbc48bd7b,0x3d55bd0e,0xbd80,0x3d6dbcc4,0x3d353d35,0xbcc43d6d,
0xbd800000,0xbd35bd35,0xbd80,0x3d35bd35,0x3d6d3cc4,0x3cc43d6d,0xbcc43d6d,0xbd6d3cc4,0x3d800000,0x3d353d35,0x3d80,0xbd353d35,0xbd6dbcc4,0xbcc4bd6d,0x3cc4bd6d,0x3d6dbcc4,
0xbd800000,0xbd35bd35,0xbd80,0x3d35bd35,0x3d6d3cc4,0x3cc43d6d,0xbcc43d6d,0xbd6d3cc4,0x3d800000,0x3d353d35,0x3d80,0xbd353d35,0xbd6dbcc4,0xbcc4bd6d,0x3cc4bd6d,0x3d6dbcc4,
0xbc483d7b,0xbd0e3d55,0xbd553d0e,0xbd7b3c48,0xbd80,0x3cc4bd6d,0x3d35bd35,0x3d6dbcc4,0x3d7b3c48,0x3d553d0e,0x3d0e3d55,0x3c483d7b,0xbd800000,0xbd6dbcc4,0xbd35bd35,0xbcc4bd6d,
0x3c48bd7b,0x3d0ebd55,0x3d55bd0e,0x3d7bbc48,0x3d80,0xbcc43d6d,0xbd353d35,0xbd6d3cc4,0xbd7bbc48,0xbd55bd0e,0xbd0ebd55,0xbc48bd7b,0x3d800000,0x3d6d3cc4,0x3d353d35,0x3cc43d6d,
0x80003d80,0x80003d80,0x80003d80,0x80003d80,0x8000bd80,0x8000bd80,0x8000bd80,0x8000bd80,0x80003d80,0x80003d80,0x80003d80,0x80003d80,0x8000bd80,0x8000bd80,0x8000bd80,0x8000bd80,
0x80003d80,0x80003d80,0x80003d80,0x80003d80,0x8000bd80,0x8000bd80,0x8000bd80,0x8000bd80,0x80003d80,0x80003d80,0x80003d80,0x80003d80,0x8000bd80,0x8000bd80,0x8000bd80,0x8000bd80,
0xbc48bd7b,0xbd0ebd55,0xbd55bd0e,0xbd7bbc48,0x80003d80,0x3cc43d6d,0x3d353d35,0x3d6d3cc4,0xbd7b3c48,0xbd553d0e,0xbd0e3d55,0xbc483d7b,0x3d800000,0x3d6dbcc4,0x3d35bd35,0x3cc4bd6d,
0x3c483d7b,0x3d0e3d55,0x3d553d0e,0x3d7b3c48,0x8000bd80,0xbcc4bd6d,0xbd35bd35,0xbd6dbcc4,0x3d7bbc48,0x3d55bd0e,0x3d0ebd55,0x3c48bd7b,0xbd800000,0xbd6d3cc4,0xbd353d35,0xbcc43d6d,
0x8000bd80,0xbd35bd35,0xbd800000,0xbd353d35,0x3cc43d6d,0x3d6d3cc4,0x3d6dbcc4,0x3cc4bd6d,0x80003d80,0x3d353d35,0x3d800000,0x3d35bd35,0xbcc4bd6d,0xbd6dbcc4,0xbd6d3cc4,0xbcc43d6d,
0x8000bd80,0xbd35bd35,0xbd800000,0xbd353d35,0x3cc43d6d,0x3d6d3cc4,0x3d6dbcc4,0x3cc4bd6d,0x80003d80,0x3d353d35,0x3d800000,0x3d35bd35,0xbcc4bd6d,0xbd6dbcc4,0xbd6d3cc4,0xbcc43d6d,
0x3d55bd0e,0xbc48bd7b,0xbd7bbc48,0xbd0e3d55,0xbd800000,0xbcc43d6d,0x3d353d35,0x3d6dbcc4,0xbd0ebd55,0xbd7b3c48,0xbc483d7b,0x3d553d0e,0x80003d80,0x3d6d3cc4,0x3d35bd35,0xbcc4bd6d,
0xbd553d0e,0x3c483d7b,0x3d7b3c48,0x3d0ebd55,0x3d800000,0x3cc4bd6d,0xbd35bd35,0xbd6d3cc4,0x3d0e3d55,0x3d7bbc48,0x3c48bd7b,0xbd55bd0e,0x8000bd80,0xbd6dbcc4,0xbd353d35,0x3cc43d6d,
0x80003d80,0x3d800000,0x8000bd80,0xbd800000,0xbd35bd35,0xbd353d35,0x3d353d35,0x3d35bd35,0x80003d80,0x3d800000,0x8000bd80,0xbd800000,0xbd35bd35,0xbd353d35,0x3d353d35,0x3d35bd35,
0x80003d80,0x3d800000,0x8000bd80,0xbd800000,0xbd35bd35,0xbd353d35,0x3d353d35,0x3d35bd35,0x80003d80,0x3d800000,0x8000bd80,0xbd800000,0xbd35bd35,0xbd353d35,0x3d353d35,0x3d35bd35,
0x3d553d0e,0x3c48bd7b,0xbd7b3c48,0x3d0e3d55,0x8000bd80,0xbd6d3cc4,0x3d353d35,0x3cc4bd6d,0x3d0ebd55,0xbd7bbc48,0x3c483d7b,0x3d55bd0e,0xbd800000,0x3cc43d6d,0x3d35bd35,0xbd6dbcc4,
0xbd55bd0e,0xbc483d7b,0x3d7bbc48,0xbd0ebd55,0x80003d80,0x3d6dbcc4,0xbd35bd35,0xbcc43d6d,0xbd0e3d55,0x3d7b3c48,0xbc48bd7b,0xbd553d0e,0x3d800000,0xbcc4bd6d,0xbd353d35,0x3d6d3cc4,
0x8000bd80,0xbd353d35,0x3d800000,0xbd35bd35,0x3d6d3cc4,0xbcc4bd6d,0xbcc43d6d,0x3d6dbcc4,0x80003d80,0x3d35bd35,0xbd800000,0x3d353d35,0xbd6dbcc4,0x3cc43d6d,0x3cc4bd6d,0xbd6d3cc4,
0x8000bd80,0xbd353d35,0x3d800000,0xbd35bd35,0x3d6d3cc4,0xbcc4bd6d,0xbcc43d6d,0x3d6dbcc4,0x80003d80,0x3d35bd35,0xbd800000,0x3d353d35,0xbd6dbcc4,0x3cc43d6d,0x3cc4bd6d,0xbd6d3cc4,
0xbc483d7b,0x3d0ebd55,0xbd553d0e,0x3d7bbc48,0x3d800000,0xbd6dbcc4,0x3d353d35,0xbcc4bd6d,0x3d7b3c48,0xbd55bd0e,0x3d0e3d55,0xbc48bd7b,0x8000bd80,0xbcc43d6d,0x3d35bd35,0xbd6d3cc4,
0x3c48bd7b,0xbd0e3d55,0x3d55bd0e,0xbd7b3c48,0xbd800000,0x3d6d3cc4,0xbd35bd35,0x3cc43d6d,0xbd7bbc48,0x3d553d0e,0xbd0ebd55,0x3c483d7b,0x80003d80,0x3cc4bd6d,0xbd353d35,0x3d6dbcc4,
0x3d800000,0x3d800000,0x3d800000,0x3d800000,0xbd800000,0xbd800000,0xbd800000,0xbd800000,0x3d800000,0x3d800000,0x3d800000,0x3d800000,0xbd800000,0xbd800000,0xbd800000,0xbd800000,
0x3d800000,0x3d800000,0x3d800000,0x3d800000,0xbd800000,0xbd800000,0xbd800000,0xbd800000,0x3d800000,0x3d800000,0x3d800000,0x3d800000,0xbd800000,0xbd800000,0xbd800000,0xbd800000,
0xbd7b3c48,0xbd553d0e,0xbd0e3d55,0xbc483d7b,0x3d800000,0x3d6dbcc4,0x3d35bd35,0x3cc4bd6d,0x3c483d7b,0x3d0e3d55,0x3d553d0e,0x3d7b3c48,0xbd80,0xbcc4bd6d,0xbd35bd35,0xbd6dbcc4,
0x3d7bbc48,0x3d55bd0e,0x3d0ebd55,0x3c48bd7b,0xbd800000,0xbd6d3cc4,0xbd353d35,0xbcc43d6d,0xbc48bd7b,0xbd0ebd55,0xbd55bd0e,0xbd7bbc48,0x3d80,0x3cc43d6d,0x3d353d35,0x3d6d3cc4,
0xbd800000,0xbd353d35,0x3d80,0x3d353d35,0x3d6dbcc4,0x3cc4bd6d,0xbcc4bd6d,0xbd6dbcc4,0x3d800000,0x3d35bd35,0xbd80,0xbd35bd35,0xbd6d3cc4,0xbcc43d6d,0x3cc43d6d,0x3d6d3cc4,
0xbd800000,0xbd353d35,0x3d80,0x3d353d35,0x3d6dbcc4,0x3cc4bd6d,0xbcc4bd6d,0xbd6dbcc4,0x3d800000,0x3d35bd35,0xbd80,0xbd35bd35,0xbd6d3cc4,0xbcc43d6d,0x3cc43d6d,0x3d6d3cc4,
0xbd0ebd55,0xbd7b3c48,0xbc483d7b,0x3d553d0e,0x3d80,0x3d6d3cc4,0x3d35bd35,0xbcc4bd6d,0xbd553d0e,0x3c483d7b,0x3d7b3c48,0x3d0ebd55,0x3d800000,0x3cc4bd6d,0xbd35bd35,0xbd6d3cc4,
0x3d0e3d55,0x3d7bbc48,0x3c48bd7b,0xbd55bd0e,0xbd80,0xbd6dbcc4,0xbd353d35,0x3cc43d6d,0x3d55bd0e,0xbc48bd7b,0xbd7bbc48,0xbd0e3d55,0xbd800000,0xbcc43d6d,0x3d353d35,0x3d6dbcc4,
0x3d800000,0xbd80,0xbd800000,0x3d80,0xbd353d35,0x3d353d35,0x3d35bd35,0xbd35bd35,0x3d800000,0xbd80,0xbd800000,0x3d80,0xbd353d35,0x3d353d35,0x3d35bd35,0xbd35bd35,
0x3d800000,0xbd80,0xbd800000,0x3d80,0xbd353d35,0x3d353d35,0x3d35bd35,0xbd35bd35,0x3d800000,0xbd80,0xbd800000,0x3d80,0xbd353d35,0x3d353d35,0x3d35bd35,0xbd35bd35,
0x3d0ebd55,0xbd7bbc48,0x3c483d7b,0x3d55bd0e,0xbd800000,0x3cc43d6d,0x3d35bd35,0xbd6dbcc4,0xbd55bd0e,0xbc483d7b,0x3d7bbc48,0xbd0ebd55,0x3d80,0x3d6dbcc4,0xbd35bd35,0xbcc43d6d,
0xbd0e3d55,0x3d7b3c48,0xbc48bd7b,0xbd553d0e,0x3d800000,0xbcc4bd6d,0xbd353d35,0x3d6d3cc4,0x3d553d0e,0x3c48bd7b,0xbd7b3c48,0x3d0e3d55,0xbd80,0xbd6d3cc4,0x3d353d35,0x3cc4bd6d,
0xbd800000,0x3d353d35,0xbd80,0xbd353d35,0x3cc4bd6d,0xbd6d3cc4,0x3d6d3cc4,0xbcc4bd6d,0x3d800000,0xbd35bd35,0x3d80,0x3d35bd35,0xbcc43d6d,0x3d6dbcc4,0xbd6dbcc4,0x3cc43d6d,
0xbd800000,0x3d353d35,0xbd80,0xbd353d35,0x3cc4bd6d,0xbd6d3cc4,0x3d6d3cc4,0xbcc4bd6d,0x3d800000,0xbd35bd35,0x3d80,0x3d35bd35,0xbcc43d6d,0x3d6dbcc4,0xbd6dbcc4,0x3cc43d6d,
0x3d7b3c48,0xbd55bd0e,0x3d0e3d55,0xbc48bd7b,0xbd80,0xbcc43d6d,0x3d35bd35,0xbd6d3cc4,0x3c48bd7b,0xbd0e3d55,0x3d55bd0e,0xbd7b3c48,0xbd800000,0x3d6d3cc4,0xbd35bd35,0x3cc43d6d,
0xbd7bbc48,0x3d553d0e,0xbd0ebd55,0x3c483d7b,0x3d80,0x3cc4bd6d,0xbd353d35,0x3d6dbcc4,0xbc483d7b,0x3d0ebd55,0xbd553d0e,0x3d7bbc48,0x3d800000,0xbd6dbcc4,0x3d353d35,0xbcc4bd6d,
0x80003d80,0x8000bd80,0x80003d80,0x8000bd80,0xbd800000,0x3d800000,0xbd800000,0x3d800000,0x80003d80,0x8000bd80,0x80003d80,0x8000bd80,0xbd800000,0x3d800000,0xbd800000,0x3d800000,
0x80003d80,0x8000bd80,0x80003d80,0x8000bd80,0xbd800000,0x3d800000,0xbd800000,0x3d800000,0x80003d80,0x8000bd80,0x80003d80,0x8000bd80,0xbd800000,0x3d800000,0xbd800000,0x3d800000,
0xbd7b3c48,0x3d55bd0e,0xbd0e3d55,0x3c48bd7b,0x80003d80,0xbcc4bd6d,0x3d353d35,0xbd6dbcc4,0x3c483d7b,0xbd0ebd55,0x3d553d0e,0xbd7bbc48,0x3d800000,0xbd6d3cc4,0x3d35bd35,0xbcc43d6d,
0x3d7bbc48,0xbd553d0e,0x3d0ebd55,0xbc483d7b,0x8000bd80,0x3cc43d6d,0xbd35bd35,0x3d6d3cc4,0xbc48bd7b,0x3d0e3d55,0xbd55bd0e,0x3d7b3c48,0xbd800000,0x3d6dbcc4,0xbd353d35,0x3cc4bd6d,
0x8000bd80,0x3d353d35,0xbd800000,0x3d35bd35,0x3d6dbcc4,0xbcc43d6d,0xbcc4bd6d,0x3d6d3cc4,0x80003d80,0xbd35bd35,0x3d800000,0xbd353d35,0xbd6d3cc4,0x3cc4bd6d,0x3cc43d6d,0xbd6dbcc4,
0x8000bd80,0x3d353d35,0xbd800000,0x3d35bd35,0x3d6dbcc4,0xbcc43d6d,0xbcc4bd6d,0x3d6d3cc4,0x80003d80,0xbd35bd35,0x3d800000,0xbd353d35,0xbd6d3cc4,0x3cc4bd6d,0x3cc43d6d,0xbd6dbcc4,
0xbd0ebd55,0x3d7bbc48,0xbc483d7b,0xbd55bd0e,0xbd800000,0x3cc4bd6d,0x3d353d35,0xbd6d3cc4,0xbd553d0e,0xbc48bd7b,0x3d7b3c48,0xbd0e3d55,0x80003d80,0xbd6dbcc4,0x3d35bd35,0x3cc43d6d,
0x3d0e3d55,0xbd7b3c48,0x3c48bd7b,0x3d553d0e,0x3d800000,0xbcc43d6d,0xbd35bd35,0x3d6dbcc4,0x3d55bd0e,0x3c483d7b,0xbd7bbc48,0x3d0ebd55,0x8000bd80,0x3d6d3cc4,0xbd353d35,0xbcc4bd6d,
0x80003d80,0xbd800000,0x8000bd80,0x3d800000,0xbd353d35,0xbd35bd35,0x3d35bd35,0x3d353d35,0x80003d80,0xbd800000,0x8000bd80,0x3d800000,0xbd353d35,0xbd35bd35,0x3d35bd35,0x3d353d35,
0x80003d80,0xbd800000,0x8000bd80,0x3d800000,0xbd353d35,0xbd35bd35,0x3d35bd35,0x3d353d35,0x80003d80,0xbd800000,0x8000bd80,0x3d800000,0xbd353d35,0xbd35bd35,0x3d35bd35,0x3d353d35,
0x3d0ebd55,0x3d7b3c48,0x3c483d7b,0xbd553d0e,0x8000bd80,0x3d6dbcc4,0x3d353d35,0xbcc43d6d,0xbd55bd0e,0x3c48bd7b,0x3d7bbc48,0x3d0e3d55,0xbd800000,0xbcc4bd6d,0x3d35bd35,0x3d6d3cc4,
0xbd0e3d55,0xbd7bbc48,0xbc48bd7b,0x3d55bd0e,0x80003d80,0xbd6d3cc4,0xbd35bd35,0x3cc4bd6d,0x3d553d0e,0xbc483d7b,0xbd7b3c48,0xbd0ebd55,0x3d800000,0x3cc43d6d,0xbd353d35,0xbd6dbcc4,
0x8000bd80,0x3d35bd35,0x3d800000,0x3d353d35,0x3cc4bd6d,0x3d6dbcc4,0x3d6d3cc4,0x3cc43d6d,0x80003d80,0xbd353d35,0xbd800000,0xbd35bd35,0xbcc43d6d,0xbd6d3cc4,0xbd6dbcc4,0xbcc4bd6d,
0x8000bd80,0x3d35bd35,0x3d800000,0x3d353d35,0x3cc4bd6d,0x3d6dbcc4,0x3d6d3cc4,0x3cc43d6d,0x80003d80,0xbd353d35,0xbd800000,0xbd35bd35,0xbcc43d6d,0xbd6d3cc4,0xbd6dbcc4,0xbcc4bd6d,
0x3d7b3c48,0x3d553d0e,0x3d0e3d55,0x3c483d7b,0x3d800000,0x3d6d3cc4,0x3d353d35,0x3cc43d6d,0x3c48bd7b,0x3d0ebd55,0x3d55bd0e,0x3d7bbc48,0x8000bd80,0x3cc4bd6d,0x3d35bd35,0x3d6dbcc4,
0xbd7bbc48,0xbd55bd0e,0xbd0ebd55,0xbc48bd7b,0xbd800000,0xbd6dbcc4,0xbd35bd35,0xbcc4bd6d,0xbc483d7b,0xbd0e3d55,0xbd553d0e,0xbd7b3c48,0x80003d80,0xbcc43d6d,0xbd353d35,0xbd6d3cc4,
0x3d800000,0xbd800000,0x3d800000,0xbd800000,0x3d80,0xbd80,0x3d80,0xbd80,0x3d800000,0xbd800000,0x3d800000,0xbd800000,0x3d80,0xbd80,0x3d80,0xbd80,
0x3d800000,0xbd800000,0x3d800000,0xbd800000,0x3d80,0xbd80,0x3d80,0xbd80,0x3d800000,0xbd800000,0x3d800000,0xbd800000,0x3d80,0xbd80,0x3d80,0xbd80,
0x3c483d7b,0xbd0ebd55,0x3d553d0e,0xbd7bbc48,0x3d800000,0xbd6d3cc4,0x3d35bd35,0xbcc43d6d,0x3d7bbc48,0xbd553d0e,0x3d0ebd55,0xbc483d7b,0xbd80,0x3cc43d6d,0xbd35bd35,0x3d6d3cc4,
0xbc48bd7b,0x3d0e3d55,0xbd55bd0e,0x3d7b3c48,0xbd800000,0x3d6dbcc4,0xbd353d35,0x3cc4bd6d,0xbd7b3c48,0x3d55bd0e,0xbd0e3d55,0x3c48bd7b,0x3d80,0xbcc4bd6d,0x3d353d35,0xbd6dbcc4,
0xbd800000,0x3d35bd35,0x3d80,0xbd35bd35,0xbcc4bd6d,0x3d6d3cc4,0xbd6d3cc4,0x3cc4bd6d,0x3d800000,0xbd353d35,0xbd80,0x3d353d35,0x3cc43d6d,0xbd6dbcc4,0x3d6dbcc4,0xbcc43d6d,
0xbd800000,0x3d35bd35,0x3d80,0xbd35bd35,0xbcc4bd6d,0x3d6d3cc4,0xbd6d3cc4,0x3cc4bd6d,0x3d800000,0xbd353d35,0xbd80,0x3d353d35,0x3cc43d6d,0xbd6dbcc4,0x3d6dbcc4,0xbcc43d6d,
0xbd553d0e,0xbc48bd7b,0x3d7b3c48,0xbd0e3d55,0x3d80,0xbd6dbcc4,0x3d35bd35,0x3cc43d6d,0x3d0e3d55,0xbd7b3c48,0x3c48bd7b,0x3d553d0e,0x3d800000,0xbcc43d6d,0xbd35bd35,0x3d6dbcc4,
0x3d55bd0e,0x3c483d7b,0xbd7bbc48,0x3d0ebd55,0xbd80,0x3d6d3cc4,0xbd353d35,0xbcc4bd6d,0xbd0ebd55,0x3d7bbc48,0xbc483d7b,0xbd55bd0e,0xbd800000,0x3cc4bd6d,0x3d353d35,0xbd6d3cc4,
0x3d800000,0x3d80,0xbd800000,0xbd80,0x3d353d35,0xbd353d35,0xbd35bd35,0x3d35bd35,0x3d800000,0x3d80,0xbd800000,0xbd80,0x3d353d35,0xbd353d35,0xbd35bd35,0x3d35bd35,
0x3d800000,0x3d80,0xbd800000,0xbd80,0x3d353d35,0xbd353d35,0xbd35bd35,0x3d35bd35,0x3d800000,0x3d80,0xbd800000,0xbd80,0x3d353d35,0xbd353d35,0xbd35bd35,0x3d35bd35,
0xbd55bd0e,0x3c48bd7b,0x3d7bbc48,0x3d0e3d55,0xbd800000,0xbcc4bd6d,0x3d35bd35,0x3d6d3cc4,0xbd0e3d55,0xbd7bbc48,0xbc48bd7b,0x3d55bd0e,0x3d80,0xbd6d3cc4,0xbd35bd35,0x3cc4bd6d,
0x3d553d0e,0xbc483d7b,0xbd7b3c48,0xbd0ebd55,0x3d800000,0x3cc43d6d,0xbd353d35,0xbd6dbcc4,0x3d0ebd55,0x3d7b3c48,0x3c483d7b,0xbd553d0e,0xbd80,0x3d6dbcc4,0x3d353d35,0xbcc43d6d,
0xbd800000,0xbd35bd35,0xbd80,0x3d35bd35,0xbd6dbcc4,0xbcc4bd6d,0x3cc4bd6d,0x3d6dbcc4,0x3d800000,0x3d353d35,0x3d80,0xbd353d35,0x3d6d3cc4,0x3cc43d6d,0xbcc43d6d,0xbd6d3cc4,
0xbd800000,0xbd35bd35,0xbd80,0x3d35bd35,0xbd6dbcc4,0xbcc4bd6d,0x3cc4bd6d,0x3d6dbcc4,0x3d800000,0x3d353d35,0x3d80,0xbd353d35,0x3d6d3cc4,0x3cc43d6d,0xbcc43d6d,0xbd6d3cc4,
0x3c48bd7b,0x3d0ebd55,0x3d55bd0e,0x3d7bbc48,0xbd80,0x3cc4bd6d,0x3d35bd35,0x3d6dbcc4,0xbd7bbc48,0xbd55bd0e,0xbd0ebd55,0xbc48bd7b,0xbd800000,0xbd6dbcc4,0xbd35bd35,0xbcc4bd6d,
0xbc483d7b,0xbd0e3d55,0xbd553d0e,0xbd7b3c48,0x3d80,0xbcc43d6d,0xbd353d35,0xbd6d3cc4,0x3d7b3c48,0x3d553d0e,0x3d0e3d55,0x3c483d7b,0x3d800000,0x3d6d3cc4,0x3d353d35,0x3cc43d6d,
0x3f003f00,0xbf003f00,0x3f003f00,0xbf003f00,0x3f003f00,0xbf003f00,0x3f003f00,0xbf003f00,0x3f003f00,0xbf003f00,0x3f003f00,0xbf003f00,0x3f003f00,0xbf003f00,0x3f003f00,0xbf003f00,
0x3eff3f00,0xbd490000,0x3ea23eb5,0xbec6beb5,0x3ef53efb,0xbe15bdc8,0x3e713e8e,0xbee2bed5,0x3ee23eed,0xbe71be44,0x3e153e44,0xbef5beed,0x3ec63ed5,0xbea2be8e,0x3d493dc8,0xbeffbefb,
0x3efb3f00,0xbdc80000,0xbdc80000,0xbefbbf00,0x3ed53eed,0xbe8ebe44,0xbe8ebe44,0xbed5beed,0x3e8e3eb5,0xbed5beb5,0xbed5beb5,0xbe8ebeb5,0x3dc83e44,0xbefbbeed,0xbefbbeed,0xbdc8be44,
0x3ef53f00,0xbe150000,0xbee2beb5,0xbe71beb5,0x3ea23ed5,0xbec6be8e,0xbeffbefb,0x3d49bdc8,0x3d493e44,0xbeffbeed,0xbec6beed,0x3ea23e44,0xbe71bdc8,0xbee2befb,0xbe15be8e,0x3ef53ed5,
0x3eed3f00,0xbe440000,0xbeedbf00,0x3e440000,0x3e443eb5,0xbeedbeb5,0xbe44beb5,0x3eed3eb5,0xbe440000,0xbeedbf00,0x3e440000,0x3eed3f00,0xbeedbeb5,0xbe44beb5,0x3eed3eb5,0x3e443eb5,
0x3ee23f00,0xbe710000,0xbe15beb5,0x3ef53eb5,0x3d493e8e,0xbeffbed5,0x3ea23dc8,0x3ec63efb,0xbec6be44,0xbea2beed,0x3eff3eed,0xbd493e44,0xbef5befb,0x3e15bdc8,0x3e713ed5,0xbee2be8e,
0x3ed53f00,0xbe8e0000,0x3e8e0000,0x3ed53f00,0xbdc83e44,0xbefbbeed,0x3efb3eed,0xbdc83e44,0xbefbbeb5,0xbdc8beb5,0x3dc83eb5,0xbefbbeb5,0xbe8ebeed,0x3ed53e44,0xbed5be44,0xbe8ebeed,
0x3ec63f00,0xbea20000,0x3eff3eb5,0x3d493eb5,0xbe713dc8,0xbee2befb,0x3e153ed5,0xbef5be8e,0xbef5beed,0x3e15be44,0xbee2be44,0xbe71beed,0x3d49be8e,0x3eff3ed5,0xbea2befb,0x3ec63dc8,
0x3eb53f00,0xbeb50000,0x3eb53f00,0xbeb50000,0xbeb50000,0xbeb5bf00,0xbeb50000,0xbeb5bf00,0xbeb5bf00,0x3eb50000,0xbeb5bf00,0x3eb50000,0x3eb50000,0x3eb53f00,0x3eb50000,0x3eb53f00,
0x3ea23f00,0xbec60000,0xbd493eb5,0xbeffbeb5,0xbee2bdc8,0xbe71befb,0xbef5bed5,0x3e15be8e,0xbe15beed,0x3ef53e44,0x3e71be44,0x3ee23eed,0x3eff3e8e,0x3d493ed5,0x3ec63efb,0xbea23dc8,
0x3e8e3f00,0xbed50000,0xbed50000,0xbe8ebf00,0xbefbbe44,0xbdc8beed,0xbdc8beed,0x3efb3e44,0x3dc8beb5,0x3efb3eb5,0x3efb3eb5,0xbdc83eb5,0x3ed53eed,0xbe8e3e44,0xbe8e3e44,0xbed5beed,
0x3e713f00,0xbee20000,0xbef5beb5,0x3e15beb5,0xbeffbe8e,0x3d49bed5,0x3ec6bdc8,0x3ea23efb,0x3ea2be44,0x3ec63eed,0x3d493eed,0xbeffbe44,0x3e153efb,0xbef5bdc8,0xbee2bed5,0x3e71be8e,
0x3e443f00,0xbeed0000,0xbe44bf00,0x3eed0000,0xbeedbeb5,0x3e44beb5,0x3eed3eb5,0xbe443eb5,0x3eed0000,0x3e443f00,0xbeed0000,0xbe44bf00,0xbe443eb5,0xbeedbeb5,0x3e44beb5,0x3eed3eb5,
0x3e153f00,0xbef50000,0x3e71beb5,0x3ee23eb5,0xbec6bed5,0x3ea2be8e,0x3d493efb,0xbeffbdc8,0x3eff3e44,0xbd493eed,0xbea2beed,0x3ec6be44,0xbee23dc8,0xbe71befb,0x3ef53e8e,0xbe153ed5,
0x3dc83f00,0xbefb0000,0x3efb0000,0x3dc83f00,0xbe8ebeed,0x3ed5be44,0xbed53e44,0xbe8ebeed,0x3ed53eb5,0xbe8e3eb5,0x3e8ebeb5,0x3ed53eb5,0xbefbbe44,0x3dc8beed,0xbdc83eed,0xbefbbe44,
0x3d493f00,0xbeff0000,0x3ec63eb5,0xbea23eb5,0xbe15befb,0x3ef5bdc8,0xbee2be8e,0x3e71bed5,0x3e713eed,0xbee23e44,0x3ef53e44,0xbe153eed,0xbea2bed5,0x3ec6be8e,0xbeffbdc8,0x3d49befb,
0x3f00,0xbf000000,0x3f00,0xbf000000,0xbf00,0x3f000000,0xbf00,0x3f000000,0x3f00,0xbf000000,0x3f00,0xbf000000,0xbf00,0x3f000000,0xbf00,0x3f000000,
0xbd493f00,0xbeff0000,0xbec63eb5,0xbea2beb5,0x3e15befb,0x3ef53dc8,0x3ee2be8e,0x3e713ed5,0xbe713eed,0xbee2be44,0xbef53e44,0xbe15beed,0x3ea2bed5,0x3ec63e8e,0x3effbdc8,0x3d493efb,
0xbdc83f00,0xbefb0000,0xbefb0000,0x3dc8bf00,0x3e8ebeed,0x3ed53e44,0x3ed53e44,0xbe8e3eed,0xbed53eb5,0xbe8ebeb5,0xbe8ebeb5,0x3ed5beb5,0x3efbbe44,0x3dc83eed,0x3dc83eed,0xbefb3e44,
0xbe153f00,0xbef50000,0xbe71beb5,0x3ee2beb5,0x3ec6bed5,0x3ea23e8e,0xbd493efb,0xbeff3dc8,0xbeff3e44,0xbd49beed,0x3ea2beed,0x3ec63e44,0x3ee23dc8,0xbe713efb,0xbef53e8e,0xbe15bed5,
0xbe443f00,0xbeed0000,0x3e44bf00,0x3eed0000,0x3eedbeb5,0x3e443eb5,0xbeed3eb5,0xbe44beb5,0xbeed0000,0x3e44bf00,0x3eed0000,0xbe443f00,0x3e443eb5,0xbeed3eb5,0xbe44beb5,0x3eedbeb5,
0xbe713f00,0xbee20000,0x3ef5beb5,0x3e153eb5,0x3effbe8e,0x3d493ed5,0xbec6bdc8,0x3ea2befb,0xbea2be44,0x3ec6beed,0xbd493eed,0xbeff3e44,0xbe153efb,0xbef53dc8,0x3ee2bed5,0x3e713e8e,
0xbe8e3f00,0xbed50000,0x3ed50000,0xbe8e3f00,0x3efbbe44,0xbdc83eed,0x3dc8beed,0x3efbbe44,0xbdc8beb5,0x3efbbeb5,0xbefb3eb5,0xbdc8beb5,0xbed53eed,0xbe8ebe44,0x3e8e3e44,0xbed53eed,
0xbea23f00,0xbec60000,0x3d493eb5,0xbeff3eb5,0x3ee2bdc8,0xbe713efb,0x3ef5bed5,0x3e153e8e,0x3e15beed,0x3ef5be44,0xbe71be44,0x3ee2beed,0xbeff3e8e,0x3d49bed5,0xbec63efb,0xbea2bdc8,
0xbeb53f00,0xbeb50000,0xbeb53f00,0xbeb50000,0x3eb50000,0xbeb53f00,0x3eb50000,0xbeb53f00,0x3eb5bf00,0x3eb50000,0x3eb5bf00,0x3eb50000,0xbeb50000,0x3eb5bf00,0xbeb50000,0x3eb5bf00,
0xbec63f00,0xbea20000,0xbeff3eb5,0x3d49beb5,0x3e713dc8,0xbee23efb,0xbe153ed5,0xbef53e8e,0x3ef5beed,0x3e153e44,0x3ee2be44,0xbe713eed,0xbd49be8e,0x3effbed5,0x3ea2befb,0x3ec6bdc8,
0xbed53f00,0xbe8e0000,0xbe8e0000,0x3ed5bf00,0x3dc83e44,0xbefb3eed,0xbefb3eed,0xbdc8be44,0x3efbbeb5,0xbdc83eb5,0xbdc83eb5,0xbefb3eb5,0x3e8ebeed,0x3ed5be44,0x3ed5be44,0xbe8e3eed,
0xbee23f00,0xbe710000,0x3e15beb5,0x3ef5beb5,0xbd493e8e,0xbeff3ed5,0xbea23dc8,0x3ec6befb,0x3ec6be44,0xbea23eed,0xbeff3eed,0xbd49be44,0x3ef5befb,0x3e153dc8,0xbe713ed5,0xbee23e8e,
0xbeed3f00,0xbe440000,0x3eedbf00,0x3e440000,0xbe443eb5,0xbeed3eb5,0x3e44beb5,0x3eedbeb5,0x3e440000,0xbeed3f00,0xbe440000,0x3eedbf00,0x3eedbeb5,0xbe443eb5,0xbeed3eb5,0x3e44beb5,
0xbef53f00,0xbe150000,0x3ee2beb5,0xbe713eb5,0xbea23ed5,0xbec63e8e,0x3effbefb,0x3d493dc8,0xbd493e44,0xbeff3eed,0x3ec6beed,0x3ea2be44,0x3e71bdc8,0xbee23efb,0x3e15be8e,0x3ef5bed5,
0xbefb3f00,0xbdc80000,0x3dc80000,0xbefb3f00,0xbed53eed,0xbe8e3e44,0x3e8ebe44,0xbed53eed,0xbe8e3eb5,0xbed53eb5,0x3ed5beb5,0xbe8e3eb5,0xbdc83e44,0xbefb3eed,0x3efbbeed,0xbdc83e44,
0xbeff3f00,0xbd490000,0xbea23eb5,0xbec63eb5,0xbef53efb,0xbe153dc8,0xbe713e8e,0xbee23ed5,0xbee23eed,0xbe713e44,0xbe153e44,0xbef53eed,0xbec63ed5,0xbea23e8e,0xbd493dc8,0xbeff3efb,
0x3f003f00,0xbf003f00,0x3f003f00,0xbf003f00,0x3f003f00,0xbf003f00,0x3f003f00,0xbf003f00,0x3f003f00,0xbf003f00,0x3f003f00,0xbf003f00,0x3f003f00,0xbf003f00,0x3f003f00,0xbf003f00,
0xbd490000,0xbeffbf00,0xbec6beb5,0xbea2beb5,0xbe15bdc8,0xbef5befb,0xbee2bed5,0xbe71be8e,0xbe71be44,0xbee2beed,0xbef5beed,0xbe15be44,0xbea2be8e,0xbec6bed5,0xbeffbefb,0xbd49bdc8,
0xbefbbf00,0x3dc80000,0x3dc80000,0x3efb3f00,0xbed5beed,0x3e8e3e44,0x3e8e3e44,0x3ed53eed,0xbe8ebeb5,0x3ed53eb5,0x3ed53eb5,0x3e8e3eb5,0xbdc8be44,0x3efb3eed,0x3efb3eed,0x3dc83e44,
0x3e150000,0x3ef53f00,0x3e713eb5,0xbee2beb5,0x3ec63e8e,0x3ea23ed5,0xbd493dc8,0xbeffbefb,0x3eff3eed,0x3d493e44,0xbea2be44,0xbec6beed,0x3ee23efb,0xbe71bdc8,0xbef5bed5,0xbe15be8e,
0x3eed3f00,0xbe440000,0xbeedbf00,0x3e440000,0x3e443eb5,0xbeedbeb5,0xbe44beb5,0x3eed3eb5,0xbe440000,0xbeedbf00,0x3e440000,0x3eed3f00,0xbeedbeb5,0xbe44beb5,0x3eed3eb5,0x3e443eb5,
0xbe710000,0xbee2bf00,0x3ef53eb5,0x3e153eb5,0xbeffbed5,0xbd49be8e,0x3ec63efb,0xbea2bdc8,0xbea2beed,0x3ec63e44,0xbd493e44,0xbeffbeed,0x3e15bdc8,0x3ef53efb,0xbee2be8e,0xbe71bed5,
0xbed5bf00,0x3e8e0000,0xbe8e0000,0xbed5bf00,0x3dc8be44,0x3efb3eed,0xbefbbeed,0x3dc8be44,0x3efb3eb5,0x3dc83eb5,0xbdc8beb5,0x3efb3eb5,0x3e8e3eed,0xbed5be44,0x3ed53e44,0x3e8e3eed,
0x3ea20000,0x3ec63f00,0xbd49beb5,0x3eff3eb5,0x3ee23efb,0xbe713dc8,0x3ef53e8e,0x3e153ed5,0xbe153e44,0xbef5beed,0x3e713eed,0xbee2be44,0xbeffbed5,0x3d49be8e,0xbec6bdc8,0xbea2befb,
0x3eb53f00,0xbeb50000,0x3eb53f00,0xbeb50000,0xbeb50000,0xbeb5bf00,0xbeb50000,0xbeb5bf00,0xbeb5bf00,0x3eb50000,0xbeb5bf00,0x3eb50000,0x3eb50000,0x3eb53f00,0x3eb50000,0x3eb53f00,
0xbec60000,0xbea2bf00,0xbeffbeb5,0x3d49beb5,0xbe71befb,0x3ee23dc8,0x3e15be8e,0x3ef53ed5,0x3ef53e44,0x3e153eed,0x3ee23eed,0xbe713e44,0x3d493ed5,0xbeffbe8e,0xbea23dc8,0xbec6befb,
0xbe8ebf00,0x3ed50000,0x3ed50000,0x3e8e3f00,0x3efb3e44,0x3dc83eed,0x3dc83eed,0xbefbbe44,0xbdc83eb5,0xbefbbeb5,0xbefbbeb5,0x3dc8beb5,0xbed5beed,0x3e8ebe44,0x3e8ebe44,0x3ed53eed,
0x3ee20000,0x3e713f00,0xbe153eb5,0xbef5beb5,0xbd493ed5,0xbeffbe8e,0xbea2befb,0x3ec6bdc8,0xbec6beed,0x3ea2be44,0x3eff3e44,0x3d493eed,0x3ef53dc8,0x3e153efb,0xbe713e8e,0xbee2bed5,
0x3e443f00,0xbeed0000,0xbe44bf00,0x3eed0000,0xbeedbeb5,0x3e44beb5,0x3eed3eb5,0xbe443eb5,0x3eed0000,0x3e443f00,0xbeed0000,0xbe44bf00,0xbe443eb5,0xbeedbeb5,0x3e44beb5,0x3eed3eb5,
0xbef50000,0xbe15bf00,0x3ee23eb5,0xbe713eb5,0x3ea2be8e,0x3ec63ed5,0xbeffbdc8,0xbd49befb,0xbd493eed,0xbeffbe44,0x3ec6be44,0x3ea23eed,0xbe71befb,0x3ee2bdc8,0xbe153ed5,0xbef5be8e,
0xbdc8bf00,0x3efb0000,0xbefb0000,0xbdc8bf00,0x3e8e3eed,0xbed53e44,0x3ed5be44,0x3e8e3eed,0xbed5beb5,0x3e8ebeb5,0xbe8e3eb5,0xbed5beb5,0x3efb3e44,0xbdc83eed,0x3dc8beed,0x3efb3e44,
0x3eff0000,0x3d493f00,0x3ea2beb5,0x3ec63eb5,0xbef53dc8,0xbe15befb,0xbe713ed5,0xbee2be8e,0x3ee2be44,0x3e713eed,0x3e15beed,0x3ef53e44,0xbec63e8e,0xbea2bed5,0xbd493efb,0xbeffbdc8,
0x3f00,0xbf000000,0x3f00,0xbf000000,0xbf00,0x3f000000,0xbf00,0x3f000000,0x3f00,0xbf000000,0x3f00,0xbf000000,0xbf00,0x3f000000,0xbf00,0x3f000000,
0xbeff0000,0x3d49bf00,0xbea2beb5,0x3ec6beb5,0x3ef53dc8,0xbe153efb,0x3e713ed5,0xbee23e8e,0xbee2be44,0x3e71beed,0xbe15beed,0x3ef5be44,0x3ec63e8e,0xbea23ed5,0x3d493efb,0xbeff3dc8,
0x3dc8bf00,0x3efb0000,0x3efb0000,0xbdc83f00,0xbe8e3eed,0xbed5be44,0xbed5be44,0x3e8ebeed,0x3ed5beb5,0x3e8e3eb5,0x3e8e3eb5,0xbed53eb5,0xbefb3e44,0xbdc8beed,0xbdc8beed,0x3efbbe44,
0x3ef50000,0xbe153f00,0xbee23eb5,0xbe71beb5,0xbea2be8e,0x3ec6bed5,0x3effbdc8,0xbd493efb,0x3d493eed,0xbeff3e44,0xbec6be44,0x3ea2beed,0x3e71befb,0x3ee23dc8,0x3e153ed5,0xbef53e8e,
0xbe443f00,0xbeed0000,0x3e44bf00,0x3eed0000,0x3eedbeb5,0x3e443eb5,0xbeed3eb5,0xbe44beb5,0xbeed0000,0x3e44bf00,0x3eed0000,0xbe443f00,0x3e443eb5,0xbeed3eb5,0xbe44beb5,0x3eedbeb5,
0xbee20000,0x3e71bf00,0x3e153eb5,0xbef53eb5,0x3d493ed5,0xbeff3e8e,0x3ea2befb,0x3ec63dc8,0x3ec6beed,0x3ea23e44,0xbeff3e44,0x3d49beed,0xbef53dc8,0x3e15befb,0x3e713e8e,0xbee23ed5,
0x3e8ebf00,0x3ed50000,0xbed50000,0x3e8ebf00,0xbefb3e44,0x3dc8beed,0xbdc83eed,0xbefb3e44,0x3dc83eb5,0xbefb3eb5,0x3efbbeb5,0x3dc83eb5,0x3ed5beed,0x3e8e3e44,0xbe8ebe44,0x3ed5beed,
0x3ec60000,0xbea23f00,0x3effbeb5,0x3d493eb5,0x3e71befb,0x3ee2bdc8,0xbe15be8e,0x3ef5bed5,0xbef53e44,0x3e15beed,0xbee23eed,0xbe71be44,0xbd493ed5,0xbeff3e8e,0x3ea23dc8,0xbec63efb,
0xbeb53f00,0xbeb50000,0xbeb53f00,0xbeb50000,0x3eb50000,0xbeb53f00,0x3eb50000,0xbeb53f00,0x3eb5bf00,0x3eb50000,0x3eb5bf00,0x3eb50000,0xbeb50000,0x3eb5bf00,0xbeb50000,0x3eb5bf00,
0xbea20000,0x3ec6bf00,0x3d49beb5,0x3effbeb5,0xbee23efb,0xbe71bdc8,0xbef53e8e,0x3e15bed5,0x3e153e44,0xbef53eed,0xbe713eed,0xbee23e44,0x3effbed5,0x3d493e8e,0x3ec6bdc8,0xbea23efb,
0x3ed5bf00,0x3e8e0000,0x3e8e0000,0xbed53f00,0xbdc8be44,0x3efbbeed,0x3efbbeed,0x3dc83e44,0xbefb3eb5,0x3dc8beb5,0x3dc8beb5,0x3efbbeb5,0xbe8e3eed,0xbed53e44,0xbed53e44,0x3e8ebeed,
0x3e710000,0xbee23f00,0xbef53eb5,0x3e15beb5,0x3effbed5,0xbd493e8e,0xbec63efb,0xbea23dc8,0x3ea2beed,0x3ec6be44,0x3d493e44,0xbeff3eed,0xbe15bdc8,0x3ef5befb,0x3ee2be8e,0xbe713ed5,
0xbeed3f00,0xbe440000,0x3eedbf00,0x3e440000,0xbe443eb5,0xbeed3eb5,0x3e44beb5,0x3eedbeb5,0x3e440000,0xbeed3f00,0xbe440000,0x3eedbf00,0x3eedbeb5,0xbe443eb5,0xbeed3eb5,0x3e44beb5,
0xbe150000,0x3ef5bf00,0xbe713eb5,0xbee23eb5,0xbec63e8e,0x3ea2bed5,0x3d493dc8,0xbeff3efb,0xbeff3eed,0x3d49be44,0x3ea2be44,0xbec63eed,0xbee23efb,0xbe713dc8,0x3ef5bed5,0xbe153e8e,
0x3efbbf00,0x3dc80000,0xbdc80000,0x3efbbf00,0x3ed5beed,0x3e8ebe44,0xbe8e3e44,0x3ed5beed,0x3e8ebeb5,0x3ed5beb5,0xbed53eb5,0x3e8ebeb5,0x3dc8be44,0x3efbbeed,0xbefb3eed,0x3dc8be44,
0x3d490000,0xbeff3f00,0x3ec6beb5,0xbea23eb5,0x3e15bdc8,0xbef53efb,0x3ee2bed5,0xbe713e8e,0x3e71be44,0xbee23eed,0x3ef5beed,0xbe153e44,0x3ea2be8e,0xbec63ed5,0x3effbefb,0xbd493dc8,
0x3f003f00,0xbf003f00,0x3f003f00,0xbf003f00,0x3f003f00,0xbf003f00,0x3f003f00,0xbf003f00,0x3f003f00,0xbf003f00,0x3f003f00,0xbf003f00,0x3f003f00,0xbf003f00,0x3f003f00,0xbf003f00,
0xbeffbf00,0x3d490000,0xbea2beb5,0x3ec63eb5,0xbef5befb,0x3e153dc8,0xbe71be8e,0x3ee23ed5,0xbee2beed,0x3e713e44,0xbe15be44,0x3ef53eed,0xbec6bed5,0x3ea23e8e,0xbd49bdc8,0x3eff3efb,
0x3efb3f00,0xbdc80000,0xbdc80000,0xbefbbf00,0x3ed53eed,0xbe8ebe44,0xbe8ebe44,0xbed5beed,0x3e8e3eb5,0xbed5beb5,0xbed5beb5,0xbe8ebeb5,0x3dc83e44,0xbefbbeed,0xbefbbeed,0xbdc8be44,
0xbef5bf00,0x3e150000,0x3ee23eb5,0x3e713eb5,0xbea2bed5,0x3ec63e8e,0x3eff3efb,0xbd493dc8,0xbd49be44,0x3eff3eed,0x3ec63eed,0xbea2be44,0x3e713dc8,0x3ee23efb,0x3e153e8e,0xbef5bed5,
0x3eed3f00,0xbe440000,0xbeedbf00,0x3e440000,0x3e443eb5,0xbeedbeb5,0xbe44beb5,0x3eed3eb5,0xbe440000,0xbeedbf00,0x3e440000,0x3eed3f00,0xbeedbeb5,0xbe44beb5,0x3eed3eb5,0x3e443eb5,
0xbee2bf00,0x3e710000,0x3e153eb5,0xbef5beb5,0xbd49be8e,0x3eff3ed5,0xbea2bdc8,0xbec6befb,0x3ec63e44,0x3ea23eed,0xbeffbeed,0x3d49be44,0x3ef53efb,0xbe153dc8,0xbe71bed5,0x3ee23e8e,
0x3ed53f00,0xbe8e0000,0x3e8e0000,0x3ed53f00,0xbdc83e44,0xbefbbeed,0x3efb3eed,0xbdc83e44,0xbefbbeb5,0xbdc8beb5,0x3dc83eb5,0xbefbbeb5,0xbe8ebeed,0x3ed53e44,0xbed5be44,0xbe8ebeed,
0xbec6bf00,0x3ea20000,0xbeffbeb5,0xbd49beb5,0x3e71bdc8,0x3ee23efb,0xbe15bed5,0x3ef53e8e,0x3ef53eed,0xbe153e44,0x3ee23e44,0x3e713eed,0xbd493e8e,0xbeffbed5,0x3ea23efb,0xbec6bdc8,
0x3eb53f00,0xbeb50000,0x3eb53f00,0xbeb50000,0xbeb50000,0xbeb5bf00,0xbeb50000,0xbeb5bf00,0xbeb5bf00,0x3eb50000,0xbeb5bf00,0x3eb50000,0x3eb50000,0x3eb53f00,0x3eb50000,0x3eb53f00,
0xbea2bf00,0x3ec60000,0x3d49beb5,0x3eff3eb5,0x3ee23dc8,0x3e713efb,0x3ef53ed5,0xbe153e8e,0x3e153eed,0xbef5be44,0xbe713e44,0xbee2beed,0xbeffbe8e,0xbd49bed5,0xbec6befb,0x3ea2bdc8,
0x3e8e3f00,0xbed50000,0xbed50000,0xbe8ebf00,0xbefbbe44,0xbdc8beed,0xbdc8beed,0x3efb3e44,0x3dc8beb5,0x3efb3eb5,0x3efb3eb5,0xbdc83eb5,0x3ed53eed,0xbe8e3e44,0xbe8e3e44,0xbed5beed,
0xbe71bf00,0x3ee20000,0x3ef53eb5,0xbe153eb5,0x3eff3e8e,0xbd493ed5,0xbec63dc8,0xbea2befb,0xbea23e44,0xbec6beed,0xbd49beed,0x3eff3e44,0xbe15befb,0x3ef53dc8,0x3ee23ed5,0xbe713e8e,
0x3e443f00,0xbeed0000,0xbe44bf00,0x3eed0000,0xbeedbeb5,0x3e44beb5,0x3eed3eb5,0xbe443eb5,0x3eed0000,0x3e443f00,0xbeed0000,0xbe44bf00,0xbe443eb5,0xbeedbeb5,0x3e44beb5,0x3eed3eb5,
0xbe15bf00,0x3ef50000,0xbe713eb5,0xbee2beb5,0x3ec63ed5,0xbea23e8e,0xbd49befb,0x3eff3dc8,0xbeffbe44,0x3d49beed,0x3ea23eed,0xbec63e44,0x3ee2bdc8,0x3e713efb,0xbef5be8e,0x3e15bed5,
0x3dc83f00,0xbefb0000,0x3efb0000,0x3dc83f00,0xbe8ebeed,0x3ed5be44,0xbed53e44,0xbe8ebeed,0x3ed53eb5,0xbe8e3eb5,0x3e8ebeb5,0x3ed53eb5,0xbefbbe44,0x3dc8beed,0xbdc83eed,0xbefbbe44,
0xbd49bf00,0x3eff0000,0xbec6beb5,0x3ea2beb5,0x3e153efb,0xbef53dc8,0x3ee23e8e,0xbe713ed5,0xbe71beed,0x3ee2be44,0xbef5be44,0x3e15beed,0x3ea23ed5,0xbec63e8e,0x3eff3dc8,0xbd493efb,
0x3f00,0xbf000000,0x3f00,0xbf000000,0xbf00,0x3f000000,0xbf00,0x3f000000,0x3f00,0xbf000000,0x3f00,0xbf000000,0xbf00,0x3f000000,0xbf00,0x3f000000,
0x3d49bf00,0x3eff0000,0x3ec6beb5,0x3ea23eb5,0xbe153efb,0xbef5bdc8,0xbee23e8e,0xbe71bed5,0x3e71beed,0x3ee23e44,0x3ef5be44,0x3e153eed,0xbea23ed5,0xbec6be8e,0xbeff3dc8,0xbd49befb,
0xbdc83f00,0xbefb0000,0xbefb0000,0x3dc8bf00,0x3e8ebeed,0x3ed53e44,0x3ed53e44,0xbe8e3eed,0xbed53eb5,0xbe8ebeb5,0xbe8ebeb5,0x3ed5beb5,0x3efbbe44,0x3dc83eed,0x3dc83eed,0xbefb3e44,
0x3e15bf00,0x3ef50000,0x3e713eb5,0xbee23eb5,0xbec63ed5,0xbea2be8e,0x3d49befb,0x3effbdc8,0x3effbe44,0x3d493eed,0xbea23eed,0xbec6be44,0xbee2bdc8,0x3e71befb,0x3ef5be8e,0x3e153ed5,
0xbe443f00,0xbeed0000,0x3e44bf00,0x3eed0000,0x3eedbeb5,0x3e443eb5,0xbeed3eb5,0xbe44beb5,0xbeed0000,0x3e44bf00,0x3eed0000,0xbe443f00,0x3e443eb5,0xbeed3eb5,0xbe44beb5,0x3eedbeb5,
0x3e71bf00,0x3ee20000,0xbef53eb5,0xbe15beb5,0xbeff3e8e,0xbd49bed5,0x3ec63dc8,0xbea23efb,0x3ea23e44,0xbec63eed,0x3d49beed,0x3effbe44,0x3e15befb,0x3ef5bdc8,0xbee23ed5,0xbe71be8e,
0xbe8e3f00,0xbed50000,0x3ed50000,0xbe8e3f00,0x3efbbe44,0xbdc83eed,0x3dc8beed,0x3efbbe44,0xbdc8beb5,0x3efbbeb5,0xbefb3eb5,0xbdc8beb5,0xbed53eed,0xbe8ebe44,0x3e8e3e44,0xbed53eed,
0x3ea2bf00,0x3ec60000,0xbd49beb5,0x3effbeb5,0xbee23dc8,0x3e71befb,0xbef53ed5,0xbe15be8e,0xbe153eed,0xbef53e44,0x3e713e44,0xbee23eed,0x3effbe8e,0xbd493ed5,0x3ec6befb,0x3ea23dc8,
0xbeb53f00,0xbeb50000,0xbeb53f00,0xbeb50000,0x3eb50000,0xbeb53f00,0x3eb50000,0xbeb53f00,0x3eb5bf00,0x3eb50000,0x3eb5bf00,0x3eb50000,0xbeb50000,0x3eb5bf00,0xbeb50000,0x3eb5bf00,
0x3ec6bf00,0x3ea20000,0x3effbeb5,0xbd493eb5,0xbe71bdc8,0x3ee2befb,0x3e15bed5,0x3ef5be8e,0xbef53eed,0xbe15be44,0xbee23e44,0x3e71beed,0x3d493e8e,0xbeff3ed5,0xbea23efb,0xbec63dc8,
0xbed53f00,0xbe8e0000,0xbe8e0000,0x3ed5bf00,0x3dc83e44,0xbefb3eed,0xbefb3eed,0xbdc8be44,0x3efbbeb5,0xbdc83eb5,0xbdc83eb5,0xbefb3eb5,0x3e8ebeed,0x3ed5be44,0x3ed5be44,0xbe8e3eed,
0x3ee2bf00,0x3e710000,0xbe153eb5,0xbef53eb5,0x3d49be8e,0x3effbed5,0x3ea2bdc8,0xbec63efb,0xbec63e44,0x3ea2beed,0x3effbeed,0x3d493e44,0xbef53efb,0xbe15bdc8,0x3e71bed5,0x3ee2be8e,
0xbeed3f00,0xbe440000,0x3eedbf00,0x3e440000,0xbe443eb5,0xbeed3eb5,0x3e44beb5,0x3eedbeb5,0x3e440000,0xbeed3f00,0xbe440000,0x3eedbf00,0x3eedbeb5,0xbe443eb5,0xbeed3eb5,0x3e44beb5,
0x3ef5bf00,0x3e150000,0xbee23eb5,0x3e71beb5,0x3ea2bed5,0x3ec6be8e,0xbeff3efb,0xbd49bdc8,0x3d49be44,0x3effbeed,0xbec63eed,0xbea23e44,0xbe713dc8,0x3ee2befb,0xbe153e8e,0xbef53ed5,
0xbefb3f00,0xbdc80000,0x3dc80000,0xbefb3f00,0xbed53eed,0xbe8e3e44,0x3e8ebe44,0xbed53eed,0xbe8e3eb5,0xbed53eb5,0x3ed5beb5,0xbe8e3eb5,0xbdc83e44,0xbefb3eed,0x3efbbeed,0xbdc83e44,
0x3effbf00,0x3d490000,0x3ea2beb5,0x3ec6beb5,0x3ef5befb,0x3e15bdc8,0x3e71be8e,0x3ee2bed5,0x3ee2beed,0x3e71be44,0x3e15be44,0x3ef5beed,0x3ec6bed5,0x3ea2be8e,0x3d49bdc8,0x3effbefb,
0x3f003f00,0xbf003f00,0x3f003f00,0xbf003f00,0x3f003f00,0xbf003f00,0x3f003f00,0xbf003f00,0x3f003f00,0xbf003f00,0x3f003f00,0xbf003f00,0x3f003f00,0xbf003f00,0x3f003f00,0xbf003f00,
0x3d490000,0x3eff3f00,0x3ec63eb5,0x3ea23eb5,0x3e153dc8,0x3ef53efb,0x3ee23ed5,0x3e713e8e,0x3e713e44,0x3ee23eed,0x3ef53eed,0x3e153e44,0x3ea23e8e,0x3ec63ed5,0x3eff3efb,0x3d493dc8,
0xbefbbf00,0x3dc80000,0x3dc80000,0x3efb3f00,0xbed5beed,0x3e8e3e44,0x3e8e3e44,0x3ed53eed,0xbe8ebeb5,0x3ed53eb5,0x3ed53eb5,0x3e8e3eb5,0xbdc8be44,0x3efb3eed,0x3efb3eed,0x3dc83e44,
0xbe150000,0xbef5bf00,0xbe71beb5,0x3ee23eb5,0xbec6be8e,0xbea2bed5,0x3d49bdc8,0x3eff3efb,0xbeffbeed,0xbd49be44,0x3ea23e44,0x3ec63eed,0xbee2befb,0x3e713dc8,0x3ef53ed5,0x3e153e8e,
0x3eed3f00,0xbe440000,0xbeedbf00,0x3e440000,0x3e443eb5,0xbeedbeb5,0xbe44beb5,0x3eed3eb5,0xbe440000,0xbeedbf00,0x3e440000,0x3eed3f00,0xbeedbeb5,0xbe44beb5,0x3eed3eb5,0x3e443eb5,
0x3e710000,0x3ee23f00,0xbef5beb5,0xbe15beb5,0x3eff3ed5,0x3d493e8e,0xbec6befb,0x3ea23dc8,0x3ea23eed,0xbec6be44,0x3d49be44,0x3eff3eed,0xbe153dc8,0xbef5befb,0x3ee23e8e,0x3e713ed5,
0xbed5bf00,0x3e8e0000,0xbe8e0000,0xbed5bf00,0x3dc8be44,0x3efb3eed,0xbefbbeed,0x3dc8be44,0x3efb3eb5,0x3dc83eb5,0xbdc8beb5,0x3efb3eb5,0x3e8e3eed,0xbed5be44,0x3ed53e44,0x3e8e3eed,
0xbea20000,0xbec6bf00,0x3d493eb5,0xbeffbeb5,0xbee2befb,0x3e71bdc8,0xbef5be8e,0xbe15bed5,0x3e15be44,0x3ef53eed,0xbe71beed,0x3ee23e44,0x3eff3ed5,0xbd493e8e,0x3ec63dc8,0x3ea23efb,
0x3eb53f00,0xbeb50000,0x3eb53f00,0xbeb50000,0xbeb50000,0xbeb5bf00,0xbeb50000,0xbeb5bf00,0xbeb5bf00,0x3eb50000,0xbeb5bf00,0x3eb50000,0x3eb50000,0x3eb53f00,0x3eb50000,0x3eb53f00,
0x3ec60000,0x3ea23f00,0x3eff3eb5,0xbd493eb5,0x3e713efb,0xbee2bdc8,0xbe153e8e,0xbef5bed5,0xbef5be44,0xbe15beed,0xbee2beed,0x3e71be44,0xbd49bed5,0x3eff3e8e,0x3ea2bdc8,0x3ec63efb,
0xbe8ebf00,0x3ed50000,0x3ed50000,0x3e8e3f00,0x3efb3e44,0x3dc83eed,0x3dc83eed,0xbefbbe44,0xbdc83eb5,0xbefbbeb5,0xbefbbeb5,0x3dc8beb5,0xbed5beed,0x3e8ebe44,0x3e8ebe44,0x3ed53eed,
0xbee20000,0xbe71bf00,0x3e15beb5,0x3ef53eb5,0x3d49bed5,0x3eff3e8e,0x3ea23efb,0xbec63dc8,0x3ec63eed,0xbea23e44,0xbeffbe44,0xbd49beed,0xbef5bdc8,0xbe15befb,0x3e71be8e,0x3ee23ed5,
0x3e443f00,0xbeed0000,0xbe44bf00,0x3eed0000,0xbeedbeb5,0x3e44beb5,0x3eed3eb5,0xbe443eb5,0x3eed0000,0x3e443f00,0xbeed0000,0xbe44bf00,0xbe443eb5,0xbeedbeb5,0x3e44beb5,0x3eed3eb5,
0x3ef50000,0x3e153f00,0xbee2beb5,0x3e71beb5,0xbea23e8e,0xbec6bed5,0x3eff3dc8,0x3d493efb,0x3d49beed,0x3eff3e44,0xbec63e44,0xbea2beed,0x3e713efb,0xbee23dc8,0x3e15bed5,0x3ef53e8e,
0xbdc8bf00,0x3efb0000,0xbefb0000,0xbdc8bf00,0x3e8e3eed,0xbed53e44,0x3ed5be44,0x3e8e3eed,0xbed5beb5,0x3e8ebeb5,0xbe8e3eb5,0xbed5beb5,0x3efb3e44,0xbdc83eed,0x3dc8beed,0x3efb3e44,
0xbeff0000,0xbd49bf00,0xbea23eb5,0xbec6beb5,0x3ef5bdc8,0x3e153efb,0x3e71bed5,0x3ee23e8e,0xbee23e44,0xbe71beed,0xbe153eed,0xbef5be44,0x3ec6be8e,0x3ea23ed5,0x3d49befb,0x3eff3dc8,
0x3f00,0xbf000000,0x3f00,0xbf000000,0xbf00,0x3f000000,0xbf00,0x3f000000,0x3f00,0xbf000000,0x3f00,0xbf000000,0xbf00,0x3f000000,0xbf00,0x3f000000,
0x3eff0000,0xbd493f00,0x3ea23eb5,0xbec63eb5,0xbef5bdc8,0x3e15befb,0xbe71bed5,0x3ee2be8e,0x3ee23e44,0xbe713eed,0x3e153eed,0xbef53e44,0xbec6be8e,0x3ea2bed5,0xbd49befb,0x3effbdc8,
0x3dc8bf00,0x3efb0000,0x3efb0000,0xbdc83f00,0xbe8e3eed,0xbed5be44,0xbed5be44,0x3e8ebeed,0x3ed5beb5,0x3e8e3eb5,0x3e8e3eb5,0xbed53eb5,0xbefb3e44,0xbdc8beed,0xbdc8beed,0x3efbbe44,
0xbef50000,0x3e15bf00,0x3ee2beb5,0x3e713eb5,0x3ea23e8e,0xbec63ed5,0xbeff3dc8,0x3d49befb,0xbd49beed,0x3effbe44,0x3ec63e44,0xbea23eed,0xbe713efb,0xbee2bdc8,0xbe15bed5,0x3ef5be8e,
0xbe443f00,0xbeed0000,0x3e44bf00,0x3eed0000,0x3eedbeb5,0x3e443eb5,0xbeed3eb5,0xbe44beb5,0xbeed0000,0x3e44bf00,0x3eed0000,0xbe443f00,0x3e443eb5,0xbeed3eb5,0xbe44beb5,0x3eedbeb5,
0x3ee20000,0xbe713f00,0xbe15beb5,0x3ef5beb5,0xbd49bed5,0x3effbe8e,0xbea23efb,0xbec6bdc8,0xbec63eed,0xbea2be44,0x3effbe44,0xbd493eed,0x3ef5bdc8,0xbe153efb,0xbe71be8e,0x3ee2bed5,
0x3e8ebf00,0x3ed50000,0xbed50000,0x3e8ebf00,0xbefb3e44,0x3dc8beed,0xbdc83eed,0xbefb3e44,0x3dc83eb5,0xbefb3eb5,0x3efbbeb5,0x3dc83eb5,0x3ed5beed,0x3e8e3e44,0xbe8ebe44,0x3ed5beed,
0xbec60000,0x3ea2bf00,0xbeff3eb5,0xbd49beb5,0xbe713efb,0xbee23dc8,0x3e153e8e,0xbef53ed5,0x3ef5be44,0xbe153eed,0x3ee2beed,0x3e713e44,0x3d49bed5,0x3effbe8e,0xbea2bdc8,0x3ec6befb,
0xbeb53f00,0xbeb50000,0xbeb53f00,0xbeb50000,0x3eb50000,0xbeb53f00,0x3eb50000,0xbeb53f00,0x3eb5bf00,0x3eb50000,0x3eb5bf00,0x3eb50000,0xbeb50000,0x3eb5bf00,0xbeb50000,0x3eb5bf00,
0x3ea20000,0xbec63f00,0xbd493eb5,0xbeff3eb5,0x3ee2befb,0x3e713dc8,0x3ef5be8e,0xbe153ed5,0xbe15be44,0x3ef5beed,0x3e71beed,0x3ee2be44,0xbeff3ed5,0xbd49be8e,0xbec63dc8,0x3ea2befb,
0x3ed5bf00,0x3e8e0000,0x3e8e0000,0xbed53f00,0xbdc8be44,0x3efbbeed,0x3efbbeed,0x3dc83e44,0xbefb3eb5,0x3dc8beb5,0x3dc8beb5,0x3efbbeb5,0xbe8e3eed,0xbed53e44,0xbed53e44,0x3e8ebeed,
0xbe710000,0x3ee2bf00,0x3ef5beb5,0xbe153eb5,0xbeff3ed5,0x3d49be8e,0x3ec6befb,0x3ea2bdc8,0xbea23eed,0xbec63e44,0xbd49be44,0x3effbeed,0x3e153dc8,0xbef53efb,0xbee23e8e,0x3e71bed5,
0xbeed3f00,0xbe440000,0x3eedbf00,0x3e440000,0xbe443eb5,0xbeed3eb5,0x3e44beb5,0x3eedbeb5,0x3e440000,0xbeed3f00,0xbe440000,0x3eedbf00,0x3eedbeb5,0xbe443eb5,0xbeed3eb5,0x3e44beb5,
0x3e150000,0xbef53f00,0x3e71beb5,0x3ee2beb5,0x3ec6be8e,0xbea23ed5,0xbd49bdc8,0x3effbefb,0x3effbeed,0xbd493e44,0xbea23e44,0x3ec6beed,0x3ee2befb,0x3e71bdc8,0xbef53ed5,0x3e15be8e,
0x3efbbf00,0x3dc80000,0xbdc80000,0x3efbbf00,0x3ed5beed,0x3e8ebe44,0xbe8e3e44,0x3ed5beed,0x3e8ebeb5,0x3ed5beb5,0xbed53eb5,0x3e8ebeb5,0x3dc8be44,0x3efbbeed,0xbefb3eed,0x3dc8be44,
0xbd490000,0x3effbf00,0xbec63eb5,0x3ea2beb5,0xbe153dc8,0x3ef5befb,0xbee23ed5,0x3e71be8e,0xbe713e44,0x3ee2beed,0xbef53eed,0x3e15be44,0xbea23e8e,0x3ec6bed5,0xbeff3efb,0x3d49bdc8,
0x3f800000,0x0,0x3f800000,0x0,0x3f800000,0x0,0x3f800000,0x0,0x3f800000,0x0,0x3f800000,0x0,0x3f800000,0x0,0x3f800000,0x0,
0x3f800000,0x0,0x3f7ffec4,0xbbc90f88,0x3f7ffb11,0xbc490e90,0x3f7ff4e6,0xbc96c9b6,0x3f7fec43,0xbcc90ab0,0x3f7fe129,0xbcfb49ba,0x3f7fd397,0xbd16c32c,0x3f7fc38f,0xbd2fe007,
0x3f800000,0x0,0x3f7ffb11,0xbc490e90,0x3f7fec43,0xbcc90ab0,0x3f7fd397,0xbd16c32c,0x3f7fb10f,0xbd48fb30,0x3f7f84ab,0xbd7b2b74,0x3f7f4e6d,0xbd96a905,0x3f7f0e58,0xbdafb680,
0x3f800000,0x0,0x3f7ff4e6,0xbc96c9b6,0x3f7fd397,0xbd16c32c,0x3f7f9c18,0xbd621469,0x3f7f4e6d,0xbd96a905,0x3f7eea9d,0xbdbc3ac3,0x3f7e70b0,0xbde1bc2e,0x3f7de0b1,0xbe039502,
0x3f800000,0x0,0x3f7fec43,0xbcc90ab0,0x3f7fb10f,0xbd48fb30,0x3f7f4e6d,0xbd96a905,0x3f7ec46d,0xbdc8bd36,0x3f7e1324,0xbdfab273,0x3f7d3aac,0xbe164083,0x3f7c3b28,0xbe2f10a2,
0x3f800000,0x0,0x3f7fe129,0xbcfb49ba,0x3f7f84ab,0xbd7b2b74,0x3f7eea9d,0xbdbc3ac3,0x3f7e1324,0xbdfab273,0x3f7cfe73,0xbe1c76de,0x3f7baccd,0xbe3b6ecf,0x3f7a1e84,0xbe5a3997,
0x3f800000,0x0,0x3f7fd397,0xbd16c32c,0x3f7f4e6d,0xbd96a905,0x3f7e70b0,0xbde1bc2e,0x3f7d3aac,0xbe164083,0x3f7baccd,0xbe3b6ecf,0x3f79c79d,0xbe605c13,0x3f778bc5,0xbe827dc0,
0x3f800000,0x0,0x3f7fc38f,0xbd2fe007,0x3f7f0e58,0xbdafb680,0x3f7de0b1,0xbe039502,0x3f7c3b28,0xbe2f10a2,0x3f7a1e84,0xbe5a3997,0x3f778bc5,0xbe827dc0,0x3f748422,0xbe97a117,
0x3f800000,0x0,0x3f7fb10f,0xbd48fb30,0x3f7ec46d,0xbdc8bd36,0x3f7d3aac,0xbe164083,0x3f7b14be,0xbe47c5c2,0x3f7853f8,0xbe78cfcc,0x3f74fa0b,0xbe94a031,0x3f710908,0xbeac7cd4,
0x3f800000,0x0,0x3f7f9c18,0xbd621469,0x3f7e70b0,0xbde1bc2e,0x3f7c7eb0,0xbe28defc,0x3f79c79d,0xbe605c13,0x3f764d97,0xbe8b9507,0x3f721352,0xbea68f12,0x3f6d1c1d,0xbec1071e,
0x3f800000,0x0,0x3f7f84ab,0xbd7b2b74,0x3f7e1324,0xbdfab273,0x3f7baccd,0xbe3b6ecf,0x3f7853f8,0xbe78cfcc,0x3f740bdd,0xbe9aa086,0x3f6ed89e,0xbeb8442a,0x3f68bf3c,0xbed53641,
0x3f800000,0x0,0x3f7f6ac7,0xbd8a200a,0x3f7dabcc,0xbe09cf86,0x3f7ac516,0xbe4dee60,0x3f76ba07,0xbe888e93,0x3f718f57,0xbea986c4,0x3f6b4b0c,0xbec9b953,0x3f63f473,0xbee900b7,
0x3f800000,0x0,0x3f7f4e6d,0xbd96a905,0x3f7d3aac,0xbe164083,0x3f79c79d,0xbe605c13,0x3f74fa0b,0xbe94a031,0x3f6ed89e,0xbeb8442a,0x3f676bd8,0xbedae880,0x3f5ebe05,0xbefc5d27,
0x3f800000,0x0,0x3f7f2f9d,0xbda3308c,0x3f7cbfc9,0xbe22abb6,0x3f78b47b,0xbe72b651,0x3f731447,0xbea09ae5,0x3f6be858,0xbec6d529,0x3f633c5a,0xbeebcbbb,0x3f591e6a,0xbf07a136,
0x3f800000,0x0,0x3f7f0e58,0xbdafb680,0x3f7c3b28,0xbe2f10a2,0x3f778bc5,0xbe827dc0,0x3f710908,0xbeac7cd4,0x3f68bf3c,0xbed53641,0x3f5ebe05,0xbefc5d27,0x3f531849,0xbf10d3cd,
0x3f800000,0x0,0x3f7eea9d,0xbdbc3ac3,0x3f7baccd,0xbe3b6ecf,0x3f764d97,0xbe8b9507,0x3f6ed89e,0xbeb8442a,0x3f655e0b,0xbee363fa,0x3f59f26a,0xbf064b82,0x3f4cae79,0xbf19c200,
0x3f800000,0x0,0x3f7ec46d,0xbdc8bd36,0x3f7b14be,0xbe47c5c2,0x3f74fa0b,0xbe94a031,0x3f6c835e,0xbec3ef15,0x3f61c598,0xbef15aea,0x3f54db31,0xbf0e39da,0x3f45e403,0xbf226799,
0x3f800000,0x0,0x3f7e9bc9,0xbdd53db9,0x3f7a7302,0xbe541501,0x3f73913f,0xbe9d9e78,0x3f6a09a7,0xbecf7bca,0x3f5df6be,0xbeff17b2,0x3f4f7a1f,0xbf15f6d9,0x3f3ebc1b,0xbf2ac082,
0x3f800000,0x0,0x3f7e70b0,0xbde1bc2e,0x3f79c79d,0xbe605c13,0x3f721352,0xbea68f12,0x3f676bd8,0xbedae880,0x3f59f26a,0xbf064b82,0x3f49d112,0xbf1d7fd1,0x3f373a23,0xbf32c8c9,
0x3f800000,0x0,0x3f7e4323,0xbdee3876,0x3f791298,0xbe6c9a7f,0x3f708066,0xbeaf713a,0x3f64aa59,0xbee63375,0x3f55b993,0xbf0cead0,0x3f43e200,0xbf24d225,0x3f2f61a5,0xbf3a7ca4,
0x3f800000,0x0,0x3f7e1324,0xbdfab273,0x3f7853f8,0xbe78cfcc,0x3f6ed89e,0xbeb8442a,0x3f61c598,0xbef15aea,0x3f514d3d,0xbf13682a,0x3f3daef9,0xbf2beb4a,0x3f273656,0xbf41d870,
0x3f800000,0x0,0x3f7de0b1,0xbe039502,0x3f778bc5,0xbe827dc0,0x3f6d1c1d,0xbec1071e,0x3f5ebe05,0xbefc5d27,0x3f4cae79,0xbf19c200,0x3f373a23,0xbf32c8c9,0x3f1ebc12,0xbf48d8b3,
0x3f800000,0x0,0x3f7dabcc,0xbe09cf86,0x3f76ba07,0xbe888e93,0x3f6b4b0c,0xbec9b953,0x3f5b941a,0xbf039c3d,0x3f47de65,0xbf1ff6cb,0x3f3085bb,0xbf396842,0x3f15f6d9,0xbf4f7a1f,
0x3f800000,0x0,0x3f7d7474,0xbe1008b7,0x3f75dec6,0xbe8e9a22,0x3f696591,0xbed25a09,0x3f584853,0xbf08f59b,0x3f42de29,0xbf26050a,0x3f299415,0xbf3fc767,0x3f0cead0,0xbf55b993,
0x3f800000,0x0,0x3f7d3aac,0xbe164083,0x3f74fa0b,0xbe94a031,0x3f676bd8,0xbedae880,0x3f54db31,0xbf0e39da,0x3f3daef9,0xbf2beb4a,0x3f226799,0xbf45e403,0x3f039c3d,0xbf5b941a,
0x3f800000,0x0,0x3f7cfe73,0xbe1c76de,0x3f740bdd,0xbe9aa086,0x3f655e0b,0xbee363fa,0x3f514d3d,0xbf13682a,0x3f385216,0xbf31a81d,0x3f1b02c6,0xbf4bbbf8,0x3ef41f07,0xbf6106f2,
0x3f800000,0x0,0x3f7cbfc9,0xbe22abb6,0x3f731447,0xbea09ae5,0x3f633c5a,0xbeebcbbb,0x3f4d9f02,0xbf187fc0,0x3f32c8c9,0xbf373a23,0x3f13682a,0xbf514d3d,0x3ee0924f,0xbf660f88,
0x3f800000,0x0,0x3f7c7eb0,0xbe28defc,0x3f721352,0xbea68f12,0x3f6106f2,0xbef41f07,0x3f49d112,0xbf1d7fd1,0x3f2d1469,0xbf3ca003,0x3f0b9a6b,0xbf5695e5,0x3ecc9b8b,0xbf6aab7b,
0x3f800000,0x0,0x3f7c3b28,0xbe2f10a2,0x3f710908,0xbeac7cd4,0x3f5ebe05,0xbefc5d27,0x3f45e403,0xbf226799,0x3f273656,0xbf41d870,0x3f039c3d,0xbf5b941a,0x3eb8442a,0xbf6ed89e,
0x3f800000,0x0,0x3f7bf531,0xbe354098,0x3f6ff573,0xbeb263ef,0x3f5c61c7,0xbf0242b1,0x3f41d870,0xbf273656,0x3f212ff9,0xbf46e22a,0x3ef6e0cb,0xbf604621,0x3ea395c5,0xbf7294f8,
0x3f800000,0x0,0x3f7baccd,0xbe3b6ecf,0x3f6ed89e,0xbeb8442a,0x3f59f26a,0xbf064b82,0x3f3daef9,0xbf2beb4a,0x3f1b02c6,0xbf4bbbf8,0x3ee63375,0xbf64aa59,0x3e8e9a22,0xbf75dec6,
0x3f800000,0x0,0x3f7b61fc,0xbe419b37,0x3f6db293,0xbebe1d4a,0x3f577026,0xbf0a48ad,0x3f396842,0xbf3085bb,0x3f14b039,0xbf5064af,0x3ed53641,0xbf68bf3c,0x3e72b651,0xbf78b47b,
0x3f800000,0x0,0x3f800000,0x0,0x3f800000,0x0,0x3f800000,0x0,0x3f800000,0x0,0x3f800000,0x0,0x3f800000,0x0,0x3f800000,0x0,
0x3f7fb10f,0xbd48fb30,0x3f7f9c18,0xbd621469,0x3f7f84ab,0xbd7b2b74,0x3f7f6ac7,0xbd8a200a,0x3f7f4e6d,0xbd96a905,0x3f7f2f9d,0xbda3308c,0x3f7f0e58,0xbdafb680,0x3f7eea9d,0xbdbc3ac3,
0x3f7ec46d,0xbdc8bd36,0x3f7e70b0,0xbde1bc2e,0x3f7e1324,0xbdfab273,0x3f7dabcc,0xbe09cf86,0x3f7d3aac,0xbe164083,0x3f7cbfc9,0xbe22abb6,0x3f7c3b28,0xbe2f10a2,0x3f7baccd,0xbe3b6ecf,
0x3f7d3aac,0xbe164083,0x3f7c7eb0,0xbe28defc,0x3f7baccd,0xbe3b6ecf,0x3f7ac516,0xbe4dee60,0x3f79c79d,0xbe605c13,0x3f78b47b,0xbe72b651,0x3f778bc5,0xbe827dc0,0x3f764d97,0xbe8b9507,
0x3f7b14be,0xbe47c5c2,0x3f79c79d,0xbe605c13,0x3f7853f8,0xbe78cfcc,0x3f76ba07,0xbe888e93,0x3f74fa0b,0xbe94a031,0x3f731447,0xbea09ae5,0x3f710908,0xbeac7cd4,0x3f6ed89e,0xbeb8442a,
0x3f7853f8,0xbe78cfcc,0x3f764d97,0xbe8b9507,0x3f740bdd,0xbe9aa086,0x3f718f57,0xbea986c4,0x3f6ed89e,0xbeb8442a,0x3f6be858,0xbec6d529,0x3f68bf3c,0xbed53641,0x3f655e0b,0xbee363fa,
0x3f74fa0b,0xbe94a031,0x3f721352,0xbea68f12,0x3f6ed89e,0xbeb8442a,0x3f6b4b0c,0xbec9b953,0x3f676bd8,0xbedae880,0x3f633c5a,0xbeebcbbb,0x3f5ebe05,0xbefc5d27,0x3f59f26a,0xbf064b82,
0x3f710908,0xbeac7cd4,0x3f6d1c1d,0xbec1071e,0x3f68bf3c,0xbed53641,0x3f63f473,0xbee900b7,0x3f5ebe05,0xbefc5d27,0x3f591e6a,0xbf07a136,0x3f531849,0xbf10d3cd,0x3f4cae79,0xbf19c200,
0x3f6c835e,0xbec3ef15,0x3f676bd8,0xbedae880,0x3f61c598,0xbef15aea,0x3f5b941a,0xbf039c3d,0x3f54db31,0xbf0e39da,0x3f4d9f02,0xbf187fc0,0x3f45e403,0xbf226799,0x3f3daef9,0xbf2beb4a,
0x3f676bd8,0xbedae880,0x3f6106f2,0xbef41f07,0x3f59f26a,0xbf064b82,0x3f5233c6,0xbf121eb0,0x3f49d112,0xbf1d7fd1,0x3f40d0da,0xbf286605,0x3f373a23,0xbf32c8c9,0x3f2d1469,0xbf3ca003,
0x3f61c598,0xbef15aea,0x3f59f26a,0xbf064b82,0x3f514d3d,0xbf13682a,0x3f47de65,0xbf1ff6cb,0x3f3daef9,0xbf2beb4a,0x3f32c8c9,0xbf373a23,0x3f273656,0xbf41d870,0x3f1b02c6,0xbf4bbbf8,
0x3f5b941a,0xbf039c3d,0x3f5233c6,0xbf121eb0,0x3f47de65,0xbf1ff6cb,0x3f3ca003,0xbf2d1469,0x3f3085bb,0xbf396842,0x3f239da9,0xbf44e3f5,0x3f15f6d9,0xbf4f7a1f,0x3f07a136,0xbf591e6a,
0x3f54db31,0xbf0e39da,0x3f49d112,0xbf1d7fd1,0x3f3daef9,0xbf2beb4a,0x3f3085bb,0xbf396842,0x3f226799,0xbf45e403,0x3f13682a,0xbf514d3d,0x3f039c3d,0xbf5b941a,0x3ee63375,0xbf64aa59,
0x3f4d9f02,0xbf187fc0,0x3f40d0da,0xbf286605,0x3f32c8c9,0xbf373a23,0x3f239da9,0xbf44e3f5,0x3f13682a,0xbf514d3d,0x3f0242b1,0xbf5c61c7,0x3ee0924f,0xbf660f88,0x3ebb31a0,0xbf6e46be,
0x3f45e403,0xbf226799,0x3f373a23,0xbf32c8c9,0x3f273656,0xbf41d870,0x3f15f6d9,0xbf4f7a1f,0x3f039c3d,0xbf5b941a,0x3ee0924f,0xbf660f88,0x3eb8442a,0xbf6ed89e,0x3e8e9a22,0xbf75dec6,
0x3f3daef9,0xbf2beb4a,0x3f2d1469,0xbf3ca003,0x3f1b02c6,0xbf4bbbf8,0x3f07a136,0xbf591e6a,0x3ee63375,0xbf64aa59,0x3ebb31a0,0xbf6e46be,0x3e8e9a22,0xbf75dec6,0x3e419b37,0xbf7b61fc,
0x3f3504f3,0xbf3504f3,0x3f226799,0xbf45e403,0x3f0e39da,0xbf54db31,0x3ef15aea,0xbf61c598,0x3ec3ef15,0xbf6c835e,0x3e94a031,0xbf74fa0b,0x3e47c5c2,0xbf7b14be,0x3dc8bd36,0xbf7ec46d,
0x3f2beb4a,0xbf3daef9,0x3f173c07,0xbf4e8d90,0x3f00e7e4,0xbf5d2d53,0x3ed25a09,0xbf696591,0x3ea09ae5,0xbf731447,0x3e5a3997,0xbf7a1e84,0x3de1bc2e,0xbf7e70b0,0x3bc90f88,0xbf7ffec4,
0x3f226799,0xbf45e403,0x3f0b9a6b,0xbf5695e5,0x3ee63375,0xbf64aa59,0x3eb263ef,0xbf6ff573,0x3e78cfcc,0xbf7853f8,0x3e09cf86,0xbf7dabcc,0x3cc90ab0,0xbf7fec43,0xbdafb680,0xbf7f0e58,
0x3f187fc0,0xbf4d9f02,0x3eff17b2,0xbf5df6be,0x3ec9b953,0xbf6b4b0c,0x3e919ddd,0xbf756d97,0x3e2f10a2,0xbf7c3b28,0x3d621469,0xbf7f9c18,0xbd7b2b74,0xbf7f84ab,0xbe354098,0xbf7bf531,
0x3f0e39da,0xbf54db31,0x3ee63375,0xbf64aa59,0x3eac7cd4,0xbf710908,0x3e605c13,0xbf79c79d,0x3dc8bd36,0xbf7ec46d,0xbcc90ab0,0xbf7fec43,0xbe164083,0xbf7d3aac,0xbe888e93,0xbf76ba07,
0x3f039c3d,0xbf5b941a,0x3ecc9b8b,0xbf6aab7b,0x3e8e9a22,0xbf75dec6,0x3e1c76de,0xbf7cfe73,0x3cc90ab0,0xbf7fec43,0xbdd53db9,0xbf7e9bc9,0xbe6c9a7f,0xbf791298,0xbeb554ec,0xbf6f6830,
0x3ef15aea,0xbf61c598,0x3eb263ef,0xbf6ff573,0x3e605c13,0xbf79c79d,0x3dafb680,0xbf7f0e58,0xbd48fb30,0xbf7fb10f,0xbe3b6ecf,0xbf7baccd,0xbea09ae5,0xbf731447,0xbee0924f,0xbf660f88,
0x3edae880,0xbf676bd8,0x3e97a117,0xbf748422,0x3e22abb6,0xbf7cbfc9,0x3c96c9b6,0xbf7ff4e6,0xbdfab273,0xbf7e1324,0xbe8586ce,0xbf772417,0xbec9b953,0xbf6b4b0c,0xbf04f484,0xbf5ac450,
0x3ec3ef15,0xbf6c835e,0x3e78cfcc,0xbf7853f8,0x3dc8bd36,0xbf7ec46d,0xbd48fb30,0xbf7fb10f,0xbe47c5c2,0xbf7b14be,0xbeac7cd4,0xbf710908,0xbef15aea,0xbf61c598,0xbf187fc0,0xbf4d9f02,
0x3eac7cd4,0xbf710908,0x3e419b37,0xbf7b61fc,0x3d16c32c,0xbf7fd397,0xbdee3876,0xbf7e4323,0xbe888e93,0xbf76ba07,0xbed25a09,0xbf696591,0xbf0b9a6b,0xbf5695e5,0xbf2ac082,0xbf3ebc1b,
0x3e94a031,0xbf74fa0b,0x3e09cf86,0xbf7dabcc,0xbcc90ab0,0xbf7fec43,0xbe3b6ecf,0xbf7baccd,0xbeac7cd4,0xbf710908,0xbef6e0cb,0xbf604621,0xbf1d7fd1,0xbf49d112,0xbf3b8f3b,0xbf2e3bde,
0x3e78cfcc,0xbf7853f8,0x3da3308c,0xbf7f2f9d,0xbdafb680,0xbf7f0e58,0xbe7ee6e1,0xbf77f110,0xbecf7bca,0xbf6a09a7,0xbf0cead0,0xbf55b993,0xbf2e3bde,0xbf3b8f3b,0xbf4ac77f,0xbf1c420c,
0x3e47c5c2,0xbf7b14be,0x3cc90ab0,0xbf7fec43,0xbe164083,0xbf7d3aac,0xbea09ae5,0xbf731447,0xbef15aea,0xbf61c598,0xbf1d7fd1,0xbf49d112,0xbf3daef9,0xbf2beb4a,0xbf584853,0xbf08f59b,
0x3e164083,0xbf7d3aac,0xbcfb49ba,0xbf7fe129,0xbe541501,0xbf7a7302,0xbec1071e,0xbf6d1c1d,0xbf08f59b,0xbf584853,0xbf2d1469,0xbf3ca003,0xbf4bbbf8,0xbf1b02c6,0xbf63f473,0xbee900b7,
0x3dc8bd36,0xbf7ec46d,0xbdafb680,0xbf7f0e58,0xbe888e93,0xbf76ba07,0xbee0924f,0xbf660f88,0xbf187fc0,0xbf4d9f02,0xbf3b8f3b,0xbf2e3bde,0xbf584853,0xbf08f59b,0xbf6db293,0xbebe1d4a,
0x3d48fb30,0xbf7fb10f,0xbe1008b7,0xbf7d7474,0xbea68f12,0xbf721352,0xbeff17b2,0xbf5df6be,0xbf273656,0xbf41d870,0xbf48d8b3,0xbf1ebc12,0xbf633c5a,0xbeebcbbb,0xbf756d97,0xbe919ddd,
0x3f800000,0x0,0x3f800000,0x0,0x3f800000,0x0,0x3f800000,0x0,0x3f800000,0x0,0x3f800000,0x0,0x3f800000,0x0,0x3f800000,0x0,
0x3f7ec46d,0xbdc8bd36,0x3f7e9bc9,0xbdd53db9,0x3f7e70b0,0xbde1bc2e,0x3f7e4323,0xbdee3876,0x3f7e1324,0xbdfab273,0x3f7de0b1,0xbe039502,0x3f7dabcc,0xbe09cf86,0x3f7d7474,0xbe1008b7,
0x3f7b14be,0xbe47c5c2,0x3f7a7302,0xbe541501,0x3f79c79d,0xbe605c13,0x3f791298,0xbe6c9a7f,0x3f7853f8,0xbe78cfcc,0x3f778bc5,0xbe827dc0,0x3f76ba07,0xbe888e93,0x3f75dec6,0xbe8e9a22,
0x3f74fa0b,0xbe94a031,0x3f73913f,0xbe9d9e78,0x3f721352,0xbea68f12,0x3f708066,0xbeaf713a,0x3f6ed89e,0xbeb8442a,0x3f6d1c1d,0xbec1071e,0x3f6b4b0c,0xbec9b953,0x3f696591,0xbed25a09,
0x3f6c835e,0xbec3ef15,0x3f6a09a7,0xbecf7bca,0x3f676bd8,0xbedae880,0x3f64aa59,0xbee63375,0x3f61c598,0xbef15aea,0x3f5ebe05,0xbefc5d27,0x3f5b941a,0xbf039c3d,0x3f584853,0xbf08f59b,
0x3f61c598,0xbef15aea,0x3f5df6be,0xbeff17b2,0x3f59f26a,0xbf064b82,0x3f55b993,0xbf0cead0,0x3f514d3d,0xbf13682a,0x3f4cae79,0xbf19c200,0x3f47de65,0xbf1ff6cb,0x3f42de29,0xbf26050a,
0x3f54db31,0xbf0e39da,0x3f4f7a1f,0xbf15f6d9,0x3f49d112,0xbf1d7fd1,0x3f43e200,0xbf24d225,0x3f3daef9,0xbf2beb4a,0x3f373a23,0xbf32c8c9,0x3f3085bb,0xbf396842,0x3f299415,0xbf3fc767,
0x3f45e403,0xbf226799,0x3f3ebc1b,0xbf2ac082,0x3f373a23,0xbf32c8c9,0x3f2f61a5,0xbf3a7ca4,0x3f273656,0xbf41d870,0x3f1ebc12,0xbf48d8b3,0x3f15f6d9,0xbf4f7a1f,0x3f0cead0,0xbf55b993,
0x3f3504f3,0xbf3504f3,0x3f2beb4a,0xbf3daef9,0x3f226799,0xbf45e403,0x3f187fc0,0xbf4d9f02,0x3f0e39da,0xbf54db31,0x3f039c3d,0xbf5b941a,0x3ef15aea,0xbf61c598,0x3edae880,0xbf676bd8,
0x3f226799,0xbf45e403,0x3f173c07,0xbf4e8d90,0x3f0b9a6b,0xbf5695e5,0x3eff17b2,0xbf5df6be,0x3ee63375,0xbf64aa59,0x3ecc9b8b,0xbf6aab7b,0x3eb263ef,0xbf6ff573,0x3e97a117,0xbf748422,
0x3f0e39da,0xbf54db31,0x3f00e7e4,0xbf5d2d53,0x3ee63375,0xbf64aa59,0x3ec9b953,0xbf6b4b0c,0x3eac7cd4,0xbf710908,0x3e8e9a22,0xbf75dec6,0x3e605c13,0xbf79c79d,0x3e22abb6,0xbf7cbfc9,
0x3ef15aea,0xbf61c598,0x3ed25a09,0xbf696591,0x3eb263ef,0xbf6ff573,0x3e919ddd,0xbf756d97,0x3e605c13,0xbf79c79d,0x3e1c76de,0xbf7cfe73,0x3dafb680,0xbf7f0e58,0x3c96c9b6,0xbf7ff4e6,
0x3ec3ef15,0xbf6c835e,0x3ea09ae5,0xbf731447,0x3e78cfcc,0xbf7853f8,0x3e2f10a2,0xbf7c3b28,0x3dc8bd36,0xbf7ec46d,0x3cc90ab0,0xbf7fec43,0xbd48fb30,0xbf7fb10f,0xbdfab273,0xbf7e1324,
0x3e94a031,0xbf74fa0b,0x3e5a3997,0xbf7a1e84,0x3e09cf86,0xbf7dabcc,0x3d621469,0xbf7f9c18,0xbcc90ab0,0xbf7fec43,0xbdd53db9,0xbf7e9bc9,0xbe3b6ecf,0xbf7baccd,0xbe8586ce,0xbf772417,
0x3e47c5c2,0xbf7b14be,0x3de1bc2e,0xbf7e70b0,0x3cc90ab0,0xbf7fec43,0xbd7b2b74,0xbf7f84ab,0xbe164083,0xbf7d3aac,0xbe6c9a7f,0xbf791298,0xbea09ae5,0xbf731447,0xbec9b953,0xbf6b4b0c,
0x3dc8bd36,0xbf7ec46d,0x3bc90f88,0xbf7ffec4,0xbdafb680,0xbf7f0e58,0xbe354098,0xbf7bf531,0xbe888e93,0xbf76ba07,0xbeb554ec,0xbf6f6830,0xbee0924f,0xbf660f88,0xbf04f484,0xbf5ac450,
0x0,0xbf800000,0xbdc8bd36,0xbf7ec46d,0xbe47c5c2,0xbf7b14be,0xbe94a031,0xbf74fa0b,0xbec3ef15,0xbf6c835e,0xbef15aea,0xbf61c598,0xbf0e39da,0xbf54db31,0xbf226799,0xbf45e403,
0xbdc8bd36,0xbf7ec46d,0xbe4dee60,0xbf7ac516,0xbe9aa086,0xbf740bdd,0xbecc9b8b,0xbf6aab7b,0xbefc5d27,0xbf5ebe05,0xbf14b039,0xbf5064af,0xbf299415,0xbf3fc767,0xbf3ca003,0xbf2d1469,
0xbe47c5c2,0xbf7b14be,0xbe9aa086,0xbf740bdd,0xbecf7bca,0xbf6a09a7,0xbf00e7e4,0xbf5d2d53,0xbf187fc0,0xbf4d9f02,0xbf2e3bde,0xbf3b8f3b,0xbf41d870,0xbf273656,0xbf531849,0xbf10d3cd,
0xbe94a031,0xbf74fa0b,0xbecc9b8b,0xbf6aab7b,0xbf00e7e4,0xbf5d2d53,0xbf19c200,0xbf4cae79,0xbf3085bb,0xbf396842,0xbf44e3f5,0xbf239da9,0xbf5695e5,0xbf0b9a6b,0xbf655e0b,0xbee363fa,
0xbec3ef15,0xbf6c835e,0xbefc5d27,0xbf5ebe05,0xbf187fc0,0xbf4d9f02,0xbf3085bb,0xbf396842,0xbf45e403,0xbf226799,0xbf584853,0xbf08f59b,0xbf676bd8,0xbedae880,0xbf731447,0xbea09ae5,
0xbef15aea,0xbf61c598,0xbf14b039,0xbf5064af,0xbf2e3bde,0xbf3b8f3b,0xbf44e3f5,0xbf239da9,0xbf584853,0xbf08f59b,0xbf6816a8,0xbed8106b,0xbf740bdd,0xbe9aa086,0xbf7bf531,0xbe354098,
0xbf0e39da,0xbf54db31,0xbf299415,0xbf3fc767,0xbf41d870,0xbf273656,0xbf5695e5,0xbf0b9a6b,0xbf676bd8,0xbedae880,0xbf740bdd,0xbe9aa086,0xbf7c3b28,0xbe2f10a2,0xbf7fd397,0xbd16c32c,
0xbf226799,0xbf45e403,0xbf3ca003,0xbf2d1469,0xbf531849,0xbf10d3cd,0xbf655e0b,0xbee363fa,0xbf731447,0xbea09ae5,0xbf7bf531,0xbe354098,0xbf7fd397,0xbd16c32c,0xbf7e9bc9,0x3dd53db9,
0xbf3504f3,0xbf3504f3,0xbf4d9f02,0xbf187fc0,0xbf61c598,0xbef15aea,0xbf710908,0xbeac7cd4,0xbf7b14be,0xbe47c5c2,0xbf7fb10f,0xbd48fb30,0xbf7ec46d,0x3dc8bd36,0xbf7853f8,0x3e78cfcc,
0xbf45e403,0xbf226799,0xbf5c61c7,0xbf0242b1,0xbf6db293,0xbebe1d4a,0xbf796e4e,0xbe667c66,0xbf7f4e6d,0xbd96a905,0xbf7f2f9d,0x3da3308c,0xbf791298,0x3e6c9a7f,0xbf6d1c1d,0x3ec1071e,
0xbf54db31,0xbf0e39da,0xbf68bf3c,0xbed53641,0xbf76ba07,0xbe888e93,0xbf7e70b0,0xbde1bc2e,0xbf7fb10f,0x3d48fb30,0xbf7a7302,0x3e541501,0xbf6ed89e,0x3eb8442a,0xbf5d2d53,0x3f00e7e4,
0xbf61c598,0xbef15aea,0xbf7294f8,0xbea395c5,0xbf7cbfc9,0xbe22abb6,0xbf7ffec4,0x3bc90f88,0xbf7c3b28,0x3e2f10a2,0xbf718f57,0x3ea986c4,0xbf604621,0x3ef6e0cb,0xbf48d8b3,0x3f1ebc12,
0xbf6c835e,0xbec3ef15,0xbf79c79d,0xbe605c13,0xbf7fb10f,0xbd48fb30,0xbf7e1324,0x3dfab273,0xbf74fa0b,0x3e94a031,0xbf64aa59,0x3ee63375,0xbf4d9f02,0x3f187fc0,0xbf3085bb,0x3f396842,
0xbf74fa0b,0xbe94a031,0xbf7e4323,0xbdee3876,0xbf7f84ab,0x3d7b2b74,0xbf78b47b,0x3e72b651,0xbf6a09a7,0x3ecf7bca,0xbf53fac3,0x3f0f8784,0xbf373a23,0x3f32c8c9,0xbf14b039,0x3f5064af,
0xbf7b14be,0xbe47c5c2,0xbf7ffb11,0xbc490e90,0xbf7c3b28,0x3e2f10a2,0xbf6ff573,0x3eb263ef,0xbf5b941a,0x3f039c3d,0xbf3fc767,0x3f299415,0xbf1d7fd1,0x3f49d112,0xbeebcbbb,0x3f633c5a,
0xbf7ec46d,0xbdc8bd36,0xbf7eea9d,0x3dbc3ac3,0xbf75dec6,0x3e8e9a22,0xbf63f473,0x3ee900b7,0xbf49d112,0x3f1d7fd1,0xbf286605,0x3f40d0da,0xbf00e7e4,0x3f5d2d53,0xbea986c4,0x3f718f57,
0x3f800000,0x0,0x3f800000,0x0,0x3f800000,0x0,0x3f800000,0x0,0x3f800000,0x0,0x3f800000,0x0,0x3f800000,0x0,0x3f800000,0x0,
0x3f7d3aac,0xbe164083,0x3f7cfe73,0xbe1c76de,0x3f7cbfc9,0xbe22abb6,0x3f7c7eb0,0xbe28defc,0x3f7c3b28,0xbe2f10a2,0x3f7bf531,0xbe354098,0x3f7baccd,0xbe3b6ecf,0x3f7b61fc,0xbe419b37,
0x3f74fa0b,0xbe94a031,0x3f740bdd,0xbe9aa086,0x3f731447,0xbea09ae5,0x3f721352,0xbea68f12,0x3f710908,0xbeac7cd4,0x3f6ff573,0xbeb263ef,0x3f6ed89e,0xbeb8442a,0x3f6db293,0xbebe1d4a,
0x3f676bd8,0xbedae880,0x3f655e0b,0xbee363fa,0x3f633c5a,0xbeebcbbb,0x3f6106f2,0xbef41f07,0x3f5ebe05,0xbefc5d27,0x3f5c61c7,0xbf0242b1,0x3f59f26a,0xbf064b82,0x3f577026,0xbf0a48ad,
0x3f54db31,0xbf0e39da,0x3f514d3d,0xbf13682a,0x3f4d9f02,0xbf187fc0,0x3f49d112,0xbf1d7fd1,0x3f45e403,0xbf226799,0x3f41d870,0xbf273656,0x3f3daef9,0xbf2beb4a,0x3f396842,0xbf3085bb,
0x3f3daef9,0xbf2beb4a,0x3f385216,0xbf31a81d,0x3f32c8c9,0xbf373a23,0x3f2d1469,0xbf3ca003,0x3f273656,0xbf41d870,0x3f212ff9,0xbf46e22a,0x3f1b02c6,0xbf4bbbf8,0x3f14b039,0xbf5064af,
0x3f226799,0xbf45e403,0x3f1b02c6,0xbf4bbbf8,0x3f13682a,0xbf514d3d,0x3f0b9a6b,0xbf5695e5,0x3f039c3d,0xbf5b941a,0x3ef6e0cb,0xbf604621,0x3ee63375,0xbf64aa59,0x3ed53641,0xbf68bf3c,
0x3f039c3d,0xbf5b941a,0x3ef41f07,0xbf6106f2,0x3ee0924f,0xbf660f88,0x3ecc9b8b,0xbf6aab7b,0x3eb8442a,0xbf6ed89e,0x3ea395c5,0xbf7294f8,0x3e8e9a22,0xbf75dec6,0x3e72b651,0xbf78b47b,
0x3ec3ef15,0xbf6c835e,0x3eac7cd4,0xbf710908,0x3e94a031,0xbf74fa0b,0x3e78cfcc,0xbf7853f8,0x3e47c5c2,0xbf7b14be,0x3e164083,0xbf7d3aac,0x3dc8bd36,0xbf7ec46d,0x3d48fb30,0xbf7fb10f,
0x3e78cfcc,0xbf7853f8,0x3e419b37,0xbf7b61fc,0x3e09cf86,0xbf7dabcc,0x3da3308c,0xbf7f2f9d,0x3cc90ab0,0xbf7fec43,0xbcfb49ba,0xbf7fe129,0xbdafb680,0xbf7f0e58,0xbe1008b7,0xbf7d7474,
0x3dc8bd36,0xbf7ec46d,0x3d16c32c,0xbf7fd397,0xbcc90ab0,0xbf7fec43,0xbdafb680,0xbf7f0e58,0xbe164083,0xbf7d3aac,0xbe541501,0xbf7a7302,0xbe888e93,0xbf76ba07,0xbea68f12,0xbf721352,
0xbd48fb30,0xbf7fb10f,0xbdee3876,0xbf7e4323,0xbe3b6ecf,0xbf7baccd,0xbe7ee6e1,0xbf77f110,0xbea09ae5,0xbf731447,0xbec1071e,0xbf6d1c1d,0xbee0924f,0xbf660f88,0xbeff17b2,0xbf5df6be,
0xbe47c5c2,0xbf7b14be,0xbe888e93,0xbf76ba07,0xbeac7cd4,0xbf710908,0xbecf7bca,0xbf6a09a7,0xbef15aea,0xbf61c598,0xbf08f59b,0xbf584853,0xbf187fc0,0xbf4d9f02,0xbf273656,0xbf41d870,
0xbeac7cd4,0xbf710908,0xbed25a09,0xbf696591,0xbef6e0cb,0xbf604621,0xbf0cead0,0xbf55b993,0xbf1d7fd1,0xbf49d112,0xbf2d1469,0xbf3ca003,0xbf3b8f3b,0xbf2e3bde,0xbf48d8b3,0xbf1ebc12,
0xbef15aea,0xbf61c598,0xbf0b9a6b,0xbf5695e5,0xbf1d7fd1,0xbf49d112,0xbf2e3bde,0xbf3b8f3b,0xbf3daef9,0xbf2beb4a,0xbf4bbbf8,0xbf1b02c6,0xbf584853,0xbf08f59b,0xbf633c5a,0xbeebcbbb,
0xbf187fc0,0xbf4d9f02,0xbf2ac082,0xbf3ebc1b,0xbf3b8f3b,0xbf2e3bde,0xbf4ac77f,0xbf1c420c,0xbf584853,0xbf08f59b,0xbf63f473,0xbee900b7,0xbf6db293,0xbebe1d4a,0xbf756d97,0xbe919ddd,
0xbf3504f3,0xbf3504f3,0xbf45e403,0xbf226799,0xbf54db31,0xbf0e39da,0xbf61c598,0xbef15aea,0xbf6c835e,0xbec3ef15,0xbf74fa0b,0xbe94a031,0xbf7b14be,0xbe47c5c2,0xbf7ec46d,0xbdc8bd36,
0xbf4d9f02,0xbf187fc0,0xbf5c61c7,0xbf0242b1,0xbf68bf3c,0xbed53641,0xbf7294f8,0xbea395c5,0xbf79c79d,0xbe605c13,0xbf7e4323,0xbdee3876,0xbf7ffb11,0xbc490e90,0xbf7eea9d,0x3dbc3ac3,
0xbf61c598,0xbef15aea,0xbf6db293,0xbebe1d4a,0xbf76ba07,0xbe888e93,0xbf7cbfc9,0xbe22abb6,0xbf7fb10f,0xbd48fb30,0xbf7f84ab,0x3d7b2b74,0xbf7c3b28,0x3e2f10a2,0xbf75dec6,0x3e8e9a22,
0xbf710908,0xbeac7cd4,0xbf796e4e,0xbe667c66,0xbf7e70b0,0xbde1bc2e,0xbf7ffec4,0x3bc90f88,0xbf7e1324,0x3dfab273,0xbf78b47b,0x3e72b651,0xbf6ff573,0x3eb263ef,0xbf63f473,0x3ee900b7,
0xbf7b14be,0xbe47c5c2,0xbf7f4e6d,0xbd96a905,0xbf7fb10f,0x3d48fb30,0xbf7c3b28,0x3e2f10a2,0xbf74fa0b,0x3e94a031,0xbf6a09a7,0x3ecf7bca,0xbf5b941a,0x3f039c3d,0xbf49d112,0x3f1d7fd1,
0xbf7fb10f,0xbd48fb30,0xbf7f2f9d,0x3da3308c,0xbf7a7302,0x3e541501,0xbf718f57,0x3ea986c4,0xbf64aa59,0x3ee63375,0xbf53fac3,0x3f0f8784,0xbf3fc767,0x3f299415,0xbf286605,0x3f40d0da,
0xbf7ec46d,0x3dc8bd36,0xbf791298,0x3e6c9a7f,0xbf6ed89e,0x3eb8442a,0xbf604621,0x3ef6e0cb,0xbf4d9f02,0x3f187fc0,0xbf373a23,0x3f32c8c9,0xbf1d7fd1,0x3f49d112,0xbf00e7e4,0x3f5d2d53,
0xbf7853f8,0x3e78cfcc,0xbf6d1c1d,0x3ec1071e,0xbf5d2d53,0x3f00e7e4,0xbf48d8b3,0x3f1ebc12,0xbf3085bb,0x3f396842,0xbf14b039,0x3f5064af,0xbeebcbbb,0x3f633c5a,0xbea986c4,0x3f718f57,
0xbf6c835e,0x3ec3ef15,0xbf5b941a,0x3f039c3d,0xbf45e403,0x3f226799,0xbf2beb4a,0x3f3daef9,0xbf0e39da,0x3f54db31,0xbedae880,0x3f676bd8,0xbe94a031,0x3f74fa0b,0xbe164083,0x3f7d3aac,
0xbf5b941a,0x3f039c3d,0xbf44e3f5,0x3f239da9,0xbf299415,0x3f3fc767,0xbf0a48ad,0x3f577026,0xbecf7bca,0x3f6a09a7,0xbe8586ce,0x3f772417,0xbde1bc2e,0x3f7e70b0,0x3d2fe007,0x3f7fc38f,
0xbf45e403,0x3f226799,0xbf299415,0x3f3fc767,0xbf08f59b,0x3f584853,0xbec9b953,0x3f6b4b0c,0xbe78cfcc,0x3f7853f8,0xbdafb680,0x3f7f0e58,0x3d96a905,0x3f7f4e6d,0x3e6c9a7f,0x3f791298,
0xbf2beb4a,0x3f3daef9,0xbf0a48ad,0x3f577026,0xbec9b953,0x3f6b4b0c,0xbe72b651,0x3f78b47b,0xbd96a905,0x3f7f4e6d,0x3dbc3ac3,0x3f7eea9d,0x3e827dc0,0x3f778bc5,0x3ed25a09,0x3f696591,
0xbf0e39da,0x3f54db31,0xbecf7bca,0x3f6a09a7,0xbe78cfcc,0x3f7853f8,0xbd96a905,0x3f7f4e6d,0x3dc8bd36,0x3f7ec46d,0x3e888e93,0x3f76ba07,0x3edae880,0x3f676bd8,0x3f13682a,0x3f514d3d,
0xbedae880,0x3f676bd8,0xbe8586ce,0x3f772417,0xbdafb680,0x3f7f0e58,0x3dbc3ac3,0x3f7eea9d,0x3e888e93,0x3f76ba07,0x3eddbe79,0x3f66becc,0x3f15f6d9,0x3f4f7a1f,0x3f385216,0x3f31a81d,
0xbe94a031,0x3f74fa0b,0xbde1bc2e,0x3f7e70b0,0x3d96a905,0x3f7f4e6d,0x3e827dc0,0x3f778bc5,0x3edae880,0x3f676bd8,0x3f15f6d9,0x3f4f7a1f,0x3f396842,0x3f3085bb,0x3f5695e5,0x3f0b9a6b,
0xbe164083,0x3f7d3aac,0x3d2fe007,0x3f7fc38f,0x3e6c9a7f,0x3f791298,0x3ed25a09,0x3f696591,0x3f13682a,0x3f514d3d,0x3f385216,0x3f31a81d,0x3f5695e5,0x3f0b9a6b,0x3f6d1c1d,0x3ec1071e,
0xbd803d80,0x80003e00,0x80003e00,0x80003e00,0x80003e00,0x80003e00,0x80003e00,0x80003e00,0x80003e00,0x80003e00,0x80003e00,0x80003e00,0x80003e00,0x80003e00,0x80003e00,0x80003e00,
0x3d803d80,0x3cc83dfb,0x3e000000,0x3dfbbcc8,0x3d443ded,0x3d8e3dd5,0x3dedbd44,0x3dd5bd8e,0x3db53db5,0x3dd53d8e,0x3db5bdb5,0x3d8ebdd5,0x3ded3d44,0x3dfb3cc8,0x3d44bded,0x3cc8bdfb,
0xbd803d80,0x3d443ded,0x8000be00,0xbd44bded,0x3db53db5,0x3ded3d44,0xbdb5bdb5,0xbdedbd44,0x3e000000,0x3dedbd44,0xbe000000,0xbded3d44,0x3db5bdb5,0x3d44bded,0xbdb53db5,0xbd443ded,
0x3d803d80,0x3d8e3dd5,0xbe000000,0xbdd53d8e,0x3ded3d44,0x3dfbbcc8,0xbd443ded,0x3cc83dfb,0x3db5bdb5,0x3cc8bdfb,0x3db53db5,0x3dfb3cc8,0xbd44bded,0xbdd5bd8e,0x3dedbd44,0x3d8ebdd5,
0xbd803d80,0x3db53db5,0x80003e00,0x3db53db5,0x3e000000,0x3db5bdb5,0x3e000000,0x3db5bdb5,0x8000be00,0xbdb5bdb5,0x8000be00,0xbdb5bdb5,0xbe000000,0xbdb53db5,0xbe000000,0xbdb53db5,
0x3d803d80,0x3dd53d8e,0x3e000000,0x3d8ebdd5,0x3dedbd44,0x3cc8bdfb,0xbd44bded,0xbdfbbcc8,0xbdb5bdb5,0xbdfb3cc8,0xbdb53db5,0x3cc83dfb,0xbd443ded,0x3d8e3dd5,0x3ded3d44,0x3dd5bd8e,
0xbd803d80,0x3ded3d44,0x8000be00,0xbdedbd44,0x3db5bdb5,0xbd44bded,0xbdb53db5,0x3d443ded,0xbe000000,0xbd443ded,0x3e000000,0x3d44bded,0x3db53db5,0x3dedbd44,0xbdb5bdb5,0xbded3d44,
0x3d803d80,0x3dfb3cc8,0xbe000000,0xbcc83dfb,0x3d44bded,0xbdd5bd8e,0x3ded3d44,0x3d8ebdd5,0xbdb53db5,0x3d8e3dd5,0xbdb5bdb5,0xbdd53d8e,0x3dedbd44,0xbcc8bdfb,0x3d443ded,0x3dfbbcc8,
0xbd803d80,0x3e000000,0x80003e00,0x3e000000,0x8000be00,0xbe000000,0x8000be00,0xbe000000,0x80003e00,0x3e000000,0x80003e00,0x3e000000,0x8000be00,0xbe000000,0x8000be00,0xbe000000,
0x3d803d80,0x3dfbbcc8,0x3e000000,0xbcc8bdfb,0xbd44bded,0xbdd53d8e,0xbded3d44,0x3d8e3dd5,0x3db53db5,0x3d8ebdd5,0x3db5bdb5,0xbdd5bd8e,0xbdedbd44,0xbcc83dfb,0xbd443ded,0x3dfb3cc8,
0xbd803d80,0x3dedbd44,0x8000be00,0xbded3d44,0xbdb5bdb5,0xbd443ded,0x3db53db5,0x3d44bded,0x3e000000,0xbd44bded,0xbe000000,0x3d443ded,0xbdb53db5,0x3ded3d44,0x3db5bdb5,0xbdedbd44,
0x3d803d80,0x3dd5bd8e,0xbe000000,0x3d8e3dd5,0xbdedbd44,0x3cc83dfb,0x3d44bded,0xbdfb3cc8,0x3db5bdb5,0xbdfbbcc8,0x3db53db5,0x3cc8bdfb,0x3d443ded,0x3d8ebdd5,0xbded3d44,0x3dd53d8e,
0xbd803d80,0x3db5bdb5,0x80003e00,0x3db5bdb5,0xbe000000,0x3db53db5,0xbe000000,0x3db53db5,0x8000be00,0xbdb53db5,0x8000be00,0xbdb53db5,0x3e000000,0xbdb5bdb5,0x3e000000,0xbdb5bdb5,
0x3d803d80,0x3d8ebdd5,0x3e000000,0xbdd5bd8e,0xbded3d44,0x3dfb3cc8,0x3d443ded,0x3cc8bdfb,0xbdb5bdb5,0x3cc83dfb,0xbdb53db5,0x3dfbbcc8,0x3d44bded,0xbdd53d8e,0xbdedbd44,0x3d8e3dd5,
0xbd803d80,0x3d44bded,0x8000be00,0xbd443ded,0xbdb53db5,0x3dedbd44,0x3db5bdb5,0xbded3d44,0xbe000000,0x3ded3d44,0x3e000000,0xbdedbd44,0xbdb5bdb5,0x3d443ded,0x3db53db5,0xbd44bded,
0x3d803d80,0x3cc8bdfb,0xbe000000,0x3dfb3cc8,0xbd443ded,0x3d8ebdd5,0xbdedbd44,0x3dd53d8e,0xbdb53db5,0x3dd5bd8e,0xbdb5bdb5,0x3d8e3dd5,0xbded3d44,0x3dfbbcc8,0xbd44bded,0x3cc83dfb,
0xbd803d80,0x8000be00,0x80003e00,0x8000be00,0x80003e00,0x8000be00,0x80003e00,0x8000be00,0x80003e00,0x8000be00,0x80003e00,0x8000be00,0x80003e00,0x8000be00,0x80003e00,0x8000be00,
0x3d803d80,0xbcc8bdfb,0x3e000000,0xbdfb3cc8,0x3d443ded,0xbd8ebdd5,0x3dedbd44,0xbdd53d8e,0x3db53db5,0xbdd5bd8e,0x3db5bdb5,0xbd8e3dd5,0x3ded3d44,0xbdfbbcc8,0x3d44bded,0xbcc83dfb,
0xbd803d80,0xbd44bded,0x8000be00,0x3d443ded,0x3db53db5,0xbdedbd44,0xbdb5bdb5,0x3ded3d44,0x3e000000,0xbded3d44,0xbe000000,0x3dedbd44,0x3db5bdb5,0xbd443ded,0xbdb53db5,0x3d44bded,
0x3d803d80,0xbd8ebdd5,0xbe000000,0x3dd5bd8e,0x3ded3d44,0xbdfb3cc8,0xbd443ded,0xbcc8bdfb,0x3db5bdb5,0xbcc83dfb,0x3db53db5,0xbdfbbcc8,0xbd44bded,0x3dd53d8e,0x3dedbd44,0xbd8e3dd5,
0xbd803d80,0xbdb5bdb5,0x80003e00,0xbdb5bdb5,0x3e000000,0xbdb53db5,0x3e000000,0xbdb53db5,0x8000be00,0x3db53db5,0x8000be00,0x3db53db5,0xbe000000,0x3db5bdb5,0xbe000000,0x3db5bdb5,
0x3d803d80,0xbdd5bd8e,0x3e000000,0xbd8e3dd5,0x3dedbd44,0xbcc83dfb,0xbd44bded,0x3dfb3cc8,0xbdb5bdb5,0x3dfbbcc8,0xbdb53db5,0xbcc8bdfb,0xbd443ded,0xbd8ebdd5,0x3ded3d44,0xbdd53d8e,
0xbd803d80,0xbdedbd44,0x8000be00,0x3ded3d44,0x3db5bdb5,0x3d443ded,0xbdb53db5,0xbd44bded,0xbe000000,0x3d44bded,0x3e000000,0xbd443ded,0x3db53db5,0xbded3d44,0xbdb5bdb5,0x3dedbd44,
0x3d803d80,0xbdfbbcc8,0xbe000000,0x3cc8bdfb,0x3d44bded,0x3dd53d8e,0x3ded3d44,0xbd8e3dd5,0xbdb53db5,0xbd8ebdd5,0xbdb5bdb5,0x3dd5bd8e,0x3dedbd44,0x3cc83dfb,0x3d443ded,0xbdfb3cc8,
0xbd803d80,0xbe000000,0x80003e00,0xbe000000,0x8000be00,0x3e000000,0x8000be00,0x3e000000,0x80003e00,0xbe000000,0x80003e00,0xbe000000,0x8000be00,0x3e000000,0x8000be00,0x3e000000,
0x3d803d80,0xbdfb3cc8,0x3e000000,0x3cc83dfb,0xbd44bded,0x3dd5bd8e,0xbded3d44,0xbd8ebdd5,0x3db53db5,0xbd8e3dd5,0x3db5bdb5,0x3dd53d8e,0xbdedbd44,0x3cc8bdfb,0xbd443ded,0xbdfbbcc8,
0xbd803d80,0xbded3d44,0x8000be00,0x3dedbd44,0xbdb5bdb5,0x3d44bded,0x3db53db5,0xbd443ded,0x3e000000,0x3d443ded,0xbe000000,0xbd44bded,0xbdb53db5,0xbdedbd44,0x3db5bdb5,0x3ded3d44,
0x3d803d80,0xbdd53d8e,0xbe000000,0xbd8ebdd5,0xbdedbd44,0xbcc8bdfb,0x3d44bded,0x3dfbbcc8,0x3db5bdb5,0x3dfb3cc8,0x3db53db5,0xbcc83dfb,0x3d443ded,0xbd8e3dd5,0xbded3d44,0xbdd5bd8e,
0xbd803d80,0xbdb53db5,0x80003e00,0xbdb53db5,0xbe000000,0xbdb5bdb5,0xbe000000,0xbdb5bdb5,0x8000be00,0x3db5bdb5,0x8000be00,0x3db5bdb5,0x3e000000,0x3db53db5,0x3e000000,0x3db53db5,
0x3d803d80,0xbd8e3dd5,0x3e000000,0x3dd53d8e,0xbded3d44,0xbdfbbcc8,0x3d443ded,0xbcc83dfb,0xbdb5bdb5,0xbcc8bdfb,0xbdb53db5,0xbdfb3cc8,0x3d44bded,0x3dd5bd8e,0xbdedbd44,0xbd8ebdd5,
0xbd803d80,0xbd443ded,0x8000be00,0x3d44bded,0xbdb53db5,0xbded3d44,0x3db5bdb5,0x3dedbd44,0xbe000000,0xbdedbd44,0x3e000000,0x3ded3d44,0xbdb5bdb5,0xbd44bded,0x3db53db5,0x3d443ded,
0x3d803d80,0xbcc83dfb,0xbe000000,0xbdfbbcc8,0xbd443ded,0xbd8e3dd5,0xbdedbd44,0xbdd5bd8e,0xbdb53db5,0xbdd53d8e,0xbdb5bdb5,0xbd8ebdd5,0xbded3d44,0xbdfb3cc8,0xbd44bded,0xbcc8bdfb,
0x80003e00,0x80003e00,0x80003e00,0x80003e00,0x80003e00,0x80003e00,0x80003e00,0x80003e00,0x80003e00,0x80003e00,0x80003e00,0x80003e00,0x80003e00,0x80003e00,0x80003e00,0x80003e00,
0x3c493dff,0x3d153df5,0x3dffbc49,0x3df5bd15,0x3d713de2,0x3da23dc6,0x3de2bd71,0x3dc6bda2,0x3dc63da2,0x3de23d71,0x3da2bdc6,0x3d71bde2,0x3df53d15,0x3dff3c49,0x3d15bdf5,0x3c49bdff,
0x3cc83dfb,0x3d8e3dd5,0xbcc8bdfb,0xbd8ebdd5,0x3dd53d8e,0x3dfb3cc8,0xbdd5bd8e,0xbdfbbcc8,0x3dfbbcc8,0x3dd5bd8e,0xbdfb3cc8,0xbdd53d8e,0x3d8ebdd5,0x3cc8bdfb,0xbd8e3dd5,0xbcc83dfb,
0x3d153df5,0x3dc63da2,0xbdf53d15,0xbda23dc6,0x3dff3c49,0x3de2bd71,0xbc493dff,0x3d713de2,0x3d71bde2,0xbc49bdff,0x3de23d71,0x3dffbc49,0xbda2bdc6,0xbdf5bd15,0x3dc6bda2,0x3d15bdf5,
0x3d443ded,0x3ded3d44,0x3d443ded,0x3ded3d44,0x3dedbd44,0x3d44bded,0x3dedbd44,0x3d44bded,0xbd44bded,0xbdedbd44,0xbd44bded,0xbdedbd44,0xbded3d44,0xbd443ded,0xbded3d44,0xbd443ded,
0x3d713de2,0x3dff3c49,0x3de2bd71,0x3c49bdff,0x3da2bdc6,0xbd15bdf5,0xbdc6bda2,0xbdf53d15,0xbdf5bd15,0xbdc63da2,0xbd153df5,0x3da23dc6,0x3c493dff,0x3de23d71,0x3dffbc49,0x3d71bde2,
0x3d8e3dd5,0x3dfbbcc8,0xbd8ebdd5,0xbdfb3cc8,0x3cc8bdfb,0xbdd5bd8e,0xbcc83dfb,0x3dd53d8e,0xbdd53d8e,0x3cc83dfb,0x3dd5bd8e,0xbcc8bdfb,0x3dfb3cc8,0x3d8ebdd5,0xbdfbbcc8,0xbd8e3dd5,
0x3da23dc6,0x3de2bd71,0xbdc63da2,0x3d713de2,0xbd15bdf5,0xbdff3c49,0x3df5bd15,0xbc49bdff,0xbc493dff,0x3df53d15,0xbdffbc49,0xbd153df5,0x3d71bde2,0xbdc6bda2,0x3de23d71,0x3da2bdc6,
0x3db53db5,0x3db5bdb5,0x3db53db5,0x3db5bdb5,0xbdb5bdb5,0xbdb53db5,0xbdb5bdb5,0xbdb53db5,0x3db53db5,0x3db5bdb5,0x3db53db5,0x3db5bdb5,0xbdb5bdb5,0xbdb53db5,0xbdb5bdb5,0xbdb53db5,
0x3dc63da2,0x3d71bde2,0x3da2bdc6,0xbde2bd71,0xbdf5bd15,0xbc493dff,0xbd153df5,0x3dff3c49,0x3dffbc49,0xbd15bdf5,0xbc49bdff,0xbdf53d15,0xbde23d71,0x3da23dc6,0x3d713de2,0x3dc6bda2,
0x3dd53d8e,0x3cc8bdfb,0xbdd5bd8e,0xbcc83dfb,0xbdfb3cc8,0x3d8e3dd5,0x3dfbbcc8,0xbd8ebdd5,0x3d8ebdd5,0xbdfbbcc8,0xbd8e3dd5,0x3dfb3cc8,0x3cc83dfb,0x3dd5bd8e,0xbcc8bdfb,0xbdd53d8e,
0x3de23d71,0xbc49bdff,0xbd713de2,0x3dffbc49,0xbdc63da2,0x3df53d15,0xbda2bdc6,0xbd153df5,0xbd15bdf5,0xbda23dc6,0x3df5bd15,0xbdc6bda2,0x3dff3c49,0xbd71bde2,0xbc493dff,0x3de2bd71,
0x3ded3d44,0xbd44bded,0x3ded3d44,0xbd44bded,0xbd443ded,0x3dedbd44,0xbd443ded,0x3dedbd44,0xbdedbd44,0x3d443ded,0xbdedbd44,0x3d443ded,0x3d44bded,0xbded3d44,0x3d44bded,0xbded3d44,
0x3df53d15,0xbda2bdc6,0x3d15bdf5,0xbdc63da2,0x3c493dff,0x3d71bde2,0x3dffbc49,0xbde2bd71,0xbde23d71,0x3dff3c49,0x3d713de2,0x3c49bdff,0xbdc6bda2,0x3d153df5,0xbda23dc6,0x3df5bd15,
0x3dfb3cc8,0xbdd5bd8e,0xbdfbbcc8,0x3dd53d8e,0x3d8e3dd5,0xbcc8bdfb,0xbd8ebdd5,0x3cc83dfb,0xbcc83dfb,0x3d8ebdd5,0x3cc8bdfb,0xbd8e3dd5,0xbdd53d8e,0x3dfbbcc8,0x3dd5bd8e,0xbdfb3cc8,
0x3dff3c49,0xbdf5bd15,0xbc493dff,0x3d15bdf5,0x3de23d71,0xbdc6bda2,0xbd713de2,0x3da2bdc6,0x3da23dc6,0xbd71bde2,0xbdc63da2,0x3de2bd71,0x3d153df5,0xbc49bdff,0xbdf53d15,0x3dffbc49,
0x3e000000,0xbe000000,0x3e000000,0xbe000000,0x3e000000,0xbe000000,0x3e000000,0xbe000000,0x3e000000,0xbe000000,0x3e000000,0xbe000000,0x3e000000,0xbe000000,0x3e000000,0xbe000000,
0x3dffbc49,0xbdf53d15,0xbc49bdff,0x3d153df5,0x3de2bd71,0xbdc63da2,0xbd71bde2,0x3da23dc6,0x3da2bdc6,0xbd713de2,0xbdc6bda2,0x3de23d71,0x3d15bdf5,0xbc493dff,0xbdf5bd15,0x3dff3c49,
0x3dfbbcc8,0xbdd53d8e,0xbdfb3cc8,0x3dd5bd8e,0x3d8ebdd5,0xbcc83dfb,0xbd8e3dd5,0x3cc8bdfb,0xbcc8bdfb,0x3d8e3dd5,0x3cc83dfb,0xbd8ebdd5,0xbdd5bd8e,0x3dfb3cc8,0x3dd53d8e,0xbdfbbcc8,
0x3df5bd15,0xbda23dc6,0x3d153df5,0xbdc6bda2,0x3c49bdff,0x3d713de2,0x3dff3c49,0xbde23d71,0xbde2bd71,0x3dffbc49,0x3d71bde2,0x3c493dff,0xbdc63da2,0x3d15bdf5,0xbda2bdc6,0x3df53d15,
0x3dedbd44,0xbd443ded,0x3dedbd44,0xbd443ded,0xbd44bded,0x3ded3d44,0xbd44bded,0x3ded3d44,0xbded3d44,0x3d44bded,0xbded3d44,0x3d44bded,0x3d443ded,0xbdedbd44,0x3d443ded,0xbdedbd44,
0x3de2bd71,0xbc493dff,0xbd71bde2,0x3dff3c49,0xbdc6bda2,0x3df5bd15,0xbda23dc6,0xbd15bdf5,0xbd153df5,0xbda2bdc6,0x3df53d15,0xbdc63da2,0x3dffbc49,0xbd713de2,0xbc49bdff,0x3de23d71,
0x3dd5bd8e,0x3cc83dfb,0xbdd53d8e,0xbcc8bdfb,0xbdfbbcc8,0x3d8ebdd5,0x3dfb3cc8,0xbd8e3dd5,0x3d8e3dd5,0xbdfb3cc8,0xbd8ebdd5,0x3dfbbcc8,0x3cc8bdfb,0x3dd53d8e,0xbcc83dfb,0xbdd5bd8e,
0x3dc6bda2,0x3d713de2,0x3da23dc6,0xbde23d71,0xbdf53d15,0xbc49bdff,0xbd15bdf5,0x3dffbc49,0x3dff3c49,0xbd153df5,0xbc493dff,0xbdf5bd15,0xbde2bd71,0x3da2bdc6,0x3d71bde2,0x3dc63da2,
0x3db5bdb5,0x3db53db5,0x3db5bdb5,0x3db53db5,0xbdb53db5,0xbdb5bdb5,0xbdb53db5,0xbdb5bdb5,0x3db5bdb5,0x3db53db5,0x3db5bdb5,0x3db53db5,0xbdb53db5,0xbdb5bdb5,0xbdb53db5,0xbdb5bdb5,
0x3da2bdc6,0x3de23d71,0xbdc6bda2,0x3d71bde2,0xbd153df5,0xbdffbc49,0x3df53d15,0xbc493dff,0xbc49bdff,0x3df5bd15,0xbdff3c49,0xbd15bdf5,0x3d713de2,0xbdc63da2,0x3de2bd71,0x3da23dc6,
0x3d8ebdd5,0x3dfb3cc8,0xbd8e3dd5,0xbdfbbcc8,0x3cc83dfb,0xbdd53d8e,0xbcc8bdfb,0x3dd5bd8e,0xbdd5bd8e,0x3cc8bdfb,0x3dd53d8e,0xbcc83dfb,0x3dfbbcc8,0x3d8e3dd5,0xbdfb3cc8,0xbd8ebdd5,
0x3d71bde2,0x3dffbc49,0x3de23d71,0x3c493dff,0x3da23dc6,0xbd153df5,0xbdc63da2,0xbdf5bd15,0xbdf53d15,0xbdc6bda2,0xbd15bdf5,0x3da2bdc6,0x3c49bdff,0x3de2bd71,0x3dff3c49,0x3d713de2,
0x3d44bded,0x3dedbd44,0x3d44bded,0x3dedbd44,0x3ded3d44,0x3d443ded,0x3ded3d44,0x3d443ded,0xbd443ded,0xbded3d44,0xbd443ded,0xbded3d44,0xbdedbd44,0xbd44bded,0xbdedbd44,0xbd44bded,
0x3d15bdf5,0x3dc6bda2,0xbdf5bd15,0xbda2bdc6,0x3dffbc49,0x3de23d71,0xbc49bdff,0x3d71bde2,0x3d713de2,0xbc493dff,0x3de2bd71,0x3dff3c49,0xbda23dc6,0xbdf53d15,0x3dc63da2,0x3d153df5,
0x3cc8bdfb,0x3d8ebdd5,0xbcc83dfb,0xbd8e3dd5,0x3dd5bd8e,0x3dfbbcc8,0xbdd53d8e,0xbdfb3cc8,0x3dfb3cc8,0x3dd53d8e,0xbdfbbcc8,0xbdd5bd8e,0x3d8e3dd5,0x3cc83dfb,0xbd8ebdd5,0xbcc8bdfb,
0x3c49bdff,0x3d15bdf5,0x3dff3c49,0x3df53d15,0x3d71bde2,0x3da2bdc6,0x3de23d71,0x3dc63da2,0x3dc6bda2,0x3de2bd71,0x3da23dc6,0x3d713de2,0x3df5bd15,0x3dffbc49,0x3d153df5,0x3c493dff,
0x3f800000,0x0,0x3f800000,0x0,0x3f800000,0x0,0x3f800000,0x0,0x3f800000,0x0,0x3f800000,0x0,0x3f800000,0x0,0x3f800000,0x0,
0x3f800000,0x0,0x3f7ffb11,0xbc490e90,0x3f7fec43,0xbcc90ab0,0x3f7fd397,0xbd16c32c,0x3f7fb10f,0xbd48fb30,0x3f7f84ab,0xbd7b2b74,0x3f7f4e6d,0xbd96a905,0x3f7f0e58,0xbdafb680,
0x3f800000,0x0,0x3f7fec43,0xbcc90ab0,0x3f7fb10f,0xbd48fb30,0x3f7f4e6d,0xbd96a905,0x3f7ec46d,0xbdc8bd36,0x3f7e1324,0xbdfab273,0x3f7d3aac,0xbe164083,0x3f7c3b28,0xbe2f10a2,
0x3f800000,0x0,0x3f7fd397,0xbd16c32c,0x3f7f4e6d,0xbd96a905,0x3f7e70b0,0xbde1bc2e,0x3f7d3aac,0xbe164083,0x3f7baccd,0xbe3b6ecf,0x3f79c79d,0xbe605c13,0x3f778bc5,0xbe827dc0,
0x3f800000,0x0,0x3f7fb10f,0xbd48fb30,0x3f7ec46d,0xbdc8bd36,0x3f7d3aac,0xbe164083,0x3f7b14be,0xbe47c5c2,0x3f7853f8,0xbe78cfcc,0x3f74fa0b,0xbe94a031,0x3f710908,0xbeac7cd4,
0x3f800000,0x0,0x3f7f84ab,0xbd7b2b74,0x3f7e1324,0xbdfab273,0x3f7baccd,0xbe3b6ecf,0x3f7853f8,0xbe78cfcc,0x3f740bdd,0xbe9aa086,0x3f6ed89e,0xbeb8442a,0x3f68bf3c,0xbed53641,
0x3f800000,0x0,0x3f7f4e6d,0xbd96a905,0x3f7d3aac,0xbe164083,0x3f79c79d,0xbe605c13,0x3f74fa0b,0xbe94a031,0x3f6ed89e,0xbeb8442a,0x3f676bd8,0xbedae880,0x3f5ebe05,0xbefc5d27,
0x3f800000,0x0,0x3f7f0e58,0xbdafb680,0x3f7c3b28,0xbe2f10a2,0x3f778bc5,0xbe827dc0,0x3f710908,0xbeac7cd4,0x3f68bf3c,0xbed53641,0x3f5ebe05,0xbefc5d27,0x3f531849,0xbf10d3cd,
0x3f800000,0x0,0x3f7ec46d,0xbdc8bd36,0x3f7b14be,0xbe47c5c2,0x3f74fa0b,0xbe94a031,0x3f6c835e,0xbec3ef15,0x3f61c598,0xbef15aea,0x3f54db31,0xbf0e39da,0x3f45e403,0xbf226799,
0x3f800000,0x0,0x3f7e70b0,0xbde1bc2e,0x3f79c79d,0xbe605c13,0x3f721352,0xbea68f12,0x3f676bd8,0xbedae880,0x3f59f26a,0xbf064b82,0x3f49d112,0xbf1d7fd1,0x3f373a23,0xbf32c8c9,
0x3f800000,0x0,0x3f7e1324,0xbdfab273,0x3f7853f8,0xbe78cfcc,0x3f6ed89e,0xbeb8442a,0x3f61c598,0xbef15aea,0x3f514d3d,0xbf13682a,0x3f3daef9,0xbf2beb4a,0x3f273656,0xbf41d870,
0x3f800000,0x0,0x3f7dabcc,0xbe09cf86,0x3f76ba07,0xbe888e93,0x3f6b4b0c,0xbec9b953,0x3f5b941a,0xbf039c3d,0x3f47de65,0xbf1ff6cb,0x3f3085bb,0xbf396842,0x3f15f6d9,0xbf4f7a1f,
0x3f800000,0x0,0x3f7d3aac,0xbe164083,0x3f74fa0b,0xbe94a031,0x3f676bd8,0xbedae880,0x3f54db31,0xbf0e39da,0x3f3daef9,0xbf2beb4a,0x3f226799,0xbf45e403,0x3f039c3d,0xbf5b941a,
0x3f800000,0x0,0x3f7cbfc9,0xbe22abb6,0x3f731447,0xbea09ae5,0x3f633c5a,0xbeebcbbb,0x3f4d9f02,0xbf187fc0,0x3f32c8c9,0xbf373a23,0x3f13682a,0xbf514d3d,0x3ee0924f,0xbf660f88,
0x3f800000,0x0,0x3f7c3b28,0xbe2f10a2,0x3f710908,0xbeac7cd4,0x3f5ebe05,0xbefc5d27,0x3f45e403,0xbf226799,0x3f273656,0xbf41d870,0x3f039c3d,0xbf5b941a,0x3eb8442a,0xbf6ed89e,
0x3f800000,0x0,0x3f7baccd,0xbe3b6ecf,0x3f6ed89e,0xbeb8442a,0x3f59f26a,0xbf064b82,0x3f3daef9,0xbf2beb4a,0x3f1b02c6,0xbf4bbbf8,0x3ee63375,0xbf64aa59,0x3e8e9a22,0xbf75dec6,
0x3f800000,0x0,0x3f7b14be,0xbe47c5c2,0x3f6c835e,0xbec3ef15,0x3f54db31,0xbf0e39da,0x3f3504f3,0xbf3504f3,0x3f0e39da,0xbf54db31,0x3ec3ef15,0xbf6c835e,0x3e47c5c2,0xbf7b14be,
0x3f800000,0x0,0x3f7a7302,0xbe541501,0x3f6a09a7,0xbecf7bca,0x3f4f7a1f,0xbf15f6d9,0x3f2beb4a,0xbf3daef9,0x3f00e7e4,0xbf5d2d53,0x3ea09ae5,0xbf731447,0x3de1bc2e,0xbf7e70b0,
0x3f800000,0x0,0x3f79c79d,0xbe605c13,0x3f676bd8,0xbedae880,0x3f49d112,0xbf1d7fd1,0x3f226799,0xbf45e403,0x3ee63375,0xbf64aa59,0x3e78cfcc,0xbf7853f8,0x3cc90ab0,0xbf7fec43,
0x3f800000,0x0,0x3f791298,0xbe6c9a7f,0x3f64aa59,0xbee63375,0x3f43e200,0xbf24d225,0x3f187fc0,0xbf4d9f02,0x3ec9b953,0xbf6b4b0c,0x3e2f10a2,0xbf7c3b28,0xbd7b2b74,0xbf7f84ab,
0x3f800000,0x0,0x3f7853f8,0xbe78cfcc,0x3f61c598,0xbef15aea,0x3f3daef9,0xbf2beb4a,0x3f0e39da,0xbf54db31,0x3eac7cd4,0xbf710908,0x3dc8bd36,0xbf7ec46d,0xbe164083,0xbf7d3aac,
0x3f800000,0x0,0x3f778bc5,0xbe827dc0,0x3f5ebe05,0xbefc5d27,0x3f373a23,0xbf32c8c9,0x3f039c3d,0xbf5b941a,0x3e8e9a22,0xbf75dec6,0x3cc90ab0,0xbf7fec43,0xbe6c9a7f,0xbf791298,
0x3f800000,0x0,0x3f76ba07,0xbe888e93,0x3f5b941a,0xbf039c3d,0x3f3085bb,0xbf396842,0x3ef15aea,0xbf61c598,0x3e605c13,0xbf79c79d,0xbd48fb30,0xbf7fb10f,0xbea09ae5,0xbf731447,
0x3f800000,0x0,0x3f75dec6,0xbe8e9a22,0x3f584853,0xbf08f59b,0x3f299415,0xbf3fc767,0x3edae880,0xbf676bd8,0x3e22abb6,0xbf7cbfc9,0xbdfab273,0xbf7e1324,0xbec9b953,0xbf6b4b0c,
0x3f800000,0x0,0x3f74fa0b,0xbe94a031,0x3f54db31,0xbf0e39da,0x3f226799,0xbf45e403,0x3ec3ef15,0xbf6c835e,0x3dc8bd36,0xbf7ec46d,0xbe47c5c2,0xbf7b14be,0xbef15aea,0xbf61c598,
0x3f800000,0x0,0x3f740bdd,0xbe9aa086,0x3f514d3d,0xbf13682a,0x3f1b02c6,0xbf4bbbf8,0x3eac7cd4,0xbf710908,0x3d16c32c,0xbf7fd397,0xbe888e93,0xbf76ba07,0xbf0b9a6b,0xbf5695e5,
0x3f800000,0x0,0x3f731447,0xbea09ae5,0x3f4d9f02,0xbf187fc0,0x3f13682a,0xbf514d3d,0x3e94a031,0xbf74fa0b,0xbcc90ab0,0xbf7fec43,0xbeac7cd4,0xbf710908,0xbf1d7fd1,0xbf49d112,
0x3f800000,0x0,0x3f721352,0xbea68f12,0x3f49d112,0xbf1d7fd1,0x3f0b9a6b,0xbf5695e5,0x3e78cfcc,0xbf7853f8,0xbdafb680,0xbf7f0e58,0xbecf7bca,0xbf6a09a7,0xbf2e3bde,0xbf3b8f3b,
0x3f800000,0x0,0x3f710908,0xbeac7cd4,0x3f45e403,0xbf226799,0x3f039c3d,0xbf5b941a,0x3e47c5c2,0xbf7b14be,0xbe164083,0xbf7d3aac,0xbef15aea,0xbf61c598,0xbf3daef9,0xbf2beb4a,
0x3f800000,0x0,0x3f6ff573,0xbeb263ef,0x3f41d870,0xbf273656,0x3ef6e0cb,0xbf604621,0x3e164083,0xbf7d3aac,0xbe541501,0xbf7a7302,0xbf08f59b,0xbf584853,0xbf4bbbf8,0xbf1b02c6,
0x3f800000,0x0,0x3f6ed89e,0xbeb8442a,0x3f3daef9,0xbf2beb4a,0x3ee63375,0xbf64aa59,0x3dc8bd36,0xbf7ec46d,0xbe888e93,0xbf76ba07,0xbf187fc0,0xbf4d9f02,0xbf584853,0xbf08f59b,
0x3f800000,0x0,0x3f6db293,0xbebe1d4a,0x3f396842,0xbf3085bb,0x3ed53641,0xbf68bf3c,0x3d48fb30,0xbf7fb10f,0xbea68f12,0xbf721352,0xbf273656,0xbf41d870,0xbf633c5a,0xbeebcbbb,
0x3f800000,0x3f800000,0x3f800000,0x3f800000,0x3f800000,0x3f800000,0x3f800000,0x3f800000,0x3f800000,0xbf800000,0x3f800000,0xbf800000,0x3f800000,0xbf800000,0x3f800000,0xbf800000,
0x3f800000,0x3f3504f3,0x0,0xbf3504f3,0xbf800000,0xbf3504f3,0x0,0x3f3504f3,0x0,0xbf3504f3,0xbf800000,0xbf3504f3,0x0,0x3f3504f3,0x3f800000,0x3f3504f3,
0x3f800000,0x0,0xbf800000,0x0,0x3f800000,0x0,0xbf800000,0x0,0x0,0xbf800000,0x0,0x3f800000,0x0,0xbf800000,0x0,0x3f800000,
0x3f800000,0xbf3504f3,0x0,0x3f3504f3,0xbf800000,0x3f3504f3,0x0,0xbf3504f3,0x0,0xbf3504f3,0x3f800000,0xbf3504f3,0x0,0x3f3504f3,0xbf800000,0x3f3504f3,
0x3f800000,0x3f6c835e,0x3f3504f3,0x3ec3ef15,0x0,0xbec3ef15,0xbf3504f3,0xbf6c835e,0x0,0xbec3ef15,0xbf3504f3,0xbf6c835e,0xbf800000,0xbf6c835e,0xbf3504f3,0xbec3ef15,
0x3f800000,0x3ec3ef15,0xbf3504f3,0xbf6c835e,0x0,0x3f6c835e,0x3f3504f3,0xbec3ef15,0x0,0xbf6c835e,0xbf3504f3,0x3ec3ef15,0x3f800000,0x3ec3ef15,0xbf3504f3,0xbf6c835e,
0x3f800000,0xbec3ef15,0xbf3504f3,0x3f6c835e,0x0,0xbf6c835e,0x3f3504f3,0x3ec3ef15,0x0,0xbf6c835e,0x3f3504f3,0x3ec3ef15,0xbf800000,0x3ec3ef15,0x3f3504f3,0xbf6c835e,
0x3f800000,0xbf6c835e,0x3f3504f3,0xbec3ef15,0x0,0x3ec3ef15,0xbf3504f3,0x3f6c835e,0x0,0xbec3ef15,0x3f3504f3,0xbf6c835e,0x3f800000,0xbf6c835e,0x3f3504f3,0xbec3ef15,
};

struct Params {
    const __nv_bfloat16 *xb, *lre, *lim, *ldt, *dsk;
    float* out;
    int zero[8];
    uint64_t da[4];
    uint32_t unit[258];
};

struct Maps { CUtensorMap m[12]; };

struct cf { float x, y; };
__device__ __forceinline__ uint32_t smem_u32(const void* p) { return (uint32_t)__cvta_generic_to_shared(p); }
__device__ __forceinline__ void mbar_init(uint32_t a, uint32_t c) { asm volatile("mbarrier.init.shared::cta.b64 [%0], %1;" ::"r"(a), "r"(c) : "memory"); }
__device__ __forceinline__ void mbar_expect_tx(uint32_t a, uint32_t b) { asm volatile("mbarrier.arrive.expect_tx.shared::cta.b64 _, [%0], %1;" ::"r"(a), "r"(b) : "memory"); }
__device__ __forceinline__ void mbar_arrive(uint32_t a) { asm volatile("mbarrier.arrive.shared::cta.b64 _, [%0];" ::"r"(a) : "memory"); }
__device__ __forceinline__ void mbar_wait(uint32_t a, uint32_t ph) {
    asm volatile("{.reg .pred p; .reg .u32 n;\n"
                 "mov.u32 n, 0;\n"
                 "LOOP: mbarrier.try_wait.parity.shared::cta.b64 p, [%0], %1;\n"
                 "@p bra DONE;\n"
                 "add.u32 n, n, 1;\n"
                 "setp.lt.u32 p, n, %2;\n"
                 "@p bra LOOP;\n"
                 "DONE: }" ::"r"(a), "r"(ph), "n"(SPIN_LIMIT) : "memory");
}
__device__ __forceinline__ unsigned ld_rlx(const unsigned* p) { unsigned v; asm volatile("ld.relaxed.gpu.global.u32 %0, [%1];" : "=r"(v) : "l"(p) : "memory"); return v; }
__device__ __forceinline__ void wait_cnt(const unsigned* p, unsigned target) {
    unsigned n = 0;
    while ((int)(ld_rlx(p) - target) < 0 && ++n < SPIN_LIMIT) __nanosleep(20);
}
__device__ __forceinline__ void red_hint(unsigned* p) { asm volatile("red.relaxed.gpu.global.add.u32 [%0], 1;" ::"l"(p) : "memory"); }
__device__ __forceinline__ void fence_async() { asm volatile("fence.proxy.async.global;" ::: "memory"); }
__device__ __forceinline__ void fence_async_sm() { asm volatile("fence.proxy.async.shared::cta;" ::: "memory"); }
#define bar_sync(id, n) asm volatile("bar.sync %0, %1;" ::"n"(id), "n"(n) : "memory")
#define bar_arrive(id, n) asm volatile("bar.arrive %0, %1;" ::"n"(id), "n"(n) : "memory")
__device__ __forceinline__ bool elect_one() {
    uint32_t r;
    asm volatile("{.reg .pred p; elect.sync _|p, 0xffffffff; selp.u32 %0, 1, 0, p;}" : "=r"(r));
    return r != 0;
}

__device__ __forceinline__ void tma2d(uint32_t dst, const CUtensorMap* m, int c0, int c1, uint32_t bar) {
    asm volatile("cp.async.bulk.tensor.2d.shared::cluster.global.mbarrier::complete_tx::bytes [%0], [%1, {%3,%4}], [%2];" ::"r"(dst), "l"(m), "r"(bar), "r"(c0), "r"(c1) : "memory");
}
__device__ __forceinline__ void tma4d(uint32_t dst, const CUtensorMap* m, int c0, int c1, int c2, int c3, uint32_t bar) {
    asm volatile("cp.async.bulk.tensor.4d.shared::cluster.global.mbarrier::complete_tx::bytes [%0], [%1, {%3,%4,%5,%6}], [%2];" ::"r"(dst), "l"(m), "r"(bar), "r"(c0), "r"(c1), "r"(c2), "r"(c3) : "memory");
}
__device__ __forceinline__ void tma4d_mc(uint32_t dst, const CUtensorMap* m, int c0, int c3, uint32_t bar) {
    asm volatile("cp.async.bulk.tensor.4d.shared::cluster.global.mbarrier::complete_tx::bytes.multicast::cluster [%0], [%1, {%3,%6,%6,%4}], [%2], %5;" ::"r"(dst), "l"(m), "r"(bar), "r"(c0), "r"(c3), "h"((uint16_t)3), "r"(0) : "memory");
}
__device__ __forceinline__ void tma2d_st(const CUtensorMap* m, int c0, int c1, uint32_t src) {
    asm volatile("cp.async.bulk.tensor.2d.global.shared::cta.bulk_group [%0, {%2,%3}], [%1];" ::"l"(m), "r"(src), "r"(c0), "r"(c1) : "memory");
}
__device__ __forceinline__ void tma5d(uint32_t dst, const CUtensorMap* m, int c0, int c1, int c2, int c3, int c4, uint32_t bar) {
    asm volatile("cp.async.bulk.tensor.5d.shared::cluster.global.mbarrier::complete_tx::bytes [%0], [%1, {%3,%4,%5,%6,%7}], [%2];" ::"r"(dst), "l"(m), "r"(bar), "r"(c0), "r"(c1), "r"(c2), "r"(c3), "r"(c4) : "memory");
}
__device__ __forceinline__ void bulk_ld(uint32_t dst, const void* src, uint32_t n, uint32_t bar) {
    asm volatile("cp.async.bulk.shared::cluster.global.mbarrier::complete_tx::bytes [%0], [%1], %2, [%3];" ::"r"(dst), "l"(src), "r"(n), "r"(bar) : "memory");
}
__device__ __forceinline__ void pf_map(const CUtensorMap* m) { asm volatile("prefetch.tensormap [%0];" ::"l"(m) : "memory"); }
__device__ __forceinline__ void bulk_commit() { asm volatile("cp.async.bulk.commit_group;" ::: "memory"); }
template <int N> __device__ __forceinline__ void bulk_wait_read() { asm volatile("cp.async.bulk.wait_group.read %0;" ::"n"(N) : "memory"); }
__device__ __forceinline__ void stsm4(uint32_t a, uint32_t r0, uint32_t r1, uint32_t r2, uint32_t r3) {
    asm volatile("stmatrix.sync.aligned.m8n8.x4.shared.b16 [%0], {%1,%2,%3,%4};" ::"r"(a), "r"(r0), "r"(r1), "r"(r2), "r"(r3) : "memory");
}
__device__ __forceinline__ void sts128f(uint32_t a, cf u, cf v) {
    asm volatile("st.shared.v4.f32 [%0], {%1,%2,%3,%4};" ::"r"(a), "f"(u.x), "f"(u.y), "f"(v.x), "f"(v.y) : "memory");
}
__device__ __forceinline__ void stg128(const void* a, uint32_t r0, uint32_t r1, uint32_t r2, uint32_t r3) {
    asm volatile("st.global.v4.b32 [%0], {%1,%2,%3,%4};" ::"l"(a), "r"(r0), "r"(r1), "r"(r2), "r"(r3) : "memory");
}
__device__ __forceinline__ void lds128f(uint32_t a, float& x, float& y, float& z, float& u) { asm volatile("ld.shared.v4.f32 {%0,%1,%2,%3}, [%4];" : "=f"(x), "=f"(y), "=f"(z), "=f"(u) : "r"(a) : "memory"); }
__device__ __forceinline__ cf lds_cf(uint32_t a) { cf v; asm volatile("ld.shared.v2.f32 {%0,%1}, [%2];" : "=f"(v.x), "=f"(v.y) : "r"(a) : "memory"); return v; }
__device__ __forceinline__ uint4 ldtab(int word) { return __ldg((const uint4*)(g_tab + word)); }
__device__ __forceinline__ void load_tw(cf (&tw)[8], int k1) {
#pragma unroll
    for (int i = 0; i < 4; i++) {
        const uint4 v = ldtab(TAB_TW + k1 * 16 + i * 4);
        tw[2 * i] = {__uint_as_float(v.x), __uint_as_float(v.y)};
        tw[2 * i + 1] = {__uint_as_float(v.z), __uint_as_float(v.w)};
    }
}
__device__ __forceinline__ void load_T(cf (&T)[8], int t7) {
#pragma unroll
    for (int i = 0; i < 4; i++)
        asm volatile("ld.global.nc.v4.f32 {%0,%1,%2,%3}, [%4];" : "=f"(T[2 * i].x), "=f"(T[2 * i].y), "=f"(T[2 * i + 1].x), "=f"(T[2 * i + 1].y) : "l"(g_tab + TAB_T + i * 512 + t7 * 4));
}
__device__ __forceinline__ uint32_t lds_u16(uint32_t a) { uint32_t v; asm volatile("ld.shared.u16 %0, [%1];" : "=r"(v) : "r"(a)); return v; }
__device__ __forceinline__ float up(uint32_t v) { return __uint_as_float(v << 16); }
__device__ __forceinline__ unsigned get_epoch(uint32_t bars) {
    mbar_wait(bars + B_EP, 0);
    unsigned e;
    asm volatile("ld.shared.u32 %0, [%1];" : "=r"(e) : "r"(bars + B_EPOCH) : "memory");
    return e;
}
__device__ __forceinline__ void sts64f(uint32_t a, float x, float y) { asm volatile("st.shared.v2.f32 [%0], {%1,%2};" ::"r"(a), "f"(x), "f"(y) : "memory"); }
__device__ __forceinline__ uint32_t pk(float lo, float hi) { uint32_t r; asm("cvt.rn.bf16x2.f32 %0, %1, %2;" : "=r"(r) : "f"(hi), "f"(lo)); return r; }
__device__ __forceinline__ uint32_t bitsel(uint32_t a, uint32_t m, uint32_t b) {
    uint32_t r;
    asm("lop3.b32 %0, %1, %2, %3, 0xea;" : "=r"(r) : "r"(a), "r"(m), "r"(b));
    return r;
}

__host__ __device__ constexpr uint64_t mkdesc(uint32_t off, uint32_t lbo, uint32_t sbo, uint32_t swz) {
    return (uint64_t)((SB0 + off) >> 4) | ((uint64_t)(lbo >> 4) << 16) | ((uint64_t)(sbo >> 4) << 32) | ((uint64_t)swz << 62);
}
__device__ __forceinline__ void wg_fence() { asm volatile("wgmma.fence.sync.aligned;" ::: "memory"); }
__device__ __forceinline__ void wg_commit() { asm volatile("wgmma.commit_group.sync.aligned;" ::: "memory"); }
template <int N> __device__ __forceinline__ void wg_wait() { asm volatile("wgmma.wait_group.sync.aligned %0;" ::"n"(N) : "memory"); }
template <int N> __device__ __forceinline__ void pin(float (&d)[N]) {
#pragma unroll
    for (int i = 0; i < N; i++) asm volatile("" : "+f"(d[i])::"memory");
}
template <int N> __device__ __forceinline__ void pinu(uint32_t (&d)[N]) {
#pragma unroll
    for (int i = 0; i < N; i++) asm volatile("" : "+r"(d[i])::"memory");
}

#define R8(d, o) "+f"(d[o]), "+f"(d[o + 1]), "+f"(d[o + 2]), "+f"(d[o + 3]), "+f"(d[o + 4]), "+f"(d[o + 5]), "+f"(d[o + 6]), "+f"(d[o + 7])
#define L8 "%0,%1,%2,%3,%4,%5,%6,%7"
#define L24 L8 ",%8,%9,%10,%11,%12,%13,%14,%15,%16,%17,%18,%19,%20,%21,%22,%23"
#define L32 L24 ",%24,%25,%26,%27,%28,%29,%30,%31"
#define L64 L32 ",%32,%33,%34,%35,%36,%37,%38,%39,%40,%41,%42,%43,%44,%45,%46,%47,%48,%49,%50,%51,%52,%53,%54,%55,%56,%57,%58,%59,%60,%61,%62,%63"

template <int O, int TA, int TB, int SC, int N> __device__ __forceinline__ void mma128_ss(float (&d)[N], uint64_t da, uint64_t db) {
    asm volatile("wgmma.mma_async.sync.aligned.m64n128k16.f32.bf16.bf16 {" L64 "}, %64, %65, %66, 1, 1, %67, %68;"
                 : R8(d, O), R8(d, O + 8), R8(d, O + 16), R8(d, O + 24), R8(d, O + 32), R8(d, O + 40), R8(d, O + 48), R8(d, O + 56)
                 : "l"(da), "l"(db), "n"(SC), "n"(TA), "n"(TB));
}
#define W8(d, o) "=f"(d[o]), "=f"(d[o + 1]), "=f"(d[o + 2]), "=f"(d[o + 3]), "=f"(d[o + 4]), "=f"(d[o + 5]), "=f"(d[o + 6]), "=f"(d[o + 7])
__device__ __forceinline__ void mma128_first(float (&d)[64], uint64_t da, uint64_t db) {
    asm volatile("wgmma.mma_async.sync.aligned.m64n128k16.f32.bf16.bf16 {" L64 "}, %64, %65, 0, 1, 1, 0, 1;"
                 : W8(d, 0), W8(d, 8), W8(d, 16), W8(d, 24), W8(d, 32), W8(d, 40), W8(d, 48), W8(d, 56) : "l"(da), "l"(db));
}
template <int TB, int SC> __device__ __forceinline__ void mma128_rs(float (&d)[64], const uint32_t* a, uint64_t db) {
    asm volatile("wgmma.mma_async.sync.aligned.m64n128k16.f32.bf16.bf16 {" L64 "}, {%64,%65,%66,%67}, %68, %69, 1, 1, %70;"
                 : R8(d, 0), R8(d, 8), R8(d, 16), R8(d, 24), R8(d, 32), R8(d, 40), R8(d, 48), R8(d, 56)
                 : "r"(a[0]), "r"(a[1]), "r"(a[2]), "r"(a[3]), "l"(db), "n"(SC), "n"(TB));
}
template <int TB, int SC> __device__ __forceinline__ void mma64_rs(float (&d)[32], const uint32_t* a, uint64_t db) {
    asm volatile("wgmma.mma_async.sync.aligned.m64n64k16.f32.bf16.bf16 {" L32 "}, {%32,%33,%34,%35}, %36, %37, 1, 1, %38;"
                 : R8(d, 0), R8(d, 8), R8(d, 16), R8(d, 24)
                 : "r"(a[0]), "r"(a[1]), "r"(a[2]), "r"(a[3]), "l"(db), "n"(SC), "n"(TB));
}
template <int TA, int SC> __device__ __forceinline__ void mma64_ss(float (&d)[32], uint64_t da, uint64_t db) {
    asm volatile("wgmma.mma_async.sync.aligned.m64n64k16.f32.bf16.bf16 {" L32 "}, %32, %33, %34, 1, 1, %35, 1;"
                 : R8(d, 0), R8(d, 8), R8(d, 16), R8(d, 24)
                 : "l"(da), "l"(db), "n"(SC), "n"(TA));
}
template <int SC> __device__ __forceinline__ void mma48_ss(float (&d)[32], uint64_t da, uint64_t db) {
    asm volatile("wgmma.mma_async.sync.aligned.m64n48k16.f32.bf16.bf16 {" L24 "}, %24, %25, %26, 1, 1, 0, 1;"
                 : R8(d, 8), R8(d, 16), R8(d, 24)
                 : "l"(da), "l"(db), "n"(SC));
}
template <int SC> __device__ __forceinline__ void mma16_rs(float (&d)[32], uint32_t a0, uint32_t a1, uint32_t a2, uint32_t a3, uint64_t db) {
    asm volatile("wgmma.mma_async.sync.aligned.m64n16k16.f32.bf16.bf16 {" L8 "}, {%8,%9,%10,%11}, %12, %13, 1, 1, 1;"
                 : R8(d, 0)
                 : "r"(a0), "r"(a1), "r"(a2), "r"(a3), "l"(db), "n"(SC));
}

__device__ __forceinline__ cf cmul(cf a, cf b) { return {fmaf(a.x, b.x, -a.y * b.y), fmaf(a.x, b.y, a.y * b.x)}; }
__device__ __forceinline__ cf csq(cf a) { return {fmaf(a.x, a.x, -a.y * a.y), (a.x + a.x) * a.y}; }
__device__ __forceinline__ cf cmulc(cf a, cf b) { return {fmaf(a.x, b.x, a.y * b.y), fmaf(a.y, b.x, -a.x * b.y)}; }
__device__ __forceinline__ cf cfma(cf a, cf b, cf c) { return {fmaf(a.x, b.x, fmaf(-a.y, b.y, c.x)), fmaf(a.x, b.y, fmaf(a.y, b.x, c.y))}; }
__device__ __forceinline__ cf csel(int c, cf a, cf b) {
    cf r;
    asm("{.reg .pred p; setp.ne.s32 p, %6, 0; selp.f32 %0, %2, %4, p; selp.f32 %1, %3, %5, p;}" : "=f"(r.x), "=f"(r.y) : "f"(a.x), "f"(a.y), "f"(b.x), "f"(b.y), "r"(c));
    return r;
}
__device__ __forceinline__ cf cadd(cf a, cf b) { return {a.x + b.x, a.y + b.y}; }
__device__ __forceinline__ cf csub(cf a, cf b) { return {a.x - b.x, a.y - b.y}; }
__device__ __forceinline__ cf twice_minus(cf a, cf s) { return {fmaf(2.f, a.x, -s.x), fmaf(2.f, a.y, -s.y)}; }
struct v2 { float a, b; };
struct c2 { v2 x, y; };
#define OP2(name, args, txt, ...) \
    __device__ __forceinline__ v2 name args { v2 r; asm volatile(txt : "=f"(r.a) : __VA_ARGS__(a)); asm volatile(txt : "=f"(r.b) : __VA_ARGS__(b)); return r; }
#define A_XY(e) "f"(x.e), "f"(y.e)
#define A_XYZ(e) "f"(x.e), "f"(y.e), "f"(z.e)
OP2(add2, (v2 x, v2 y), "add.rn.f32 %0, %1, %2;", A_XY)
OP2(sub2, (v2 x, v2 y), "sub.rn.f32 %0, %1, %2;", A_XY)
OP2(mul2, (v2 x, v2 y), "mul.rn.f32 %0, %1, %2;", A_XY)
OP2(tw2, (v2 x, v2 y), "{.reg .f32 n; neg.f32 n, %2; fma.rn.f32 %0, %1, 0f40000000, n;}", A_XY)
OP2(fma2, (v2 x, v2 y, v2 z), "fma.rn.f32 %0, %1, %2, %3;", A_XYZ)
OP2(fms2, (v2 x, v2 y, v2 z), "{.reg .f32 n; neg.f32 n, %3; fma.rn.f32 %0, %1, %2, n;}", A_XYZ)
OP2(fnm2, (v2 x, v2 y, v2 z), "{.reg .f32 n; neg.f32 n, %1; fma.rn.f32 %0, n, %2, %3;}", A_XYZ)
__device__ __forceinline__ c2 both(cf a) { return {{a.x, a.x}, {a.y, a.y}}; }
__device__ __forceinline__ c2 tw2(c2 a, c2 s) { c2 r; r.x = tw2(a.x, s.x); r.y = tw2(a.y, s.y); return r; }
template <bool CJ> __device__ __forceinline__ c2 cmul2(c2 a, c2 t) {
    const v2 p = mul2(a.y, t.y), q = mul2(a.x, t.y);
    c2 r;
    r.x = CJ ? fma2(a.x, t.x, p) : fms2(a.x, t.x, p);
    r.y = CJ ? fms2(a.y, t.x, q) : fma2(a.y, t.x, q);
    return r;
}
template <bool CJ> __device__ __forceinline__ c2 cfma2(c2 a, c2 t, c2 c) {
    const v2 p = CJ ? fma2(a.y, t.y, c.x) : fnm2(a.y, t.y, c.x), q = CJ ? fnm2(a.x, t.y, c.y) : fma2(a.x, t.y, c.y);
    c2 r;
    r.x = fma2(a.x, t.x, p);
    r.y = fma2(a.y, t.x, q);
    return r;
}
__device__ __forceinline__ void bfly2(c2 a, c2 b, c2& s, c2& d) { s.x = add2(a.x, b.x); d.x = sub2(a.x, b.x); s.y = add2(a.y, b.y); d.y = sub2(a.y, b.y); }
__device__ __forceinline__ void bflyi2(c2 a, c2 b, c2& s, c2& d) { s.x = add2(a.x, b.y); d.x = sub2(a.x, b.y); s.y = sub2(a.y, b.x); d.y = add2(a.y, b.x); }
__device__ __forceinline__ uint32_t pkv(float lo, float hi) { uint32_t r; asm volatile("cvt.rn.bf16x2.f32 %0, %1, %2;" : "=r"(r) : "f"(hi), "f"(lo)); return r; }
__device__ __forceinline__ uint32_t pkv(v2 v) { return pkv(v.a, v.b); }
__device__ __forceinline__ float upv(uint32_t v) { float r; asm volatile("shl.b32 %0, %1, 16;" : "=f"(r) : "r"(v)); return r; }
__device__ __forceinline__ cf twid(int m, int M) {
    int r = ((m + M / 2) & (M - 1)) - M / 2;
    float s, c;
    __sincosf((float)r * (-6.283185307179586f / (float)M), &s, &c);
    return {c, s};
}
template <int YL, class F> __device__ __forceinline__ void dft8_end(const c2 (&e)[4], c2 a4, c2 a5, c2 a6, c2 a7, F out) {
    const v2 s = {0.70710678118654752f, 0.70710678118654752f};
    c2 o0, o1, o2, o3, u, v;
    bfly2(a4, a6, o0, o2);
    YLD(YL, 4);
    bfly2(e[0], o0, u, v);
    out(0, u, v);
    YLD(YL, 2);
    bflyi2(e[2], o2, u, v);
    out(2, u, v);
    YLD(YL, 4);
    bflyi2(a5, a7, o1, o3);
    YLD(YL, 1);
    o0.x = add2(o1.y, o1.x); o0.y = sub2(o1.y, o1.x);
    u.x = fma2(o0.x, s, e[1].x); v.x = fnm2(o0.x, s, e[1].x); u.y = fma2(o0.y, s, e[1].y); v.y = fnm2(o0.y, s, e[1].y);
    out(1, u, v);
    YLD(YL, 2);
    o2.x = sub2(o3.y, o3.x); o2.y = add2(o3.y, o3.x);
    u.x = fma2(o2.x, s, e[3].x); v.x = fnm2(o2.x, s, e[3].x); u.y = fnm2(o2.y, s, e[3].y); v.y = fma2(o2.y, s, e[3].y);
    out(3, u, v);
    YLD(YL, 1);
}

__device__ __forceinline__ void bid2tile(int b, int& tc, int& cb) {
    const int c = b >> 1, e = c - 36, t7 = (e * 37) >> 8;
    int g;
    asm("{.reg .pred p, q; setp.lt.s32 p, %2, 4; setp.lt.s32 q, %2, 36; selp.s32 %0, %3, %4, q; selp.s32 %1, %5, %6, q; selp.s32 %0, 0, %0, p; selp.s32 %1, %7, %1, p;}"
        : "=&r"(g), "=&r"(cb) : "r"(c), "r"((c + 4) & 7), "r"(1 + e - 7 * t7), "r"((c - 4) >> 3), "r"(4 + t7), "r"(4 + c));
    tc = 2 * g + (b & 1);
}
__host__ __device__ __forceinline__ int pos_of(int n) { return (n & 24) + 4 * (n & 1) + ((n >> 1) & 3); }
static int kappa_of(int b, int gi) {
    const int r = b >> 4, k1 = 2 * ((b & 15) ^ (4 * gi)) + gi;
    return b >= 128 ? gi * 256 : (k1 || r < 4 ? k1 + 64 * r : 64 * r - 224);
}
static int slot3_of(int kap, int& cj) {
    int m = kap & 15;
    cj = (m > 8) || ((m & 7) == 0 && kap > 256);
    const int kk = cj ? 512 - kap : kap;
    m = kk & 15;
    return kk == 256 ? 0 : (m & 1) * 128 + (m & 6) * 16 + pos_of((kk >> 4) + 2 * (m & 8));
}

__device__ __forceinline__ uint32_t tag_bad(uint32_t a, uint32_t tag) {
    uint32_t v;
    asm volatile("ld.shared.u32 %0, [%1];" : "=r"(v) : "r"(a) : "memory");
    return (v ^ tag) & 1;
}
__device__ __forceinline__ bool wg_all_ok(uint32_t bad, int id) {
    uint32_t ok;
    asm volatile("{.reg .pred p, q; setp.eq.u32 q, %1, 0; barrier.red.and.aligned.pred p, %2, 128, q; selp.u32 %0, 1, 0, p;}" : "=r"(ok) : "r"(bad), "r"(id) : "memory");
    return __all_sync(~0u, ok);
}

__device__ __forceinline__ uint32_t lines_bad(uint32_t va, uint32_t tag, uint32_t bit) {
    uint32_t bad;
    asm volatile("{.reg .b32 a, b, c, d;\n"
                 "ld.shared.u32 a, [%1]; ld.shared.u32 b, [%1+4096]; ld.shared.u32 c, [%1+8192]; ld.shared.u32 d, [%1+12288];\n"
                 "lop3.b32 a, a, b, %2, 0x7e; lop3.b32 c, c, d, %2, 0x7e; lop3.b32 %0, a, c, %3, 0xa8;}"
                 : "=r"(bad) : "r"(va), "r"(tag), "r"(bit) : "memory");
    return bad;
}
__device__ __forceinline__ void load_w(uint32_t sb, const CUtensorMap* m, int kap, uint32_t more) {
    mbar_expect_tx(sb + OFF_BAR + B_WIN, 16 * WPITCH + more);
#pragma unroll 1
    for (int i = 0; i < 4; i++) {
        if (i) __nanosleep(PACE_W);
        tma2d(sb + OFF_W + i * (4 * WPITCH), m + (i & 1), ((i & 2 ? (512 - kap) & 511 : kap) * 1026 >> 4) * 2, 0, sb + OFF_BAR + B_WIN);
    }
}
__device__ __forceinline__ void carry_poll(unsigned __int128 (&f)[4], const uint4* a, int n, uint32_t tag) {
    f[0] = f[1] = f[2] = f[3] = tag;
    asm volatile("{.reg .pred p<4>;\n"
                 "setp.ge.s32 p0, %5, 0; setp.ge.s32 p1, %5, 4; setp.ge.s32 p2, %5, 8; setp.ge.s32 p3, %5, 12;\n"
                 "@p0 ld.relaxed.gpu.global.b128 %0, [%4];\n"
                 "@p1 ld.relaxed.gpu.global.b128 %1, [%4+-32768];\n"
                 "@p2 ld.relaxed.gpu.global.b128 %2, [%4+-65536];\n"
                 "@p3 ld.relaxed.gpu.global.b128 %3, [%4+-98304];}"
                 : "+q"(f[0]), "+q"(f[1]), "+q"(f[2]), "+q"(f[3]) : "l"(a), "r"(n) : "memory");
}
__device__ __forceinline__ uint32_t carry_sum(const unsigned __int128 (&f)[4], const cf (&m4)[2], uint32_t tag, cf (&P)[2]) {
#pragma unroll
    for (int h = 0; h < 2; h++)
#pragma unroll
        for (int a = 3; a >= 0; a--) {
            const cf v = {__uint_as_float((uint32_t)(f[a] >> (64 * h))), __uint_as_float((uint32_t)(f[a] >> (64 * h + 32)))};
            P[h] = a == 3 ? v : cfma(m4[h], P[h], v);
        }
    return (((uint32_t)f[0] ^ tag) | ((uint32_t)f[1] ^ tag) | ((uint32_t)f[2] ^ tag) | ((uint32_t)f[3] ^ tag)) & 15u;
}

struct Ring {
    uint32_t full, rel;
    uint32_t ph, bh;
    uint64_t da;
    bool sig;
    uint32_t k;
};
__device__ __forceinline__ void ring_release(const Ring& r, int slot) {
    if (r.sig) asm volatile("mbarrier.arrive.shared::cluster.b64 _, [%0];" ::"r"(r.rel + 8 * slot) : "memory");
}
__device__ __forceinline__ void ring_wait(Ring& r, int slot) {
    if (slot == 0) r.ph ^= 1;
    mbar_wait(r.full + 8 * slot, r.ph);
}
template <int SLOT, int TA, int HF, int J> __device__ __forceinline__ void mma_g(float (&d)[128], const Ring& r, int sc) {
    constexpr int O = 64 * HF;
    asm volatile("{.reg .b64 da, db; .reg .b32 l; .reg .pred p; setp.ne.s32 p, %67, 0; add.u64 da, %64, %69; mov.b32 l, %65; mov.b64 db, {l,%66};\n"
                 "wgmma.mma_async.sync.aligned.m64n128k16.f32.bf16.bf16 {" L64 "}, da, db, p, 1, 1, %68, 0;}"
                 : R8(d, O), R8(d, O + 8), R8(d, O + 16), R8(d, O + 24), R8(d, O + 32), R8(d, O + 40), R8(d, O + 48), R8(d, O + 56)
                 : "l"(r.da), "n"((uint32_t)mkdesc(SLOT * 32768 + 16384 + J * 32, 16, 0, 0)), "r"(r.bh), "r"(sc), "n"(TA),
                   "n"(1 + SLOT * 2048 + (TA ? HF * 64 + J * 256 : HF * 512 + J * 2)));
}
static_assert((GRP >> HAND & 1) && (GRP >> 7 & 1), "hand-over at the end of a group");
template <int SLOT, int TA, int I, int BAR> __device__ __forceinline__ void gemm_mmas(float (&d)[128], Ring& r, int sc, bool last) {
    mma_g<SLOT, TA, I & 1, I / 2>(d, r, I < 2 ? sc : 1);
    constexpr int G = TA ? GRP2 : GRP;
    if (G >> I & 1) {
        wg_commit();
        if (BAR && I == HAND) asm volatile("{.reg .pred p; setp.ne.s32 p, %1, 0; @p bar.arrive %0, 256;}" ::"n"(BAR), "r"((int)last) : "memory");
        wg_wait<1>();
        if ((G & (1 << I) - 1) == 0 && sc) ring_release(r, (SLOT + NST - 1) % NST);
    }
    if constexpr (I < 7) gemm_mmas<SLOT, TA, I + 1, BAR>(d, r, sc, last);
}
template <int SLOT, int TA, int BAR = 0> __device__ __forceinline__ void gemm_step(float (&d)[128], Ring& r, int sc, bool last = false) {
    ring_wait(r, SLOT);
    wg_fence();
    gemm_mmas<SLOT, TA, 0, BAR>(d, r, sc, last);
}
template <int K, int HF> __device__ __forceinline__ void gemm_half(float (&d)[128], Ring& r) {
    if (HF == 0) { ring_wait(r, K % NST); wg_fence(); }
    mma_g<K % NST, 1, HF, 0>(d, r, 1); mma_g<K % NST, 1, HF, 1>(d, r, 1); mma_g<K % NST, 1, HF, 2>(d, r, 1); mma_g<K % NST, 1, HF, 3>(d, r, 1);
    if constexpr (HF == 0 && K < 64 - SKEW) { mma_g<K % NST, 1, 1, 0>(d, r, 1); mma_g<K % NST, 1, 1, 1>(d, r, 1); mma_g<K % NST, 1, 1, 2>(d, r, 1); mma_g<K % NST, 1, 1, 3>(d, r, 1); }
    if constexpr (K < 63) gemm_half<K + 1, HF>(d, r);
}
struct Prod {
    uint32_t b0, b1, b2, b3, b4, dbase;
    unsigned* prof;
    __device__ __forceinline__ Prod(uint32_t sb, int slot, uint32_t off) {
        const uint32_t bars = sb + OFF_BAR;
        b0 = bars + slot % NST * 8; b1 = bars + (slot + 1) % NST * 8; b2 = bars + (slot + 2) % NST * 8; b3 = bars + (slot + 3) % NST * 8; b4 = bars + (slot + 4) % NST * 8;
        dbase = sb + off - bars * 4096;
    }
    __device__ __forceinline__ uint32_t dst() const { return b0 * 4096 + dbase; }
    __device__ __forceinline__ void next() { const uint32_t t = b0; b0 = b1; b1 = b2; b2 = b3; b3 = b4; b4 = t; }
};
__device__ __forceinline__ void load_shared(Prod& r, uint32_t ph, const CUtensorMap* m, int c0, int c3) {
    uint32_t dst = r.dst();
    asm volatile("pmevent 0;" : "+r"(dst), "+r"(c0), "+r"(c3), "+l"(m));
    mbar_wait(r.b0 + B_EMPTY, ph);
    tma4d_mc(dst, m, c0, c3, r.b0);
    YIELD();
    r.next();
}
__host__ __device__ constexpr uint64_t phases_from(int k) {
    uint64_t v = 0;
    for (int i = 0; i < 64; i++) v |= (uint64_t)((k + i) / NST & 1) << i;
    return v;
}
__device__ __forceinline__ uint32_t phases(int k, int n) { return ((uint32_t)(phases_from(0) >> k) & ((1u << n) - 1)) | 1u << n; }

__global__ void __cluster_dims__(2, 1, 1) __launch_bounds__(512, 1)
fused_kernel(const __grid_constant__ Maps tm, const __grid_constant__ Params p) {
    const CUtensorMap &tmX = tm.m[0], &tmBre = tm.m[1], &tmBim = tm.m[2], &tmXA = tm.m[5], &tmUst = tm.m[6], &tmVst = tm.m[7], &tmWr = tm.m[8], &tmVld = tm.m[10];
    extern __shared__ __align__(1024) uint8_t smraw[];
    const uint32_t sb = smem_u32(smraw);
    const uint32_t bars = sb + OFF_BAR;
    const int bid = blockIdx.x;
    const bool extra = bid >= 128;
    if (threadIdx.x == 480) RECL(0);
    int tc, cb;
    if (threadIdx.x < 32) {
        if (elect_one()) {
            pf_map(&tmX);
            pf_map(&tmBre);
            pf_map(&tmBim);
#pragma unroll
            for (int s = 0; s < NST; s++) mbar_init(bars + B_FULL + s * 8, 33);
            asm volatile("fence.mbarrier_init.release.cluster;" ::: "memory");
            bid2tile(bid, tc, cb);
            mbar_expect_tx(bars + B_FULL, 32768);
            tma5d(sb + 16384, &tmX, 0, 0, 0, 0, tc, bars + B_FULL);
            tma4d(sb, &tmBre, 0, 0, 0, cb * 4, bars + B_FULL);
            tma4d(sb + 8192, &tmBim, 0, 0, 0, cb * 4, bars + B_FULL);
            asm volatile("mbarrier.arrive.shared::cta.b64 _, [%0], 32;" ::"r"(bars + B_FULL) : "memory");
            STAMP(56);
        }
        __syncwarp();
    }
    const int wid = __shfl_sync(~0u, threadIdx.x >> 5, 0);
    if (wid == 1) {
        if (elect_one()) {
#pragma unroll
            for (int o = B_EMPTY; o < B_END; o += 8) mbar_init(bars + o, o < B_STGU ? 2 : (o == B_STGU ? 8 : (o < B_EP ? 4 : 1)));
            asm volatile("fence.mbarrier_init.release.cluster;" ::: "memory");
        }
        __syncwarp();
    }
    const int wg = ((wid >> 2) + 3) & 3, w = wid & 3;
    const int fb = bid >> 5, fcb = bid & 31, fpos = pos_of(fcb);
    const int vrow = ((bid & ~3) | (bid & 1) << 1 | (bid >> 1 & 1)) * 256;
    bid2tile(bid, tc, cb);
    asm volatile("barrier.cluster.arrive.relaxed.aligned;" ::: "memory");

    if (wg == 3) {
        asm volatile("setmaxnreg.dec.sync.aligned.u32 24;");
        if (w == 0) {
            if (extra) mbar_wait(bars + B_FULL, 0);
            else if (KMC > 1 && elect_one()) {
#pragma unroll 1
                for (int k = 1 + (bid >> 8); k < KMC; k++) {
                    mbar_expect_tx(bars + B_FULL + k * 8, 32768);
                    tma5d(sb + k * 32768 + 16384, &tmX, k * 64, 0, 0, 0, tc, bars + B_FULL + k * 8);
                    tma4d(sb + k * 32768, &tmBre, k * 64, 0, 0, cb * 4, bars + B_FULL + k * 8);
                    tma4d(sb + k * 32768 + 8192, &tmBim, k * 64, 0, 0, cb * 4, bars + B_FULL + k * 8);
                    asm volatile("mbarrier.arrive.shared::cta.b64 _, [%0], 32;" ::"r"(bars + B_FULL + k * 8) : "memory");
                }
                STAMP(28);
            }
            __syncwarp();
        }
        asm volatile("barrier.cluster.wait.aligned;" ::: "memory");
        if (bid == 129 || (sb & 0x3FFFF) != SB0) return;
        if (w < 2) {
            if (extra || !elect_one()) return;
            const int rank = bid & 1;
            if (w == 0) {
                Prod r(sb, KMC, 16384);
                int c0 = 64 * KMC;
#pragma unroll 1
                for (uint32_t pat = phases(NST + KMC, 32 - KMC); pat != 1; pat >>= 1) {
                    uint32_t dst = r.dst();
                    asm volatile("pmevent 0;" : "+r"(dst));
                    mbar_wait(r.b0 + B_EMPTY, pat);
                    if (c0 >= 0) tma5d(dst, &tmX, c0, 0, 0, 0, tc, r.b0);
                    mbar_expect_tx(r.b0, c0 >= 0 ? 32768 : 16384);
                    asm volatile("mbarrier.arrive.shared::cta.b64 _, [%0], 32;" ::"r"(r.b0) : "memory");
                    c0 = c0 == 960 ? -64 * NST : c0 + 64;
                    r.next();
                }
                r.dbase -= 16384;
                const uint8_t* src = g_H + (size_t)tc * (32 * 16384);
                uint32_t all = (uint32_t)phases_from(32 - NST);
#pragma unroll 1
                for (int hh = 0; hh < 4; hh++) {
                    uint32_t pat = (all & 255) | 256;
                    all >>= 8;
                    if (PPOLL >> hh & 1) wait_cnt(g_hcnt + tc * 64 + hh * 16, 32 * get_epoch(bars) - EARLY_H);
                    else mbar_wait(bars + B_HGO + 8 * hh, 0);
                    STAMPR(45 + hh);
#pragma unroll 1
                    do {
                        uint32_t dst = r.dst(), hb = r.b0 + B_HLD;
                        asm volatile("pmevent 0;" : "+r"(dst), "+r"(hb));
                        mbar_wait(r.b0 + B_EMPTY, pat);
                        bulk_ld(dst, src, 16384, hb);
                        YIELD();
                        mbar_expect_tx(r.b0 + B_HLD, 16384);
                        mbar_expect_tx(r.b0, 16384);
                        src += 16384;
                        r.next();
                        pat >>= 1;
                    } while (pat != 1);
                }
            } else {
                Prod r(sb, KMC, rank * 8192);
                int c = 64 * KMC;
#pragma unroll 1
                for (uint32_t pat = phases(NST + KMC, 32 - KMC); pat != 1; pat >>= 1) {
                    load_shared(r, pat, &tmBre + rank, c & 1023, cb * 4 + ((c >> 5) & 64));
                    c += c == 960 ? 2112 - 64 * NST : 64;
                }
                r.dbase += 16384;
                uint32_t pat = (uint32_t)phases_from(32 - NST);
#pragma unroll 1
                for (c = 0; c != 1024; c += 64) {
                    load_shared(r, pat, &tmBre + 2, c, cb * 8 + rank * 4);
                    load_shared(r, pat >> 1, &tmBre + 3, c, cb * 8 + rank * 4);
                    pat >>= 2;
                }
                mbar_arrive(bars + B_LDONE);
            }
        } else if (w == 2) {
            if (!elect_one()) return;
            STAMP5(39);
            if (!extra) {
                mbar_expect_tx(bars + B_XIN, 16384);
                mbar_expect_tx(bars + B_XIN + 8, 16384);
#pragma unroll 1
                for (int i = 0; i < 8; i++) {
                    const int k = i - XA_FIRST + XA_AT;
                    if (i >= XA_FIRST) mbar_wait(bars + B_EMPTY + (k < NST ? k : k - NST) * 8, k >= NST);
                    tma4d(sb + OFF_P + i * 2048, &tmXA, fcb * 32, 0, ((2 * i) & 7) + (i >> 2), fb, bars + B_XIN + (i & 4) * 2);
                    tma4d(sb + OFF_P + 16384 + i * 2048, &tmXA, fcb * 32 + 16, 0, ((2 * i) & 7) + (i >> 2), fb, bars + B_XIN + (i & 4) * 2);
                    if (!i) STAMP5(30);
                    STAMP5(31);
                }
            }
            pf_map(&tmWr);
            pf_map(&tmWr + 1);
            const unsigned ep = get_epoch(bars);
            if (!extra) mbar_wait(bars + B_XIN + 8, 0);
            STAMP5(32);
            load_w(sb, &tmWr, p.unit[2 * bid] & 0xffff, 8192);
            pf_map(&tmUst);
            if (!extra) mbar_wait(bars + B_STGU, 0);
            STAMP(21);
#pragma unroll 1
            for (int gi = 0; gi < 2; gi++) {
                if (!extra) {
#pragma unroll 1
                    for (int r = 128 * gi; r < 128 * gi + 128; r += UBOX) {
                        if (gi) __nanosleep(PACE_U);
                        tma2d_st(&tmUst, fb * 2048 + fpos * 64, r, sb + OFF_P + r * 128);
                        bulk_commit();
                    }
                    bulk_wait_read<HINT_U>();
                    red_hint(g_cnt + gi * 32);
                }
                if (!gi) bulk_ld(sb + OFF_F, g_tab + TAB_FG, 8192, bars + B_WIN);
                bulk_wait_read<0>();
                STAMPR(40 + gi);
                wait_cnt(g_cnt + 32 * gi, 128 * ep - (gi ? 0 : EARLY_U));
                {
                    if (gi) __nanosleep(UDELAY);
                    else STAMP(42);
                    mbar_expect_tx(bars + B_UIN + 8 * gi, 16384);
                    bulk_ld(sb + OFF_P + gi * 16384, g_U + (size_t)(extra ? 0 : bid + 128 * gi) * 16384, 16384, bars + B_UIN + 8 * gi);
                }
            }
            pf_map(&tmBre + 2); pf_map(&tmBre + 3); pf_map(&tmVst); pf_map(&tmVld);
            mbar_wait(bars + B_WFREE, 0);
            load_w(sb, &tmWr, p.unit[2 * bid + 1] & 0xffff, 0);
#pragma unroll 1
            for (int gi = 0; gi < 2; gi++) {
                const int vc = ((p.unit[2 * bid + gi] >> 16) & 255) * 64, go = vc >> 13;
                const uint32_t src = extra ? sb + 32768 : sb + OFF_P + gi * 16384;
                mbar_wait(bars + B_STG, gi);
                STAMPR(23 + gi);
                if (extra && !gi) continue;
                if (bid + gi != 0) {
#pragma unroll 1
                    for (int r = 0; r < 128; r += 32) {
                        if (r && !gi) __nanosleep(PACE_V);
                        tma2d_st(&tmVst, vc, r, src + r * 128);
                        bulk_commit();
                    }
                }
                bulk_wait_read<HINT_V>();
                red_hint(g_cnt + 64 + 32 * go);
                bulk_wait_read<0>();
                STAMP(49);
                if (extra) break;
                wait_cnt(g_cnt + 64 + 32 * gi, (129 - gi) * ep - gi * EARLY_V);
                {
                    STAMPR(43 + gi);
#pragma unroll
                    for (int h = 0; h < 2; h++) {
                        mbar_expect_tx(bars + B_VIN + gi * 16 + h * 8, 8192);
                        tma2d(src + h * 8192, &tmVld, h * 32, vrow + gi * 128, bars + B_VIN + gi * 16 + h * 8);
                    }
                }
                if (XT && !gi) {
                    mbar_wait(bars + B_WFREE, 1);
                    mbar_expect_tx(bars + B_WIN, 16384);
#pragma unroll 1
                    for (int i = 0; i < 4; i++) {
                        tma2d(sb + OFF_W + i * 4096, tm.m + 11, cb * 128, tc * 128 + 32 * i + 16, bars + B_WIN);
                    }
                }
            }
        } else {
            const uint32_t tag = ld_rlx(g_epoch + bid * 8) + 1;
            __syncwarp();
            if (elect_one()) {
                asm volatile("st.shared.u32 [%0], %1;" ::"r"(bars + B_EPOCH), "r"(tag) : "memory");
                mbar_arrive(bars + B_EP);
                asm volatile("st.relaxed.gpu.global.u32 [%0], %1;" ::"l"(g_epoch + bid * 8), "r"(tag) : "memory");
            }
            __syncwarp();
            if (extra) return;
            const int lane = (threadIdx.x + p.zero[0]) & 31;
            Prod r(sb, 32, 0);
            uint32_t va = (lane & 3) * 516 + (lane >> 4) * 2048 + (lane & 12) * 32 + (lane >> 2) * 16 + r.dbase;
            asm volatile("" : "+r"(va));
            uint32_t n = 0;
#pragma unroll 1
            for (int half = 0; half < 2; half++) {
#pragma unroll 1
                for (uint32_t pat = phases(16 * half, 16); pat != 1; pat >>= 1) {
                    uint32_t la = r.b0 * 4096 + va;
                    asm volatile("pmevent 0;" : "+r"(la));
                    mbar_wait(r.b0 + B_HLD, pat);
                    uint32_t bad = lines_bad(la, tag, 1);
                    if (!bad) mbar_arrive(r.b0);
                    asm volatile("pmevent 0;" : "+r"(bad));
#pragma unroll 1
                    while (__any_sync(~0u, bad)) {
                        const int kk = __shfl_sync(~0u, pat, 0);
                        if (elect_one()) {
                            mbar_expect_tx(bars + B_HRTY, 16384);
                            bulk_ld(r.dst(), g_H + (uint32_t)(tc * 32 + half * 16 + __clz(kk) - 15) * 16384, 16384, bars + B_HRTY);
                        }
                        __syncwarp();
                        mbar_wait(bars + B_HRTY, n++);
                        if (bad && !lines_bad(la, tag, n < SPIN_LIMIT)) { bad = 0; mbar_arrive(r.b0); }
                        __syncwarp();
                    }
                    if (pat >> 16) STAMPR(6 + 23 * half);
                    r.next();
                }
            }
        }
    } else {
        asm volatile("setmaxnreg.inc.sync.aligned.u32 152;");
        asm volatile("barrier.cluster.wait.aligned;" ::: "memory");
        STAMP(55);
        if ((extra && (wg != 2 || bid == 129)) || (sb & 0x3FFFF) != SB0) return;
        const int hf = wg - 1;
#define INDICES(i) const int t7 = (threadIdx.x + p.zero[i]) & 127, lane = t7 & 31, g = lane >> 2, q = lane & 3, k1 = t7 >> 2, mi = lane >> 3, gl = lane & 7; \
                   const uint32_t tmask = q == 0 ? ~1u : ~0u;
        if (wg == 1) {
            INDICES(1)
            const int ch = (t7 >> 6) * 512 + (t7 & 8) * 32 + cb * 32 + ((t7 >> 1) & 24) + (t7 & 7);
            const float lr = __bfloat162float(p.lre[ch]), li = __bfloat162float(p.lim[ch]);
            const float dt = __bfloat162float(__float2bfloat16(expf(__bfloat162float(p.ldt[ch]))));
            float sn, cs;
            sincospif(dt * li * 0.31830988618379067f, &sn, &cs);
            const float ex = expf(dt * lr), br = ex * cs, bi = ex * sn;
            const float inv = __fdividef(2.0f, lr * lr + li * li);
            const cf lam = {br, -bi}, gam = {((br - 1.f) * lr + bi * li) * inv, -(bi * lr - (br - 1.f) * li) * inv};
            const cf l32 = csq(csq(csq(csq(csq(lam))))), l64 = csq(l32), m1 = csq(l64), m2 = csq(m1), g2 = cmul(gam, l64);
            sts128f(sb + OFF_T1 + t7 * 16, lam, l32);
            sts128f(sb + OFF_TL + t7 * 32, gam, cmul(gam, l32));
            sts128f(sb + OFF_TL + t7 * 32 + 16, g2, cmul(g2, l32));
            sts128f(sb + OFF_TM + t7 * 32, csq(m2), m1);
            sts128f(sb + OFF_TM + t7 * 32 + 16, m2, cmul(m2, m1));
            __syncwarp();
            if (lane == 0) mbar_arrive(bars + B_LAM);
        }
        if (wg != 0 && !extra) {
            INDICES(2)
            uint32_t f1[16];
#pragma unroll
            for (int j = 0; j < 4; j++) { const uint4 v = ldtab(TAB_F1 + j * 512 + t7 * 4); f1[4 * j] = v.x; f1[4 * j + 1] = v.y; f1[4 * j + 2] = v.z; f1[4 * j + 3] = v.w; }
            cf tw[8];
            load_tw(tw, k1);
            const uint32_t tbit = get_epoch(bars) & ~tmask;
            const uint64_t dx = mkdesc(OFF_P, 2048, 256, 3) + hf * 1024;
            const int gr = gl & 1, jr = (gl >> 1) + 4 * ((w ^ gl) & 1);
            const uint32_t a0 = w + gl ? sb + OFF_P + (gr * 128 + 8 * (w >> 1) + jr + 64 * (mi >> 1)) * 128 : sb + OFF_F + 2048;
            const uint32_t rs = w + gl ? 2048 : 0;
            const uint32_t scr = sb + OFF_F + hf * 1024;
            float acc[32];
            c2 ev[2][4];
            uint4 fx0, fx1;
            float s0, s1;
#pragma unroll 1
            for (int od = 0;; od++) {
                if (od) STAMP5(33 + hf);
                mbar_wait(bars + B_XIN + od * 8, 0);
                if (od) STAMP(20);
                pinu(f1);
                wg_fence();
                mma64_rs<1, 0>(acc, f1, dx + od * 512);
                mma64_rs<1, 1>(acc, f1 + 4, dx + od * 512 + 32);
                mma64_rs<1, 1>(acc, f1 + 8, dx + od * 512 + 64);
                mma64_rs<1, 1>(acc, f1 + 12, dx + od * 512 + 96);
                wg_commit();
                wg_wait<0>();
                pin(acc);
                pinu(f1);
                if (od) STAMP5(35);
                if (k1 == 0) {
#pragma unroll
                    for (int i = 0; i < 8; i++) sts128f(scr + (i >> 1) * 256 + od * 128 + (i & 1) * 64 + q * 16, {acc[4 * i], acc[4 * i + 1]}, {acc[4 * i + 2], acc[4 * i + 3]});
                }
                if (od) break;
                asm volatile("ld.global.nc.v4.b32 {%0,%1,%2,%3}, [%4];" : "=r"(fx0.x), "=r"(fx0.y), "=r"(fx0.z), "=r"(fx0.w) : "l"(g_tab + TAB_FX + (t7 & 120)));
                asm volatile("ld.global.nc.v4.b32 {%0,%1,%2,%3}, [%4];" : "=r"(fx1.x), "=r"(fx1.y), "=r"(fx1.z), "=r"(fx1.w) : "l"(g_tab + TAB_FX + (t7 & 120) + 4));
#pragma unroll
                for (int cl = 0; cl < 2; cl++) {
                    auto in = [&](int n) { const int i = 4 * (n + cl); return c2{{acc[i], acc[i + 1]}, {acc[i + 2], acc[i + 3]}}; };
                    const c2 a0 = cfma2<false>(in(4), both(tw[4]), in(0)), a1 = tw2(in(0), a0);
                    YIELD();
                    const c2 t2 = cmul2<false>(in(2), both(tw[2]));
                    YIELD();
                    const c2 a2 = cfma2<false>(in(6), both(tw[6]), t2), a3 = tw2(t2, a2);
                    YIELD();
                    bfly2(a0, a2, ev[cl][0], ev[cl][2]);
                    YIELD();
                    bflyi2(a1, a3, ev[cl][1], ev[cl][3]);
                    YIELD();
                }
                wg_all_ok(0, hf ? 3 : 8);
                const uint32_t sa = scr + gl * 16 + (w >> 1) * 8;
                const cf x0 = lds_cf(sa), x2 = lds_cf(sa + 256), x4 = lds_cf(sa + 512), x6 = lds_cf(sa + 768);
                const float c0 = __uint_as_float(fx0.x), c2 = __uint_as_float(fx0.z), c4 = __uint_as_float(fx1.x), c6 = __uint_as_float(fx1.z);
                s0 = fmaf(c6, x6.x, fmaf(c4, x4.x, fmaf(c2, x2.x, c0 * x0.x)));
                s1 = fmaf(c6, x6.y, fmaf(c4, x4.y, fmaf(c2, x2.y, c0 * x0.y)));
            }
#pragma unroll
            for (int cl = 0; cl < 2; cl++) {
                auto in = [&](int n) { const int i = 4 * (n - 1 + cl); return c2{{acc[i], acc[i + 1]}, {acc[i + 2], acc[i + 3]}}; };
                const c2 t1 = cmul2<false>(in(1), both(tw[1]));
                YLD(YF1, 2);
                const c2 a4 = cfma2<false>(in(5), both(tw[5]), t1), a5 = tw2(t1, a4);
                YLD(YF1, 3);
                cf sx[8];
                if (cl == 0) {
                    bar_sync(6, 256);
                    STAMP5(36);
#pragma unroll
                    for (int n = 1; n < 8; n += 2) sx[n] = lds_cf(scr + n * 128 + gl * 16 + (w >> 1) * 8);
                }
                const c2 t3 = cmul2<false>(in(3), both(tw[3]));
                YLD(YF1, 1);
                const c2 a6 = cfma2<false>(in(7), both(tw[7]), t3), a7 = tw2(t3, a6);
                YLD(YF1, 2);
                const uint32_t a1 = a0 + (((((mi & 1) << 2) | ((2 * hf + cl) ^ (fpos & 3))) ^ jr) << 4);
                dft8_end<YF1>(ev[cl], a4, a5, a6, a7, [&](int r, c2 u, c2 v) {
                    uint32_t o0 = pkv(u.x), o1 = pkv(u.y), o2 = pkv(v.x), o3 = pkv(v.y);
                    if (cl == 0) { o0 = bitsel(o0, tmask, tbit); o2 = bitsel(o2, tmask, tbit); }
                    stsm4(a1 + r * rs, o0, o1, o2, o3);
                });
                if (cl == 0) {
                    YLD(YF1, 2);
#pragma unroll
                    for (int n = 1; n < 8; n += 2) {
                        const float c = __uint_as_float(n < 4 ? (n == 0 ? fx0.x : n == 1 ? fx0.y : n == 2 ? fx0.z : fx0.w) : (n == 4 ? fx1.x : n == 5 ? fx1.y : n == 6 ? fx1.z : fx1.w));
                        s0 = fmaf(c, sx[n].x, s0); s1 = fmaf(c, sx[n].y, s1);
                    }
                    asm volatile("st.shared.b32 [%0], %1;" ::"r"(sb + OFF_P + (t7 >> 4) * 2048 + (((mi & 1) * 4 + ((2 * hf + (g & 1)) ^ (fpos & 3))) << 4) + q * 4), "r"(bitsel(pk(s0, s1), tmask, tbit)) : "memory");
                    YLD(YF1, 1);
                }
            }
            fence_async_sm();
            __syncwarp();
            if (lane == 0) mbar_arrive(bars + B_STGU);
        }
        if (wg != 2) {
        if (wg == 0) bar_sync(4, 128);
        asm volatile("setmaxnreg.inc.sync.aligned.u32 168;");
        float d[128];
        Ring rg;
        rg.full = bars + B_FULL;
        asm("mapa.shared::cluster.u32 %0, %1, %2;" : "=r"(rg.rel) : "r"(bars + B_EMPTY), "r"(w & 1));
        rg.sig = ((threadIdx.x + p.zero[7]) & 95) == 0;
        rg.bh = (uint32_t)(mkdesc(0, 0, 1024, 1) >> 32) + p.zero[0];
        rg.da = p.da[0];
        rg.ph = 1;
        rg.k = 130 * 66 + bid * 66 + 16 * wg;
        if (wg == 0) {
            STAMP(0);
            gemm_step<0, 0>(d, rg, 0);
        } else {
            bar_sync(1, 256);
            STAMP(10);
        }
        rg.da = p.da[1];
#pragma unroll 1
        for (int i = 0; i < 3; i++) {
            gemm_step<1, 0>(d, rg, i >= wg);
            gemm_step<2, 0>(d, rg, 1);
            gemm_step<3, 0>(d, rg, 1);
            gemm_step<4, 0>(d, rg, 1);
            gemm_step<0, 0, 1>(d, rg, 1, i - wg == 2);
        }
        if (wg != p.zero[1]) {
            rg.da = p.da[0];
            gemm_step<1, 0, 2>(d, rg, 1, true);
        }
        {
            INDICES(3)
            cf lam[2], l32[2], l2[2];
            const uint32_t ta = sb + (wg * 64 + 16 * w + g) * 16;
            mbar_wait(bars + B_LAM, 0);
            const unsigned ep = get_epoch(bars), tag = ep & 15u;
            lds128f(ta + OFF_T1, lam[0].x, lam[0].y, l32[0].x, l32[0].y);
            lds128f(ta + OFF_T1 + 128, lam[1].x, lam[1].y, l32[1].x, l32[1].y);
            const uint4* cpub = g_carry + (uint32_t)(wg * 256 + cb * 32 + 8 * w + tc * 512 + g);
            l2[0] = csq(lam[0]);
            l2[1] = csq(lam[1]);
            asm volatile("pmevent 0;" : "+l"(cpub), "+f"(l2[0].x), "+f"(l2[0].y), "+f"(l2[1].x), "+f"(l2[1].y));
            wg_wait<0>();
            ring_release(rg, wg);
            pin(d);
            STAMPW(1, 11);
            cf f[2];
#pragma unroll
            for (int h = 0; h < 2; h++) {
                c2 c = {{d[2 * h], d[2 * h + 1]}, {d[64 + 2 * h], d[65 + 2 * h]}};
#pragma unroll
                for (int i = 1; i < 16; i++) {
                    const int r = 4 * i + 2 * h;
#define P1A "fma.rn.f32 a0, %2, %9, %4; fma.rn.f32 a1, %3, %9, %5;\n"
#define P1B "fma.rn.f32 b0, %0, n, %6; fma.rn.f32 b1, %1, n, %7;\n"
#define P1X "fma.rn.f32 %0, %0, %8, a0; fma.rn.f32 %1, %1, %8, a1;\n"
#define P1Y "fma.rn.f32 %2, %2, %8, b0; fma.rn.f32 %3, %3, %8, b1;\n"
#define P1ARG : "+f"(c.x.a), "+f"(c.x.b), "+f"(c.y.a), "+f"(c.y.b) : "f"(d[r]), "f"(d[r + 1]), "f"(d[64 + r]), "f"(d[65 + r]), "f"(l2[h].x), "f"(l2[h].y)
                    if (i & 1) asm volatile("{.reg .f32 a0, a1, b0, b1, n; neg.f32 n, %9;\n" P1A P1B P1X P1Y "}" P1ARG);
                    else asm volatile("{.reg .f32 a0, a1, b0, b1, n; neg.f32 n, %9;\n" P1B P1A P1Y P1X "}" P1ARG);
                    if (i % YS == 0) YIELD();
                    if (i == 12) lds128f(ta + OFF_T1 + 128 * h, lam[h].x, lam[h].y, l32[h].x, l32[h].y);
                }
                f[h] = cfma(lam[h], {c.x.a, -c.y.a}, {c.x.b, -c.y.b});
            }
            cf st[2], gam[2];
            gam[0] = lds_cf(2 * ta - sb + OFF_TL);
            gam[1] = lds_cf(2 * ta - sb + OFF_TL + 256);
            cf v0[2], v1[2], v2[2];
#pragma unroll
            for (int h = 0; h < 2; h++) {
                v0[h] = {__shfl_sync(~0u, f[h].x, 0, 4), __shfl_sync(~0u, f[h].y, 0, 4)};
                v1[h] = {__shfl_sync(~0u, f[h].x, 1, 4), __shfl_sync(~0u, f[h].y, 1, 4)};
                v2[h] = {__shfl_sync(~0u, f[h].x, 2, 4), __shfl_sync(~0u, f[h].y, 2, 4)};
            }
#pragma unroll
            for (int h = 0; h < 2; h++) {
                v1[h] = cfma(l32[h], v0[h], v1[h]);
                v2[h] = cfma(l32[h], v1[h], v2[h]);
                f[h] = cfma(l32[h], v2[h], f[h]);
            }
            asm volatile("{.reg .pred p; .reg .b64 a, b; .reg .b128 v; setp.eq.u32 p, %5, 3; mov.b64 a, {%1,%2}; mov.b64 b, {%3,%4}; mov.b128 v, {a, b};\n"
                         "@p st.relaxed.gpu.global.b128 [%0], v;}" ::"l"(cpub),
                         "r"(bitsel(__float_as_uint(f[0].x), ~15u, tag)), "r"(__float_as_uint(f[0].y)), "r"(__float_as_uint(f[1].x)), "r"(__float_as_uint(f[1].y)), "r"(q) : "memory");
            STAMPX(2, 12);
            YIELD();
#pragma unroll
            for (int h = 0; h < 2; h++) st[h] = cmul(gam[h], csel(q & 2, csel(q & 1, v2[h], v1[h]), csel(q & 1, v0[h], cf{0.f, 0.f})));
            const uint4* cget = cpub + (gl - g) - (1 + mi) * 512;
            const int nget = tc - 1 - mi;
            unsigned __int128 fq[4];
            auto prescale = [&](int i) {
                const int h = i >> 4, r = 4 * (i & 15) + 2 * h;
                asm volatile("{.reg .f32 s0, s1, n; neg.f32 n, %4; mul.f32 s0, %5, %1; mul.f32 s1, %5, %3; mul.f32 %1, n, %1; mul.f32 %3, n, %3;\n"
                             "fma.rn.f32 %1, %5, %0, %1; fma.rn.f32 %3, %5, %2, %3; fma.rn.f32 %0, %4, %0, s0; fma.rn.f32 %2, %4, %2, s1;}"
                             : "+f"(d[r]), "+f"(d[64 + r]), "+f"(d[r + 1]), "+f"(d[65 + r]) : "f"(gam[h].x), "f"(gam[h].y));
            };
#pragma unroll
            for (int i = 0; i < 32; i++) {
                if (i == POLL_AT) carry_poll(fq, cget, nget, tag);
                if (i % YS2 == 0) YIELD();
                prescale(i);
            }
            YIELD();
            const uint32_t tm = sb + OFF_TM + (wg * 64 + 16 * w) * 32;
            cf m4[2], mj[2], P[2], lq[2];
#pragma unroll
            for (int h = 0; h < 2; h++) {
                m4[h] = lds_cf(tm + gl * 32 + h * 256);
                mj[h] = lds_cf(tm + gl * 32 + h * 256 + mi * 8);
            }
            uint32_t bad = carry_sum(fq, m4, tag, P);
            unsigned n = 0;
            while (__any_sync(~0u, bad) && ++n < SPIN_LIMIT) {
                unsigned __int128 fr[4];
                carry_poll(fr, cget, nget, tag);
                bad = carry_sum(fr, m4, tag, P);
                YIELD();
                mj[0] = lds_cf(tm + gl * 32 + mi * 8);
                mj[1] = lds_cf(tm + gl * 32 + 256 + mi * 8);
            }
            STAMPX(53, 54);
            P[0] = csel(mi, cmul(P[0], mj[0]), P[0]);
            P[1] = csel(mi, cmul(P[1], mj[1]), P[1]);
            __syncwarp();
            sts128f(tm + lane * 16, P[0], P[1]);
#pragma unroll
            for (int h = 0; h < 2; h++) {
                lq[h] = lds_cf(2 * ta - sb + OFF_TL + h * 256 + q * 8);
                lam[h] = lds_cf(ta + OFF_T1 + h * 128);
            }
            __syncwarp();
            float ps[4][4];
#pragma unroll
            for (int j = 0; j < 4; j++) lds128f(tm + g * 16 + j * 128, ps[j][0], ps[j][1], ps[j][2], ps[j][3]);
            const uint8_t* hp = g_H + (uint32_t)((tc * 32 + wg * 16 + (cb & 6)) * 16384 + ((cb & 1) * 4 + w) * 2048 + g * 64 + ((q ^ (g >> 1)) << 4));
#pragma unroll
            for (int h = 0; h < 2; h++)
                st[h] = cfma(lq[h], {(ps[0][2 * h] + ps[1][2 * h]) + (ps[2][2 * h] + ps[3][2 * h]), (ps[0][2 * h + 1] + ps[1][2 * h + 1]) + (ps[2][2 * h + 1] + ps[3][2 * h + 1])}, st[h]);
            STAMPX(3, 13);
            uint32_t hv[32];
#pragma unroll
            for (int h = 0; h < 2; h++) {
                YIELD();
                cf c = st[h];
#pragma unroll
                for (int i = 0; i < 16; i++) {
                    const int r = 4 * i + 2 * h;
                    const cf a = cfma(lam[h], c, {d[r], d[64 + r]});
                    c = cfma(lam[h], a, {d[r + 1], d[65 + r]});
                    hv[i] = pk(a.x, c.x);
                    hv[16 + i] = pk(a.y, c.y);
                    if ((i & 3) == (i >> 2)) { hv[i] = bitsel(hv[i], ~1u, ep & 1); hv[16 + i] = bitsel(hv[16 + i], ~1u, ep & 1); }
                    if (h == 0 && (i & 3) == 3) {
                        stg128(hp + (i >> 2) * 512, hv[i - 3], hv[i - 2], hv[i - 1], hv[i]);
                        stg128(hp + 16384 + (i >> 2) * 512, hv[13 + i], hv[14 + i], hv[15 + i], hv[16 + i]);
                    }
                }
                if (h == 0) {
                    STAMPW(4, 14);
                    if (lane == 0) red_hint(g_hcnt + tc * 64 + wg * 32);
                }
            }
            YIELD();
            if (w == 0 && !(PPOLL >> (2 * wg) & 1)) {
                wait_cnt(g_hcnt + tc * 64 + wg * 32, 32 * ep - EARLY_H);
                if (lane < 4) mbar_arrive(bars + B_HGO + 16 * wg);
            }
#pragma unroll
            for (int j = 0; j < 8; j++) {
                const int n0 = (HP0 >> (4 * j) & 15) * 60, n1 = (HP1 >> (4 * j) & 15) * 60;
                if (n0 | n1) __nanosleep(n0 + wg * (n1 - n0));
                stg128(hp + (8 + (j >> 2)) * 16384 + (j & 3) * 512, hv[4 * j], hv[4 * j + 1], hv[4 * j + 2], hv[4 * j + 3]);
            }
            __syncwarp();
            if (lane == 0) mbar_arrive(bars + B_HGO + 16 * wg + 8);
            STAMPW(5, 15);
        }
        if (wg == p.zero[2]) {
            INDICES(1)
            float y[128];
            const uint32_t sa = sb + w * 4096 + g * 512 + q * 8;
            bar_sync(2, 256);
            STAMP(7);
            rg.da = p.da[2];
            rg.ph = 0;
            rg.k = 130 * 66 + bid * 66 + 32;
#pragma unroll 1
            for (int i = 0;; i++) {
                gemm_step<2, 1>(y, rg, i);
                gemm_step<3, 1>(y, rg, 1);
                gemm_step<4, 1>(y, rg, 1);
                if (i == 5) break;
                gemm_step<0, 1>(y, rg, 1);
                gemm_step<1, 1>(y, rg, 1);
            }
            rg.da = p.da[3];
            gemm_half<60, 0>(y, rg);
            wg_commit();
            gemm_half<64 - SKEW, 1>(y, rg);
            wg_commit();
#pragma unroll
            for (int r = 0; r < 4; r++) {
                if (r == 0) {
                    wg_wait<1>();
#pragma unroll
                    for (int i = 0; i < 64; i++) asm volatile("" : "+f"(y[i])::"memory");
                    STAMP(16);
                    bar_sync(4, 128);
                }
                if (r == 2) {
                    STAMP(18);
                    wg_wait<0>();
#pragma unroll
                    for (int i = 64; i < 128; i++) asm volatile("" : "+f"(y[i])::"memory");
                    STAMP(8);
                    bar_sync(4, 128);
                }
#pragma unroll
                for (int c = 0; c < 16; c++) {
                    const int yi = 64 * (r >> 1) + 4 * c + 2 * (r & 1);
                    sts64f(sa + (r < 2 ? (NST - 1) * 32768 : 0) + (r & 1) * 16384 + (c >> 2) * 128 + (((c ^ g) & 3) << 5), y[yi], y[yi + 1]);
                }
                if (r == 0) bar_arrive(9, 256);
                if (r == 1) bar_arrive(10, 256);
                if (r == 2) bar_arrive(11, 256);
                if (r == 3) bar_arrive(12, 256);
            }
            STAMP(19);
            return;
        }
        bar_sync(8, 128);
        asm volatile("setmaxnreg.dec.sync.aligned.u32 152;");
        } else {
            INDICES(4)
            cf T[8];
            load_T(T, t7);
            const uint32_t tag = get_epoch(bars) & 1;
            float acc[64];
            constexpr uint64_t dF = mkdesc(OFF_F, 16, 1024, 1);
            const uint32_t tga = sb + OFF_P + t7 * 128 + (((t7 & 1) ^ (g & 2)) << 4);
            bool ok = false;
            mbar_wait(bars + B_WIN, 0);
#pragma unroll 1
            for (int gi = 0;; gi++) {
                const uint32_t un = p.unit[2 * bid + gi];
                const int kap = un & 0xffff;
                const uint32_t buf = sb + OFF_P + gi * 16384;
                STAMP3(39);
                float za[32], zb[32], ya[32], yb[32];
                const uint64_t dB = mkdesc(OFF_P, 4096, 512, 2) + gi * 1024;
                uint32_t ad, am, pa, pb;
                if (w == 2) {
                    ad = sb + OFF_W + (lane & 8) * 128;
                    am = ad + ((lane & 4) | (((kap ? 3 : 4) - lane) & 3)) * WPITCH + (8 * WPITCH + ((-2 * kap) & 15));
                    ad += gl * WPITCH + ((2 * kap) & 15);
                    asm volatile("" : "+r"(ad), "+r"(am));
                    mbar_wait(bars + B_WIN, gi);
                    pa = lds_u16(ad);
                    pb = lds_u16(am);
                }
#pragma unroll 1
                for (int n = gi; !ok && n < 4096; n++) {
                    if (n) bar_sync(3, 128);
                    if (n && w == 0 && elect_one()) { mbar_expect_tx(bars + B_UIN + gi * 8, 16384); bulk_ld(buf, g_U + (size_t)(extra ? 0 : bid + gi * 128) * 16384, 16384, bars + B_UIN + gi * 8); }
                    mbar_wait(bars + B_UIN + gi * 8, n & 1);
                    STAMP3(22);
                    wg_fence();
                    mma128_first(acc, dF, dB);
                    mma128_ss<0, 0, 1, 1>(acc, dF + 2, dB + 64);
                    mma128_ss<0, 0, 1, 1>(acc, dF + 4, dB + 128);
                    mma128_ss<0, 0, 1, 1>(acc, dF + 6, dB + 192);
                    wg_commit();
                    YIELD();
                    ok = wg_all_ok(tag_bad(tga + gi * 16384, tag), 3);
                    wg_wait<0>();
                    pin(acc);
                }
                STAMP3(30);
                uint32_t af[32];
#pragma unroll
                for (int b = 0; b < 4; b++) {
#pragma unroll
                    for (int c = 0; c < 4; c++) {
                        const int i = 4 * (4 * b + c);
                        cf x0 = cmul({acc[i], acc[i + 2]}, T[2 * c]), x1 = cmul({acc[i + 1], acc[i + 3]}, T[2 * c + 1]);
                        af[16 * (b >> 1) + 4 * c + (b & 1)] = pk(x0.x, x0.y);
                        af[16 * (b >> 1) + 4 * c + 2 + (b & 1)] = pk(x1.x, x1.y);
                        YLD(YF2, c == 3 ? 1 : (c == 1 ? 2 : 3));
                    }
                    if (b == 0 && w == 2) {
                        const uint32_t sg = (lane & 4) << 13, v = pk(0.5f * (up(pa) + up(pb ^ sg)), 0.f);
                        asm volatile("st.shared.u16 [%0], %1;" ::"r"(ad), "r"(v) : "memory");
                        asm volatile("st.shared.u16 [%0], %1;" ::"r"(am), "r"(v ^ sg) : "memory");
                    }
                    if (b == 1) {
                        wg_fence();
                        mma64_rs<0, 0>(za, af, dF); mma64_rs<0, 1>(za, af + 4, dF + 2); mma64_rs<0, 1>(za, af + 8, dF + 4); mma64_rs<0, 1>(za, af + 12, dF + 6);
                        wg_commit();
                    }
                }
                wg_fence();
                mma64_rs<0, 0>(zb, af + 16, dF); mma64_rs<0, 1>(zb, af + 20, dF + 2); mma64_rs<0, 1>(zb, af + 24, dF + 4); mma64_rs<0, 1>(zb, af + 28, dF + 6);
                wg_commit();
                STAMP3(31);
                int kq;
                asm volatile("mad.lo.s32 %0, %1, 512, %2;" : "=r"(kq) : "r"(q), "r"(kap));
                uint32_t wad[4];
#pragma unroll
                for (int j = 0; j < 4; j++) wad[j] = sb + OFF_W + ((j + (kq >> 9)) & 3) * WPITCH + ((2 * kap) & 15) + 2 * k1 + 128 * q;
                if (gi) fence_async_sm();
                bar_sync(3, 128);
                if (lane < gi) mbar_arrive(bars + B_STG);
                uint32_t wn[16];
#pragma unroll
                for (int j = 0; j < 16; j++) wn[j] = lds_u16(wad[j >> 2] + (j & 1) * 64 + (j & 2) * (2 * WPITCH));
                const cf be1 = twid(kq, 2048), be2 = cmul(be1, be1), be3 = cmul(be1, be2);
                YLD(YF2, 1);
                wg_wait<0>();
                pin(za);
                pin(zb);
                pinu(af);
                STAMP3(32);
                c2 z[4];
                auto pack = [&](int jb, int b) {
                    af[16 * (b >> 1) + 4 * jb + (b & 1)] = pkv(z[b].x);
                    af[16 * (b >> 1) + 4 * jb + 2 + (b & 1)] = pkv(z[b].y);
                };
#pragma unroll
                for (int jb = 0; jb < 4; jb++) {
                    if (jb == 2) STAMP3(37);
                    if (jb == 1) {
#pragma unroll
                        for (int j = 0; j < 4; j++)
                            wad[j] = sb + OFF_W + (8 + (((kap ? 3 : 4) - j - q) & 3)) * WPITCH + ((-2 * kap) & 15) + 1024 - 2 * k1 - 128 * q;
                    }
                    c2 W[4];
                    auto next = [&](int j) {
                        W[j] = {{upv(wn[4 * j]), upv(wn[4 * j + 1])}, {upv(wn[4 * j + 2]), upv(wn[4 * j + 3])}};
                        if (jb < 3) {
#pragma unroll
                            for (int n = 0; n < 4; n++) wn[4 * j + n] = lds_u16(wad[j] + (jb ? 512 - 512 * jb - (n & 1) * 64 : 512 + (n & 1) * 64) + (n & 2) * (2 * WPITCH));
                        }
                    };
                    const int i = 8 * jb;
                    const c2 z0 = {{za[i], za[i + 1]}, {za[i + 4], za[i + 5]}};
                    if (jb) pack(jb - 1, 1);
                    next(0);
                    c2 s0 = cfma2<false>({{zb[i], zb[i + 1]}, {zb[i + 4], zb[i + 5]}}, both(be2), z0), s1 = tw2(z0, s0);
                    YLD(YF2, 2);
                    if (jb) pack(jb - 1, 3);
                    if (jb == 3) load_T(T, t7);
                    next(1);
                    const c2 z1 = cmul2<false>({{za[i + 2], za[i + 3]}, {za[i + 6], za[i + 7]}}, both(be1));
                    YLD(YF2, 3);
                    c2 s2 = cfma2<false>({{zb[i + 2], zb[i + 3]}, {zb[i + 6], zb[i + 7]}}, both(be3), z1), s3 = tw2(z1, s2);
                    YLD(YF2, 1);
                    c2 x0, x1, x2, x3;
                    next(2);
                    bfly2(s0, s2, x0, x2);
                    const c2 y0 = jb < 2 ? cmul2<false>(x0, W[0]) : cmul2<true>(x0, W[0]);
                    YLD(YF2, 2);
                    next(3);
                    bflyi2(s1, s3, x1, x3);
                    const c2 y1 = jb < 2 ? cmul2<false>(x1, W[1]) : cmul2<true>(x1, W[1]);
                    YLD(YF2, 1);
                    s0 = jb < 2 ? cfma2<false>(x2, W[2], y0) : cfma2<true>(x2, W[2], y0);
                    s1 = tw2(y0, s0);
                    YLD(YF2, 3);
                    s2 = jb < 2 ? cfma2<false>(x3, W[3], y1) : cfma2<true>(x3, W[3], y1);
                    s3 = tw2(y1, s2);
                    YLD(YF2, 2);
                    bfly2(s0, s2, z[0], x2);
                    z[2] = cmul2<true>(x2, both(be2));
                    pack(jb, 0);
                    YLD(YF2, 1);
                    bflyi2(s1, s3, x3, x1);
                    pack(jb, 2);
                    z[1] = cmul2<true>(x1, both(be1));
                    YLD(YF2, 3);
                    z[3] = cmul2<true>(x3, both(be3));
                    YLD(YF2, 1);
                }
                pack(3, 1);
                pack(3, 3);
                pinu(af);
                wg_fence();
                mma64_rs<1, 0>(ya, af, dF); mma64_rs<1, 1>(ya, af + 4, dF + 128); mma64_rs<1, 1>(ya, af + 8, dF + 256); mma64_rs<1, 1>(ya, af + 12, dF + 384);
                wg_commit();
                mma64_rs<1, 0>(yb, af + 16, dF); mma64_rs<1, 1>(yb, af + 20, dF + 128); mma64_rs<1, 1>(yb, af + 24, dF + 256); mma64_rs<1, 1>(yb, af + 28, dF + 384);
                wg_commit();
                STAMP3(33);
                if (w == 2) fence_async_sm();
                __syncwarp();
                if (lane == 0) mbar_arrive(bars + B_WFREE);
                {
                    const uint32_t a0 = buf + (mi & 1) * 4096 + (16 * w + 8 * (mi >> 1) + gl) * 64;
#pragma unroll
                    for (int u = 0; u < 2; u++)
#pragma unroll
                        for (int c = 0; c < 4; c++) {
                            if (c == 0) {
                                if (u == 0) { wg_wait<1>(); pin(ya); STAMP3(34); }
                                else { wg_wait<0>(); pin(yb); pinu(af); }
                            }
                            const int i = 8 * c;
                            const float(&yy)[32] = u ? yb : ya;
                            const cf x0 = cmulc({yy[i], yy[i + 1]}, T[2 * c]), x1 = cmulc({yy[i + 4], yy[i + 5]}, T[2 * c + 1]);
                            const uint32_t o0 = pk(x0.x, x1.x), o2 = pk(x0.y, x1.y);
                            YLD(YF2, 3);
                            const cf y0 = cmulc({yy[i + 2], yy[i + 3]}, T[2 * c]), y1 = cmulc({yy[i + 6], yy[i + 7]}, T[2 * c + 1]);
                            stsm4(a0 + u * 8192 + ((c ^ (gl >> 1)) << 4), o0, pk(y0.x, y1.x), o2, pk(y0.y, y1.y));
                            YLD(YF2, 2 - (c & 1));
                        }
                }
                STAMP3(38);
                const uint32_t flip = ((g & 1) && !(un >> 24)) ? 0x80008000u : 0u, flipt = flip | (tag & ~tmask);
                const int rw = 8 * w + (gl & 4) + 2 * (mi & 1) + ((gl >> 1) & 1);
                const uint32_t a0 = (extra ? ((gl & 1) == gi ? sb + 32768 : sb + 65536) : buf) + rw * 128 +
                                    (((((gl & 1) << 1) | ((mi >> 1) ^ ((un >> 17) & 1))) ^ (rw & 7)) << 4);
                auto put = [&](const float (&v)[32], uint32_t a) {
#pragma unroll
                    for (int i = 0; i < 32; i += 8)
                        stsm4((a ^ ((i & 8) * 8)) + (i >> 4) * 4096, (pk(v[i], v[i + 1]) & tmask) ^ flipt, (pk(v[i + 2], v[i + 3]) & tmask) ^ flipt,
                              pk(v[i + 4], v[i + 5]) ^ flip, pk(v[i + 6], v[i + 7]) ^ flip);
                };
                fence_async_sm();
                bar_sync(3, 128);
                float va[32], vb[32];
                wg_fence();
                mma64_ss<1, 0>(va, dF, dB); mma64_ss<1, 0>(vb, dF, dB + 512);
                mma64_ss<1, 1>(va, dF + 128, dB + 64); mma64_ss<1, 1>(vb, dF + 128, dB + 576);
                mma64_ss<1, 1>(va, dF + 256, dB + 128); mma64_ss<1, 1>(vb, dF + 256, dB + 640);
                mma64_ss<1, 1>(va, dF + 384, dB + 192); mma64_ss<1, 1>(vb, dF + 384, dB + 704);
                wg_commit();
                STAMP3(35);
                uint32_t bad = 0;
                if (!gi) {
                    mbar_wait(bars + B_UIN + 8, 0);
                    bad = tag_bad(tga + 16384, tag);
                }
                wg_wait<0>();
                pin(va);
                pin(vb);
                STAMP3(36);
                ok = wg_all_ok(bad, 3);
                put(va, a0);
                if (gi) {
                    put(vb, a0 + 8192);
                    fence_async_sm();
                    __syncwarp();
                    if (lane == 0) mbar_arrive(bars + B_STG);
                    break;
                }
                constexpr uint64_t dN = mkdesc(OFF_P + 16384, 4096, 512, 2);
                wg_fence();
                mma128_first(acc, dF, dN);
                mma128_ss<0, 0, 1, 1>(acc, dF + 2, dN + 64);
                mma128_ss<0, 0, 1, 1>(acc, dF + 4, dN + 128);
                mma128_ss<0, 0, 1, 1>(acc, dF + 6, dN + 192);
                wg_commit();
                put(vb, a0 + 8192);
                wg_wait<0>();
                pin(acc);
            }
            if (extra) return;
        }
        uint2 xd[16], dd;
        auto skip = [&]() {
            const int lane = (threadIdx.x + p.zero[2]) & 31;
            const uint2* xp = (const uint2*)(p.xb + (uint32_t)((tc * 128 + 64 * (w & 1) + 32 * hf + 8 * (w >> 1)) * 1024 + cb * 128)) + lane;
            dd = __ldg((const uint2*)(p.dsk + cb * 128) + lane);
#pragma unroll
            for (int j = 0; j < (XT ? 8 : 16); j++) {
                asm volatile("ld.global.nc.L1::no_allocate.v2.b32 {%0,%1}, [%2];" : "=r"(xd[j].x), "=r"(xd[j].y) : "l"(xp + ((j >> 3) * 16 + (j & 7)) * 256));
            }
        };
        auto skip2 = [&]() {
            if (XT) {
                const uint32_t xa = sb + OFF_W + (2 * (w & 1) + hf) * 4096 + (w >> 1) * 2048 + ((threadIdx.x + p.zero[3]) & 31) * 8;
                mbar_wait(bars + B_WIN, 0);
#pragma unroll
                for (int j = 0; j < 8; j++) asm volatile("ld.shared.v2.b32 {%0,%1}, [%2];" : "=r"(xd[8 + j].x), "=r"(xd[8 + j].y) : "r"(xa + j * 256) : "memory");
            }
#pragma unroll
            for (int j = 0; j < 16; j++) {
                if (j % 4 == 0) YIELD();
                asm volatile("fma.rn.bf16x2 %0, %0, %1, %2;" : "+r"(xd[j].x) : "r"(dd.x), "r"(0x80008000u));
                asm volatile("fma.rn.bf16x2 %0, %0, %1, %2;" : "+r"(xd[j].y) : "r"(dd.y), "r"(0x80008000u));
            }
            YIELD();
        };
        {
            INDICES(5)
            uint32_t sp[8];
#pragma unroll
            for (int j = 0; j < 2; j++) { const uint4 v = ldtab(TAB_SP + j * 512 + t7 * 4); sp[4 * j] = v.x; sp[4 * j + 1] = v.y; sp[4 * j + 2] = v.z; sp[4 * j + 3] = v.w; }
            cf tw[8];
            load_tw(tw, k1);
            tw[4].x *= 2.f; tw[4].y *= 2.f;
            const uint32_t tag = get_epoch(bars) & 1;
            const uint32_t in = sb + OFF_P + hf * 8192;
            constexpr uint64_t dF = mkdesc(OFF_F, 16, 1024, 1);
            const uint64_t dB = mkdesc(OFF_P, 2048, 256, 3) + hf * 512;
            float ae[32], ao[32];
            c2 ev[2][4];
            auto blk = [&](const float (&a)[32], int i) { return c2{{a[i], a[i + 1]}, {a[i + 2], a[i + 3]}}; };
            auto unfold = [&](c2 a, c2 u, int n, c2& zn, c2& zm, int yl) {
                const float wc = n == 1 ? 0.92387953251128674f : (n == 2 ? 0.70710678118654752f : 0.38268343236508977f);
                const float ws = n == 3 ? 0.92387953251128674f : (n == 2 ? 0.70710678118654752f : 0.38268343236508977f);
                const v2 c = {wc, wc}, s = {ws, ws}, two = {2.f, 2.f};
                const c2 y = cmul2<false>(a, both(tw[n])), t = both(tw[8 - n]);
                YLD(yl, 3);
                c2 E;
                E.x = fnm2(u.y, t.y, y.x); E.y = fnm2(u.x, t.y, y.y); E.x = fma2(u.x, t.x, E.x); E.y = fnm2(u.y, t.x, E.y);
                YLD(yl, 2);
                const c2 D = tw2(y, E);
                zn.x = fnm2(D.y, c, E.x); zn.y = fma2(D.y, s, E.y); zn.x = fma2(D.x, s, zn.x); zn.y = fma2(D.x, c, zn.y);
                YLD(yl, 4);
                zm.x = tw2(E.x, zn.x); zm.y = fnm2(E.y, two, zn.y);
                YLD(yl, 1);
            };
#pragma unroll
            for (int rgn = 0; rgn < 2; rgn++) {
#pragma unroll 1
                for (int n = 0; n < 4096; n++) {
                    mbar_wait(bars + B_VIN + rgn * 16 + hf * 8, n & 1);
                    if (rgn) STAMP(25);
                    if (rgn == 0) {
                        pinu(sp);
                        wg_fence();
                        mma48_ss<0>(ae, dF, dB + 128); mma16_rs<0>(ae, sp[0], 0u, sp[1], 0u, dB);
                        mma48_ss<1>(ae, dF + 2, dB + 160); mma16_rs<1>(ae, sp[2], 0u, sp[3], 0u, dB + 32);
                        mma48_ss<1>(ae, dF + 4, dB + 192); mma16_rs<1>(ae, 0u, sp[4], 0u, sp[5], dB + 64);
                        mma48_ss<1>(ae, dF + 6, dB + 224); mma16_rs<1>(ae, 0u, sp[6], 0u, sp[7], dB + 96);
                    } else {
                        wg_fence();
                        mma64_ss<0, 0>(ao, dF, dB + 1024);
                        mma64_ss<0, 1>(ao, dF + 2, dB + 1056);
                        mma64_ss<0, 1>(ao, dF + 4, dB + 1088);
                        mma64_ss<0, 1>(ao, dF + 6, dB + 1120);
                    }
                    wg_commit();
                    const bool ok = wg_all_ok(tag_bad(in + rgn * 16384 + t7 * 64 + (t7 & 6) * 8, tag), hf ? 3 : 8);
                    wg_wait<0>();
                    if (rgn) pin(ao);
                    else { pin(ae); pinu(sp); }
                    if (ok) break;
                    wg_all_ok(0, hf ? 3 : 8);
                    if (w == 0 && elect_one()) {
                        mbar_expect_tx(bars + B_VIN + rgn * 16 + hf * 8, 8192);
                        tma2d(in + rgn * 16384, &tmVld, hf * 32, vrow + rgn * 128, bars + B_VIN + rgn * 16 + hf * 8);
                    }
                }
                if (rgn == 0) {
#pragma unroll
                    for (int cl = 0; cl < 2; cl++) {
                        const c2 b = blk(ae, 4 * cl), z0 = {add2(b.x, b.y), sub2(b.x, b.y)};
                        const c2 a0 = cfma2<false>(blk(ae, 16 + 4 * cl), both(tw[4]), z0), a1 = tw2(z0, a0);
                        YIELD();
                        c2 z2, z6, a2, a3;
                        unfold(blk(ae, 8 + 4 * cl), blk(ae, 24 + 4 * cl), 2, z2, z6, YF3);
                        bfly2(z2, z6, a2, a3);
                        bfly2(a0, a2, ev[cl][0], ev[cl][2]);
                        YIELD();
                        bflyi2(a1, a3, ev[cl][1], ev[cl][3]);
                    }
                    YIELD();
                }
            }
            skip();
            const uint32_t a0 = in + (8 * w + (gl ^ (2 * hf)) + 32 * (mi & 1)) * 32 + (mi >> 1) * 16384 + (gl & 4) * 4;
#pragma unroll
            for (int cl = 0; cl < 2; cl++) {
                c2 z1, z3, z5, z7, a4, a5, a6, a7;
                unfold(blk(ao, 4 * cl), blk(ao, 24 + 4 * cl), 1, z1, z7, YF3);
                if (cl == 0) wg_all_ok(0, hf ? 3 : 8);
                unfold(blk(ao, 8 + 4 * cl), blk(ao, 16 + 4 * cl), 3, z3, z5, YF3);
                bfly2(z1, z5, a4, a5);
                YLD(YF3, 3);
                bfly2(z3, z7, a6, a7);
                YLD(YF3, 2);
                dft8_end<YF3>(ev[cl], a4, a5, a6, a7, [&](int r, c2 u, c2 v) { stsm4((a0 ^ (cl * 16)) + r * 2048, pkv(u.x), pkv(u.y), pkv(v.x), pkv(v.y)); });
            }
            bar_sync(7, 256);
            STAMP(26);
        }
        INDICES(6)
        const int t0 = tc * 128 + 64 * (w & 1) + 32 * hf + 8 * (w >> 1);
        {
            const int n0 = 16 * hf + 4 * w + mi;
            uint32_t la = sb + OFF_P + (((gl >> 2) * 8256) ^ (n0 * 32)) + ((((gl >> 1) & 1) ^ (w & 1)) << 4) + (gl & 1) * 8;
            const float* op = p.out + (uint32_t)((4 * n0 + fb) * 2048 + fcb * 32 + gl * 4);
#pragma unroll 1
            for (int it = 0; it < 4; it++) {
                uint32_t u[8];
#pragma unroll
                for (int i = 0; i < 4; i++) asm volatile("ld.shared.v2.b32 {%0,%1}, [%2];" : "=r"(u[2 * i]), "=r"(u[2 * i + 1]) : "r"(la + i * 1024) : "memory");
#pragma unroll
                for (int i = 0; i < 4; i++) {
                    stg128(op + i * 128 * 2048, u[2 * i] << 16, u[2 * i] & 0xffff0000u, u[2 * i + 1] << 16, u[2 * i + 1] & 0xffff0000u);
                    if (TRYP >> i & 1) asm volatile("{.reg .pred p; mbarrier.try_wait.parity.shared::cta.b64 p, [%0], 0, %1; @p pmevent 0;}" ::"r"(bars + B_LDONE), "r"(PACE_O) : "memory");
                }
                la += it == 1 ? 12288 : 4096;
                op += 4 * 128 * 2048;
            }
            STAMP(27);
        }
        skip2();
        const uint32_t ra = sb + hf * 16384 + w * 4096;
        float* ob = p.out + (size_t)t0 * 2048 + 1024 + cb * 128 + lane * 4;
#pragma unroll
        for (int mb = 0; mb < 2; mb++) {
            if (hf == 0) { if (mb == 0) bar_sync(9, 256); else bar_sync(11, 256); }
            else { if (mb == 0) bar_sync(10, 256); else bar_sync(12, 256); }
            if (mb == 0) STAMP(17);
            float v[8][4];
#pragma unroll
            for (int j = 0; j < 8; j++) lds128f(ra + (mb ? 0 : (NST - 1) * 32768) + j * 512 + ((lane * 16) ^ ((j & 3) * 32)), v[j][0], v[j][1], v[j][2], v[j][3]);
#pragma unroll
            for (int j = 0; j < 8; j++) {
                const uint2 s = xd[8 * mb + j];
                stg128(ob + (16 * mb + j) * 2048, __float_as_uint(v[j][0] + up(s.x)), __float_as_uint(v[j][1] + __uint_as_float(s.x & 0xffff0000u)),
                       __float_as_uint(v[j][2] + up(s.y)), __float_as_uint(v[j][3] + __uint_as_float(s.y & 0xffff0000u)));
            }
        }
        STAMP(9);
        if (threadIdx.x == 480) RECL(2);
    }
}

typedef CUresult (*EncodeFn)(CUtensorMap*, CUtensorMapDataType, cuuint32_t, void*, const cuuint64_t*, const cuuint64_t*, const cuuint32_t*,
                             const cuuint32_t*, CUtensorMapInterleave, CUtensorMapSwizzle, CUtensorMapL2promotion, CUtensorMapFloatOOBfill);

static CUtensorMap make_map(EncodeFn enc, const void* ptr, int rank, const cuuint64_t* dims, const cuuint64_t* strides, const cuuint32_t* box,
                            CUtensorMapSwizzle swz, CUtensorMapL2promotion promo, CUtensorMapDataType dt = CU_TENSOR_MAP_DATA_TYPE_BFLOAT16) {
    CUtensorMap m;
    const cuuint32_t es[5] = {1, 1, 1, 1, 1};
    enc(&m, dt, rank, const_cast<void*>(ptr), dims, strides, box, es, CU_TENSOR_MAP_INTERLEAVE_NONE, swz, promo,
        CU_TENSOR_MAP_FLOAT_OOB_FILL_NONE);
    return m;
}

extern "C" void kernel_launch(void* const* d_in, const int* in_sizes, int n_in, void* d_out, int out_size) {
    void* fn = nullptr;
    cudaDriverEntryPointQueryResult qr;
    cudaGetDriverEntryPoint("cuTensorMapEncodeTiled", &fn, cudaEnableDefault, &qr);
    EncodeFn enc = (EncodeFn)fn;
    void *pU, *pV;
    cudaGetSymbolAddress(&pU, g_U);
    cudaGetSymbolAddress(&pV, g_V);
    const CUtensorMapL2promotion P256 = CU_TENSOR_MAP_L2_PROMOTION_L2_256B, P0 = CU_TENSOR_MAP_L2_PROMOTION_NONE;

    const cuuint64_t dX[5] = {1024, 2, 4, 16, 16}, sX[4] = {2048, 32 * 2048, 2 * 2048, 128 * 2048};
    const cuuint32_t bX[5] = {64, 2, 4, 16, 1};
    CUtensorMap tmX = make_map(enc, d_in[3], 5, dX, sX, bX, CU_TENSOR_MAP_SWIZZLE_128B, CU_TENSOR_MAP_L2_PROMOTION_L2_128B);
    const cuuint64_t dB[4] = {1024, 8, 2, 96}, sB[3] = {2048, 256 * 2048, 8 * 2048}, dC[4] = {1024, 8, 2, 64}, sC[3] = {2048, 8 * 2048, 16 * 2048};
    const cuuint32_t bB[4] = {64, 8, 2, 4};
    CUtensorMap tmBre = make_map(enc, d_in[6], 4, dB, sB, bB, CU_TENSOR_MAP_SWIZZLE_128B, P256);
    CUtensorMap tmBim = make_map(enc, d_in[7], 4, dB, sB, bB, CU_TENSOR_MAP_SWIZZLE_128B, P256);
    CUtensorMap tmCre = make_map(enc, d_in[8], 4, dC, sC, bB, CU_TENSOR_MAP_SWIZZLE_128B, P256);
    CUtensorMap tmCim = make_map(enc, d_in[9], 4, dC, sC, bB, CU_TENSOR_MAP_SWIZZLE_128B, P256);

    const cuuint64_t dU[2] = {8192, 256}, sU[1] = {16384};
    const cuuint32_t bS[2] = {64, UBOX};
    CUtensorMap tmUst = make_map(enc, pU, 2, dU, sU, bS, CU_TENSOR_MAP_SWIZZLE_128B, P0);
    const cuuint64_t dV[2] = {16384, 128}, sV[1] = {32768}, dL[2] = {64, 32768}, sL[1] = {128};
    const cuuint32_t bL[2] = {32, 128};
    CUtensorMap tmVst = make_map(enc, pV, 2, dV, sV, bS, CU_TENSOR_MAP_SWIZZLE_128B, P0);
    CUtensorMap tmVld = make_map(enc, pV, 2, dL, sL, bL, CU_TENSOR_MAP_SWIZZLE_NONE, P0);
    const cuuint64_t dR[2] = {1024, 2048}, sR[1] = {2048};
    const cuuint32_t bR[2] = {128, 16};
    CUtensorMap tmXR = make_map(enc, d_in[3], 2, dR, sR, bR, CU_TENSOR_MAP_SWIZZLE_NONE, P0);
    const cuuint64_t dA[4] = {1024, 64, 8, 4}, sA[3] = {32 * 2048, 4 * 2048, 2048};
    const cuuint32_t bA[4] = {16, 64, 1, 1};
    CUtensorMap tmXA = make_map(enc, d_in[0], 4, dA, sA, bA, CU_TENSOR_MAP_SWIZZLE_32B, CU_TENSOR_MAP_L2_PROMOTION_L2_128B);
    const cuuint64_t dF[2] = {512 * 1026 / 8, 4}, sF[1] = {512 * 1026};
    const cuuint32_t bF[2] = {WPITCH / 8, 4};
    CUtensorMap tmWr = make_map(enc, d_in[1], 2, dF, sF, bF, CU_TENSOR_MAP_SWIZZLE_NONE, P0, CU_TENSOR_MAP_DATA_TYPE_UINT64);
    CUtensorMap tmWi = make_map(enc, d_in[2], 2, dF, sF, bF, CU_TENSOR_MAP_SWIZZLE_NONE, P0, CU_TENSOR_MAP_DATA_TYPE_UINT64);

    Params p = {};
    p.xb = (const __nv_bfloat16*)d_in[3];
    p.lre = (const __nv_bfloat16*)d_in[4];
    p.lim = (const __nv_bfloat16*)d_in[5];
    p.ldt = (const __nv_bfloat16*)d_in[10];
    p.dsk = (const __nv_bfloat16*)d_in[11];
    p.out = (float*)d_out;
    p.da[0] = p.da[1] = mkdesc(0, 16, 1024, 1) - 1;
    p.da[2] = p.da[3] = mkdesc(0, 512, 2048, 2) - 1;
    for (int i = 0; i < 258; i++) {
        int cj;
        const int kap = kappa_of(i >> 1, i & 1), s3 = slot3_of(kap, cj);
        p.unit[i] = kap | s3 << 16 | cj << 24;
    }
    cudaFuncSetAttribute(fused_kernel, cudaFuncAttributeMaxDynamicSharedMemorySize, SMEM_BYTES);
    fused_kernel<<<130, 512, SMEM_BYTES>>>(Maps{{tmX, tmBre, tmBim, tmCre, tmCim, tmXA, tmUst, tmVst, tmWr, tmWi, tmVld, tmXR}}, p);
}
```
